```python
import torch

def _softmax(x, axis=-1):
    return torch.softmax(x, dim=axis)
def _gelu(x):
    return torch.nn.functional.gelu(x, approximate="tanh")
def _silu(x):
    return torch.nn.functional.silu(x)
def _sigmoid(x):
    return torch.sigmoid(x)
def _layernorm(x, axis=-1, eps=1e-5):
    m = x.mean(dim=axis, keepdim=True)
    v = x.var(dim=axis, keepdim=True, unbiased=False)
    return (x - m) / torch.sqrt(v + eps)
def _scatter_add(tgt, idx, src, axis=0):
    return tgt.clone().index_add_(axis, idx, src)
def _segment_sum(src, seg, n):
    out = torch.zeros((n,) + src.shape[1:], dtype=src.dtype)
    return out.index_add_(0, seg, src)
def _pad(x, pw):
    flat = tuple(v for pair in reversed(pw) for v in pair)
    return torch.nn.functional.pad(x, flat)

kernel_name = 'gated_mix__compressed_kv_cla__ssm_conv_h3__prompt'

def setup_inputs():

    _w = (lambda a: (lambda t: t.to(torch.bfloat16) if t.is_floating_point() else t)(torch.as_tensor(a)))
    def _A_setup():
        B, H, Sq, Sk, D, M = 1, 32, 2048, 2048, 128, 1024
        Dc = 4 * D
        return {
            "x": _w((lambda *s: torch.randn(*s, dtype=torch.bfloat16) * 0.05)(B, Sq, M)),
            "c_kv": _w((lambda *s: torch.randn(*s, dtype=torch.bfloat16) * 0.8)(B, Sk, Dc)),
            "w_q": _w((lambda *s: torch.randn(*s, dtype=torch.bfloat16) * 6.4)(M, H, D) * (M ** -0.5)),
            "w_uk": _w((lambda *s: torch.randn(*s, dtype=torch.bfloat16) * 6.4)(Dc, H, D) * (Dc ** -0.5)),
            "w_uv": _w((lambda *s: torch.randn(*s, dtype=torch.bfloat16) * 0.8)(Dc, H, D) * (Dc ** -0.5)),
            "w_o": _w((lambda *s: torch.randn(*s, dtype=torch.bfloat16) * 0.8)(H, D, M) * ((H * D) ** -0.5)),
        }
    _A_in = _A_setup()

    def _B_setup():
        B, S, D = 1, 2048, 1024
        ks = 4
        return {
            "q": _w((lambda *s: torch.randn(*s, dtype=torch.bfloat16) * 0.05)(B, S, D)),
            "k": _w((lambda *s: torch.randn(*s, dtype=torch.bfloat16) * 0.8)(B, S, D)),
            "v": _w((lambda *s: torch.randn(*s, dtype=torch.bfloat16) * 0.8)(B, S, D)),
            "shift_k": _w((lambda *s: torch.randn(*s, dtype=torch.bfloat16) * 0.8)(D, ks) * 0.5),
            "ssm_k": _w((lambda *s: torch.randn(*s, dtype=torch.bfloat16) * 1.6)(D, S) * (1.0 / S ** 0.5)),
            "ssm_D": _w((lambda *s: torch.randn(*s, dtype=torch.bfloat16) * 0.8)(D)),
        }
    _B_in = _B_setup()

    return {
        "A_x": _A_in["x"],
        "A_c_kv": _A_in["c_kv"],
        "A_w_q": _A_in["w_q"],
        "A_w_uk": _A_in["w_uk"],
        "A_w_uv": _A_in["w_uv"],
        "A_w_o": _A_in["w_o"],
        "B_q": _B_in["q"],
        "B_k": _B_in["k"],
        "B_v": _B_in["v"],
        "B_shift_k": _B_in["shift_k"],
        "B_ssm_k": _B_in["ssm_k"],
        "B_ssm_D": _B_in["ssm_D"],
        "gate_w": _w((lambda *s: torch.randn(*s, dtype=torch.bfloat16) * 0.05)(1024) * 16.0),
    }

def reference(A_x, A_c_kv, A_w_q, A_w_uk, A_w_uv, A_w_o, B_q, B_k, B_v, B_shift_k, B_ssm_k, B_ssm_D, gate_w):
    def _A_ref(x, c_kv, w_q, w_uk, w_uv, w_o):
        B, Sq, M = x.shape[0], x.shape[1], x.shape[2]
        Sk = c_kv.shape[1]
        H, D = w_q.shape[1], w_q.shape[2]
        q = torch.einsum("bqm,mhd->bhqd", x, w_q)
        k = torch.einsum("bkc,chd->bhkd", c_kv, w_uk)
        v = torch.einsum("bkc,chd->bhkd", c_kv, w_uv)
        scores = torch.einsum("bhqd,bhkd->bhqk", q, k) * (D ** -0.5)
        off = Sk - Sq
        qi = torch.arange(Sq)[:, None]
        kj = torch.arange(Sk)[None, :]
        cmask = kj <= (qi + off)
        scores = torch.where(cmask[None, None], scores, -1e9)
        p = _softmax(scores, axis=-1)
        ctx = torch.einsum("bhqk,bhkd->bhqd", p, v)
        return torch.einsum("bhqd,hdm->bqm", ctx, w_o)

    def _B_ref(q, k, v, shift_k, ssm_k, ssm_D):
        B, S, D = q.shape
        ks = shift_k.shape[-1]
        k_pad = _pad(k, ((0, 0), (ks - 1, 0), (0, 0)))
        k_shift = torch.zeros_like(k)
        for t in range(ks):
            k_shift = k_shift + k_pad[:, t:t + S, :] * shift_k[:, ks - 1 - t][None, None, :]
        kv = k_shift * v
        L = 2 * S
        kv_pad = _pad(kv, ((0, 0), (0, S), (0, 0)))
        kf_pad = _pad(ssm_k, ((0, 0), (0, S)))
        kv_f = (lambda x, axes=(-2,-1): torch.fft.rfft2(x.float(), dim=axes))(kv_pad[:, None, :, :], axes=(1, 2))
        kf_f = (lambda x, axes=(-2,-1): torch.fft.rfft2(x.float(), dim=axes))(kf_pad[:, None, :], axes=(1, 2))
        kf_f = (lambda x, *d: x.permute(*d))(kf_f, 1, 2, 0)
        y_f = kv_f * kf_f[None, :, :, :]
        y = (lambda x, s, axes=(-2,-1): torch.fft.irfft2(x, s=s, dim=axes).to(torch.bfloat16))(y_f, (1, L), axes=(1, 2))[:, 0, :S, :]
        y = y + kv * ssm_D[None, None, :]
        return q * y

    x = A_x
    g = _sigmoid((x * gate_w).sum(-1, keepdims=True))
    a = _A_ref(x, A_c_kv, A_w_q, A_w_uk, A_w_uv, A_w_o)
    b = _B_ref(x, B_k, B_v, B_shift_k, B_ssm_k, B_ssm_D)
    return g * a + (1 - g) * b
```

```cpp
#include <cuda_runtime.h>
#include <cuda_bf16.h>
#include <cuda.h>
#include <stdint.h>

typedef __nv_bfloat16 bf16;
#define INPLACE 3

constexpr int S_LEN = 2048;
constexpr int DM = 1024;
constexpr int NH = 32;
constexpr int HD = 128;
constexpr int DC = 512;
constexpr int HDIM = NH * HD;

__device__ __align__(1024) bf16 g_q[S_LEN * HDIM];
__device__ __align__(1024) bf16 g_k[S_LEN * HDIM];
__device__ __align__(1024) bf16 g_v[S_LEN * HDIM];
#define g_ctx g_q
__device__ __align__(1024) bf16 g_kvT[DM * S_LEN];
#define g_y2T g_kvT
__device__ __align__(1024) float g_gate[S_LEN];
enum { CNT_KV = 0, CNT_PREP = CNT_KV + 2, CNT_CTX, CNT_Y2 = CNT_CTX + 2, CNT_DONE, CNT_N };
__device__ unsigned int g_cnt[CNT_N * 32];

#define TL(k, i)
#define TL2(k, i)
#define TD(i)
#define CT(i)
#define GT(i)
#define GA(i)
#define ST(i)

__device__ __forceinline__ uint32_t smem_u32(const void* p) { return (uint32_t)__cvta_generic_to_shared(p); }

__device__ __forceinline__ void mbar_init(uint32_t bar, uint32_t count) {
  asm volatile("mbarrier.init.shared::cta.b64 [%0], %1;" ::"r"(bar), "r"(count));
}
__device__ __forceinline__ void mbar_expect_tx(uint32_t bar, uint32_t bytes) {
  asm volatile("mbarrier.arrive.expect_tx.shared::cta.b64 _, [%0], %1;" ::"r"(bar), "r"(bytes) : "memory");
}
__device__ __forceinline__ void mbar_arrive(uint32_t bar) {
  asm volatile("mbarrier.arrive.shared::cta.b64 _, [%0];" ::"r"(bar) : "memory");
}
__device__ __forceinline__ void mbar_wait(uint32_t bar, uint32_t parity) {
  uint32_t done;
  uint32_t spins = 0;
  do {
    asm volatile(
        "{\n.reg .pred p;\n"
        "mbarrier.try_wait.parity.shared::cta.b64 p, [%1], %2;\n"
        "selp.u32 %0, 1, 0, p;\n}\n"
        : "=r"(done)
        : "r"(bar), "r"(parity)
        : "memory");
    if (++spins > (1u << 22)) break;
  } while (!done);
}
__device__ __forceinline__ bool mbar_try(uint32_t bar, uint32_t parity) {
  uint32_t done;
  asm volatile(
      "{\n.reg .pred p;\n"
      "mbarrier.try_wait.parity.shared::cta.b64 p, [%1], %2;\n"
      "selp.u32 %0, 1, 0, p;\n}\n"
      : "=r"(done)
      : "r"(bar), "r"(parity)
      : "memory");
  return done != 0;
}
__device__ __forceinline__ bool elect_one() {
  uint32_t pred;
  asm volatile("{\n.reg .pred p;\nelect.sync _|p, 0xffffffff;\nselp.u32 %0, 1, 0, p;\n}\n" : "=r"(pred));
  return pred != 0;
}
__device__ __forceinline__ void mbar_arrive_if(uint32_t bar, bool pred) {
  asm volatile(
      "{\n.reg .pred p;\nsetp.ne.b32 p, %1, 0;\n"
      "@p mbarrier.arrive.shared::cta.b64 _, [%0];\n}\n" ::"r"(bar),
      "r"((uint32_t)pred)
      : "memory");
}
__device__ __forceinline__ void mbar_wait_sleep(uint32_t bar, uint32_t parity) {
  uint32_t done;
  uint32_t spins = 0;
  do {
    asm volatile(
        "{\n.reg .pred p;\n"
        "mbarrier.try_wait.parity.shared::cta.b64 p, [%1], %2, %3;\n"
        "selp.u32 %0, 1, 0, p;\n}\n"
        : "=r"(done)
        : "r"(bar), "r"(parity), "r"(20000u)
        : "memory");
    if (++spins > (1u << 16)) break;
  } while (!done);
}
__device__ __forceinline__ void fence_barrier_init() {
  asm volatile("fence.mbarrier_init.release.cluster;" ::: "memory");
}
__device__ __forceinline__ void fence_proxy_async() {
  asm volatile("fence.proxy.async.shared::cta;" ::: "memory");
}
__device__ __forceinline__ void named_bar_sync(int id, int nthreads) {
  asm volatile("bar.sync %0, %1;" ::"r"(id), "r"(nthreads) : "memory");
}
__device__ __forceinline__ void named_bar_arrive(int id, int nthreads) {
  asm volatile("bar.arrive %0, %1;" ::"r"(id), "r"(nthreads) : "memory");
}
__device__ __forceinline__ void tma_load_2d(uint32_t dst, const CUtensorMap* m, uint32_t bar, int c0, int c1) {
  asm volatile(
      "cp.async.bulk.tensor.2d.shared::cluster.global.mbarrier::complete_tx::bytes [%0], [%1, {%3, %4}], [%2];" ::"r"(dst),
      "l"(reinterpret_cast<uint64_t>(m)), "r"(bar), "r"(c0), "r"(c1)
      : "memory");
}
__device__ __forceinline__ void tma_load_3d(uint32_t dst, const CUtensorMap* m, uint32_t bar, int c0, int c1, int c2) {
  asm volatile(
      "cp.async.bulk.tensor.3d.shared::cluster.global.mbarrier::complete_tx::bytes [%0], [%1, {%3, %4, %5}], [%2];" ::"r"(dst),
      "l"(reinterpret_cast<uint64_t>(m)), "r"(bar), "r"(c0), "r"(c1), "r"(c2)
      : "memory");
}
__device__ __forceinline__ void tma_store_2d(const CUtensorMap* m, uint32_t src, int c0, int c1) {
  asm volatile("cp.async.bulk.tensor.2d.global.shared::cta.bulk_group [%0, {%2, %3}], [%1];" ::"l"(
                   reinterpret_cast<uint64_t>(m)),
               "r"(src), "r"(c0), "r"(c1)
               : "memory");
}
__device__ __forceinline__ void bulk_load(uint32_t dst, const void* src, uint32_t bytes, uint32_t bar) {
  asm volatile("cp.async.bulk.shared::cluster.global.mbarrier::complete_tx::bytes [%0], [%1], %2, [%3];" ::"r"(dst),
               "l"(src), "r"(bytes), "r"(bar)
               : "memory");
}
__device__ __forceinline__ void tma_load_2d_mc(uint32_t dst, const CUtensorMap* m, uint32_t bar, int c0, int c1,
                                               uint16_t mask) {
  asm volatile(
      "cp.async.bulk.tensor.2d.shared::cluster.global.mbarrier::complete_tx::bytes.multicast::cluster [%0], [%1, {%3, "
      "%4}], [%2], %5;" ::"r"(dst),
      "l"(reinterpret_cast<uint64_t>(m)), "r"(bar), "r"(c0), "r"(c1), "h"(mask)
      : "memory");
}
__device__ __forceinline__ void mbar_arrive_cluster_if(uint32_t bar, uint32_t cta, bool pred) {
  asm volatile(
      "{\n.reg .b32 ra;\n.reg .pred p;\nsetp.ne.b32 p, %2, 0;\n"
      "mapa.shared::cluster.u32 ra, %0, %1;\n"
      "@p mbarrier.arrive.shared::cluster.b64 _, [ra];\n}\n" ::"r"(bar),
      "r"(cta), "r"((uint32_t)pred)
      : "memory");
}
__device__ __forceinline__ uint64_t policy_evict_first() {
  uint64_t pol;
  asm volatile("createpolicy.fractional.L2::evict_first.b64 %0, 1.0;" : "=l"(pol));
  return pol;
}
__device__ __forceinline__ void tma_load_2d_hint(uint32_t dst, const CUtensorMap* m, uint32_t bar, int c0, int c1,
                                                 uint64_t pol) {
  asm volatile(
      "cp.async.bulk.tensor.2d.shared::cluster.global.mbarrier::complete_tx::bytes.L2::cache_hint [%0], [%1, {%3, %4}], "
      "[%2], %5;" ::"r"(dst),
      "l"(reinterpret_cast<uint64_t>(m)), "r"(bar), "r"(c0), "r"(c1), "l"(pol)
      : "memory");
}
__device__ __forceinline__ void tma_load_3d_hint(uint32_t dst, const CUtensorMap* m, uint32_t bar, int c0, int c1,
                                                 int c2, uint64_t pol) {
  asm volatile(
      "cp.async.bulk.tensor.3d.shared::cluster.global.mbarrier::complete_tx::bytes.L2::cache_hint [%0], [%1, {%3, %4, "
      "%5}], [%2], %6;" ::"r"(dst),
      "l"(reinterpret_cast<uint64_t>(m)), "r"(bar), "r"(c0), "r"(c1), "r"(c2), "l"(pol)
      : "memory");
}
__device__ __forceinline__ void bulk_load_hint(uint32_t dst, const void* src, uint32_t bytes, uint32_t bar, uint64_t pol) {
  asm volatile(
      "cp.async.bulk.shared::cluster.global.mbarrier::complete_tx::bytes.L2::cache_hint [%0], [%1], %2, [%3], %4;" ::"r"(dst),
      "l"(src), "r"(bytes), "r"(bar), "l"(pol)
      : "memory");
}
__device__ __forceinline__ void cnt_signal_release(int which, uint32_t n) {
  asm volatile("red.release.gpu.global.add.u32 [%0], %1;" ::"l"(g_cnt + which * 32), "r"(n) : "memory");
}
__device__ __forceinline__ void cnt_wait(int which, uint32_t target) {
  uint32_t v, spins = 0;
  while (true) {
    asm volatile("ld.acquire.gpu.global.u32 %0, [%1];" : "=r"(v) : "l"(g_cnt + which * 32) : "memory");
    if (v >= target || ++spins > (1u << 18)) break;
    __nanosleep(64);
  }
  asm volatile("fence.proxy.async.global;" ::: "memory");
}
__device__ __forceinline__ void tma_store_commit() { asm volatile("cp.async.bulk.commit_group;" ::: "memory"); }
template <int N>
__device__ __forceinline__ void tma_store_wait_read() {
  asm volatile("cp.async.bulk.wait_group.read %0;" ::"n"(N) : "memory");
}
template <int N>
__device__ __forceinline__ void tma_store_wait() {
  asm volatile("cp.async.bulk.wait_group %0;" ::"n"(N) : "memory");
}
__device__ __forceinline__ void wgmma_fence() { asm volatile("wgmma.fence.sync.aligned;" ::: "memory"); }
__device__ __forceinline__ void wgmma_commit() { asm volatile("wgmma.commit_group.sync.aligned;" ::: "memory"); }
template <int N>
__device__ __forceinline__ void wgmma_wait() {
  asm volatile("wgmma.wait_group.sync.aligned %0;" ::"n"(N) : "memory");
}
template <int R>
__device__ __forceinline__ void reg_alloc() { asm volatile("setmaxnreg.inc.sync.aligned.u32 %0;" ::"n"(R)); }
template <int R>
__device__ __forceinline__ void reg_dealloc() { asm volatile("setmaxnreg.dec.sync.aligned.u32 %0;" ::"n"(R)); }

__device__ __forceinline__ void stmatrix_x4(uint32_t addr, uint32_t r0, uint32_t r1, uint32_t r2, uint32_t r3) {
  asm volatile("stmatrix.sync.aligned.m8n8.x4.shared.b16 [%0], {%1, %2, %3, %4};" ::"r"(addr), "r"(r0), "r"(r1),
               "r"(r2), "r"(r3)
               : "memory");
}
__device__ __forceinline__ uint32_t pack_bf16(float lo, float hi) {
  uint32_t r;
  asm("cvt.rn.bf16x2.f32 %0, %1, %2;" : "=r"(r) : "f"(hi), "f"(lo));
  return r;
}
__device__ __forceinline__ float bf16_round(float x) { return __bfloat162float(__float2bfloat16_rn(x)); }
__device__ __forceinline__ float bf_lo(uint32_t v) { return __uint_as_float(v << 16); }
__device__ __forceinline__ float bf_hi(uint32_t v) { return __uint_as_float(v & 0xffff0000u); }
__device__ __forceinline__ uint4 lds128(uint32_t a) {
  uint4 v;
  asm volatile("ld.shared.v4.u32 {%0, %1, %2, %3}, [%4];" : "=r"(v.x), "=r"(v.y), "=r"(v.z), "=r"(v.w) : "r"(a));
  return v;
}
__device__ __forceinline__ void sts128(uint32_t a, uint4 v) {
  asm volatile("st.shared.v4.u32 [%0], {%1, %2, %3, %4};" ::"r"(a), "r"(v.x), "r"(v.y), "r"(v.z), "r"(v.w) : "memory");
}
__device__ __forceinline__ uint32_t mul_bf2(uint32_t a, uint32_t b) {
  uint32_t r;
  asm("mul.rn.bf16x2 %0, %1, %2;" : "=r"(r) : "r"(a), "r"(b));
  return r;
}
__device__ __forceinline__ uint32_t add_bf2(uint32_t a, uint32_t b) {
  uint32_t r;
  asm("add.rn.bf16x2 %0, %1, %2;" : "=r"(r) : "r"(a), "r"(b));
  return r;
}
__device__ __forceinline__ float ex2(float x) {
  float y;
  asm("ex2.approx.ftz.f32 %0, %1;" : "=f"(y) : "f"(x));
  return y;
}
__device__ __forceinline__ float rcp(float x) {
  float y;
  asm("rcp.approx.ftz.f32 %0, %1;" : "=f"(y) : "f"(x));
  return y;
}
template <int N>
__device__ __forceinline__ void fence_regs(float (&r)[N]) {
#pragma unroll
  for (int i = 0; i < N; i++) asm volatile("" : "+f"(r[i])::"memory");
}

template <int N>
__device__ __forceinline__ void undef_regs(float (&r)[N]) {
#pragma unroll
  for (int i = 0; i < N; i++) asm volatile("" : "=f"(r[i]));
}
template <int N>
__device__ __forceinline__ void fence_regs_u(uint32_t (&r)[N]) {
#pragma unroll
  for (int i = 0; i < N; i++) asm volatile("" : "+r"(r[i])::"memory");
}

constexpr uint64_t DESC_SW128 = 1ull << 62;
__device__ __forceinline__ uint64_t make_desc(uint32_t addr, uint32_t lbo_bytes, uint32_t sbo_bytes, uint64_t swz) {
  return (uint64_t)((addr & 0x3FFFF) >> 4) | ((uint64_t)((lbo_bytes & 0x3FFFF) >> 4) << 16) |
         ((uint64_t)((sbo_bytes & 0x3FFFF) >> 4) << 32) | swz;
}

__device__ __forceinline__ uint64_t desc_add(uint64_t d, uint32_t off16) {
  return (d & 0xFFFFFFFF00000000ull) | (uint64_t)((uint32_t)d + off16);
}

__device__ __forceinline__ void wgmma_m64n256_ss_tb(float (&d)[128], uint64_t da, uint64_t db, int sd) {
  asm volatile(
    "{\n.reg .pred p;\nsetp.ne.b32 p, %130, 0;\n"
    "wgmma.mma_async.sync.aligned.m64n256k16.f32.bf16.bf16 "
    "{%0, %1, %2, %3, %4, %5, %6, %7, %8, %9, %10, %11, %12, %13, %14, %15, %16, %17, %18, %19, %20, %21, %22, %23, %24, %25, %26, %27, %28, %29, %30, %31, %32, %33, %34, %35, %36, %37, %38, %39, %40, %41, %42, %43, %44, %45, %46, %47, %48, %49, %50, %51, %52, %53, %54, %55, %56, %57, %58, %59, %60, %61, %62, %63, %64, %65, %66, %67, %68, %69, %70, %71, %72, %73, %74, %75, %76, %77, %78, %79, %80, %81, %82, %83, %84, %85, %86, %87, %88, %89, %90, %91, %92, %93, %94, %95, %96, %97, %98, %99, %100, %101, %102, %103, %104, %105, %106, %107, %108, %109, %110, %111, %112, %113, %114, %115, %116, %117, %118, %119, %120, %121, %122, %123, %124, %125, %126, %127}, %128, %129, p, 1, 1, 0, 1;\n}\n"
    : "+f"(d[0]), "+f"(d[1]), "+f"(d[2]), "+f"(d[3]), "+f"(d[4]), "+f"(d[5]), "+f"(d[6]), "+f"(d[7]), "+f"(d[8]), "+f"(d[9]), "+f"(d[10]), "+f"(d[11]), "+f"(d[12]), "+f"(d[13]), "+f"(d[14]), "+f"(d[15]), "+f"(d[16]), "+f"(d[17]), "+f"(d[18]), "+f"(d[19]), "+f"(d[20]), "+f"(d[21]), "+f"(d[22]), "+f"(d[23]), "+f"(d[24]), "+f"(d[25]), "+f"(d[26]), "+f"(d[27]), "+f"(d[28]), "+f"(d[29]), "+f"(d[30]), "+f"(d[31]), "+f"(d[32]), "+f"(d[33]), "+f"(d[34]), "+f"(d[35]), "+f"(d[36]), "+f"(d[37]), "+f"(d[38]), "+f"(d[39]), "+f"(d[40]), "+f"(d[41]), "+f"(d[42]), "+f"(d[43]), "+f"(d[44]), "+f"(d[45]), "+f"(d[46]), "+f"(d[47]), "+f"(d[48]), "+f"(d[49]), "+f"(d[50]), "+f"(d[51]), "+f"(d[52]), "+f"(d[53]), "+f"(d[54]), "+f"(d[55]), "+f"(d[56]), "+f"(d[57]), "+f"(d[58]), "+f"(d[59]), "+f"(d[60]), "+f"(d[61]), "+f"(d[62]), "+f"(d[63]), "+f"(d[64]), "+f"(d[65]), "+f"(d[66]), "+f"(d[67]), "+f"(d[68]), "+f"(d[69]), "+f"(d[70]), "+f"(d[71]), "+f"(d[72]), "+f"(d[73]), "+f"(d[74]), "+f"(d[75]), "+f"(d[76]), "+f"(d[77]), "+f"(d[78]), "+f"(d[79]), "+f"(d[80]), "+f"(d[81]), "+f"(d[82]), "+f"(d[83]), "+f"(d[84]), "+f"(d[85]), "+f"(d[86]), "+f"(d[87]), "+f"(d[88]), "+f"(d[89]), "+f"(d[90]), "+f"(d[91]), "+f"(d[92]), "+f"(d[93]), "+f"(d[94]), "+f"(d[95]), "+f"(d[96]), "+f"(d[97]), "+f"(d[98]), "+f"(d[99]), "+f"(d[100]), "+f"(d[101]), "+f"(d[102]), "+f"(d[103]), "+f"(d[104]), "+f"(d[105]), "+f"(d[106]), "+f"(d[107]), "+f"(d[108]), "+f"(d[109]), "+f"(d[110]), "+f"(d[111]), "+f"(d[112]), "+f"(d[113]), "+f"(d[114]), "+f"(d[115]), "+f"(d[116]), "+f"(d[117]), "+f"(d[118]), "+f"(d[119]), "+f"(d[120]), "+f"(d[121]), "+f"(d[122]), "+f"(d[123]), "+f"(d[124]), "+f"(d[125]), "+f"(d[126]), "+f"(d[127])
    : "l"(da), "l"(db), "r"(sd));
}

__device__ __forceinline__ void wgmma_m64n128_ss(float (&d)[64], uint64_t da, uint64_t db, int sd) {
  asm volatile(
    "{\n.reg .pred p;\nsetp.ne.b32 p, %66, 0;\n"
    "wgmma.mma_async.sync.aligned.m64n128k16.f32.bf16.bf16 "
    "{%0, %1, %2, %3, %4, %5, %6, %7, %8, %9, %10, %11, %12, %13, %14, %15, %16, %17, %18, %19, %20, %21, %22, %23, %24, %25, %26, %27, %28, %29, %30, %31, %32, %33, %34, %35, %36, %37, %38, %39, %40, %41, %42, %43, %44, %45, %46, %47, %48, %49, %50, %51, %52, %53, %54, %55, %56, %57, %58, %59, %60, %61, %62, %63}, %64, %65, p, 1, 1, 0, 0;\n}\n"
    : "+f"(d[0]), "+f"(d[1]), "+f"(d[2]), "+f"(d[3]), "+f"(d[4]), "+f"(d[5]), "+f"(d[6]), "+f"(d[7]), "+f"(d[8]), "+f"(d[9]), "+f"(d[10]), "+f"(d[11]), "+f"(d[12]), "+f"(d[13]), "+f"(d[14]), "+f"(d[15]), "+f"(d[16]), "+f"(d[17]), "+f"(d[18]), "+f"(d[19]), "+f"(d[20]), "+f"(d[21]), "+f"(d[22]), "+f"(d[23]), "+f"(d[24]), "+f"(d[25]), "+f"(d[26]), "+f"(d[27]), "+f"(d[28]), "+f"(d[29]), "+f"(d[30]), "+f"(d[31]), "+f"(d[32]), "+f"(d[33]), "+f"(d[34]), "+f"(d[35]), "+f"(d[36]), "+f"(d[37]), "+f"(d[38]), "+f"(d[39]), "+f"(d[40]), "+f"(d[41]), "+f"(d[42]), "+f"(d[43]), "+f"(d[44]), "+f"(d[45]), "+f"(d[46]), "+f"(d[47]), "+f"(d[48]), "+f"(d[49]), "+f"(d[50]), "+f"(d[51]), "+f"(d[52]), "+f"(d[53]), "+f"(d[54]), "+f"(d[55]), "+f"(d[56]), "+f"(d[57]), "+f"(d[58]), "+f"(d[59]), "+f"(d[60]), "+f"(d[61]), "+f"(d[62]), "+f"(d[63])
    : "l"(da), "l"(db), "r"(sd));
}

__device__ __forceinline__ void wgmma_m64n128_ss_tb(float (&d)[64], uint64_t da, uint64_t db, int sd) {
  asm volatile(
    "{\n.reg .pred p;\nsetp.ne.b32 p, %66, 0;\n"
    "wgmma.mma_async.sync.aligned.m64n128k16.f32.bf16.bf16 "
    "{%0, %1, %2, %3, %4, %5, %6, %7, %8, %9, %10, %11, %12, %13, %14, %15, %16, %17, %18, %19, %20, %21, %22, %23, %24, %25, %26, %27, %28, %29, %30, %31, %32, %33, %34, %35, %36, %37, %38, %39, %40, %41, %42, %43, %44, %45, %46, %47, %48, %49, %50, %51, %52, %53, %54, %55, %56, %57, %58, %59, %60, %61, %62, %63}, %64, %65, p, 1, 1, 0, 1;\n}\n"
    : "+f"(d[0]), "+f"(d[1]), "+f"(d[2]), "+f"(d[3]), "+f"(d[4]), "+f"(d[5]), "+f"(d[6]), "+f"(d[7]), "+f"(d[8]), "+f"(d[9]), "+f"(d[10]), "+f"(d[11]), "+f"(d[12]), "+f"(d[13]), "+f"(d[14]), "+f"(d[15]), "+f"(d[16]), "+f"(d[17]), "+f"(d[18]), "+f"(d[19]), "+f"(d[20]), "+f"(d[21]), "+f"(d[22]), "+f"(d[23]), "+f"(d[24]), "+f"(d[25]), "+f"(d[26]), "+f"(d[27]), "+f"(d[28]), "+f"(d[29]), "+f"(d[30]), "+f"(d[31]), "+f"(d[32]), "+f"(d[33]), "+f"(d[34]), "+f"(d[35]), "+f"(d[36]), "+f"(d[37]), "+f"(d[38]), "+f"(d[39]), "+f"(d[40]), "+f"(d[41]), "+f"(d[42]), "+f"(d[43]), "+f"(d[44]), "+f"(d[45]), "+f"(d[46]), "+f"(d[47]), "+f"(d[48]), "+f"(d[49]), "+f"(d[50]), "+f"(d[51]), "+f"(d[52]), "+f"(d[53]), "+f"(d[54]), "+f"(d[55]), "+f"(d[56]), "+f"(d[57]), "+f"(d[58]), "+f"(d[59]), "+f"(d[60]), "+f"(d[61]), "+f"(d[62]), "+f"(d[63])
    : "l"(da), "l"(db), "r"(sd));
}

__device__ __forceinline__ void wgmma_m64n128_rs_tb(float* d, uint32_t a0, uint32_t a1, uint32_t a2, uint32_t a3, uint64_t db, int sd) {
  asm volatile(
    "{\n.reg .pred p;\nsetp.ne.b32 p, %69, 0;\n"
    "wgmma.mma_async.sync.aligned.m64n128k16.f32.bf16.bf16 "
    "{%0, %1, %2, %3, %4, %5, %6, %7, %8, %9, %10, %11, %12, %13, %14, %15, %16, %17, %18, %19, %20, %21, %22, %23, %24, %25, %26, %27, %28, %29, %30, %31, %32, %33, %34, %35, %36, %37, %38, %39, %40, %41, %42, %43, %44, %45, %46, %47, %48, %49, %50, %51, %52, %53, %54, %55, %56, %57, %58, %59, %60, %61, %62, %63}, {%64, %65, %66, %67}, %68, p, 1, 1, 1;\n}\n"
    : "+f"(d[0]), "+f"(d[1]), "+f"(d[2]), "+f"(d[3]), "+f"(d[4]), "+f"(d[5]), "+f"(d[6]), "+f"(d[7]), "+f"(d[8]), "+f"(d[9]), "+f"(d[10]), "+f"(d[11]), "+f"(d[12]), "+f"(d[13]), "+f"(d[14]), "+f"(d[15]), "+f"(d[16]), "+f"(d[17]), "+f"(d[18]), "+f"(d[19]), "+f"(d[20]), "+f"(d[21]), "+f"(d[22]), "+f"(d[23]), "+f"(d[24]), "+f"(d[25]), "+f"(d[26]), "+f"(d[27]), "+f"(d[28]), "+f"(d[29]), "+f"(d[30]), "+f"(d[31]), "+f"(d[32]), "+f"(d[33]), "+f"(d[34]), "+f"(d[35]), "+f"(d[36]), "+f"(d[37]), "+f"(d[38]), "+f"(d[39]), "+f"(d[40]), "+f"(d[41]), "+f"(d[42]), "+f"(d[43]), "+f"(d[44]), "+f"(d[45]), "+f"(d[46]), "+f"(d[47]), "+f"(d[48]), "+f"(d[49]), "+f"(d[50]), "+f"(d[51]), "+f"(d[52]), "+f"(d[53]), "+f"(d[54]), "+f"(d[55]), "+f"(d[56]), "+f"(d[57]), "+f"(d[58]), "+f"(d[59]), "+f"(d[60]), "+f"(d[61]), "+f"(d[62]), "+f"(d[63])
    : "r"(a0), "r"(a1), "r"(a2), "r"(a3), "l"(db), "r"(sd));
}

__device__ __forceinline__ void wgmma_m64n64_rs_tb(float (&d)[32], const uint32_t (&a)[4], uint64_t db, int sd) {
  asm volatile(
    "{\n.reg .pred p;\nsetp.ne.b32 p, %37, 0;\n"
    "wgmma.mma_async.sync.aligned.m64n64k16.f32.bf16.bf16 "
    "{%0, %1, %2, %3, %4, %5, %6, %7, %8, %9, %10, %11, %12, %13, %14, %15, %16, %17, %18, %19, %20, %21, %22, %23, %24, %25, %26, %27, %28, %29, %30, %31}, {%32, %33, %34, %35}, %36, p, 1, 1, 1;\n}\n"
    : "+f"(d[0]), "+f"(d[1]), "+f"(d[2]), "+f"(d[3]), "+f"(d[4]), "+f"(d[5]), "+f"(d[6]), "+f"(d[7]), "+f"(d[8]), "+f"(d[9]), "+f"(d[10]), "+f"(d[11]), "+f"(d[12]), "+f"(d[13]), "+f"(d[14]), "+f"(d[15]), "+f"(d[16]), "+f"(d[17]), "+f"(d[18]), "+f"(d[19]), "+f"(d[20]), "+f"(d[21]), "+f"(d[22]), "+f"(d[23]), "+f"(d[24]), "+f"(d[25]), "+f"(d[26]), "+f"(d[27]), "+f"(d[28]), "+f"(d[29]), "+f"(d[30]), "+f"(d[31])
    : "r"(a[0]), "r"(a[1]), "r"(a[2]), "r"(a[3]), "l"(db), "r"(sd));
}

__device__ __forceinline__ void wgmma_m64n32_rs_tb(float (&d)[16], const uint32_t (&a)[4], uint64_t db, int sd) {
  asm volatile(
    "{\n.reg .pred p;\nsetp.ne.b32 p, %21, 0;\n"
    "wgmma.mma_async.sync.aligned.m64n32k16.f32.bf16.bf16 "
    "{%0, %1, %2, %3, %4, %5, %6, %7, %8, %9, %10, %11, %12, %13, %14, %15}, {%16, %17, %18, %19}, %20, p, 1, 1, 1;\n}\n"
    : "+f"(d[0]), "+f"(d[1]), "+f"(d[2]), "+f"(d[3]), "+f"(d[4]), "+f"(d[5]), "+f"(d[6]), "+f"(d[7]), "+f"(d[8]), "+f"(d[9]), "+f"(d[10]), "+f"(d[11]), "+f"(d[12]), "+f"(d[13]), "+f"(d[14]), "+f"(d[15])
    : "r"(a[0]), "r"(a[1]), "r"(a[2]), "r"(a[3]), "l"(db), "r"(sd));
}

constexpr int G_STAGES = 4;
constexpr int G_A_BYTES = 128 * 64 * 2;
constexpr int G_B_BYTES = 256 * 64 * 2;
constexpr int G_STAGE_BYTES = G_A_BYTES + G_B_BYTES;
constexpr int G_STG_OFF = G_STAGES * G_STAGE_BYTES;
constexpr int BAR_OFF = G_STG_OFF + 32768 + 2048;
constexpr int SMEM_BYTES = BAR_OFF + 1024;
constexpr int B_GFULL = 0, B_GEMPTY = 32, B_PFULL = 224;
constexpr int B_KFULL = 80, B_KEMPTY = 96, B_VFULL = 112, B_VEMPTY = 128, B_QFULL = 144, B_QEMPTY = 160,
              B_QDONE = 184;
constexpr int B_CFULL = 192;
constexpr int B_OFREE = 256, B_OFULL = 272, B_OEMPTY = 320, B_OY = 368;
constexpr int B_SFULL = 392, B_SFREE = 424, B_PEND = 456, B_SCMD = 512;

#define PHASE_PROLOGUE                                                                \
  uint32_t tid, rt_zero;                                                              \
  asm volatile("mov.u32 %0, %%tid.x;" : "=r"(tid));                                   \
  asm volatile("mov.u32 %0, %%nctaid.y;" : "=r"(rt_zero));                            \
  asm volatile("" : "+r"(smem0));                                                     \
  rt_zero = __shfl_sync(0xffffffffu, rt_zero >> 8, 0);   \
  const uint32_t sbase = __shfl_sync(0xffffffffu, smem0, 0);                          \
  const uint32_t bar = sbase + BAR_OFF;                                               \
  const int wg = __shfl_sync(0xffffffffu, tid >> 7, 0);                               \
  const int warp = (tid >> 5) & 3, lane = tid & 31, wtid = tid & 127;                 \
  (void)rt_zero; (void)bar; (void)warp; (void)lane; (void)wtid;

enum { ST_END = 0, ST_BOX1, ST_BOX2, ST_BOX2Q, ST_BOX2L };
__device__ __forceinline__ void st_post(uint32_t bar, int wg, int wtid, uint32_t n, int kind, const void* dst,
                                        uint32_t src, int c0, int c1, int sig) {
  if (wtid == 0) {
    const uint32_t c = bar + B_SCMD + wg * 64 + (n & 1) * 32;
    const uint64_t d = reinterpret_cast<uint64_t>(dst);
    sts128(c, make_uint4(kind, src, c0, c1));
    sts128(c + 16, make_uint4((uint32_t)d, (uint32_t)(d >> 32), sig, 0));
  }
  fence_proxy_async();
  __syncwarp();
  mbar_arrive_if(bar + B_SFULL + wg * 16 + (n & 1) * 8, (wtid & 31) == 0);
}
__device__ __forceinline__ void st_wait(uint32_t bar, int wg, uint32_t n) {
  const uint32_t b = bar + B_SFREE + wg * 16 + (n & 1) * 8;
  if (!mbar_try(b, ~(n >> 1) & 1)) mbar_wait(b, ~(n >> 1) & 1);
}
__device__ __forceinline__ void note(uint32_t bar, uint32_t cnt) {
  asm volatile("red.release.cta.shared.add.u32 [%0], 1;" ::"r"(bar + B_PEND + 4 * cnt) : "memory");
}
__device__ __forceinline__ void store_agent(uint32_t bar, int wg) {
  mbar_arrive(bar + B_SFREE + wg * 16);
  mbar_arrive(bar + B_SFREE + wg * 16 + 8);
  bool more = true;
  for (uint32_t n = 0;; n++) {
    mbar_wait_sleep(bar + B_SFULL + wg * 16 + (n & 1) * 8, (n >> 1) & 1);
    const uint4 c = lds128(bar + B_SCMD + wg * 64 + (n & 1) * 32);
    const uint4 d = lds128(bar + B_SCMD + wg * 64 + (n & 1) * 32 + 16);
    if (c.x == ST_END) break;
    const CUtensorMap* dst = reinterpret_cast<const CUtensorMap*>((uint64_t)d.x | ((uint64_t)d.y << 32));
    tma_store_2d(dst, c.y, c.z, c.w);
    if (c.x >= ST_BOX2) tma_store_2d(dst, c.y + 8192, c.z + 64, c.w);
    tma_store_commit();
    tma_store_wait_read<0>();
    mbar_arrive(bar + B_SFREE + wg * 16 + (n & 1) * 8);
    if (c.x == ST_BOX2L) mbar_arrive(bar + B_OFREE + 8 * wg);
    if ((int)d.z >= 0) {
      tma_store_wait<0>();
      if (d.z == 0) { TD(6) }
      asm volatile("fence.proxy.async.global;" ::: "memory");
      if (c.x == ST_BOX2Q) mbar_arrive(bar + B_QDONE);
      else note(bar, d.z);
      if (c.x == ST_BOX2L) {
        note(bar, CNT_DONE);
        more = false;
      }
    }
  }
  if (more) note(bar, CNT_DONE);
}

struct Maps {
  const bf16 *shift_k, *x, *gate_w, *ssm_k, *ssm_D;
  uint8_t id[128][4];
  CUtensorMap a[2];
  CUtensorMap b[3];
  CUtensorMap c[3];
  CUtensorMap bk, bv;
  CUtensorMap q, k, v, o;
  CUtensorMap oa, ob, oc;
  CUtensorMap y;
  CUtensorMap cu, ch;
};

constexpr int P_SLOT = 67 * 128, P_V = 35 * 128, P_TAPS = 2 * P_SLOT;
__device__ __forceinline__ void ldsm4t(uint32_t (&r)[4], uint32_t a) {
  asm volatile("ldmatrix.sync.aligned.m8n8.x4.trans.shared.b16 {%0, %1, %2, %3}, [%4];"
               : "=r"(r[0]), "=r"(r[1]), "=r"(r[2]), "=r"(r[3])
               : "r"(a));
}
__device__ __forceinline__ uint32_t fma_bf2(uint32_t a, uint32_t b, uint32_t c) {
  uint32_t r;
  asm("fma.rn.bf16x2 %0, %1, %2, %3;" : "=r"(r) : "r"(a), "r"(b), "r"(c));
  return r;
}
__device__ __forceinline__ void prep_agent(const Maps& maps, uint32_t sbase, int w, int lane) {
  const uint32_t bar = sbase + BAR_OFF, pb = bar + B_PFULL + w * 16;
  const int d0 = (blockIdx.x >> 3) * 64, t0 = (blockIdx.x & 7) * 256 + w * 128;
  mbar_wait_sleep(bar + B_GFULL + 8 * (G_STAGES - 1), 0);
#pragma unroll 1
  for (int i = -1; i < 4; i++) {
    GA(82 + 2 * i)
    if (i >= 0) mbar_wait_sleep(pb + (i & 1) * 8, i >> 1);
    GA(83 + 2 * i)
    const uint32_t so = sbase + G_STG_OFF + w * (P_TAPS + 512) + (i & 1) * P_SLOT;
    if (i < 3 && elect_one()) {
      const uint32_t b = pb + (~i & 1) * 8, dst = so + (i & 1 ? -P_SLOT : P_SLOT);
      mbar_expect_tx(b, i < 0 ? P_SLOT + 512 : P_SLOT);
      const uint64_t pol = policy_evict_first();
      tma_load_2d_hint(dst, &maps.bk, b, d0, t0 + 32 * i + 29, pol);
      tma_load_2d_hint(dst + P_V, &maps.bv, b, d0, t0 + 32 * i + 32, pol);
      if (i < 0) bulk_load(sbase + G_STG_OFF + P_TAPS, maps.shift_k + d0 * 4, 512, b);
    }
    if (i < 0) continue;
    uint32_t ak[4];
#pragma unroll
    for (int r = 0; r < 4; r++) {
      const uint32_t a = so / 128 + r + 4 * (lane & 6) + (((lane >> 2) ^ lane) & 6) + (lane & 1);
      ak[r] = a * 128 + (a & 7) * 16;
    }
    bf16* dst = g_kvT + (size_t)(d0 + (lane >> 2)) * S_LEN + t0 + ((lane & 3) + 4 * i) * 8;
#pragma unroll 1
    for (int cg = 0; cg < 128; cg += 16) {
      uint32_t t01, t23, k[4][4], v[4];
      asm volatile("ld.shared.v2.u32 {%0, %1}, [%2];"
                   : "=r"(t01), "=r"(t23)
                   : "r"(sbase + G_STG_OFF + P_TAPS + cg * 4 + (lane >> 2) * 8));
#pragma unroll
      for (int r = 0; r < 4; r++) ldsm4t(k[r], ak[r] ^ cg);
      ldsm4t(v, (ak[3] ^ cg) + 4096);
      const uint32_t w0 = __byte_perm(t01, 0, 0x1010), w1 = __byte_perm(t01, 0, 0x3232);
      const uint32_t w2 = __byte_perm(t23, 0, 0x1010), w3 = __byte_perm(t23, 0, 0x3232);
#pragma unroll
      for (int j = 0; j < 4; j++)
        v[j] = mul_bf2(fma_bf2(k[3][j], w0, fma_bf2(k[2][j], w1, fma_bf2(k[1][j], w2, mul_bf2(k[0][j], w3)))), v[j]);
      const bool s1 = lane & 1, s2 = lane & 2;
      const uint32_t a0 = s1 ? v[1] : v[0], a1 = s1 ? v[0] : v[1], a2 = s1 ? v[3] : v[2], a3 = s1 ? v[2] : v[3];
      *reinterpret_cast<uint4*>(dst) = make_uint4(s2 ? a2 : a0, s2 ? a3 : a1, s2 ? a0 : a2, s2 ? a1 : a3);
      dst += 8 * S_LEN;
    }
    fence_proxy_async();
    __syncwarp();
  }
  GA(90)
  if (lane == 0) note(bar, CNT_PREP);
  __syncwarp();
  GA(91)
}

__device__ __forceinline__ void qkv_tile(const Maps& maps, int it, int& which, int& m_tile, int& n_tile) {
  const bool q = it == 0 || it >= 5;
  const int b = maps.id[blockIdx.x][it >= 5];
  which = q ? 0 : 2 - (it & 1);
  m_tile = b & 15;
  n_tile = (b >> 4) * 2 + ((0x19 >> it) & 1);
}

constexpr int G_NTILES = 6;
__device__ __forceinline__ void qkv_producer(const Maps& maps, uint32_t sbase, bool first) {
  const uint32_t bar = sbase + BAR_OFF;
  uint32_t stage = 0, phase = 0;
#pragma unroll 1
  for (int it = 0; it < (first ? 1 : G_NTILES); it++) {
    int which, m_tile, n_tile;
    qkv_tile(maps, it, which, m_tile, n_tile);
    const CUtensorMap* ma = &maps.a[which == 0 ? 0 : 1];
    const CUtensorMap* mb = &maps.b[which];
    const int nk = first ? G_STAGES : which == 0 ? 16 : 8;
#pragma unroll 1
    for (int kt = (it == 0 && !first) ? G_STAGES : 0; kt < nk; kt++) {
      if (!first) mbar_wait_sleep(bar + B_GEMPTY + 8 * stage, phase);
      const uint32_t fb = bar + B_GFULL + 8 * stage;
      const uint32_t sa = sbase + stage * G_STAGE_BYTES;
      mbar_expect_tx(fb, G_STAGE_BYTES);
      tma_load_2d(sa, ma, fb, kt * 64, m_tile * 128);
      tma_load_3d(sa + G_A_BYTES, mb, fb, 0, kt * 64, n_tile * 4);
      if (++stage == G_STAGES) { stage = 0; phase ^= 1; }
      {
        const int b = maps.id[blockIdx.x][1];
        if (it == 2 && kt == (b & 7)) {
          for (int i = 0; i < 2; i++)
            asm volatile("cp.async.bulk.prefetch.tensor.2d.L2.global.tile [%0, {%1, %2}];" ::"l"(&maps.a[0]),
                         "r"((b >> 4) * 128 + i * 64), "r"((b & 15) * 128)
                         : "memory");
        }
        if (it == 3 && kt == (b & 7))
          asm volatile("cp.async.bulk.prefetch.tensor.3d.L2.global.tile [%0, {%1, %2, %3}];" ::"l"(&maps.b[0]), "r"(0),
                       "r"((b & 15) * 64), "r"((b >> 4) * 8)
                       : "memory");
      }
    }
  }
}

__device__ __noinline__ void publisher(uint32_t bar, int lane, uint32_t nsrc) {
  uint32_t done = 0;
#pragma unroll 1
  for (uint32_t spins = 0; done < nsrc && spins < (1u << 20); spins++) {
    uint32_t v = 0;
    if (lane < CNT_N)
      asm volatile("atom.acquire.cta.shared.exch.b32 %0, [%1], 0;" : "=r"(v) : "r"(bar + B_PEND + 4 * lane) : "memory");
    done += __shfl_sync(0xffffffffu, v, CNT_DONE);
    if (lane == CNT_DONE) v = 0;
    if (done == nsrc && lane < CNT_DONE) {
      uint32_t w;
      asm volatile("atom.acquire.cta.shared.exch.b32 %0, [%1], 0;" : "=r"(w) : "r"(bar + B_PEND + 4 * lane) : "memory");
      v += w;
    }
    if (v && lane == 0) { TD(0) }
    if (v) cnt_signal_release(lane, v);
    if (v && lane == 0) { TD(1) }
    if (!__any_sync(0xffffffffu, v != 0)) __nanosleep(200);
  }
  __threadfence();
  __syncwarp();
}

__device__ __forceinline__ void gate_rows(const Maps& maps, uint32_t sbase, int w48, int w12, int lane) {
  const uint32_t buf = sbase + w12 * 16384, gb = sbase + BAR_OFF + 768 + w12 * 16;
  if (lane == 0) {
    mbar_init(gb, 1);
    mbar_init(gb + 8, 1);
    fence_barrier_init();
    for (int i = 0; i < 2; i++) {
      mbar_expect_tx(gb + 8 * i, 8192);
      bulk_load(buf + i * 8192, maps.x + (size_t)(w48 + 48 * i) * 4 * DM, 8192, gb + 8 * i);
    }
  }
  __syncwarp();
  uint4 wv[4];
#pragma unroll
  for (int i = 0; i < 4; i++) wv[i] = __ldg(reinterpret_cast<const uint4*>(maps.gate_w + (i * 32 + lane) * 8));
  int it = 0;
#pragma unroll 1
  for (int row = w48 * 4; row < S_LEN; row += 48 * 4, it++) {
    mbar_wait(gb + 8 * (it & 1), (it >> 1) & 1);
    uint4 xv[4][4];
#pragma unroll
    for (int r = 0; r < 4; r++)
#pragma unroll
      for (int i = 0; i < 4; i++) xv[r][i] = lds128(buf + (it & 1) * 8192 + r * 2048 + (i * 32 + lane) * 16);
    float d[2][4];
#pragma unroll
    for (int pr = 0; pr < 2; pr++) {
      d[pr][0] = d[pr][1] = d[pr][2] = d[pr][3] = 0.f;
      auto acc = [&](uint32_t a0, uint32_t a2, uint32_t b0, uint32_t b2, uint32_t w0, uint32_t w2) {
        asm volatile(
            "mma.sync.aligned.m16n8k16.row.col.f32.bf16.bf16.f32 {%0, %1, %2, %3}, {%4, %5, %6, %7}, {%8, %8}, "
            "{%0, %1, %2, %3};"
            : "+f"(d[pr][0]), "+f"(d[pr][1]), "+f"(d[pr][2]), "+f"(d[pr][3])
            : "r"(mul_bf2(a0, w0)), "r"(mul_bf2(b0, w0)), "r"(mul_bf2(a2, w2)), "r"(mul_bf2(b2, w2)), "r"(0x3f803f80u));
      };
#pragma unroll
      for (int i = 0; i < 4; i++) {
        acc(xv[2 * pr][i].x, xv[2 * pr][i].y, xv[2 * pr + 1][i].x, xv[2 * pr + 1][i].y, wv[i].x, wv[i].y);
        acc(xv[2 * pr][i].z, xv[2 * pr][i].w, xv[2 * pr + 1][i].z, xv[2 * pr + 1][i].w, wv[i].z, wv[i].w);
      }
    }
    float sum = (lane & 2) ? ((lane & 1) ? d[1][2] : d[1][0]) : ((lane & 1) ? d[0][2] : d[0][0]);
#pragma unroll
    for (int off = 16; off >= 4; off >>= 1) sum += __shfl_xor_sync(0xffffffffu, sum, off);
    if (lane < 4) g_gate[row + lane] = bf16_round(rcp(1.0f + __expf(-bf16_round(sum))));
    if (lane == 0 && row + 2 * 48 * 4 < S_LEN) {
      mbar_expect_tx(gb + 8 * (it & 1), 8192);
      bulk_load(buf + (it & 1) * 8192, maps.x + (size_t)(row + 2 * 48 * 4) * DM, 8192, gb + 8 * (it & 1));
    }
  }
}

constexpr float Q_SCALE = 0.08838834764831845f * 1.4426950408889634f;
__device__ __forceinline__ uint32_t qkv_consumer(const Maps& maps, uint32_t smem0, bool fused, float (&rest)[64]) {
  PHASE_PROLOGUE
  constexpr int NTILES = G_NTILES;
  float acc[128];
  uint32_t stage = 0, phase = 0;
  const uint32_t stg = sbase + G_STG_OFF + wg * 18432;
  const int st_row = warp * 16 + (lane & 7) + ((lane >> 3) & 1) * 8;
  const int st_cb = lane >> 4;
  uint32_t pend[64];
  const CUtensorMap* pend_map = nullptr;
  int pend_c0 = 0, pend_c1 = 0;
  uint32_t sn = 0;
  auto put_box = [&](uint32_t buf, const uint32_t* v) {
#pragma unroll
    for (int jp = 0; jp < 4; jp++) {
      const int chunk = jp * 2 + st_cb;
      const uint32_t addr = buf + st_row * 128 + ((chunk ^ (st_row & 7)) << 4);
      stmatrix_x4(addr, v[jp * 4], v[jp * 4 + 1], v[jp * 4 + 2], v[jp * 4 + 3]);
    }
  };
  GT(gti++)
#pragma unroll 1
  for (int it = 0; it <= NTILES; it++) {
    int which, m_tile, n_tile;
    qkv_tile(maps, it, which, m_tile, n_tile);
    const int nk = (which == 0 && it < NTILES) ? 16 : 8;
    uint32_t prev_stage = 0;
#pragma unroll 1
    for (int kt = 0; kt < nk; kt++) {
      if (it < NTILES) {
        mbar_wait((bar + B_GFULL) + 8 * stage, phase);
        GT(gti++)
        const uint64_t da0 = make_desc(sbase + stage * G_STAGE_BYTES + wg * 8192, 16, 1024, DESC_SW128);
        const uint64_t db0 = make_desc(sbase + stage * G_STAGE_BYTES + G_A_BYTES, 8192, 1024, DESC_SW128);
        wgmma_fence();
#pragma unroll
        for (int kk = 0; kk < 4; kk++) {
          wgmma_m64n256_ss_tb(acc, desc_add(da0, kk * 2), desc_add(db0, kk * 128), (kt | kk) != 0);
        }
        wgmma_commit();
      }
      const uint32_t when = it == 0 ? 0 : it == 5 ? 0x922 << wg : wg ? 0xAA : 0x55;
      if ((when >> kt) & 1) {
        const int c = __popc(when & ~(~0u << kt));
        st_wait(bar, wg, sn - 2);
        const uint32_t buf = stg + (c & 1) * 8192;
        switch (c) {
          case 0: put_box(buf, pend); break;
          case 1: put_box(buf, pend + 16); break;
          case 2: put_box(buf, pend + 32); break;
          default: put_box(buf, pend + 48); break;
        }
        st_post(bar, wg, wtid, sn, ST_BOX1, pend_map, buf, pend_c0 + c * 64, pend_c1, (c == 3 && it > 1) ? CNT_KV + (it > 3) : -1);
        sn++;
      }
      if (it < NTILES) {
        wgmma_wait<1>();
        mbar_arrive_if((bar + B_GEMPTY) + 8 * prev_stage, wtid == 32 && kt > 0);
        prev_stage = stage;
        if (++stage == G_STAGES) { stage = 0; phase ^= 1; }
      }
    }
    wgmma_wait<0>();
    fence_regs(acc);
    if (it == NTILES) break;
    GT(gti++)
    mbar_arrive_if((bar + B_GEMPTY) + 8 * prev_stage, wtid == 32);
    if (it == NTILES - 1 && fused) break;
    if (which == 0) {
#pragma unroll
      for (int j = 0; j < 128; j++) acc[j] *= Q_SCALE;
    }
#pragma unroll
    for (int j = 0; j < 64; j++) pend[j] = pack_bf16(acc[2 * j], acc[2 * j + 1]);
    pend_map = &maps.c[which];
    pend_c0 = n_tile * 256;
    pend_c1 = m_tile * 128 + wg * 64;
  }
  mbar_wait(bar + B_GEMPTY, 1);
#pragma unroll
  for (int j = 0; j < 32; j++) pend[j] = pack_bf16(acc[2 * j] * Q_SCALE, acc[2 * j + 1] * Q_SCALE);
  put_box(sbase + wg * 8192, pend);
  put_box(sbase + 16384 + wg * 8192, pend + 16);
  fence_proxy_async();
#pragma unroll
  for (int j = 0; j < 64; j++) rest[j] = acc[64 + j];
  GT(gti++)
  return sn;
}

constexpr int A_TILE = 128 * 128 * 2;
constexpr int A_Q_OFF = 0;
constexpr int A_K_OFF = 2 * A_TILE;
constexpr int A_V_OFF = 4 * A_TILE;
constexpr int A_O_OFF = 6 * A_TILE;
constexpr int A_ITEMS = NH * (S_LEN / 128);

constexpr uint32_t A_ORDER = 0x3120, A_STEPS = 34;
__device__ __forceinline__ int item_m(uint32_t it) { return it & 15; }
__device__ __forceinline__ int item_h(uint32_t it) { return it >> 4; }

constexpr int C_V = 16384, C_MAT = 24576;
constexpr float C_ALPHA = 0.07874506561842957f;
__device__ __forceinline__ void sincos_turn(int p, float inv, float& c, float& s) {
  const float a = (float)p * (inv * 6.283185307179586f);
  asm("cos.approx.ftz.f32 %0, %1;" : "=f"(c) : "f"(a));
  asm("sin.approx.ftz.f32 %0, %1;" : "=f"(s) : "f"(a));
}

__device__ __forceinline__ uint32_t item_of(const Maps& maps, uint32_t r) {
  const uint32_t b = maps.id[blockIdx.x & 127][1];
  return (b >> 4) * 64 + ((A_ORDER >> (4 * r)) & 3) * 16 + ((b ^ ((r & 1) * 15)) & 15);
}

#define C_SIDE 64
__device__ __forceinline__ uint32_t conv_first(const Maps& maps) {
  const uint32_t b = maps.id[blockIdx.x & 127][1];
  return (b >> 4) * 128 + C_SIDE + ((b + 15) & 15);
}

__device__ __forceinline__ void conv_consumer(const Maps& maps, uint32_t smem0, uint32_t first, uint32_t step,
                                              uint32_t end, bool pp) {
  PHASE_PROLOGUE
  const uint32_t in_full = bar + B_CFULL + wg * 16;
  const uint32_t ca = sbase + (wg ? A_V_OFF + A_TILE : A_Q_OFF);
  const int w = __shfl_sync(0xffffffffu, warp, 0), g = lane >> 2, c = lane & 3;
  auto fetch = [&](uint32_t ch, uint32_t n) {
    if (w == 2 && ch < end) {
      if (elect_one()) {
        const uint32_t b = in_full + (n & 1) * 8, d = ca + (n & 1) * 8192;
        const uint64_t pol = policy_evict_first();
        mbar_expect_tx(b, 8192);
        tma_load_2d_hint(d, &maps.cu, b, 0, ch * 64, pol);
        tma_load_2d_hint(d + 4096, &maps.ch, b, 0, ch * 64, pol);
      }
    }
  };
  if (wtid == 96 && wg) { TD(15) }
  uint32_t f1[8][4];
  float tt[16], ts[16];
  uint32_t cc[4], ss[4];
#pragma unroll
  for (int i = 0; i < 16; i++) {
    const int k = 2 * (16 * w + g + 8 * (i & 1)) + 1, n = 2 * (8 * (i >> 1) + 2 * c) + 1;
    float c0, s0, c1, s1;
    sincos_turn(((k * n) << 23) >> 23, 1.f / 512, c0, s0);
    sincos_turn(((k * n + 2 * k) << 23) >> 23, 1.f / 512, c1, s1);
    f1[i >> 2][i & 3] = pack_bf16(c0 * C_ALPHA, c1 * C_ALPHA);
    f1[4 + (i >> 2)][i & 3] = pack_bf16(s0 * -C_ALPHA, s1 * -C_ALPHA);
  }
#pragma unroll
  for (int i = 0; i < 16; i++) {
    const int k = 2 * (16 * w + g + 8 * ((i >> 1) & 1)) + 1, n = 16 - (8 * (i >> 2) + 2 * c + (i & 1));
    float cs;
    sincos_turn(k * n, 1.f / 8192, cs, ts[i]);
    tt[i] = ts[i] * rcp(1.f + cs);
  }
#pragma unroll
  for (int j = 0; j < 4; j++) {
    const int k = 8 * w + g, n = 8 * c + 2 * j;
    float c0, s0, c1, s1;
    sincos_turn((int8_t)(k * n * 8), 1.f / 256, c0, s0);
    sincos_turn((int8_t)((k * n + k) * 8), 1.f / 256, c1, s1);
    cc[j] = pack_bf16(c0, c1);
    ss[j] = pack_bf16(s0, s1);
  }
  named_bar_sync(3, 256);
  fetch(first, 0);
  fetch(first + step, 1);
  const uint32_t va = ca + g * 64 + ((c ^ (g >> 1)) << 4);
  {
    const uint32_t a = va + C_MAT + w * 512, m = 0x80008000u;
    sts128(a, make_uint4(cc[0], cc[1], cc[2], cc[3]));
    sts128(a + 2048, make_uint4(ss[0], ss[1], ss[2], ss[3]));
    sts128(a + 4096, make_uint4(ss[0] ^ m, ss[1] ^ m, ss[2] ^ m, ss[3] ^ m));
    sts128(a + 6144, make_uint4(cc[0], cc[1], cc[2], cc[3]));
  }
  fence_proxy_async();
  named_bar_sync(1 + wg, 128);
  constexpr uint64_t DHI = (2ull << 62) | ((uint64_t)(512 >> 4) << 32);
  const uint32_t d0 = (uint32_t)make_desc(ca, 4096, 0, 0);
  float a5[16];
  uint4* const yb = reinterpret_cast<uint4*>(g_y2T) + (16 * w + g) * 4 + c;
  auto issue5 = [&]() {
#pragma unroll
    for (int ks = 0; ks < 8; ks++) wgmma_m64n32_rs_tb(a5, f1[ks], DHI | (d0 + (C_V >> 4) + ks * 64), ks != 0);
    wgmma_commit();
  };
  auto finish = [&](uint32_t ch, bool on) {
    fence_regs(a5);
    uint4* y = yb + (size_t)ch * 256;
    if (on) {
      y[0] = make_uint4(pack_bf16(a5[0], a5[1]), pack_bf16(a5[4], a5[5]), pack_bf16(a5[8], a5[9]), pack_bf16(a5[12], a5[13]));
      y[32] = make_uint4(pack_bf16(a5[2], a5[3]), pack_bf16(a5[6], a5[7]), pack_bf16(a5[10], a5[11]), pack_bf16(a5[14], a5[15]));
    }
  };
  auto dft32 = [&](float (&d)[32], const float* re, const float* im) {
    uint32_t a[4][4];
#pragma unroll
    for (int i = 0; i < 8; i++) {
      a[i >> 2][i & 3] = pack_bf16(re[2 * i], re[2 * i + 1]);
      a[2 + (i >> 2)][i & 3] = pack_bf16(im[2 * i], im[2 * i + 1]);
    }
    wgmma_fence();
#pragma unroll
    for (int ks = 0; ks < 4; ks++) wgmma_m64n64_rs_tb(d, a[ks], DHI | (d0 + (C_MAT >> 4) + ks * 64), ks != 0);
    wgmma_commit();
  };
  auto rot = [&](float* x, float* y) {
#pragma unroll
    for (int i = 0; i < 16; i++) {
      x[i] = fmaf(-tt[i], y[i], x[i]);
      y[i] = fmaf(ts[i], x[i], y[i]);
      x[i] = fmaf(-tt[i], y[i], x[i]);
    }
  };
  auto load_d = [&](uint32_t ch) {
    return __ldg(reinterpret_cast<const unsigned short*>(maps.ssm_D) + ((ch & (DM - 1)) | (lane & rt_zero)));
  };
  uint32_t dn = load_d(first);
  uint32_t n = 0, ch = first;
#pragma unroll 1
  for (; ch < end; n++, ch += step) {
    CT(0)
    float a1[2][32], a2[2][32], a4[32];
    const float dsk = c ? 0.f : __uint_as_float(dn << 16) * C_ALPHA;
    dn = load_d(ch + step);
    mbar_wait(in_full + (n & 1) * 8, (n >> 1) & 1);
    if (pp) named_bar_sync(4 + wg, 256);
    CT(1)
    wgmma_fence();
#pragma unroll
    for (int ks = 0; ks < 8; ks++)
      wgmma_m64n64_rs_tb(a1[ks >> 2], f1[ks], DHI | (d0 + (n & 1) * 512 + (ks & 3) * 64), (ks & 3) != 0);
    wgmma_commit();
    issue5();
    wgmma_wait<1>();
    fence_regs(a1[0]);
    fence_regs(a1[1]);
    CT(2)
    rot(a1[0], a1[1]);
    dft32(a2[0], a1[0], a1[1]);
    rot(a1[0] + 16, a1[1] + 16);
    a1[0][16] += dsk;
    a1[0][18] += dsk;
    dft32(a2[1], a1[0] + 16, a1[1] + 16);
    CT(3)
    wgmma_wait<2>();
    finish(ch - step, n > 0);
    wgmma_wait<0>();
    fence_regs(a2[0]);
    fence_regs(a2[1]);
    CT(4)
    if (pp) named_bar_arrive(5 - wg, 256);
    float re[16], im[16];
#pragma unroll
    for (int i = 0; i < 16; i++) {
      re[i] = a2[0][i] * a2[1][i] - a2[0][16 + i] * a2[1][16 + i];
      im[i] = a2[0][i] * a2[1][16 + i] + a2[0][16 + i] * a2[1][i];
    }
    dft32(a4, im, re);
    wgmma_wait<0>();
    fence_regs(a4);
    CT(5)
    rot(a4, a4 + 16);
#pragma unroll
    for (int i = 0; i < 4; i++) {
      const float* x = a4 + 16 - 16 * (i >> 1) + 2 * (i & 1);
      sts128(va + C_V + w * 1024 + (i >> 1) * 4096 + (i & 1) * 512,
             make_uint4(pack_bf16(x[0], x[1]), pack_bf16(x[4], x[5]), pack_bf16(x[8], x[9]), pack_bf16(x[12], x[13])));
    }
    CT(6)
    fence_proxy_async();
    named_bar_sync(1 + wg, 128);
    fetch(ch + 2 * step, n);
    if (wtid == 96 && n > 0) note(bar, CNT_Y2);
    CT(7)
  }
  wgmma_fence();
  issue5();
  wgmma_wait<0>();
  finish(ch - step, true);
  named_bar_sync(1 + wg, 128);
  if (wtid == 96 && wg) { TD(8) }
  if (wtid == 96) cnt_signal_release(CNT_Y2, 1);
  if (wtid == 64) note(bar, CNT_DONE);
  if (wtid == 96 && wg) { TD(9) }
  mbar_wait(bar + B_OFREE, 0);
  mbar_wait(bar + B_OFREE + 8, 0);
}

__device__ __forceinline__ void attn_producer(const Maps& maps, uint32_t sbase, bool after_qkv, bool to_out,
                                              bool dry) {
  const uint32_t bar = sbase + BAR_OFF;
  const uint32_t q_full = bar + B_QFULL, q_empty = bar + B_QEMPTY;
  const uint32_t k_full = bar + B_KFULL, k_empty = bar + B_KEMPTY, v_full = bar + B_VFULL, v_empty = bar + B_VEMPTY;
  int ndrained = after_qkv ? 0 : G_STAGES;
  auto wait = [&](uint32_t b, uint32_t par) {
    if (!dry) mbar_wait_sleep(b, par);
  };
  auto drained = [&](int upto) {
#pragma unroll 1
    for (; ndrained <= upto; ndrained++) wait(bar + B_GEMPTY + 8 * ndrained, 1);
  };
  uint32_t st = 0, ph = 1, vs = 0, vp = 1;
  int pend_j = -1, pend_h = 0;
  int round = -1, m = -1, h = 0;
  bool last = false;
#pragma unroll 1
  for (;; round++) {
    uint32_t nitem = 0;
    const int tpost = m >= 3 ? m - 1 : m;
#pragma unroll 1
    for (int t = m < 0 ? -1 : 0; t <= m; t++) {
      const int j = (t < m && (round & 1)) ? m - 1 - t : t;
      if (t >= 0) {
        drained(1 + st);
        wait(k_empty + 8 * st, ph);
        if (!dry) {
          mbar_expect_tx(k_full + 8 * st, A_TILE);
          tma_load_3d(sbase + A_K_OFF + st * A_TILE, &maps.k, k_full + 8 * st, 0, j * 128, h * 2);
        }
        if (++st == 2) { st = 0; ph ^= 1; }
      }
      if (pend_j >= 0) {
        drained(3);
        wait(v_empty + 8 * vs, vp);
        if (!dry) {
          mbar_expect_tx(v_full + 8 * vs, A_TILE);
          tma_load_3d(sbase + A_V_OFF + vs * A_TILE, &maps.v, v_full + 8 * vs, 0, pend_j * 128, pend_h * 2);
        }
        if (++vs == 2) { vs = 0; vp ^= 1; }
      }
      pend_j = j;
      pend_h = h;
      if (t == tpost && !last) {
        nitem = dry ? 1 : item_of(maps, round + 1);
        if (round == (dry ? 0 : 3) || blockIdx.x >= 128) {
          nitem = A_ITEMS;
          cnt_wait(CNT_PREP, dry ? 0 : 260);
          if (to_out) {
            cnt_wait(CNT_CTX, dry ? 0 : A_ITEMS);
            asm volatile("cp.async.bulk.prefetch.L2.global [%0], 4096;" ::"l"(maps.ssm_k + (size_t)conv_first(maps) * S_LEN));
            if (!dry)
              asm volatile("cp.async.bulk.prefetch.L2.global [%0], 4096;" ::"l"(g_kvT + (size_t)conv_first(maps) * S_LEN));
          }
        }
        const uint32_t qs = (round + 1) & 1;
        wait(q_empty + 8 * qs, (((round + 1) >> 1) & 1) ^ 1);
        if (round == 1 && after_qkv) wait(bar + B_QDONE, 0);
        if (round <= 0 && after_qkv) {
          if (!dry) { TD(2) }
          cnt_wait(CNT_KV + round + 1, dry ? 0 : 512);
          if (!dry) { TD(3) }
        }
        if (nitem >= A_ITEMS || (round < 0 && after_qkv && !dry)) {
          if (!dry) mbar_arrive(q_full + 8 * qs);
        } else {
          drained(qs);
          if (!dry) {
            mbar_expect_tx(q_full + 8 * qs, A_TILE);
            tma_load_3d_hint(sbase + A_Q_OFF + qs * A_TILE, &maps.q, q_full + 8 * qs, 0, item_m(nitem) * 128,
                             item_h(nitem) * 2, policy_evict_first());
          }
        }
      }
    }
    if (last) break;
    last = nitem >= A_ITEMS;
    m = last ? -1 : item_m(nitem);
    h = item_h(nitem);
  }
}

__device__ __forceinline__ uint32_t attn_consumer(const Maps& maps, uint32_t smem0, uint32_t sn,
                                                  float (&rest)[64], bool after_qkv) {
  PHASE_PROLOGUE
  const uint32_t q_full = bar + B_QFULL, q_empty = bar + B_QEMPTY;
  const uint32_t k_full = bar + B_KFULL, k_empty = bar + B_KEMPTY, v_full = bar + B_VFULL;
  float o[64], s[64];
  uint32_t p[32];
  float e[32];
  uint32_t dep = 0;
  constexpr int MIDJ = 5;
  float l0 = 0.f, l1 = 0.f, b0 = 0.f, b1 = 0.f;
  const int sched_own = 4 + wg, sched_other = 5 - wg;
  if (wg == 1) named_bar_arrive(4, 256);

  const uint32_t qd0 = (uint32_t)make_desc(sbase + A_Q_OFF + wg * 8192, 16, 0, 0);
  const uint32_t kd0 = (uint32_t)make_desc(sbase + A_K_OFF, 16, 0, 0);
  const uint32_t vd0 = (uint32_t)make_desc(sbase + A_V_OFF, 16384, 0, 0);
  constexpr uint64_t DHI = DESC_SW128 | ((uint64_t)(1024 >> 4) << 32);
  constexpr uint32_t DST = A_TILE >> 4;
  auto issue_qk = [&](uint32_t qd, uint32_t kd) {
#pragma unroll
    for (int kk = 0; kk < 8; kk++) {
      const uint32_t off = ((kk >> 2) * 16384 + (kk & 3) * 32) >> 4;
      wgmma_m64n128_ss(s, DHI | (qd + off), DHI | (kd + off), kk != 0);
    }
    wgmma_commit();
  };
  auto issue_pv = [&](uint32_t vd, bool accumulate, int nk) {
#pragma unroll
    for (int kk = 0; kk < 8; kk++) {
      if (kk < nk)
        wgmma_m64n128_rs_tb(o, p[4 * kk], p[4 * kk + 1], p[4 * kk + 2], p[4 * kk + 3], DHI | (vd + kk * 128),
                            accumulate || (kk != 0));
    }
    wgmma_commit();
  };
  auto exp_lo = [&](float& a0, float& a1) {
#pragma unroll
    for (int j = 0; j < 8; j++) {
      e[4 * j] = ex2(s[4 * j]);
      e[4 * j + 1] = ex2(s[4 * j + 1]);
      e[4 * j + 2] = ex2(s[4 * j + 2]);
      e[4 * j + 3] = ex2(s[4 * j + 3]);
      a0 += e[4 * j];
      a0 += e[4 * j + 1];
      a1 += e[4 * j + 2];
      a1 += e[4 * j + 3];
      if (j == MIDJ) dep = (__float_as_uint(a0) | __float_as_uint(a1)) & rt_zero;
    }
  };
  auto pack_lo = [&]() {
#pragma unroll
    for (int j = 0; j < 16; j++) p[j] = pack_bf16(e[2 * j], e[2 * j + 1]);
  };
  auto finish_p = [&](float& a0, float& a1) {
    pack_lo();
#pragma unroll
    for (int j = 8; j < 16; j++) {
      const float e0 = ex2(s[4 * j]), e1 = ex2(s[4 * j + 1]), e2 = ex2(s[4 * j + 2]), e3 = ex2(s[4 * j + 3]);
      a0 += e0;
      a0 += e1;
      a1 += e2;
      a1 += e3;
      p[2 * j] = pack_bf16(e0, e1);
      p[2 * j + 1] = pack_bf16(e2, e3);
      if (j == 8 + MIDJ) dep = __float_as_uint(a0) & rt_zero;
    }
  };
  auto quad_sum = [&](float t) {
    t += __shfl_xor_sync(0xffffffffu, t, 1);
    return t + __shfl_xor_sync(0xffffffffu, t, 2);
  };
  auto write_o = [&](float i0, float i1) {
    st_wait(bar, wg, sn - 1);
    const int st_row = warp * 16 + (lane & 7) + ((lane >> 3) & 1) * 8;
    const uint32_t so = sbase + A_O_OFF + wg * 16384 + st_row * 128;
#pragma unroll
    for (int j = 0; j < 16; j += 2)
      stmatrix_x4(so + (j >> 3) * 8192 + ((((j & 7) + (lane >> 4)) ^ (lane & 7)) << 4),
                  pack_bf16(o[4 * j] * i0, o[4 * j + 1] * i0), pack_bf16(o[4 * j + 2] * i1, o[4 * j + 3] * i1),
                  pack_bf16(o[4 * j + 4] * i0, o[4 * j + 5] * i0), pack_bf16(o[4 * j + 6] * i1, o[4 * j + 7] * i1));
  };
  auto store_o = [&](uint32_t r, int kind) {
    const uint32_t it = item_of(maps, r);
    st_post(bar, wg, wtid, sn, kind, (INPLACE & 1) || kind != ST_BOX2Q ? &maps.o : &maps.c[0], sbase + A_O_OFF + wg * 16384, item_h(it) * 128,
            item_m(it) * 128 + wg * 64, CNT_CTX + (r >> 1));
    sn++;
  };
  auto mask_half = [&](float* sh) {
    const int u = warp * 16 + (lane >> 2) - (lane & 3) * 2;
#pragma unroll
    for (int j = 0; j < 8; j++) {
      if (8 * j > u) sh[4 * j] = -INFINITY;
      if (8 * j + 1 > u) sh[4 * j + 1] = -INFINITY;
      if (8 * j - 8 > u) sh[4 * j + 2] = -INFINITY;
      if (8 * j - 7 > u) sh[4 * j + 3] = -INFINITY;
    }
  };
  ST(0)
  mbar_wait(q_full, 0);
  if (blockIdx.x >= 128) {
    mbar_arrive_if(bar + B_OFREE + 8 * wg, wtid == 0);
    return sn;
  }
  mbar_wait(k_full, 0);
  named_bar_sync(sched_own, 256);
  wgmma_fence();
  issue_qk(qd0, kd0);
  named_bar_arrive(sched_other, 256);
  fence_regs(rest);
#pragma unroll
  for (int i = 0; i < 64; i++) o[i] = rest[i] * Q_SCALE;
  fence_regs(o);
  wgmma_wait<0>();
  fence_regs(s);
  mbar_arrive_if(k_empty, wtid == 32);
  uint32_t g = 0;
  uint32_t rnd = 0;
  int rem = item_m(item_of(maps, 0));
  uint32_t first = 1;
  uint32_t fl = 0;
#define redo (fl & 1)
#define shifted (fl & 2)
  float d0 = 0.f, d1 = 0.f;
  float pi0 = 1.f, pi1 = 1.f;
  ST(1)
  for (;;) {
    if (shifted) {
#pragma unroll
      for (int j = 0; j < 16; j++) {
        s[4 * j] -= d0;
        s[4 * j + 1] -= d0;
        s[4 * j + 2] -= d1;
        s[4 * j + 3] -= d1;
      }
    }
    if (rem == 0 && !redo) {
      mbar_arrive_if(q_empty + 8 * (rnd & 1), wtid == 96);
      rnd++;
      if (wg == 0) mask_half(s);
      else mask_half(s + 32);
    }
    for (;;) {
      const bool kill = rem == 0 && wg == 0;
      const uint32_t kd = kd0 + ((g + 1) & 1) * DST, vd = vd0 + (g & 1) * DST;
      float a0 = 0.f, a1 = 0.f;
      exp_lo(a0, a1);
      fence_regs(e);
      const uint32_t kb = k_full + 8 * ((g + 1) & 1);
      const uint32_t kpar = ((((g + 1) >> 1) & 1) ^ (g == A_STEPS - 1 ? 1u : 0u)) | dep;
      if (!mbar_try(kb, kpar)) mbar_wait(kb, kpar | ((__float_as_uint(a0) | __float_as_uint(a1)) & rt_zero));
      wgmma_wait<0>();
      fence_regs(o);
      if (kill) {
        mbar_arrive_if(kb + (B_VEMPTY - B_KFULL), wtid == 64 && !redo && g > 0);
        fence_regs(e);
        pack_lo();
#pragma unroll
        for (int j = 16; j < 32; j++) asm volatile("mov.u32 %0, 0;" : "=r"(p[j]));
        goto check;
      }
#pragma unroll
      for (int i = 32; i < 64; i++) asm volatile("" : "+f"(s[i])::"memory");
      mbar_arrive_if(kb + (B_VEMPTY - B_KFULL), wtid == 64 && !redo && g > 0);
      finish_p(a0, a1);
      if (__any_sync(0xffffffffu, !(mbar_try(v_full + 8 * (g & 1), ((g >> 1) & 1) | dep) &
                                    mbar_try(q_full + 8 * (rnd & 1), ((rnd >> 1) & 1) | dep)) ||
                                      !(a0 + a1 < 1.0995116e12f) || !(fminf(a0, a1) > (first ? 9.094947e-13f : -1.f)))) {
      check:
        bool bad = !(a0 + a1 < 1.0995116e12f);
        if (first) bad |= !(fminf(quad_sum(a0), quad_sum(a1)) > 9.094947e-13f);
        if (!redo && __any_sync(0xffffffffu, bad)) {
          d0 = d1 = first ? -INFINITY : 0.f;
#pragma unroll
          for (int j = 0; j < 16; j++) {
            if (j < 8 || !kill) {
              d0 = fmaxf(d0, fmaxf(s[4 * j], s[4 * j + 1]));
              d1 = fmaxf(d1, fmaxf(s[4 * j + 2], s[4 * j + 3]));
            }
          }
#pragma unroll
          for (int x = 1; x <= 2; x++) {
            d0 = fmaxf(d0, __shfl_xor_sync(0xffffffffu, d0, x));
            d1 = fmaxf(d1, __shfl_xor_sync(0xffffffffu, d1, x));
          }
          b0 += d0;
          b1 += d1;
          if (!first) {
            const float al0 = ex2(-d0), al1 = ex2(-d1);
            l0 *= al0;
            l1 *= al1;
#pragma unroll
            for (int j = 0; j < 16; j++) {
              o[4 * j] *= al0;
              o[4 * j + 1] *= al0;
              o[4 * j + 2] *= al1;
              o[4 * j + 3] *= al1;
            }
          }
          fl = 3;
          break;
        }
        mbar_wait(v_full + 8 * (g & 1), (g >> 1) & 1);
        mbar_wait(q_full + 8 * (rnd & 1), (rnd >> 1) & 1);
      }
      named_bar_sync(sched_own, 256);
      if (g == A_STEPS - 1) {
        if (first) write_o(pi0, pi1);
        fence_regs(o);
        wgmma_fence();
        issue_pv(vd, !first, 8);
        named_bar_arrive(sched_other, 256);
        if (first) store_o(rnd - 2, ST_BOX2);
        pi0 = rcp(quad_sum(l0 + a0));
        pi1 = rcp(quad_sum(l1 + a1));
        goto done;
      }
      wgmma_fence();
      issue_qk(qd0 + (rnd & 1) * DST, kd);
      if (first) write_o(pi0, pi1);
      fence_regs(o);
      if (kill) {
        wgmma_fence();
        issue_pv(vd, !first, 4);
      } else {
        wgmma_fence();
        issue_pv(vd, !first, 8);
      }
      named_bar_arrive(sched_other, 256);
      fl &= 2;
      l0 += a0;
      l1 += a1;
      if (rem == 0 || first) {
        if (first && (g > 0 || after_qkv)) store_o(g ? rnd - (rem == 0 ? 2 : 1) : 2, g ? ST_BOX2 : ST_BOX2Q);
        first = rem == 0;
        if (first) {
          pi0 = rcp(quad_sum(l0));
          pi1 = rcp(quad_sum(l1));
          l0 = l1 = b0 = b1 = 0.f;
          fl = 0;
          rem = item_m(item_of(maps, rnd)) + 1;
        }
      }
      rem--;
      g++;
      wgmma_wait<1>();
      fence_regs(s);
      mbar_arrive_if(kb + (B_KEMPTY - B_KFULL), wtid == 32);
      ST(g + 1)
      if (rem == 0 || shifted) {
        d0 = b0;
        d1 = b1;
        break;
      }
    }
  }
done:
#undef redo
#undef shifted
  wgmma_wait<0>();
  fence_regs(o);
  write_o(pi0, pi1);
  store_o(3, ST_BOX2L);
  ST(35)
  return sn;
}

constexpr int O_STAGES = 5;
constexpr int O_STAGE_BYTES = 32768;
constexpr int O_Y_OFF = 5 * 32768;
constexpr int O_X_OFF = 6 * 32768;
constexpr int O_NK = HDIM / 64;

__device__ __forceinline__ uint32_t out_stage(uint32_t st) { return ((0x43120u >> (4 * st)) & 7) * O_STAGE_BYTES; }

__device__ __forceinline__ void out_producer(const Maps& maps, uint32_t sbase, bool after_attn, bool dry) {
  const uint32_t bar = sbase + BAR_OFF;
  const uint32_t rank = blockIdx.x & 1;
  const int m_tile = maps.id[blockIdx.x][2] & 15, n_tile = maps.id[blockIdx.x][2] >> 4;
  uint32_t stage = 0, phase = 0;
#pragma unroll 1
  for (int ki = 0; ki < (dry ? 1 : O_NK); ki++) {
    const int kt = (ki & 14) * 4 + ((A_ORDER >> ((ki >> 4) * 4)) & 3) * 2 + (ki & 1);
    const uint32_t fb = bar + B_OFULL + 8 * stage, eb = bar + B_OEMPTY + 8 * stage;
    const uint32_t sa = sbase + out_stage(stage);
    if (ki < O_STAGES) {
      constexpr uint32_t LASTB = B_KEMPTY | ((B_QEMPTY + 8) << 8) | ((B_KEMPTY + 8) << 16) | (B_VEMPTY << 24);
      if (ki > 0 && after_attn) mbar_wait_sleep(bar + ((LASTB >> (8 * ki - 8)) & 255), ki == 2);
      mbar_arrive_cluster_if(eb, 0, !dry);
      mbar_arrive_cluster_if(eb, 1, !dry);
    }
    if (ki == (dry ? 0 : 32)) cnt_wait(CNT_CTX + 1, dry ? 0 : A_ITEMS);
    if (!dry) {
      mbar_wait_sleep(eb, phase);
      mbar_expect_tx(fb, O_STAGE_BYTES);
      tma_load_2d_mc(sa + 16384 + rank * 8192, &maps.ob, fb, n_tile * 128 + rank * 64, kt * 64, (uint16_t)3);
      tma_load_2d(sa, &maps.oa, fb, kt * 64, m_tile * 128);
    }
    if (++stage == O_STAGES) { stage = 0; phase ^= 1; }
  }
  if (!dry) mbar_wait_sleep(bar + B_OY, 0);
}

__device__ __forceinline__ void out_side(const Maps& maps, uint32_t smem0, const float (&gv)[4]) {
  PHASE_PROLOGUE
  const int m_tile = maps.id[blockIdx.x][2] & 15, n_tile = maps.id[blockIdx.x][2] >> 4;
  if (__shfl_sync(0xffffffffu, warp, 0) == 0) {
    if (elect_one()) {
      mbar_expect_tx(bar + B_OY, 65536);
      tma_load_2d(sbase + O_X_OFF, &maps.a[0], bar + B_OY, n_tile * 128, m_tile * 128);
      tma_load_2d(sbase + O_X_OFF + 16384, &maps.a[0], bar + B_OY, n_tile * 128 + 64, m_tile * 128);
      TD(10)
      cnt_wait(CNT_Y2, DM);
      TD(7)
      tma_load_2d(sbase + O_Y_OFF, &maps.y, bar + B_OY, m_tile * 128, n_tile * 128);
      tma_load_2d(sbase + O_Y_OFF + 16384, &maps.y, bar + B_OY, m_tile * 128 + 64, n_tile * 128);
    }
  }
  mbar_wait_sleep(bar + B_OY, 0);
  if (wtid == 0) { TD(12) }
  const int st_row = warp * 16 + (lane & 7) + ((lane >> 3) & 1) * 8;
  const int mrow = (lane & 7) + ((lane >> 4) & 1) * 8;
  const int mchunk = warp * 2 + ((lane >> 3) & 1);
  const uint32_t xrow = sbase + O_X_OFF + st_row * 128;
  const uint32_t yrow = sbase + O_Y_OFF + mrow * 128 + ((mchunk ^ (lane & 7)) << 4);
  uint32_t y[8][4], x[8][4], om[4];
#pragma unroll
  for (int i = 0; i < 4; i++) om[i] = pack_bf16(1.0f - gv[i], 1.0f - gv[i]);
  auto xa = [&](int h, int i) { return xrow + h * 8192 + (i >> 2) * 16384 + ((((i & 3) * 2 + (lane >> 4)) ^ (lane & 7)) << 4); };
  auto load = [&](int r, int h, int i) {
    ldsm4t(y[r], yrow + h * 16384 + i * 2048);
    asm volatile("ldmatrix.sync.aligned.m8n8.x4.shared.b16 {%0, %1, %2, %3}, [%4];"
                 : "=r"(x[r][0]), "=r"(x[r][1]), "=r"(x[r][2]), "=r"(x[r][3])
                 : "r"(xa(h, i)));
  };
  auto store = [&](int r, int h, int i, uint32_t om0, uint32_t om1) {
    stmatrix_x4(xa(h, i), mul_bf2(om0, mul_bf2(x[r][0], y[r][0])), mul_bf2(om1, mul_bf2(x[r][1], y[r][1])),
                mul_bf2(om0, mul_bf2(x[r][2], y[r][2])), mul_bf2(om1, mul_bf2(x[r][3], y[r][3])));
  };
#pragma unroll 1
  for (int h = 0; h < 2; h++) {
#pragma unroll
    for (int i = 0; i < 8; i++) load(i, h, i);
#pragma unroll
    for (int i = 0; i < 8; i++) store(i, h, i, h ? om[2] : om[0], h ? om[3] : om[1]);
  }
  __syncwarp();
  mbar_arrive_if(bar + B_OY + 8, lane == 0);
  if (wtid == 0) { TD(13) }
}

__device__ __forceinline__ uint32_t out_gemm(const Maps& maps, uint32_t smem0, uint32_t sn) {
  PHASE_PROLOGUE
  const int m_tile = maps.id[blockIdx.x][2] & 15, n_tile = maps.id[blockIdx.x][2] >> 4;
  float acc[2][64];
  undef_regs(acc[0]);
  undef_regs(acc[1]);
  uint32_t stage = 0, phase = 0, prev_stage = 0;
  GT(gti++)
  const float* gp = g_gate + m_tile * 128 + warp * 16 + (lane >> 2);
  const float gv[4] = {__ldcg(gp), __ldcg(gp + 8), __ldcg(gp + 64), __ldcg(gp + 72)};
  if (wg == 1) {
    out_side(maps, smem0, gv);
    return sn;
  }
#pragma unroll 1
  for (int kt = 0; kt < O_NK; kt++) {
    uint32_t da = (uint32_t)make_desc(sbase + out_stage(stage), 16, 0, 0);
    uint32_t db = (uint32_t)make_desc(sbase + out_stage(stage) + 16384, 8192, 0, 0);
    asm volatile("" : "+r"(da), "+r"(db));
    mbar_wait(bar + B_OFULL + 8 * stage, phase);
    GT(gti++)
    constexpr int OWAIT = 2;
    constexpr uint64_t DHI = DESC_SW128 | ((uint64_t)(1024 >> 4) << 32);
#pragma unroll
    for (int kk = 0; kk < 4; kk++) {
      wgmma_wait<OWAIT>();
      if (kk == OWAIT)
        mbar_arrive_cluster_if(bar + B_OEMPTY + 8 * prev_stage, wtid >> 6,
                               (wtid & 63) == 32 && kt > 0 && kt - 1 + O_STAGES < O_NK);
      wgmma_fence();
      wgmma_m64n128_ss_tb(acc[0], DHI | (da + kk * 2), DHI | (db + kk * 128), (kt | kk) != 0);
      wgmma_m64n128_ss_tb(acc[1], DHI | (da + 512 + kk * 2), DHI | (db + kk * 128), (kt | kk) != 0);
      wgmma_commit();
    }
    prev_stage = stage;
    if (++stage == O_STAGES) { stage = 0; phase ^= 1; }
  }
  if (tid == 0) { TD(14) }
  st_wait(bar, wg, sn - 1);
  const int st_row = warp * 16 + (lane & 7) + ((lane >> 3) & 1) * 8;
  const uint32_t rowa = sbase + O_X_OFF + st_row * 128;
  wgmma_wait<0>();
  fence_regs(acc[0]);
  fence_regs(acc[1]);
  GT(gti++)
  uint32_t gg[4];
#pragma unroll
  for (int i = 0; i < 4; i++) gg[i] = pack_bf16(gv[i], gv[i]);
  mbar_wait(bar + B_OY + 8, 0);
#pragma unroll
  for (int i = 0; i < 16; i++) {
    const int h = i & 1, j = i & 14;
    const uint32_t addr = rowa + h * 8192 + (j >> 3) * 16384 + ((((j & 7) + (lane >> 4)) ^ (st_row & 7)) << 4);
    uint32_t b0, b1, b2, b3;
    asm volatile("ldmatrix.sync.aligned.m8n8.x4.shared.b16 {%0, %1, %2, %3}, [%4];"
                 : "=r"(b0), "=r"(b1), "=r"(b2), "=r"(b3)
                 : "r"(addr));
    const float* a = acc[h] + 4 * j;
    const uint32_t gg0 = gg[2 * h], gg1 = gg[2 * h + 1];
    stmatrix_x4(addr, add_bf2(mul_bf2(gg0, pack_bf16(a[0], a[1])), b0),
                add_bf2(mul_bf2(gg1, pack_bf16(a[2], a[3])), b1), add_bf2(mul_bf2(gg0, pack_bf16(a[4], a[5])), b2),
                add_bf2(mul_bf2(gg1, pack_bf16(a[6], a[7])), b3));
    if (i == 7) st_post(bar, wg, wtid, sn, ST_BOX1, &maps.oc, sbase + O_X_OFF, n_tile * 128, m_tile * 128, -1);
  }
  fence_proxy_async();
  named_bar_sync(1, 128);
  if (__shfl_sync(0xffffffffu, warp, 0) == 0) {
    if (elect_one()) {
      tma_store_2d(&maps.oc, sbase + O_X_OFF + 16384, n_tile * 128 + 64, m_tile * 128);
      tma_store_commit();
    }
  }
  GT(gti++)
  return sn + 1;
}

__device__ __noinline__ void leave_kernel(int mask) {
  if (!(mask & 4)) return;
  if (atomicAdd(g_cnt + CNT_DONE * 32, 1u) == 2 * gridDim.x - 1) {
    for (int i = 0; i < CNT_N; i++) g_cnt[i * 32] = 0;
  }
}

__device__ __noinline__ void side_jobs(const Maps& maps, uint32_t sbase) {
  const int w12 = __shfl_sync(0xffffffffu, threadIdx.x >> 5, 0);
  gate_rows(maps, sbase, (blockIdx.x - 128) * 12 + w12, w12, threadIdx.x & 31);
  fence_proxy_async();
  __syncthreads();
  if (threadIdx.x == 320) cnt_signal_release(CNT_PREP, 1);
}

__global__ void __launch_bounds__(384, 1) fused_kernel(int mask, const __grid_constant__ Maps maps) {
  extern __shared__ __align__(1024) uint8_t smem_raw[];
  {
    const uint32_t sbase = __shfl_sync(0xffffffffu, smem_u32(smem_raw), 0);
    const uint32_t bar = sbase + BAR_OFF;
    const int tid = threadIdx.x;
    const bool do_qkv = (mask & 1) && blockIdx.x < 128;
    TL(0, 0)
    if (__shfl_sync(0xffffffffu, tid >> 5, 0) == 1 && do_qkv) {
      if (elect_one()) {
        for (int i = 0; i < G_STAGES; i++) mbar_init(bar + B_GFULL + 8 * i, 1);
        fence_barrier_init();
        qkv_producer(maps, sbase, true);
      }
    }
    if (tid == 0) {
      for (int i = 0; i < G_STAGES; i++) {
        mbar_init(bar + B_GEMPTY + 8 * i, 2);
        mbar_init(bar + B_SFULL + 8 * i, 4);
        mbar_init(bar + B_SFREE + 8 * i, 1);
      }
      for (int i = 0; i < 2; i++) {
        mbar_init(bar + B_OFREE + 8 * i, 1);
        mbar_init(bar + B_QFULL + 8 * i, 1);
        mbar_init(bar + B_QEMPTY + 8 * i, 2);
        mbar_init(bar + B_KFULL + 8 * i, 1);
        mbar_init(bar + B_KEMPTY + 8 * i, 2);
        mbar_init(bar + B_VFULL + 8 * i, 1);
        mbar_init(bar + B_VEMPTY + 8 * i, 2);
      }
      for (int i = 0; i < O_STAGES; i++) {
        mbar_init(bar + B_OFULL + 8 * i, 1);
        mbar_init(bar + B_OEMPTY + 8 * i, 2);
      }
      mbar_init(bar + B_OY, 1);
      mbar_init(bar + B_OY + 8, 4);
      mbar_init(bar + B_QDONE, 2);
      for (int i = 0; i < 8; i++) mbar_init(bar + B_CFULL + 8 * i, 1);
      for (int i = 0; i < CNT_N; i++) asm volatile("st.shared.u32 [%0], 0;" ::"r"(bar + B_PEND + 4 * i) : "memory");
      fence_barrier_init();
    }
    __syncthreads();
    asm volatile("barrier.cluster.arrive.relaxed.aligned;" ::: "memory");
    if ((mask & 1) && blockIdx.x >= 128) side_jobs(maps, sbase);
  }
  uint32_t smem0 = smem_u32(smem_raw);
  PHASE_PROLOGUE
  const bool do_qkv = (mask & 1) && blockIdx.x < 128, do_out = (mask & 4) && blockIdx.x < 128;
  TL(0, 1)

  if (wg != 2) {
    reg_alloc<232>();
    uint32_t sn = 0;
    float o[64];
    if (do_qkv) {
      sn = qkv_consumer(maps, smem_u32(smem_raw), mask & 2, o);
    } else {
      undef_regs(o);
    }
    TL(0, 2) TL(1, 0) TL(1, 1)
    asm volatile("barrier.cluster.wait.acquire.aligned;" ::: "memory");
    if (mask & 2) {
      sn = attn_consumer(maps, smem_u32(smem_raw), sn, o, mask & 1);
      TL(2, 0)
      if ((mask & 4) && blockIdx.x < 128 && __shfl_sync(0xffffffffu, threadIdx.x, 0) < 128) {
        named_bar_arrive(3, 256);
      } else {
        const uint32_t b2 = blockIdx.x * 2 + (threadIdx.x >> 7);
        const bool fused = mask & 4, mainc = blockIdx.x < 128;
        const uint32_t first = __shfl_sync(0xffffffffu, !fused ? b2 : mainc ? conv_first(maps) : (b2 - 256) * 128, 0);
        conv_consumer(maps, smem_u32(smem_raw), first, !fused ? 264 : mainc ? 16 : 1,
                      !fused ? DM : mainc ? (first | 127) + 1 : first + C_SIDE, fused && !mainc);
      }
      TL(1, 2) TL(2, 1) TL(2, 2)
    }
    TL(3, 0) TL(3, 1)
    if ((mask & 4) && blockIdx.x < 128) sn = out_gemm(maps, smem_u32(smem_raw), sn);
    {
      uint32_t smem0 = smem_u32(smem_raw);
      PHASE_PROLOGUE
      st_wait(bar, wg, sn - 2);
      st_post(bar, wg, wtid, sn, ST_END, nullptr, 0, 0, 0, -1);
      tma_store_wait_read<0>();
    }
  } else {
    reg_dealloc<40>();
    asm volatile("barrier.cluster.wait.acquire.aligned;" ::: "memory");
    const int w = __shfl_sync(0xffffffffu, tid >> 5, 0) - 8;
    if (w < 2) {
      if (do_qkv) prep_agent(maps, sbase, w, lane);
      if (elect_one()) store_agent(bar, w);
      TL2(3, 2)
    } else {
      if (elect_one()) {
        const bool dry = w == 2;
        if (do_qkv && !dry) qkv_producer(maps, sbase, false);
        if (mask & 2) attn_producer(maps, sbase, do_qkv, do_out, dry);
        if (do_out) out_producer(maps, sbase, mask & 2, dry);
        if (dry) { TD(5) }
      }
      __syncwarp();
      if (w == 2) publisher(bar, tid & 31, !(mask & 2) ? 2 : do_out ? 3 : 4);
      if ((tid & 31) == 0) leave_kernel(mask);
    }
  }
}

typedef CUresult (*PFN_tmapEncode)(CUtensorMap*, CUtensorMapDataType, cuuint32_t, void*, const cuuint64_t*,
                                   const cuuint64_t*, const cuuint32_t*, const cuuint32_t*, CUtensorMapInterleave,
                                   CUtensorMapSwizzle, CUtensorMapL2promotion, CUtensorMapFloatOOBfill);
static PFN_tmapEncode s_encode = nullptr;

static void make_map_2d(CUtensorMap* m, const void* ptr, int rows, int cols, int box_rows) {
  cuuint64_t dims[2] = {(cuuint64_t)cols, (cuuint64_t)rows};
  cuuint64_t strides[1] = {(cuuint64_t)cols * 2};
  cuuint32_t box[2] = {cols < 64 ? 32u : 64u, (cuuint32_t)box_rows};
  cuuint32_t es[2] = {1, 1};
  s_encode(m, CU_TENSOR_MAP_DATA_TYPE_BFLOAT16, 2, const_cast<void*>(ptr), dims, strides, box, es,
           CU_TENSOR_MAP_INTERLEAVE_NONE, cols < 64 ? CU_TENSOR_MAP_SWIZZLE_64B : CU_TENSOR_MAP_SWIZZLE_128B, CU_TENSOR_MAP_L2_PROMOTION_L2_256B,
           CU_TENSOR_MAP_FLOAT_OOB_FILL_NONE);
}
static void make_map_3d(CUtensorMap* m, const void* ptr, int rows, int cols, int box_rows, int box_chunks) {
  cuuint64_t dims[3] = {64, (cuuint64_t)rows, (cuuint64_t)(cols / 64)};
  cuuint64_t strides[2] = {(cuuint64_t)cols * 2, 128};
  cuuint32_t box[3] = {64, (cuuint32_t)box_rows, (cuuint32_t)box_chunks};
  cuuint32_t es[3] = {1, 1, 1};
  s_encode(m, CU_TENSOR_MAP_DATA_TYPE_BFLOAT16, 3, const_cast<void*>(ptr), dims, strides, box, es,
           CU_TENSOR_MAP_INTERLEAVE_NONE, CU_TENSOR_MAP_SWIZZLE_128B, CU_TENSOR_MAP_L2_PROMOTION_L2_256B,
           CU_TENSOR_MAP_FLOAT_OOB_FILL_NONE);
}

static cudaLaunchConfig_t fused_cfg(cudaLaunchAttribute* at) {
  cudaLaunchConfig_t cfg = {};
  cfg.gridDim = dim3(132);
  cfg.blockDim = dim3(384);
  cfg.dynamicSmemBytes = SMEM_BYTES;
  cfg.stream = cudaStreamPerThread;
  at[0].id = cudaLaunchAttributeClusterDimension;
  at[0].val.clusterDim.x = 2;
  at[0].val.clusterDim.y = 1;
  at[0].val.clusterDim.z = 1;
  cfg.attrs = at;
  cfg.numAttrs = 1;
  return cfg;
}

extern "C" void kernel_launch(void* const* d_in, const int* in_sizes, int n_in, void* d_out, int out_size) {
  const bf16* x = (const bf16*)d_in[0];
  const bf16* ckv = (const bf16*)d_in[1];
  const bf16* wq = (const bf16*)d_in[2];
  const bf16* wuk = (const bf16*)d_in[3];
  const bf16* wuv = (const bf16*)d_in[4];
  const bf16* wo = (const bf16*)d_in[5];
  const bf16* bk = (const bf16*)d_in[7];
  const bf16* bv = (const bf16*)d_in[8];
  const bf16* shift_k = (const bf16*)d_in[9];
  const bf16* ssm_k = (const bf16*)d_in[10];
  const bf16* ssm_D = (const bf16*)d_in[11];
  const bf16* gate_w = (const bf16*)d_in[12];
  bf16* out = (bf16*)d_out;

  static void *pq = nullptr, *pk = nullptr, *pv = nullptr, *pctx = nullptr, *pb = nullptr, *pu = nullptr;
  static int max_clusters = 0;
  if (!s_encode) {
    void* fn = nullptr;
    cudaDriverEntryPointQueryResult qres;
    cudaGetDriverEntryPoint("cuTensorMapEncodeTiled", &fn, cudaEnableDefault, &qres);
    s_encode = (PFN_tmapEncode)fn;
    cudaGetSymbolAddress(&pq, g_q);
    cudaGetSymbolAddress(&pk, g_k);
    cudaGetSymbolAddress(&pv, g_v);
    cudaGetSymbolAddress(&pctx, g_ctx);
    cudaGetSymbolAddress(&pb, g_y2T);
    cudaGetSymbolAddress(&pu, g_kvT);
    cudaFuncSetAttribute(fused_kernel, cudaFuncAttributeMaxDynamicSharedMemorySize, SMEM_BYTES);
    cudaLaunchAttribute at[1];
    cudaLaunchConfig_t cfg = fused_cfg(at);
    if (cudaOccupancyMaxActiveClusters(&max_clusters, fused_kernel, &cfg) != cudaSuccess) max_clusters = 0;
  }

  Maps all = {};
  make_map_2d(&all.a[0], x, S_LEN, DM, 128);
  make_map_2d(&all.a[1], ckv, S_LEN, DC, 128);
  make_map_3d(&all.b[0], wq, DM, HDIM, 64, 4);
  make_map_3d(&all.b[1], wuk, DC, HDIM, 64, 4);
  make_map_3d(&all.b[2], wuv, DC, HDIM, 64, 4);
  make_map_2d(&all.c[0], pq, S_LEN, HDIM, 64);
  make_map_2d(&all.c[1], pk, S_LEN, HDIM, 64);
  make_map_2d(&all.c[2], pv, S_LEN, HDIM, 64);
  make_map_3d(&all.q, pq, S_LEN, HDIM, 128, 2);
  make_map_3d(&all.k, pk, S_LEN, HDIM, 128, 2);
  make_map_3d(&all.v, pv, S_LEN, HDIM, 128, 2);
  make_map_2d(&all.o, pctx, S_LEN, HDIM, 64);
  all.ssm_k = ssm_k;
  all.ssm_D = ssm_D;
  make_map_2d(&all.oa, pctx, S_LEN, HDIM, 128);
  make_map_2d(&all.ob, wo, HDIM, DM, 64);
  make_map_2d(&all.oc, out, S_LEN, DM, 128);
  make_map_2d(&all.y, pb, DM, S_LEN, 128);
  make_map_2d(&all.cu, pu, DM * 64, 32, 64);
  make_map_2d(&all.ch, ssm_k, DM * 64, 32, 64);

  make_map_2d(&all.bk, bk, S_LEN, DM, 35);
  make_map_2d(&all.bv, bv, S_LEN, DM, 32);
  for (int b = 0; b < 128; b++) {
    const int c = b >> 1, r = b & 1;
    const int G = c < 4 ? 0 : c < 36 ? (c - 4) % 8 : 1 + (c - 36) % 7;
    const int i = c < 4 ? 4 + c : c < 36 ? (c - 4) / 8 : 4 + (c - 36) / 7;
    all.id[b][0] = r + 2 * (i & 1) + 4 * (G & 3) + 16 * (i >> 1) + 64 * (G >> 2);
    all.id[b][1] = r + 2 * i + 16 * G;
    all.id[b][2] = r + 2 * G + 16 * i;
  }
  all.shift_k = shift_k;
  all.x = x;
  all.gate_w = gate_w;
  cudaLaunchAttribute at[1];
  cudaLaunchConfig_t cfg = fused_cfg(at);
  if (max_clusters >= 66) {
    cudaLaunchKernelEx(&cfg, fused_kernel, 7, all);
  } else {
    for (int m = 1; m <= 4; m <<= 1) cudaLaunchKernelEx(&cfg, fused_kernel, m, all);
  }
}
```

```cpp
#include <cuda_runtime.h>
#include <cuda_bf16.h>
#include <cuda.h>
#include <stdint.h>

typedef __nv_bfloat16 bf16;
#define INPLACE 3

constexpr int S_LEN = 2048;
constexpr int DM = 1024;
constexpr int NH = 32;
constexpr int HD = 128;
constexpr int DC = 512;
constexpr int HDIM = NH * HD;

__device__ __align__(1024) bf16 g_q[S_LEN * HDIM];
__device__ __align__(1024) bf16 g_k[S_LEN * HDIM];
__device__ __align__(1024) bf16 g_v[S_LEN * HDIM];
#define g_ctx g_q
__device__ __align__(1024) bf16 g_kvT[DM * S_LEN];
#define g_y2T g_kvT
__device__ __align__(1024) float g_gate[S_LEN];
enum { CNT_KV = 0, CNT_PREP = CNT_KV + 2, CNT_CTX, CNT_Y2 = CNT_CTX + 2, CNT_DONE, CNT_N };
__device__ unsigned int g_cnt[CNT_N * 32];

#define TL(k, i)
#define TL2(k, i)
#define TD(i)
#define CT(i)
#define GT(i)
#define GA(i)
#define ST(i)

__device__ __forceinline__ uint32_t smem_u32(const void* p) { return (uint32_t)__cvta_generic_to_shared(p); }

__device__ __forceinline__ void mbar_init(uint32_t bar, uint32_t count) {
  asm volatile("mbarrier.init.shared::cta.b64 [%0], %1;" ::"r"(bar), "r"(count));
}
__device__ __forceinline__ void mbar_expect_tx(uint32_t bar, uint32_t bytes) {
  asm volatile("mbarrier.arrive.expect_tx.shared::cta.b64 _, [%0], %1;" ::"r"(bar), "r"(bytes) : "memory");
}
__device__ __forceinline__ void mbar_arrive(uint32_t bar) {
  asm volatile("mbarrier.arrive.shared::cta.b64 _, [%0];" ::"r"(bar) : "memory");
}
__device__ __forceinline__ void mbar_wait(uint32_t bar, uint32_t parity) {
  uint32_t done;
  uint32_t spins = 0;
  do {
    asm volatile(
        "{\n.reg .pred p;\n"
        "mbarrier.try_wait.parity.shared::cta.b64 p, [%1], %2;\n"
        "selp.u32 %0, 1, 0, p;\n}\n"
        : "=r"(done)
        : "r"(bar), "r"(parity)
        : "memory");
    if (++spins > (1u << 22)) break;
  } while (!done);
}
__device__ __forceinline__ bool mbar_try(uint32_t bar, uint32_t parity) {
  uint32_t done;
  asm volatile(
      "{\n.reg .pred p;\n"
      "mbarrier.try_wait.parity.shared::cta.b64 p, [%1], %2;\n"
      "selp.u32 %0, 1, 0, p;\n}\n"
      : "=r"(done)
      : "r"(bar), "r"(parity)
      : "memory");
  return done != 0;
}
__device__ __forceinline__ bool elect_one() {
  uint32_t pred;
  asm volatile("{\n.reg .pred p;\nelect.sync _|p, 0xffffffff;\nselp.u32 %0, 1, 0, p;\n}\n" : "=r"(pred));
  return pred != 0;
}
__device__ __forceinline__ void mbar_arrive_if(uint32_t bar, bool pred) {
  asm volatile(
      "{\n.reg .pred p;\nsetp.ne.b32 p, %1, 0;\n"
      "@p mbarrier.arrive.shared::cta.b64 _, [%0];\n}\n" ::"r"(bar),
      "r"((uint32_t)pred)
      : "memory");
}
__device__ __forceinline__ void mbar_wait_sleep(uint32_t bar, uint32_t parity) {
  uint32_t done;
  uint32_t spins = 0;
  do {
    asm volatile(
        "{\n.reg .pred p;\n"
        "mbarrier.try_wait.parity.shared::cta.b64 p, [%1], %2, %3;\n"
        "selp.u32 %0, 1, 0, p;\n}\n"
        : "=r"(done)
        : "r"(bar), "r"(parity), "r"(20000u)
        : "memory");
    if (++spins > (1u << 16)) break;
  } while (!done);
}
__device__ __forceinline__ void fence_barrier_init() {
  asm volatile("fence.mbarrier_init.release.cluster;" ::: "memory");
}
__device__ __forceinline__ void fence_proxy_async() {
  asm volatile("fence.proxy.async.shared::cta;" ::: "memory");
}
__device__ __forceinline__ void named_bar_sync(int id, int nthreads) {
  asm volatile("bar.sync %0, %1;" ::"r"(id), "r"(nthreads) : "memory");
}
__device__ __forceinline__ void named_bar_arrive(int id, int nthreads) {
  asm volatile("bar.arrive %0, %1;" ::"r"(id), "r"(nthreads) : "memory");
}
__device__ __forceinline__ void tma_load_2d(uint32_t dst, const CUtensorMap* m, uint32_t bar, int c0, int c1) {
  asm volatile(
      "cp.async.bulk.tensor.2d.shared::cluster.global.mbarrier::complete_tx::bytes [%0], [%1, {%3, %4}], [%2];" ::"r"(dst),
      "l"(reinterpret_cast<uint64_t>(m)), "r"(bar), "r"(c0), "r"(c1)
      : "memory");
}
__device__ __forceinline__ void tma_load_3d(uint32_t dst, const CUtensorMap* m, uint32_t bar, int c0, int c1, int c2) {
  asm volatile(
      "cp.async.bulk.tensor.3d.shared::cluster.global.mbarrier::complete_tx::bytes [%0], [%1, {%3, %4, %5}], [%2];" ::"r"(dst),
      "l"(reinterpret_cast<uint64_t>(m)), "r"(bar), "r"(c0), "r"(c1), "r"(c2)
      : "memory");
}
__device__ __forceinline__ void tma_store_2d(const CUtensorMap* m, uint32_t src, int c0, int c1) {
  asm volatile("cp.async.bulk.tensor.2d.global.shared::cta.bulk_group [%0, {%2, %3}], [%1];" ::"l"(
                   reinterpret_cast<uint64_t>(m)),
               "r"(src), "r"(c0), "r"(c1)
               : "memory");
}
__device__ __forceinline__ void bulk_load(uint32_t dst, const void* src, uint32_t bytes, uint32_t bar) {
  asm volatile("cp.async.bulk.shared::cluster.global.mbarrier::complete_tx::bytes [%0], [%1], %2, [%3];" ::"r"(dst),
               "l"(src), "r"(bytes), "r"(bar)
               : "memory");
}
__device__ __forceinline__ void tma_load_2d_mc(uint32_t dst, const CUtensorMap* m, uint32_t bar, int c0, int c1,
                                               uint16_t mask) {
  asm volatile(
      "cp.async.bulk.tensor.2d.shared::cluster.global.mbarrier::complete_tx::bytes.multicast::cluster [%0], [%1, {%3, "
      "%4}], [%2], %5;" ::"r"(dst),
      "l"(reinterpret_cast<uint64_t>(m)), "r"(bar), "r"(c0), "r"(c1), "h"(mask)
      : "memory");
}
__device__ __forceinline__ void mbar_arrive_cluster_if(uint32_t bar, uint32_t cta, bool pred) {
  asm volatile(
      "{\n.reg .b32 ra;\n.reg .pred p;\nsetp.ne.b32 p, %2, 0;\n"
      "mapa.shared::cluster.u32 ra, %0, %1;\n"
      "@p mbarrier.arrive.shared::cluster.b64 _, [ra];\n}\n" ::"r"(bar),
      "r"(cta), "r"((uint32_t)pred)
      : "memory");
}
__device__ __forceinline__ uint64_t policy_evict_first() {
  uint64_t pol;
  asm volatile("createpolicy.fractional.L2::evict_first.b64 %0, 1.0;" : "=l"(pol));
  return pol;
}
__device__ __forceinline__ void tma_load_2d_hint(uint32_t dst, const CUtensorMap* m, uint32_t bar, int c0, int c1,
                                                 uint64_t pol) {
  asm volatile(
      "cp.async.bulk.tensor.2d.shared::cluster.global.mbarrier::complete_tx::bytes.L2::cache_hint [%0], [%1, {%3, %4}], "
      "[%2], %5;" ::"r"(dst),
      "l"(reinterpret_cast<uint64_t>(m)), "r"(bar), "r"(c0), "r"(c1), "l"(pol)
      : "memory");
}
__device__ __forceinline__ void tma_load_3d_hint(uint32_t dst, const CUtensorMap* m, uint32_t bar, int c0, int c1,
                                                 int c2, uint64_t pol) {
  asm volatile(
      "cp.async.bulk.tensor.3d.shared::cluster.global.mbarrier::complete_tx::bytes.L2::cache_hint [%0], [%1, {%3, %4, "
      "%5}], [%2], %6;" ::"r"(dst),
      "l"(reinterpret_cast<uint64_t>(m)), "r"(bar), "r"(c0), "r"(c1), "r"(c2), "l"(pol)
      : "memory");
}
__device__ __forceinline__ void bulk_load_hint(uint32_t dst, const void* src, uint32_t bytes, uint32_t bar, uint64_t pol) {
  asm volatile(
      "cp.async.bulk.shared::cluster.global.mbarrier::complete_tx::bytes.L2::cache_hint [%0], [%1], %2, [%3], %4;" ::"r"(dst),
      "l"(src), "r"(bytes), "r"(bar), "l"(pol)
      : "memory");
}
__device__ __forceinline__ void cnt_signal_release(int which, uint32_t n) {
  asm volatile("red.release.gpu.global.add.u32 [%0], %1;" ::"l"(g_cnt + which * 32), "r"(n) : "memory");
}
__device__ __forceinline__ void cnt_wait(int which, uint32_t target) {
  uint32_t v, spins = 0;
  while (true) {
    asm volatile("ld.acquire.gpu.global.u32 %0, [%1];" : "=r"(v) : "l"(g_cnt + which * 32) : "memory");
    if (v >= target || ++spins > (1u << 18)) break;
    __nanosleep(64);
  }
  asm volatile("fence.proxy.async.global;" ::: "memory");
}
__device__ __forceinline__ void tma_store_commit() { asm volatile("cp.async.bulk.commit_group;" ::: "memory"); }
template <int N>
__device__ __forceinline__ void tma_store_wait_read() {
  asm volatile("cp.async.bulk.wait_group.read %0;" ::"n"(N) : "memory");
}
template <int N>
__device__ __forceinline__ void tma_store_wait() {
  asm volatile("cp.async.bulk.wait_group %0;" ::"n"(N) : "memory");
}
__device__ __forceinline__ void wgmma_fence() { asm volatile("wgmma.fence.sync.aligned;" ::: "memory"); }
__device__ __forceinline__ void wgmma_commit() { asm volatile("wgmma.commit_group.sync.aligned;" ::: "memory"); }
template <int N>
__device__ __forceinline__ void wgmma_wait() {
  asm volatile("wgmma.wait_group.sync.aligned %0;" ::"n"(N) : "memory");
}
template <int R>
__device__ __forceinline__ void reg_alloc() { asm volatile("setmaxnreg.inc.sync.aligned.u32 %0;" ::"n"(R)); }
template <int R>
__device__ __forceinline__ void reg_dealloc() { asm volatile("setmaxnreg.dec.sync.aligned.u32 %0;" ::"n"(R)); }

__device__ __forceinline__ void stmatrix_x4(uint32_t addr, uint32_t r0, uint32_t r1, uint32_t r2, uint32_t r3) {
  asm volatile("stmatrix.sync.aligned.m8n8.x4.shared.b16 [%0], {%1, %2, %3, %4};" ::"r"(addr), "r"(r0), "r"(r1),
               "r"(r2), "r"(r3)
               : "memory");
}
__device__ __forceinline__ uint32_t pack_bf16(float lo, float hi) {
  uint32_t r;
  asm("cvt.rn.bf16x2.f32 %0, %1, %2;" : "=r"(r) : "f"(hi), "f"(lo));
  return r;
}
__device__ __forceinline__ float bf16_round(float x) { return __bfloat162float(__float2bfloat16_rn(x)); }
__device__ __forceinline__ float bf_lo(uint32_t v) { return __uint_as_float(v << 16); }
__device__ __forceinline__ float bf_hi(uint32_t v) { return __uint_as_float(v & 0xffff0000u); }
__device__ __forceinline__ uint4 lds128(uint32_t a) {
  uint4 v;
  asm volatile("ld.shared.v4.u32 {%0, %1, %2, %3}, [%4];" : "=r"(v.x), "=r"(v.y), "=r"(v.z), "=r"(v.w) : "r"(a));
  return v;
}
__device__ __forceinline__ void sts128(uint32_t a, uint4 v) {
  asm volatile("st.shared.v4.u32 [%0], {%1, %2, %3, %4};" ::"r"(a), "r"(v.x), "r"(v.y), "r"(v.z), "r"(v.w) : "memory");
}
__device__ __forceinline__ uint32_t mul_bf2(uint32_t a, uint32_t b) {
  uint32_t r;
  asm("mul.rn.bf16x2 %0, %1, %2;" : "=r"(r) : "r"(a), "r"(b));
  return r;
}
__device__ __forceinline__ uint32_t add_bf2(uint32_t a, uint32_t b) {
  uint32_t r;
  asm("add.rn.bf16x2 %0, %1, %2;" : "=r"(r) : "r"(a), "r"(b));
  return r;
}
__device__ __forceinline__ float ex2(float x) {
  float y;
  asm("ex2.approx.ftz.f32 %0, %1;" : "=f"(y) : "f"(x));
  return y;
}
__device__ __forceinline__ float rcp(float x) {
  float y;
  asm("rcp.approx.ftz.f32 %0, %1;" : "=f"(y) : "f"(x));
  return y;
}
template <int N>
__device__ __forceinline__ void fence_regs(float (&r)[N]) {
#pragma unroll
  for (int i = 0; i < N; i++) asm volatile("" : "+f"(r[i])::"memory");
}

template <int N>
__device__ __forceinline__ void undef_regs(float (&r)[N]) {
#pragma unroll
  for (int i = 0; i < N; i++) asm volatile("" : "=f"(r[i]));
}
template <int N>
__device__ __forceinline__ void fence_regs_u(uint32_t (&r)[N]) {
#pragma unroll
  for (int i = 0; i < N; i++) asm volatile("" : "+r"(r[i])::"memory");
}

constexpr uint64_t DESC_SW128 = 1ull << 62;
__device__ __forceinline__ uint64_t make_desc(uint32_t addr, uint32_t lbo_bytes, uint32_t sbo_bytes, uint64_t swz) {
  return (uint64_t)((addr & 0x3FFFF) >> 4) | ((uint64_t)((lbo_bytes & 0x3FFFF) >> 4) << 16) |
         ((uint64_t)((sbo_bytes & 0x3FFFF) >> 4) << 32) | swz;
}

__device__ __forceinline__ uint64_t desc_add(uint64_t d, uint32_t off16) {
  return (d & 0xFFFFFFFF00000000ull) | (uint64_t)((uint32_t)d + off16);
}

__device__ __forceinline__ void wgmma_m64n256_ss_tb(float (&d)[128], uint64_t da, uint64_t db, int sd) {
  asm volatile(
    "{\n.reg .pred p;\nsetp.ne.b32 p, %130, 0;\n"
    "wgmma.mma_async.sync.aligned.m64n256k16.f32.bf16.bf16 "
    "{%0, %1, %2, %3, %4, %5, %6, %7, %8, %9, %10, %11, %12, %13, %14, %15, %16, %17, %18, %19, %20, %21, %22, %23, %24, %25, %26, %27, %28, %29, %30, %31, %32, %33, %34, %35, %36, %37, %38, %39, %40, %41, %42, %43, %44, %45, %46, %47, %48, %49, %50, %51, %52, %53, %54, %55, %56, %57, %58, %59, %60, %61, %62, %63, %64, %65, %66, %67, %68, %69, %70, %71, %72, %73, %74, %75, %76, %77, %78, %79, %80, %81, %82, %83, %84, %85, %86, %87, %88, %89, %90, %91, %92, %93, %94, %95, %96, %97, %98, %99, %100, %101, %102, %103, %104, %105, %106, %107, %108, %109, %110, %111, %112, %113, %114, %115, %116, %117, %118, %119, %120, %121, %122, %123, %124, %125, %126, %127}, %128, %129, p, 1, 1, 0, 1;\n}\n"
    : "+f"(d[0]), "+f"(d[1]), "+f"(d[2]), "+f"(d[3]), "+f"(d[4]), "+f"(d[5]), "+f"(d[6]), "+f"(d[7]), "+f"(d[8]), "+f"(d[9]), "+f"(d[10]), "+f"(d[11]), "+f"(d[12]), "+f"(d[13]), "+f"(d[14]), "+f"(d[15]), "+f"(d[16]), "+f"(d[17]), "+f"(d[18]), "+f"(d[19]), "+f"(d[20]), "+f"(d[21]), "+f"(d[22]), "+f"(d[23]), "+f"(d[24]), "+f"(d[25]), "+f"(d[26]), "+f"(d[27]), "+f"(d[28]), "+f"(d[29]), "+f"(d[30]), "+f"(d[31]), "+f"(d[32]), "+f"(d[33]), "+f"(d[34]), "+f"(d[35]), "+f"(d[36]), "+f"(d[37]), "+f"(d[38]), "+f"(d[39]), "+f"(d[40]), "+f"(d[41]), "+f"(d[42]), "+f"(d[43]), "+f"(d[44]), "+f"(d[45]), "+f"(d[46]), "+f"(d[47]), "+f"(d[48]), "+f"(d[49]), "+f"(d[50]), "+f"(d[51]), "+f"(d[52]), "+f"(d[53]), "+f"(d[54]), "+f"(d[55]), "+f"(d[56]), "+f"(d[57]), "+f"(d[58]), "+f"(d[59]), "+f"(d[60]), "+f"(d[61]), "+f"(d[62]), "+f"(d[63]), "+f"(d[64]), "+f"(d[65]), "+f"(d[66]), "+f"(d[67]), "+f"(d[68]), "+f"(d[69]), "+f"(d[70]), "+f"(d[71]), "+f"(d[72]), "+f"(d[73]), "+f"(d[74]), "+f"(d[75]), "+f"(d[76]), "+f"(d[77]), "+f"(d[78]), "+f"(d[79]), "+f"(d[80]), "+f"(d[81]), "+f"(d[82]), "+f"(d[83]), "+f"(d[84]), "+f"(d[85]), "+f"(d[86]), "+f"(d[87]), "+f"(d[88]), "+f"(d[89]), "+f"(d[90]), "+f"(d[91]), "+f"(d[92]), "+f"(d[93]), "+f"(d[94]), "+f"(d[95]), "+f"(d[96]), "+f"(d[97]), "+f"(d[98]), "+f"(d[99]), "+f"(d[100]), "+f"(d[101]), "+f"(d[102]), "+f"(d[103]), "+f"(d[104]), "+f"(d[105]), "+f"(d[106]), "+f"(d[107]), "+f"(d[108]), "+f"(d[109]), "+f"(d[110]), "+f"(d[111]), "+f"(d[112]), "+f"(d[113]), "+f"(d[114]), "+f"(d[115]), "+f"(d[116]), "+f"(d[117]), "+f"(d[118]), "+f"(d[119]), "+f"(d[120]), "+f"(d[121]), "+f"(d[122]), "+f"(d[123]), "+f"(d[124]), "+f"(d[125]), "+f"(d[126]), "+f"(d[127])
    : "l"(da), "l"(db), "r"(sd));
}

__device__ __forceinline__ void wgmma_m64n128_ss(float (&d)[64], uint64_t da, uint64_t db, int sd) {
  asm volatile(
    "{\n.reg .pred p;\nsetp.ne.b32 p, %66, 0;\n"
    "wgmma.mma_async.sync.aligned.m64n128k16.f32.bf16.bf16 "
    "{%0, %1, %2, %3, %4, %5, %6, %7, %8, %9, %10, %11, %12, %13, %14, %15, %16, %17, %18, %19, %20, %21, %22, %23, %24, %25, %26, %27, %28, %29, %30, %31, %32, %33, %34, %35, %36, %37, %38, %39, %40, %41, %42, %43, %44, %45, %46, %47, %48, %49, %50, %51, %52, %53, %54, %55, %56, %57, %58, %59, %60, %61, %62, %63}, %64, %65, p, 1, 1, 0, 0;\n}\n"
    : "+f"(d[0]), "+f"(d[1]), "+f"(d[2]), "+f"(d[3]), "+f"(d[4]), "+f"(d[5]), "+f"(d[6]), "+f"(d[7]), "+f"(d[8]), "+f"(d[9]), "+f"(d[10]), "+f"(d[11]), "+f"(d[12]), "+f"(d[13]), "+f"(d[14]), "+f"(d[15]), "+f"(d[16]), "+f"(d[17]), "+f"(d[18]), "+f"(d[19]), "+f"(d[20]), "+f"(d[21]), "+f"(d[22]), "+f"(d[23]), "+f"(d[24]), "+f"(d[25]), "+f"(d[26]), "+f"(d[27]), "+f"(d[28]), "+f"(d[29]), "+f"(d[30]), "+f"(d[31]), "+f"(d[32]), "+f"(d[33]), "+f"(d[34]), "+f"(d[35]), "+f"(d[36]), "+f"(d[37]), "+f"(d[38]), "+f"(d[39]), "+f"(d[40]), "+f"(d[41]), "+f"(d[42]), "+f"(d[43]), "+f"(d[44]), "+f"(d[45]), "+f"(d[46]), "+f"(d[47]), "+f"(d[48]), "+f"(d[49]), "+f"(d[50]), "+f"(d[51]), "+f"(d[52]), "+f"(d[53]), "+f"(d[54]), "+f"(d[55]), "+f"(d[56]), "+f"(d[57]), "+f"(d[58]), "+f"(d[59]), "+f"(d[60]), "+f"(d[61]), "+f"(d[62]), "+f"(d[63])
    : "l"(da), "l"(db), "r"(sd));
}

__device__ __forceinline__ void wgmma_m64n128_ss_tb(float (&d)[64], uint64_t da, uint64_t db, int sd) {
  asm volatile(
    "{\n.reg .pred p;\nsetp.ne.b32 p, %66, 0;\n"
    "wgmma.mma_async.sync.aligned.m64n128k16.f32.bf16.bf16 "
    "{%0, %1, %2, %3, %4, %5, %6, %7, %8, %9, %10, %11, %12, %13, %14, %15, %16, %17, %18, %19, %20, %21, %22, %23, %24, %25, %26, %27, %28, %29, %30, %31, %32, %33, %34, %35, %36, %37, %38, %39, %40, %41, %42, %43, %44, %45, %46, %47, %48, %49, %50, %51, %52, %53, %54, %55, %56, %57, %58, %59, %60, %61, %62, %63}, %64, %65, p, 1, 1, 0, 1;\n}\n"
    : "+f"(d[0]), "+f"(d[1]), "+f"(d[2]), "+f"(d[3]), "+f"(d[4]), "+f"(d[5]), "+f"(d[6]), "+f"(d[7]), "+f"(d[8]), "+f"(d[9]), "+f"(d[10]), "+f"(d[11]), "+f"(d[12]), "+f"(d[13]), "+f"(d[14]), "+f"(d[15]), "+f"(d[16]), "+f"(d[17]), "+f"(d[18]), "+f"(d[19]), "+f"(d[20]), "+f"(d[21]), "+f"(d[22]), "+f"(d[23]), "+f"(d[24]), "+f"(d[25]), "+f"(d[26]), "+f"(d[27]), "+f"(d[28]), "+f"(d[29]), "+f"(d[30]), "+f"(d[31]), "+f"(d[32]), "+f"(d[33]), "+f"(d[34]), "+f"(d[35]), "+f"(d[36]), "+f"(d[37]), "+f"(d[38]), "+f"(d[39]), "+f"(d[40]), "+f"(d[41]), "+f"(d[42]), "+f"(d[43]), "+f"(d[44]), "+f"(d[45]), "+f"(d[46]), "+f"(d[47]), "+f"(d[48]), "+f"(d[49]), "+f"(d[50]), "+f"(d[51]), "+f"(d[52]), "+f"(d[53]), "+f"(d[54]), "+f"(d[55]), "+f"(d[56]), "+f"(d[57]), "+f"(d[58]), "+f"(d[59]), "+f"(d[60]), "+f"(d[61]), "+f"(d[62]), "+f"(d[63])
    : "l"(da), "l"(db), "r"(sd));
}

__device__ __forceinline__ void wgmma_m64n128_rs_tb(float* d, uint32_t a0, uint32_t a1, uint32_t a2, uint32_t a3, uint64_t db, int sd) {
  asm volatile(
    "{\n.reg .pred p;\nsetp.ne.b32 p, %69, 0;\n"
    "wgmma.mma_async.sync.aligned.m64n128k16.f32.bf16.bf16 "
    "{%0, %1, %2, %3, %4, %5, %6, %7, %8, %9, %10, %11, %12, %13, %14, %15, %16, %17, %18, %19, %20, %21, %22, %23, %24, %25, %26, %27, %28, %29, %30, %31, %32, %33, %34, %35, %36, %37, %38, %39, %40, %41, %42, %43, %44, %45, %46, %47, %48, %49, %50, %51, %52, %53, %54, %55, %56, %57, %58, %59, %60, %61, %62, %63}, {%64, %65, %66, %67}, %68, p, 1, 1, 1;\n}\n"
    : "+f"(d[0]), "+f"(d[1]), "+f"(d[2]), "+f"(d[3]), "+f"(d[4]), "+f"(d[5]), "+f"(d[6]), "+f"(d[7]), "+f"(d[8]), "+f"(d[9]), "+f"(d[10]), "+f"(d[11]), "+f"(d[12]), "+f"(d[13]), "+f"(d[14]), "+f"(d[15]), "+f"(d[16]), "+f"(d[17]), "+f"(d[18]), "+f"(d[19]), "+f"(d[20]), "+f"(d[21]), "+f"(d[22]), "+f"(d[23]), "+f"(d[24]), "+f"(d[25]), "+f"(d[26]), "+f"(d[27]), "+f"(d[28]), "+f"(d[29]), "+f"(d[30]), "+f"(d[31]), "+f"(d[32]), "+f"(d[33]), "+f"(d[34]), "+f"(d[35]), "+f"(d[36]), "+f"(d[37]), "+f"(d[38]), "+f"(d[39]), "+f"(d[40]), "+f"(d[41]), "+f"(d[42]), "+f"(d[43]), "+f"(d[44]), "+f"(d[45]), "+f"(d[46]), "+f"(d[47]), "+f"(d[48]), "+f"(d[49]), "+f"(d[50]), "+f"(d[51]), "+f"(d[52]), "+f"(d[53]), "+f"(d[54]), "+f"(d[55]), "+f"(d[56]), "+f"(d[57]), "+f"(d[58]), "+f"(d[59]), "+f"(d[60]), "+f"(d[61]), "+f"(d[62]), "+f"(d[63])
    : "r"(a0), "r"(a1), "r"(a2), "r"(a3), "l"(db), "r"(sd));
}

__device__ __forceinline__ void wgmma_m64n64_rs_tb(float (&d)[32], const uint32_t (&a)[4], uint64_t db, int sd) {
  asm volatile(
    "{\n.reg .pred p;\nsetp.ne.b32 p, %37, 0;\n"
    "wgmma.mma_async.sync.aligned.m64n64k16.f32.bf16.bf16 "
    "{%0, %1, %2, %3, %4, %5, %6, %7, %8, %9, %10, %11, %12, %13, %14, %15, %16, %17, %18, %19, %20, %21, %22, %23, %24, %25, %26, %27, %28, %29, %30, %31}, {%32, %33, %34, %35}, %36, p, 1, 1, 1;\n}\n"
    : "+f"(d[0]), "+f"(d[1]), "+f"(d[2]), "+f"(d[3]), "+f"(d[4]), "+f"(d[5]), "+f"(d[6]), "+f"(d[7]), "+f"(d[8]), "+f"(d[9]), "+f"(d[10]), "+f"(d[11]), "+f"(d[12]), "+f"(d[13]), "+f"(d[14]), "+f"(d[15]), "+f"(d[16]), "+f"(d[17]), "+f"(d[18]), "+f"(d[19]), "+f"(d[20]), "+f"(d[21]), "+f"(d[22]), "+f"(d[23]), "+f"(d[24]), "+f"(d[25]), "+f"(d[26]), "+f"(d[27]), "+f"(d[28]), "+f"(d[29]), "+f"(d[30]), "+f"(d[31])
    : "r"(a[0]), "r"(a[1]), "r"(a[2]), "r"(a[3]), "l"(db), "r"(sd));
}

__device__ __forceinline__ void wgmma_m64n32_rs_tb(float (&d)[16], const uint32_t (&a)[4], uint64_t db, int sd) {
  asm volatile(
    "{\n.reg .pred p;\nsetp.ne.b32 p, %21, 0;\n"
    "wgmma.mma_async.sync.aligned.m64n32k16.f32.bf16.bf16 "
    "{%0, %1, %2, %3, %4, %5, %6, %7, %8, %9, %10, %11, %12, %13, %14, %15}, {%16, %17, %18, %19}, %20, p, 1, 1, 1;\n}\n"
    : "+f"(d[0]), "+f"(d[1]), "+f"(d[2]), "+f"(d[3]), "+f"(d[4]), "+f"(d[5]), "+f"(d[6]), "+f"(d[7]), "+f"(d[8]), "+f"(d[9]), "+f"(d[10]), "+f"(d[11]), "+f"(d[12]), "+f"(d[13]), "+f"(d[14]), "+f"(d[15])
    : "r"(a[0]), "r"(a[1]), "r"(a[2]), "r"(a[3]), "l"(db), "r"(sd));
}

constexpr int G_STAGES = 4;
constexpr int G_A_BYTES = 128 * 64 * 2;
constexpr int G_B_BYTES = 256 * 64 * 2;
constexpr int G_STAGE_BYTES = G_A_BYTES + G_B_BYTES;
constexpr int G_STG_OFF = G_STAGES * G_STAGE_BYTES;
constexpr int BAR_OFF = G_STG_OFF + 32768 + 2048;
constexpr int SMEM_BYTES = BAR_OFF + 1024;
constexpr int B_GFULL = 0, B_GEMPTY = 32, B_CTX = 64, B_PFULL = 224;
constexpr int B_KFULL = 80, B_KEMPTY = 96, B_VFULL = 112, B_VEMPTY = 128, B_QFULL = 144, B_QEMPTY = 160,
              B_QDONE = 184;
constexpr int B_CFULL = 192;
constexpr int B_OFREE = 256, B_OFULL = 272, B_OEMPTY = 320, B_OY = 368;
constexpr int B_SFULL = 392, B_SFREE = 424, B_PEND = 456, B_SCMD = 512;

#define PHASE_PROLOGUE                                                                \
  uint32_t tid, rt_zero;                                                              \
  asm volatile("mov.u32 %0, %%tid.x;" : "=r"(tid));                                   \
  asm volatile("mov.u32 %0, %%nctaid.y;" : "=r"(rt_zero));                            \
  asm volatile("" : "+r"(smem0));                                                     \
  rt_zero = __shfl_sync(0xffffffffu, rt_zero >> 8, 0);   \
  const uint32_t sbase = __shfl_sync(0xffffffffu, smem0, 0);                          \
  const uint32_t bar = sbase + BAR_OFF;                                               \
  const int wg = __shfl_sync(0xffffffffu, tid >> 7, 0);                               \
  const int warp = (tid >> 5) & 3, lane = tid & 31, wtid = tid & 127;                 \
  (void)rt_zero; (void)bar; (void)warp; (void)lane; (void)wtid;

enum { ST_END = 0, ST_BOX1, ST_BOX2, ST_BOX2Q, ST_BOX2L };
__device__ __forceinline__ void st_post(uint32_t bar, int wg, int wtid, uint32_t n, int kind, const void* dst,
                                        uint32_t src, int c0, int c1, int sig) {
  if (wtid == 0) {
    const uint32_t c = bar + B_SCMD + wg * 64 + (n & 1) * 32;
    const uint64_t d = reinterpret_cast<uint64_t>(dst);
    sts128(c, make_uint4(kind, src, c0, c1));
    sts128(c + 16, make_uint4((uint32_t)d, (uint32_t)(d >> 32), sig, 0));
  }
  fence_proxy_async();
  __syncwarp();
  mbar_arrive_if(bar + B_SFULL + wg * 16 + (n & 1) * 8, (wtid & 31) == 0);
}
__device__ __forceinline__ void st_wait(uint32_t bar, int wg, uint32_t n) {
  const uint32_t b = bar + B_SFREE + wg * 16 + (n & 1) * 8;
  if (!mbar_try(b, ~(n >> 1) & 1)) mbar_wait(b, ~(n >> 1) & 1);
}
__device__ __forceinline__ void note(uint32_t bar, uint32_t cnt) {
  asm volatile("red.release.cta.shared.add.u32 [%0], 1;" ::"r"(bar + B_PEND + 4 * cnt) : "memory");
}
__device__ __forceinline__ void store_agent(uint32_t bar, int wg) {
  mbar_arrive(bar + B_SFREE + wg * 16);
  mbar_arrive(bar + B_SFREE + wg * 16 + 8);
  bool more = true;
  for (uint32_t n = 0;; n++) {
    mbar_wait_sleep(bar + B_SFULL + wg * 16 + (n & 1) * 8, (n >> 1) & 1);
    const uint4 c = lds128(bar + B_SCMD + wg * 64 + (n & 1) * 32);
    const uint4 d = lds128(bar + B_SCMD + wg * 64 + (n & 1) * 32 + 16);
    if (c.x == ST_END) break;
    const CUtensorMap* dst = reinterpret_cast<const CUtensorMap*>((uint64_t)d.x | ((uint64_t)d.y << 32));
    tma_store_2d(dst, c.y, c.z, c.w);
    if (c.x >= ST_BOX2) tma_store_2d(dst, c.y + 8192, c.z + 64, c.w);
    tma_store_commit();
    tma_store_wait_read<0>();
    mbar_arrive(bar + B_SFREE + wg * 16 + (n & 1) * 8);
    if (c.x == ST_BOX2L) mbar_arrive(bar + B_OFREE + 8 * wg);
    if ((int)d.z >= 0) {
      tma_store_wait<0>();
      if (d.z == 0) { TD(6) }
      asm volatile("fence.proxy.async.global;" ::: "memory");
      if (c.x == ST_BOX2Q) mbar_arrive(bar + B_QDONE);
      else note(bar, d.z);
      if (c.x == ST_BOX2L) {
        note(bar, CNT_DONE);
        more = false;
      }
    }
  }
  if (more) note(bar, CNT_DONE);
}

struct Maps {
  const bf16 *shift_k, *x, *gate_w, *ssm_k, *ssm_D;
  uint8_t id[128][4];
  CUtensorMap a[2];
  CUtensorMap b[3];
  CUtensorMap c[3];
  CUtensorMap bk, bv;
  CUtensorMap q, k, v, o;
  CUtensorMap oa, ob, oc;
  CUtensorMap y;
  CUtensorMap cu, ch;
};

constexpr int P_SLOT = 67 * 128, P_V = 35 * 128, P_TAPS = 2 * P_SLOT;
__device__ __forceinline__ void ldsm4t(uint32_t (&r)[4], uint32_t a) {
  asm volatile("ldmatrix.sync.aligned.m8n8.x4.trans.shared.b16 {%0, %1, %2, %3}, [%4];"
               : "=r"(r[0]), "=r"(r[1]), "=r"(r[2]), "=r"(r[3])
               : "r"(a));
}
__device__ __forceinline__ uint32_t fma_bf2(uint32_t a, uint32_t b, uint32_t c) {
  uint32_t r;
  asm("fma.rn.bf16x2 %0, %1, %2, %3;" : "=r"(r) : "r"(a), "r"(b), "r"(c));
  return r;
}
__device__ __forceinline__ void prep_agent(const Maps& maps, uint32_t sbase, int w, int lane) {
  const uint32_t bar = sbase + BAR_OFF, pb = bar + B_PFULL + w * 16;
  const int d0 = (blockIdx.x >> 3) * 64, t0 = (blockIdx.x & 7) * 256 + w * 128;
  mbar_wait_sleep(bar + B_GFULL + 8 * (G_STAGES - 1), 0);
#pragma unroll 1
  for (int i = -1; i < 4; i++) {
    GA(82 + 2 * i)
    if (i >= 0) mbar_wait_sleep(pb + (i & 1) * 8, i >> 1);
    GA(83 + 2 * i)
    const uint32_t so = sbase + G_STG_OFF + w * (P_TAPS + 512) + (i & 1) * P_SLOT;
    if (i < 3 && elect_one()) {
      const uint32_t b = pb + (~i & 1) * 8, dst = so + (i & 1 ? -P_SLOT : P_SLOT);
      mbar_expect_tx(b, i < 0 ? P_SLOT + 512 : P_SLOT);
      const uint64_t pol = policy_evict_first();
      tma_load_2d_hint(dst, &maps.bk, b, d0, t0 + 32 * i + 29, pol);
      tma_load_2d_hint(dst + P_V, &maps.bv, b, d0, t0 + 32 * i + 32, pol);
      if (i < 0) bulk_load(sbase + G_STG_OFF + P_TAPS, maps.shift_k + d0 * 4, 512, b);
    }
    if (i < 0) continue;
    uint32_t ak[4];
#pragma unroll
    for (int r = 0; r < 4; r++) {
      const uint32_t a = so / 128 + r + 4 * (lane & 6) + (((lane >> 2) ^ lane) & 6) + (lane & 1);
      ak[r] = a * 128 + (a & 7) * 16;
    }
    bf16* dst = g_kvT + (size_t)(d0 + (lane >> 2)) * S_LEN + t0 + ((lane & 3) + 4 * i) * 8;
#pragma unroll 1
    for (int cg = 0; cg < 128; cg += 16) {
      uint32_t t01, t23, k[4][4], v[4];
      asm volatile("ld.shared.v2.u32 {%0, %1}, [%2];"
                   : "=r"(t01), "=r"(t23)
                   : "r"(sbase + G_STG_OFF + P_TAPS + cg * 4 + (lane >> 2) * 8));
#pragma unroll
      for (int r = 0; r < 4; r++) ldsm4t(k[r], ak[r] ^ cg);
      ldsm4t(v, (ak[3] ^ cg) + 4096);
      const uint32_t w0 = __byte_perm(t01, 0, 0x1010), w1 = __byte_perm(t01, 0, 0x3232);
      const uint32_t w2 = __byte_perm(t23, 0, 0x1010), w3 = __byte_perm(t23, 0, 0x3232);
#pragma unroll
      for (int j = 0; j < 4; j++)
        v[j] = mul_bf2(fma_bf2(k[3][j], w0, fma_bf2(k[2][j], w1, fma_bf2(k[1][j], w2, mul_bf2(k[0][j], w3)))), v[j]);
      const bool s1 = lane & 1, s2 = lane & 2;
      const uint32_t a0 = s1 ? v[1] : v[0], a1 = s1 ? v[0] : v[1], a2 = s1 ? v[3] : v[2], a3 = s1 ? v[2] : v[3];
      *reinterpret_cast<uint4*>(dst) = make_uint4(s2 ? a2 : a0, s2 ? a3 : a1, s2 ? a0 : a2, s2 ? a1 : a3);
      dst += 8 * S_LEN;
    }
    fence_proxy_async();
    __syncwarp();
  }
  GA(90)
  if (lane == 0) note(bar, CNT_PREP);
  __syncwarp();
  GA(91)
}

__device__ __forceinline__ void qkv_tile(const Maps& maps, int it, int& which, int& m_tile, int& n_tile) {
  const bool q = it == 0 || it >= 5;
  const int b = maps.id[blockIdx.x][it >= 5];
  which = q ? 0 : 2 - (it & 1);
  m_tile = b & 15;
  n_tile = (b >> 4) * 2 + ((0x19 >> it) & 1);
}

constexpr int G_NTILES = 6;
__device__ __forceinline__ void qkv_producer(const Maps& maps, uint32_t sbase, bool first) {
  const uint32_t bar = sbase + BAR_OFF;
  uint32_t stage = 0, phase = 0;
#pragma unroll 1
  for (int it = 0; it < (first ? 1 : G_NTILES); it++) {
    int which, m_tile, n_tile;
    qkv_tile(maps, it, which, m_tile, n_tile);
    const CUtensorMap* ma = &maps.a[which == 0 ? 0 : 1];
    const CUtensorMap* mb = &maps.b[which];
    const int nk = first ? G_STAGES : which == 0 ? 16 : 8;
#pragma unroll 1
    for (int kt = (it == 0 && !first) ? G_STAGES : 0; kt < nk; kt++) {
      if (!first) mbar_wait_sleep(bar + B_GEMPTY + 8 * stage, phase);
      const uint32_t fb = bar + B_GFULL + 8 * stage;
      const uint32_t sa = sbase + stage * G_STAGE_BYTES;
      mbar_expect_tx(fb, G_STAGE_BYTES);
      tma_load_2d(sa, ma, fb, kt * 64, m_tile * 128);
      tma_load_3d(sa + G_A_BYTES, mb, fb, 0, kt * 64, n_tile * 4);
      if (++stage == G_STAGES) { stage = 0; phase ^= 1; }
      {
        const int b = maps.id[blockIdx.x][1];
        if (it == 2 && kt == (b & 7)) {
          for (int i = 0; i < 2; i++)
            asm volatile("cp.async.bulk.prefetch.tensor.2d.L2.global.tile [%0, {%1, %2}];" ::"l"(&maps.a[0]),
                         "r"((b >> 4) * 128 + i * 64), "r"((b & 15) * 128)
                         : "memory");
        }
        if (it == 3 && kt == (b & 7))
          asm volatile("cp.async.bulk.prefetch.tensor.3d.L2.global.tile [%0, {%1, %2, %3}];" ::"l"(&maps.b[0]), "r"(0),
                       "r"((b & 15) * 64), "r"((b >> 4) * 8)
                       : "memory");
      }
    }
  }
}

__device__ __noinline__ void publisher(uint32_t bar, int lane, uint32_t nsrc, uint32_t poll) {
  uint32_t done = 0;
#pragma unroll 1
  for (uint32_t spins = 0; (done < nsrc || poll <= nsrc) && spins < (1u << 20); spins++) {
    if (done >= poll) {
      uint32_t v;
      asm volatile("ld.acquire.gpu.global.u32 %0, [%1];" : "=r"(v) : "l"(g_cnt + (CNT_CTX + 1) * 32) : "memory");
      if (__all_sync(0xffffffffu, v >= NH * (S_LEN / 128))) {
        asm volatile("fence.proxy.async.global;" ::: "memory");
        mbar_arrive_if(bar + B_CTX, lane == 0);
        poll = ~0u;
      }
    }
    uint32_t v = 0;
    if (lane < CNT_N)
      asm volatile("atom.acquire.cta.shared.exch.b32 %0, [%1], 0;" : "=r"(v) : "r"(bar + B_PEND + 4 * lane) : "memory");
    done += __shfl_sync(0xffffffffu, v, CNT_DONE);
    if (lane == CNT_DONE) v = 0;
    if (done == nsrc && lane < CNT_DONE) {
      uint32_t w;
      asm volatile("atom.acquire.cta.shared.exch.b32 %0, [%1], 0;" : "=r"(w) : "r"(bar + B_PEND + 4 * lane) : "memory");
      v += w;
    }
    if (v && lane == 0) { TD(0) }
    if (v) cnt_signal_release(lane, v);
    if (v && lane == 0) { TD(1) }
    if (!__any_sync(0xffffffffu, v != 0)) __nanosleep(200);
  }
  __threadfence();
  __syncwarp();
}

__device__ __forceinline__ void gate_rows(const Maps& maps, uint32_t sbase, int w48, int w12, int lane) {
  const uint32_t buf = sbase + w12 * 16384, gb = sbase + BAR_OFF + 768 + w12 * 16;
  if (lane == 0) {
    mbar_init(gb, 1);
    mbar_init(gb + 8, 1);
    fence_barrier_init();
    for (int i = 0; i < 2; i++) {
      mbar_expect_tx(gb + 8 * i, 8192);
      bulk_load(buf + i * 8192, maps.x + (size_t)(w48 + 48 * i) * 4 * DM, 8192, gb + 8 * i);
    }
  }
  __syncwarp();
  uint4 wv[4];
#pragma unroll
  for (int i = 0; i < 4; i++) wv[i] = __ldg(reinterpret_cast<const uint4*>(maps.gate_w + (i * 32 + lane) * 8));
  int it = 0;
#pragma unroll 1
  for (int row = w48 * 4; row < S_LEN; row += 48 * 4, it++) {
    mbar_wait(gb + 8 * (it & 1), (it >> 1) & 1);
    uint4 xv[4][4];
#pragma unroll
    for (int r = 0; r < 4; r++)
#pragma unroll
      for (int i = 0; i < 4; i++) xv[r][i] = lds128(buf + (it & 1) * 8192 + r * 2048 + (i * 32 + lane) * 16);
    float d[2][4];
#pragma unroll
    for (int pr = 0; pr < 2; pr++) {
      d[pr][0] = d[pr][1] = d[pr][2] = d[pr][3] = 0.f;
      auto acc = [&](uint32_t a0, uint32_t a2, uint32_t b0, uint32_t b2, uint32_t w0, uint32_t w2) {
        asm volatile(
            "mma.sync.aligned.m16n8k16.row.col.f32.bf16.bf16.f32 {%0, %1, %2, %3}, {%4, %5, %6, %7}, {%8, %8}, "
            "{%0, %1, %2, %3};"
            : "+f"(d[pr][0]), "+f"(d[pr][1]), "+f"(d[pr][2]), "+f"(d[pr][3])
            : "r"(mul_bf2(a0, w0)), "r"(mul_bf2(b0, w0)), "r"(mul_bf2(a2, w2)), "r"(mul_bf2(b2, w2)), "r"(0x3f803f80u));
      };
#pragma unroll
      for (int i = 0; i < 4; i++) {
        acc(xv[2 * pr][i].x, xv[2 * pr][i].y, xv[2 * pr + 1][i].x, xv[2 * pr + 1][i].y, wv[i].x, wv[i].y);
        acc(xv[2 * pr][i].z, xv[2 * pr][i].w, xv[2 * pr + 1][i].z, xv[2 * pr + 1][i].w, wv[i].z, wv[i].w);
      }
    }
    float sum = (lane & 2) ? ((lane & 1) ? d[1][2] : d[1][0]) : ((lane & 1) ? d[0][2] : d[0][0]);
#pragma unroll
    for (int off = 16; off >= 4; off >>= 1) sum += __shfl_xor_sync(0xffffffffu, sum, off);
    if (lane < 4) g_gate[row + lane] = bf16_round(rcp(1.0f + __expf(-bf16_round(sum))));
    if (lane == 0 && row + 2 * 48 * 4 < S_LEN) {
      mbar_expect_tx(gb + 8 * (it & 1), 8192);
      bulk_load(buf + (it & 1) * 8192, maps.x + (size_t)(row + 2 * 48 * 4) * DM, 8192, gb + 8 * (it & 1));
    }
  }
}

constexpr float Q_SCALE = 0.08838834764831845f * 1.4426950408889634f;
__device__ __forceinline__ uint32_t qkv_consumer(const Maps& maps, uint32_t smem0, bool fused, float (&rest)[64]) {
  PHASE_PROLOGUE
  constexpr int NTILES = G_NTILES;
  float acc[128];
  uint32_t stage = 0, phase = 0;
  const uint32_t stg = sbase + G_STG_OFF + wg * 18432;
  const int st_row = warp * 16 + (lane & 7) + ((lane >> 3) & 1) * 8;
  const int st_cb = lane >> 4;
  uint32_t pend[64];
  const CUtensorMap* pend_map = nullptr;
  int pend_c0 = 0, pend_c1 = 0;
  uint32_t sn = 0;
  auto put_box = [&](uint32_t buf, const uint32_t* v) {
#pragma unroll
    for (int jp = 0; jp < 4; jp++) {
      const int chunk = jp * 2 + st_cb;
      const uint32_t addr = buf + st_row * 128 + ((chunk ^ (st_row & 7)) << 4);
      stmatrix_x4(addr, v[jp * 4], v[jp * 4 + 1], v[jp * 4 + 2], v[jp * 4 + 3]);
    }
  };
  GT(gti++)
#pragma unroll 1
  for (int it = 0; it <= NTILES; it++) {
    int which, m_tile, n_tile;
    qkv_tile(maps, it, which, m_tile, n_tile);
    const int nk = (which == 0 && it < NTILES) ? 16 : 8;
    uint32_t prev_stage = 0;
#pragma unroll 1
    for (int kt = 0; kt < nk; kt++) {
      if (it < NTILES) {
        mbar_wait((bar + B_GFULL) + 8 * stage, phase);
        GT(gti++)
        const uint64_t da0 = make_desc(sbase + stage * G_STAGE_BYTES + wg * 8192, 16, 1024, DESC_SW128);
        const uint64_t db0 = make_desc(sbase + stage * G_STAGE_BYTES + G_A_BYTES, 8192, 1024, DESC_SW128);
        wgmma_fence();
#pragma unroll
        for (int kk = 0; kk < 4; kk++) {
          wgmma_m64n256_ss_tb(acc, desc_add(da0, kk * 2), desc_add(db0, kk * 128), (kt | kk) != 0);
        }
        wgmma_commit();
      }
      const uint32_t when = it == 0 ? 0 : it == 5 ? 0x922 << wg : wg ? 0xAA : 0x55;
      if ((when >> kt) & 1) {
        const int c = __popc(when & ~(~0u << kt));
        st_wait(bar, wg, sn - 2);
        const uint32_t buf = stg + (c & 1) * 8192;
        switch (c) {
          case 0: put_box(buf, pend); break;
          case 1: put_box(buf, pend + 16); break;
          case 2: put_box(buf, pend + 32); break;
          default: put_box(buf, pend + 48); break;
        }
        st_post(bar, wg, wtid, sn, ST_BOX1, pend_map, buf, pend_c0 + c * 64, pend_c1, (c == 3 && it > 1) ? CNT_KV + (it > 3) : -1);
        sn++;
      }
      if (it < NTILES) {
        wgmma_wait<1>();
        mbar_arrive_if((bar + B_GEMPTY) + 8 * prev_stage, wtid == 32 && kt > 0);
        prev_stage = stage;
        if (++stage == G_STAGES) { stage = 0; phase ^= 1; }
      }
    }
    wgmma_wait<0>();
    fence_regs(acc);
    if (it == NTILES) break;
    GT(gti++)
    mbar_arrive_if((bar + B_GEMPTY) + 8 * prev_stage, wtid == 32);
    if (it == NTILES - 1 && fused) break;
    if (which == 0) {
#pragma unroll
      for (int j = 0; j < 128; j++) acc[j] *= Q_SCALE;
    }
#pragma unroll
    for (int j = 0; j < 64; j++) pend[j] = pack_bf16(acc[2 * j], acc[2 * j + 1]);
    pend_map = &maps.c[which];
    pend_c0 = n_tile * 256;
    pend_c1 = m_tile * 128 + wg * 64;
  }
  mbar_wait(bar + B_GEMPTY, 1);
#pragma unroll
  for (int j = 0; j < 32; j++) pend[j] = pack_bf16(acc[2 * j] * Q_SCALE, acc[2 * j + 1] * Q_SCALE);
  put_box(sbase + wg * 8192, pend);
  put_box(sbase + 16384 + wg * 8192, pend + 16);
  fence_proxy_async();
#pragma unroll
  for (int j = 0; j < 64; j++) rest[j] = acc[64 + j];
  GT(gti++)
  return sn;
}

constexpr int A_TILE = 128 * 128 * 2;
constexpr int A_Q_OFF = 0;
constexpr int A_K_OFF = 2 * A_TILE;
constexpr int A_V_OFF = 4 * A_TILE;
constexpr int A_O_OFF = 6 * A_TILE;
constexpr int A_ITEMS = NH * (S_LEN / 128);

constexpr uint32_t A_ORDER = 0x3120, A_STEPS = 34;
__device__ __forceinline__ int item_m(uint32_t it) { return it & 15; }
__device__ __forceinline__ int item_h(uint32_t it) { return it >> 4; }

constexpr int C_V = 16384, C_MAT = 24576;
constexpr float C_ALPHA = 0.07874506561842957f;
__device__ __forceinline__ void sincos_turn(int p, float inv, float& c, float& s) {
  const float a = (float)p * (inv * 6.283185307179586f);
  asm("cos.approx.ftz.f32 %0, %1;" : "=f"(c) : "f"(a));
  asm("sin.approx.ftz.f32 %0, %1;" : "=f"(s) : "f"(a));
}

__device__ __forceinline__ uint32_t item_of(const Maps& maps, uint32_t r) {
  const uint32_t b = maps.id[blockIdx.x & 127][1];
  return (b >> 4) * 64 + ((A_ORDER >> (4 * r)) & 3) * 16 + ((b ^ ((r & 1) * 15)) & 15);
}

#define C_SIDE 64
__device__ __forceinline__ uint32_t conv_first(const Maps& maps) {
  const uint32_t b = maps.id[blockIdx.x & 127][1];
  return (b >> 4) * 128 + C_SIDE + ((b + 15) & 15);
}

__device__ __forceinline__ void conv_consumer(const Maps& maps, uint32_t smem0, uint32_t first, uint32_t step,
                                              uint32_t end, bool pp) {
  PHASE_PROLOGUE
  const uint32_t in_full = bar + B_CFULL + wg * 16;
  const uint32_t ca = sbase + (wg ? A_V_OFF + A_TILE : A_Q_OFF);
  const int w = __shfl_sync(0xffffffffu, warp, 0), g = lane >> 2, c = lane & 3;
  auto fetch = [&](uint32_t ch, uint32_t n) {
    if (w == 2 && ch < end) {
      if (elect_one()) {
        const uint32_t b = in_full + (n & 1) * 8, d = ca + (n & 1) * 8192;
        const uint64_t pol = policy_evict_first();
        mbar_expect_tx(b, 8192);
        tma_load_2d_hint(d, &maps.cu, b, 0, ch * 64, pol);
        tma_load_2d_hint(d + 4096, &maps.ch, b, 0, ch * 64, pol);
      }
    }
  };
  if (wtid == 96 && wg) { TD(15) }
  uint32_t f1[8][4];
  float tt[16], ts[16];
  uint32_t cc[4], ss[4];
#pragma unroll
  for (int i = 0; i < 16; i++) {
    const int k = 2 * (16 * w + g + 8 * (i & 1)) + 1, n = 2 * (8 * (i >> 1) + 2 * c) + 1;
    float c0, s0, c1, s1;
    sincos_turn(((k * n) << 23) >> 23, 1.f / 512, c0, s0);
    sincos_turn(((k * n + 2 * k) << 23) >> 23, 1.f / 512, c1, s1);
    f1[i >> 2][i & 3] = pack_bf16(c0 * C_ALPHA, c1 * C_ALPHA);
    f1[4 + (i >> 2)][i & 3] = pack_bf16(s0 * -C_ALPHA, s1 * -C_ALPHA);
  }
#pragma unroll
  for (int i = 0; i < 16; i++) {
    const int k = 2 * (16 * w + g + 8 * ((i >> 1) & 1)) + 1, n = 16 - (8 * (i >> 2) + 2 * c + (i & 1));
    float cs;
    sincos_turn(k * n, 1.f / 8192, cs, ts[i]);
    tt[i] = ts[i] * rcp(1.f + cs);
  }
#pragma unroll
  for (int j = 0; j < 4; j++) {
    const int k = 8 * w + g, n = 8 * c + 2 * j;
    float c0, s0, c1, s1;
    sincos_turn((int8_t)(k * n * 8), 1.f / 256, c0, s0);
    sincos_turn((int8_t)((k * n + k) * 8), 1.f / 256, c1, s1);
    cc[j] = pack_bf16(c0, c1);
    ss[j] = pack_bf16(s0, s1);
  }
  named_bar_sync(3, 256);
  fetch(first, 0);
  fetch(first + step, 1);
  const uint32_t va = ca + g * 64 + ((c ^ (g >> 1)) << 4);
  {
    const uint32_t a = va + C_MAT + w * 512, m = 0x80008000u;
    sts128(a, make_uint4(cc[0], cc[1], cc[2], cc[3]));
    sts128(a + 2048, make_uint4(ss[0], ss[1], ss[2], ss[3]));
    sts128(a + 4096, make_uint4(ss[0] ^ m, ss[1] ^ m, ss[2] ^ m, ss[3] ^ m));
    sts128(a + 6144, make_uint4(cc[0], cc[1], cc[2], cc[3]));
  }
  fence_proxy_async();
  named_bar_sync(1 + wg, 128);
  constexpr uint64_t DHI = (2ull << 62) | ((uint64_t)(512 >> 4) << 32);
  const uint32_t d0 = (uint32_t)make_desc(ca, 4096, 0, 0);
  float a5[16];
  uint4* const yb = reinterpret_cast<uint4*>(g_y2T) + (16 * w + g) * 4 + c;
  auto issue5 = [&]() {
#pragma unroll
    for (int ks = 0; ks < 8; ks++) wgmma_m64n32_rs_tb(a5, f1[ks], DHI | (d0 + (C_V >> 4) + ks * 64), ks != 0);
    wgmma_commit();
  };
  auto finish = [&](uint32_t ch, bool on) {
    fence_regs(a5);
    uint4* y = yb + (size_t)ch * 256;
    if (on) {
      y[0] = make_uint4(pack_bf16(a5[0], a5[1]), pack_bf16(a5[4], a5[5]), pack_bf16(a5[8], a5[9]), pack_bf16(a5[12], a5[13]));
      y[32] = make_uint4(pack_bf16(a5[2], a5[3]), pack_bf16(a5[6], a5[7]), pack_bf16(a5[10], a5[11]), pack_bf16(a5[14], a5[15]));
    }
  };
  auto dft32 = [&](float (&d)[32], const float* re, const float* im) {
    uint32_t a[4][4];
#pragma unroll
    for (int i = 0; i < 8; i++) {
      a[i >> 2][i & 3] = pack_bf16(re[2 * i], re[2 * i + 1]);
      a[2 + (i >> 2)][i & 3] = pack_bf16(im[2 * i], im[2 * i + 1]);
    }
    wgmma_fence();
#pragma unroll
    for (int ks = 0; ks < 4; ks++) wgmma_m64n64_rs_tb(d, a[ks], DHI | (d0 + (C_MAT >> 4) + ks * 64), ks != 0);
    wgmma_commit();
  };
  auto rot = [&](float* x, float* y) {
#pragma unroll
    for (int i = 0; i < 16; i++) {
      x[i] = fmaf(-tt[i], y[i], x[i]);
      y[i] = fmaf(ts[i], x[i], y[i]);
      x[i] = fmaf(-tt[i], y[i], x[i]);
    }
  };
  auto load_d = [&](uint32_t ch) {
    return __ldg(reinterpret_cast<const unsigned short*>(maps.ssm_D) + ((ch & (DM - 1)) | (lane & rt_zero)));
  };
  uint32_t dn = load_d(first);
  uint32_t n = 0, ch = first;
#pragma unroll 1
  for (; ch < end; n++, ch += step) {
    CT(0)
    float a1[2][32], a2[2][32], a4[32];
    const float dsk = c ? 0.f : __uint_as_float(dn << 16) * C_ALPHA;
    dn = load_d(ch + step);
    mbar_wait(in_full + (n & 1) * 8, (n >> 1) & 1);
    if (pp) named_bar_sync(4 + wg, 256);
    CT(1)
    wgmma_fence();
#pragma unroll
    for (int ks = 0; ks < 8; ks++)
      wgmma_m64n64_rs_tb(a1[ks >> 2], f1[ks], DHI | (d0 + (n & 1) * 512 + (ks & 3) * 64), (ks & 3) != 0);
    wgmma_commit();
    issue5();
    wgmma_wait<1>();
    fence_regs(a1[0]);
    fence_regs(a1[1]);
    CT(2)
    rot(a1[0], a1[1]);
    dft32(a2[0], a1[0], a1[1]);
    rot(a1[0] + 16, a1[1] + 16);
    a1[0][16] += dsk;
    a1[0][18] += dsk;
    dft32(a2[1], a1[0] + 16, a1[1] + 16);
    CT(3)
    wgmma_wait<2>();
    finish(ch - step, n > 0);
    wgmma_wait<0>();
    fence_regs(a2[0]);
    fence_regs(a2[1]);
    CT(4)
    if (pp) named_bar_arrive(5 - wg, 256);
    float re[16], im[16];
#pragma unroll
    for (int i = 0; i < 16; i++) {
      re[i] = a2[0][i] * a2[1][i] - a2[0][16 + i] * a2[1][16 + i];
      im[i] = a2[0][i] * a2[1][16 + i] + a2[0][16 + i] * a2[1][i];
    }
    dft32(a4, im, re);
    wgmma_wait<0>();
    fence_regs(a4);
    CT(5)
    rot(a4, a4 + 16);
#pragma unroll
    for (int i = 0; i < 4; i++) {
      const float* x = a4 + 16 - 16 * (i >> 1) + 2 * (i & 1);
      sts128(va + C_V + w * 1024 + (i >> 1) * 4096 + (i & 1) * 512,
             make_uint4(pack_bf16(x[0], x[1]), pack_bf16(x[4], x[5]), pack_bf16(x[8], x[9]), pack_bf16(x[12], x[13])));
    }
    CT(6)
    fence_proxy_async();
    named_bar_sync(1 + wg, 128);
    fetch(ch + 2 * step, n);
    if (wtid == 96 && n > 0) note(bar, CNT_Y2);
    CT(7)
  }
  wgmma_fence();
  issue5();
  wgmma_wait<0>();
  finish(ch - step, true);
  named_bar_sync(1 + wg, 128);
  if (wtid == 96 && wg) { TD(8) }
  if (wtid == 96) cnt_signal_release(CNT_Y2, 1);
  if (wtid == 64) note(bar, CNT_DONE);
  if (wtid == 96 && wg) { TD(9) }
  mbar_wait(bar + B_OFREE, 0);
  mbar_wait(bar + B_OFREE + 8, 0);
}

__device__ __forceinline__ void attn_producer(const Maps& maps, uint32_t sbase, bool after_qkv, bool to_out,
                                              bool dry) {
  const uint32_t bar = sbase + BAR_OFF;
  const uint32_t q_full = bar + B_QFULL, q_empty = bar + B_QEMPTY;
  const uint32_t k_full = bar + B_KFULL, k_empty = bar + B_KEMPTY, v_full = bar + B_VFULL, v_empty = bar + B_VEMPTY;
  int ndrained = after_qkv ? 0 : G_STAGES;
  auto wait = [&](uint32_t b, uint32_t par) {
    if (!dry) mbar_wait_sleep(b, par);
  };
  auto drained = [&](int upto) {
#pragma unroll 1
    for (; ndrained <= upto; ndrained++) wait(bar + B_GEMPTY + 8 * ndrained, 1);
  };
  uint32_t st = 0, ph = 1, vs = 0, vp = 1;
  int pend_j = -1, pend_h = 0;
  int round = -1, m = -1, h = 0;
  bool last = false;
#pragma unroll 1
  for (;; round++) {
    uint32_t nitem = 0;
    const int tpost = m >= 3 ? m - 1 : m;
#pragma unroll 1
    for (int t = m < 0 ? -1 : 0; t <= m; t++) {
      const int j = (t < m && (round & 1)) ? m - 1 - t : t;
      if (t >= 0) {
        drained(1 + st);
        wait(k_empty + 8 * st, ph);
        if (!dry) {
          mbar_expect_tx(k_full + 8 * st, A_TILE);
          tma_load_3d(sbase + A_K_OFF + st * A_TILE, &maps.k, k_full + 8 * st, 0, j * 128, h * 2);
        }
        if (++st == 2) { st = 0; ph ^= 1; }
      }
      if (pend_j >= 0) {
        drained(3);
        wait(v_empty + 8 * vs, vp);
        if (!dry) {
          mbar_expect_tx(v_full + 8 * vs, A_TILE);
          tma_load_3d(sbase + A_V_OFF + vs * A_TILE, &maps.v, v_full + 8 * vs, 0, pend_j * 128, pend_h * 2);
        }
        if (++vs == 2) { vs = 0; vp ^= 1; }
      }
      pend_j = j;
      pend_h = h;
      if (t == tpost && !last) {
        nitem = dry ? 1 : item_of(maps, round + 1);
        if (round == (dry ? 0 : 3) || blockIdx.x >= 128) {
          nitem = A_ITEMS;
          cnt_wait(CNT_PREP, dry ? 0 : 260);
          if (to_out) {
            cnt_wait(CNT_CTX, dry ? 0 : A_ITEMS);
            asm volatile("cp.async.bulk.prefetch.L2.global [%0], 4096;" ::"l"(maps.ssm_k + (size_t)conv_first(maps) * S_LEN));
            if (!dry)
              asm volatile("cp.async.bulk.prefetch.L2.global [%0], 4096;" ::"l"(g_kvT + (size_t)conv_first(maps) * S_LEN));
          }
        }
        const uint32_t qs = (round + 1) & 1;
        wait(q_empty + 8 * qs, (((round + 1) >> 1) & 1) ^ 1);
        if (round == 1 && after_qkv) wait(bar + B_QDONE, 0);
        if (round <= 0 && after_qkv) {
          if (!dry) { TD(2) }
          cnt_wait(CNT_KV + round + 1, dry ? 0 : 512);
          if (!dry) { TD(3) }
        }
        if (nitem >= A_ITEMS || (round < 0 && after_qkv && !dry)) {
          if (!dry) mbar_arrive(q_full + 8 * qs);
        } else {
          drained(qs);
          if (!dry) {
            mbar_expect_tx(q_full + 8 * qs, A_TILE);
            tma_load_3d_hint(sbase + A_Q_OFF + qs * A_TILE, &maps.q, q_full + 8 * qs, 0, item_m(nitem) * 128,
                             item_h(nitem) * 2, policy_evict_first());
          }
        }
      }
    }
    if (last) break;
    last = nitem >= A_ITEMS;
    m = last ? -1 : item_m(nitem);
    h = item_h(nitem);
  }
}

__device__ __forceinline__ uint32_t attn_consumer(const Maps& maps, uint32_t smem0, uint32_t sn,
                                                  float (&rest)[64], bool after_qkv) {
  PHASE_PROLOGUE
  const uint32_t q_full = bar + B_QFULL, q_empty = bar + B_QEMPTY;
  const uint32_t k_full = bar + B_KFULL, k_empty = bar + B_KEMPTY, v_full = bar + B_VFULL;
  float o[64], s[64];
  uint32_t p[32];
  float e[32];
  uint32_t dep = 0;
  constexpr int MIDJ = 5;
  float l0 = 0.f, l1 = 0.f, b0 = 0.f, b1 = 0.f;
  const int sched_own = 4 + wg, sched_other = 5 - wg;
  if (wg == 1) named_bar_arrive(4, 256);

  const uint32_t qd0 = (uint32_t)make_desc(sbase + A_Q_OFF + wg * 8192, 16, 0, 0);
  const uint32_t kd0 = (uint32_t)make_desc(sbase + A_K_OFF, 16, 0, 0);
  const uint32_t vd0 = (uint32_t)make_desc(sbase + A_V_OFF, 16384, 0, 0);
  constexpr uint64_t DHI = DESC_SW128 | ((uint64_t)(1024 >> 4) << 32);
  constexpr uint32_t DST = A_TILE >> 4;
  auto issue_qk = [&](uint32_t qd, uint32_t kd) {
#pragma unroll
    for (int kk = 0; kk < 8; kk++) {
      const uint32_t off = ((kk >> 2) * 16384 + (kk & 3) * 32) >> 4;
      wgmma_m64n128_ss(s, DHI | (qd + off), DHI | (kd + off), kk != 0);
    }
    wgmma_commit();
  };
  auto issue_pv = [&](uint32_t vd, bool accumulate, int nk) {
#pragma unroll
    for (int kk = 0; kk < 8; kk++) {
      if (kk < nk)
        wgmma_m64n128_rs_tb(o, p[4 * kk], p[4 * kk + 1], p[4 * kk + 2], p[4 * kk + 3], DHI | (vd + kk * 128),
                            accumulate || (kk != 0));
    }
    wgmma_commit();
  };
  auto exp_lo = [&](float& a0, float& a1) {
#pragma unroll
    for (int j = 0; j < 8; j++) {
      e[4 * j] = ex2(s[4 * j]);
      e[4 * j + 1] = ex2(s[4 * j + 1]);
      e[4 * j + 2] = ex2(s[4 * j + 2]);
      e[4 * j + 3] = ex2(s[4 * j + 3]);
      a0 += e[4 * j];
      a0 += e[4 * j + 1];
      a1 += e[4 * j + 2];
      a1 += e[4 * j + 3];
      if (j == MIDJ) dep = (__float_as_uint(a0) | __float_as_uint(a1)) & rt_zero;
    }
  };
  auto pack_lo = [&]() {
#pragma unroll
    for (int j = 0; j < 16; j++) p[j] = pack_bf16(e[2 * j], e[2 * j + 1]);
  };
  auto finish_p = [&](float& a0, float& a1) {
    pack_lo();
#pragma unroll
    for (int j = 8; j < 16; j++) {
      const float e0 = ex2(s[4 * j]), e1 = ex2(s[4 * j + 1]), e2 = ex2(s[4 * j + 2]), e3 = ex2(s[4 * j + 3]);
      a0 += e0;
      a0 += e1;
      a1 += e2;
      a1 += e3;
      p[2 * j] = pack_bf16(e0, e1);
      p[2 * j + 1] = pack_bf16(e2, e3);
      if (j == 8 + MIDJ) dep = __float_as_uint(a0) & rt_zero;
    }
  };
  auto quad_sum = [&](float t) {
    t += __shfl_xor_sync(0xffffffffu, t, 1);
    return t + __shfl_xor_sync(0xffffffffu, t, 2);
  };
  auto write_o = [&](float i0, float i1) {
    st_wait(bar, wg, sn - 1);
    const int st_row = warp * 16 + (lane & 7) + ((lane >> 3) & 1) * 8;
    const uint32_t so = sbase + A_O_OFF + wg * 16384 + st_row * 128;
#pragma unroll
    for (int j = 0; j < 16; j += 2)
      stmatrix_x4(so + (j >> 3) * 8192 + ((((j & 7) + (lane >> 4)) ^ (lane & 7)) << 4),
                  pack_bf16(o[4 * j] * i0, o[4 * j + 1] * i0), pack_bf16(o[4 * j + 2] * i1, o[4 * j + 3] * i1),
                  pack_bf16(o[4 * j + 4] * i0, o[4 * j + 5] * i0), pack_bf16(o[4 * j + 6] * i1, o[4 * j + 7] * i1));
  };
  auto store_o = [&](uint32_t r, int kind) {
    const uint32_t it = item_of(maps, r);
    st_post(bar, wg, wtid, sn, kind, (INPLACE & 1) || kind != ST_BOX2Q ? &maps.o : &maps.c[0], sbase + A_O_OFF + wg * 16384, item_h(it) * 128,
            item_m(it) * 128 + wg * 64, CNT_CTX + (r >> 1));
    sn++;
  };
  auto mask_half = [&](float* sh) {
    const int u = warp * 16 + (lane >> 2) - (lane & 3) * 2;
#pragma unroll
    for (int j = 0; j < 8; j++) {
      if (8 * j > u) sh[4 * j] = -INFINITY;
      if (8 * j + 1 > u) sh[4 * j + 1] = -INFINITY;
      if (8 * j - 8 > u) sh[4 * j + 2] = -INFINITY;
      if (8 * j - 7 > u) sh[4 * j + 3] = -INFINITY;
    }
  };
  ST(0)
  mbar_wait(q_full, 0);
  if (blockIdx.x >= 128) {
    mbar_arrive_if(bar + B_OFREE + 8 * wg, wtid == 0);
    return sn;
  }
  mbar_wait(k_full, 0);
  named_bar_sync(sched_own, 256);
  wgmma_fence();
  issue_qk(qd0, kd0);
  named_bar_arrive(sched_other, 256);
  fence_regs(rest);
#pragma unroll
  for (int i = 0; i < 64; i++) o[i] = rest[i] * Q_SCALE;
  fence_regs(o);
  wgmma_wait<0>();
  fence_regs(s);
  mbar_arrive_if(k_empty, wtid == 32);
  uint32_t g = 0;
  uint32_t rnd = 0;
  int rem = item_m(item_of(maps, 0));
  uint32_t first = 1;
  uint32_t fl = 0;
#define redo (fl & 1)
#define shifted (fl & 2)
  float d0 = 0.f, d1 = 0.f;
  float pi0 = 1.f, pi1 = 1.f;
  ST(1)
  for (;;) {
    if (shifted) {
#pragma unroll
      for (int j = 0; j < 16; j++) {
        s[4 * j] -= d0;
        s[4 * j + 1] -= d0;
        s[4 * j + 2] -= d1;
        s[4 * j + 3] -= d1;
      }
    }
    if (rem == 0 && !redo) {
      mbar_arrive_if(q_empty + 8 * (rnd & 1), wtid == 96);
      rnd++;
      if (wg == 0) mask_half(s);
      else mask_half(s + 32);
    }
    for (;;) {
      const bool kill = rem == 0 && wg == 0;
      const uint32_t kd = kd0 + ((g + 1) & 1) * DST, vd = vd0 + (g & 1) * DST;
      float a0 = 0.f, a1 = 0.f;
      exp_lo(a0, a1);
      fence_regs(e);
      const uint32_t kb = k_full + 8 * ((g + 1) & 1);
      const uint32_t kpar = ((((g + 1) >> 1) & 1) ^ (g == A_STEPS - 1 ? 1u : 0u)) | dep;
      if (!mbar_try(kb, kpar)) mbar_wait(kb, kpar | ((__float_as_uint(a0) | __float_as_uint(a1)) & rt_zero));
      wgmma_wait<0>();
      fence_regs(o);
      if (kill) {
        mbar_arrive_if(kb + (B_VEMPTY - B_KFULL), wtid == 64 && !redo && g > 0);
        fence_regs(e);
        pack_lo();
#pragma unroll
        for (int j = 16; j < 32; j++) asm volatile("mov.u32 %0, 0;" : "=r"(p[j]));
        goto check;
      }
#pragma unroll
      for (int i = 32; i < 64; i++) asm volatile("" : "+f"(s[i])::"memory");
      mbar_arrive_if(kb + (B_VEMPTY - B_KFULL), wtid == 64 && !redo && g > 0);
      finish_p(a0, a1);
      if (__any_sync(0xffffffffu, !(mbar_try(v_full + 8 * (g & 1), ((g >> 1) & 1) | dep) &
                                    mbar_try(q_full + 8 * (rnd & 1), ((rnd >> 1) & 1) | dep)) ||
                                      !(a0 + a1 < 1.0995116e12f) || !(fminf(a0, a1) > (first ? 9.094947e-13f : -1.f)))) {
      check:
        bool bad = !(a0 + a1 < 1.0995116e12f);
        if (first) bad |= !(fminf(quad_sum(a0), quad_sum(a1)) > 9.094947e-13f);
        if (!redo && __any_sync(0xffffffffu, bad)) {
          d0 = d1 = first ? -INFINITY : 0.f;
#pragma unroll
          for (int j = 0; j < 16; j++) {
            if (j < 8 || !kill) {
              d0 = fmaxf(d0, fmaxf(s[4 * j], s[4 * j + 1]));
              d1 = fmaxf(d1, fmaxf(s[4 * j + 2], s[4 * j + 3]));
            }
          }
#pragma unroll
          for (int x = 1; x <= 2; x++) {
            d0 = fmaxf(d0, __shfl_xor_sync(0xffffffffu, d0, x));
            d1 = fmaxf(d1, __shfl_xor_sync(0xffffffffu, d1, x));
          }
          b0 += d0;
          b1 += d1;
          if (!first) {
            const float al0 = ex2(-d0), al1 = ex2(-d1);
            l0 *= al0;
            l1 *= al1;
#pragma unroll
            for (int j = 0; j < 16; j++) {
              o[4 * j] *= al0;
              o[4 * j + 1] *= al0;
              o[4 * j + 2] *= al1;
              o[4 * j + 3] *= al1;
            }
          }
          fl = 3;
          break;
        }
        mbar_wait(v_full + 8 * (g & 1), (g >> 1) & 1);
        mbar_wait(q_full + 8 * (rnd & 1), (rnd >> 1) & 1);
      }
      named_bar_sync(sched_own, 256);
      if (g == A_STEPS - 1) {
        if (first) write_o(pi0, pi1);
        fence_regs(o);
        wgmma_fence();
        issue_pv(vd, !first, 8);
        named_bar_arrive(sched_other, 256);
        if (first) store_o(rnd - 2, ST_BOX2);
        pi0 = rcp(quad_sum(l0 + a0));
        pi1 = rcp(quad_sum(l1 + a1));
        goto done;
      }
      wgmma_fence();
      issue_qk(qd0 + (rnd & 1) * DST, kd);
      if (first) write_o(pi0, pi1);
      fence_regs(o);
      if (kill) {
        wgmma_fence();
        issue_pv(vd, !first, 4);
      } else {
        wgmma_fence();
        issue_pv(vd, !first, 8);
      }
      named_bar_arrive(sched_other, 256);
      fl &= 2;
      l0 += a0;
      l1 += a1;
      if (rem == 0 || first) {
        if (first && (g > 0 || after_qkv)) store_o(g ? rnd - (rem == 0 ? 2 : 1) : 2, g ? ST_BOX2 : ST_BOX2Q);
        first = rem == 0;
        if (first) {
          pi0 = rcp(quad_sum(l0));
          pi1 = rcp(quad_sum(l1));
          l0 = l1 = b0 = b1 = 0.f;
          fl = 0;
          rem = item_m(item_of(maps, rnd)) + 1;
        }
      }
      rem--;
      g++;
      wgmma_wait<1>();
      fence_regs(s);
      mbar_arrive_if(kb + (B_KEMPTY - B_KFULL), wtid == 32);
      ST(g + 1)
      if (rem == 0 || shifted) {
        d0 = b0;
        d1 = b1;
        break;
      }
    }
  }
done:
#undef redo
#undef shifted
  wgmma_wait<0>();
  fence_regs(o);
  write_o(pi0, pi1);
  store_o(3, ST_BOX2L);
  ST(35)
  return sn;
}

constexpr int O_STAGES = 5;
constexpr int O_STAGE_BYTES = 32768;
constexpr int O_Y_OFF = 5 * 32768;
constexpr int O_X_OFF = 6 * 32768;
constexpr int O_NK = HDIM / 64;

__device__ __forceinline__ uint32_t out_stage(uint32_t st) { return ((0x43120u >> (4 * st)) & 7) * O_STAGE_BYTES; }

__device__ __forceinline__ void out_producer(const Maps& maps, uint32_t sbase, bool after_attn, bool dry) {
  const uint32_t bar = sbase + BAR_OFF;
  const uint32_t rank = blockIdx.x & 1;
  const int m_tile = maps.id[blockIdx.x][2] & 15, n_tile = maps.id[blockIdx.x][2] >> 4;
  uint32_t stage = 0, phase = 0;
#pragma unroll 1
  for (int ki = 0; ki < (dry ? 1 : O_NK); ki++) {
    const int kt = (ki & 14) * 4 + ((A_ORDER >> ((ki >> 4) * 4)) & 3) * 2 + (ki & 1);
    const uint32_t fb = bar + B_OFULL + 8 * stage, eb = bar + B_OEMPTY + 8 * stage;
    const uint32_t sa = sbase + out_stage(stage);
    if (ki < O_STAGES) {
      constexpr uint32_t LASTB = B_KEMPTY | ((B_QEMPTY + 8) << 8) | ((B_KEMPTY + 8) << 16) | (B_VEMPTY << 24);
      if (ki > 0 && after_attn) mbar_wait_sleep(bar + ((LASTB >> (8 * ki - 8)) & 255), ki == 2);
      mbar_arrive_cluster_if(eb, 0, !dry);
      mbar_arrive_cluster_if(eb, 1, !dry);
    }
    if (ki == 32) mbar_wait_sleep(bar + B_CTX, 0);
    if (!dry) {
      mbar_wait_sleep(eb, phase);
      mbar_expect_tx(fb, O_STAGE_BYTES);
      tma_load_2d_mc(sa + 16384 + rank * 8192, &maps.ob, fb, n_tile * 128 + rank * 64, kt * 64, (uint16_t)3);
      tma_load_2d(sa, &maps.oa, fb, kt * 64, m_tile * 128);
    }
    if (++stage == O_STAGES) { stage = 0; phase ^= 1; }
  }
  if (!dry) mbar_wait_sleep(bar + B_OY, 0);
}

__device__ __forceinline__ void out_side(const Maps& maps, uint32_t smem0, const float (&gv)[4]) {
  PHASE_PROLOGUE
  const int m_tile = maps.id[blockIdx.x][2] & 15, n_tile = maps.id[blockIdx.x][2] >> 4;
  if (__shfl_sync(0xffffffffu, warp, 0) == 0) {
    if (elect_one()) {
      mbar_expect_tx(bar + B_OY, 65536);
      tma_load_2d(sbase + O_X_OFF, &maps.a[0], bar + B_OY, n_tile * 128, m_tile * 128);
      tma_load_2d(sbase + O_X_OFF + 16384, &maps.a[0], bar + B_OY, n_tile * 128 + 64, m_tile * 128);
      TD(10)
      cnt_wait(CNT_Y2, DM);
      TD(7)
      tma_load_2d(sbase + O_Y_OFF, &maps.y, bar + B_OY, m_tile * 128, n_tile * 128);
      tma_load_2d(sbase + O_Y_OFF + 16384, &maps.y, bar + B_OY, m_tile * 128 + 64, n_tile * 128);
    }
  }
  mbar_wait_sleep(bar + B_OY, 0);
  if (wtid == 0) { TD(12) }
  const int st_row = warp * 16 + (lane & 7) + ((lane >> 3) & 1) * 8;
  const int mrow = (lane & 7) + ((lane >> 4) & 1) * 8;
  const int mchunk = warp * 2 + ((lane >> 3) & 1);
  const uint32_t xrow = sbase + O_X_OFF + st_row * 128;
  const uint32_t yrow = sbase + O_Y_OFF + mrow * 128 + ((mchunk ^ (lane & 7)) << 4);
  uint32_t y[8][4], x[8][4], om[4];
#pragma unroll
  for (int i = 0; i < 4; i++) om[i] = pack_bf16(1.0f - gv[i], 1.0f - gv[i]);
  auto xa = [&](int h, int i) { return xrow + h * 8192 + (i >> 2) * 16384 + ((((i & 3) * 2 + (lane >> 4)) ^ (lane & 7)) << 4); };
  auto load = [&](int r, int h, int i) {
    ldsm4t(y[r], yrow + h * 16384 + i * 2048);
    asm volatile("ldmatrix.sync.aligned.m8n8.x4.shared.b16 {%0, %1, %2, %3}, [%4];"
                 : "=r"(x[r][0]), "=r"(x[r][1]), "=r"(x[r][2]), "=r"(x[r][3])
                 : "r"(xa(h, i)));
  };
  auto store = [&](int r, int h, int i, uint32_t om0, uint32_t om1) {
    stmatrix_x4(xa(h, i), mul_bf2(om0, mul_bf2(x[r][0], y[r][0])), mul_bf2(om1, mul_bf2(x[r][1], y[r][1])),
                mul_bf2(om0, mul_bf2(x[r][2], y[r][2])), mul_bf2(om1, mul_bf2(x[r][3], y[r][3])));
  };
#pragma unroll 1
  for (int h = 0; h < 2; h++) {
#pragma unroll
    for (int i = 0; i < 8; i++) load(i, h, i);
#pragma unroll
    for (int i = 0; i < 8; i++) store(i, h, i, h ? om[2] : om[0], h ? om[3] : om[1]);
  }
  __syncwarp();
  mbar_arrive_if(bar + B_OY + 8, lane == 0);
  if (wtid == 0) { TD(13) }
}

__device__ __forceinline__ uint32_t out_gemm(const Maps& maps, uint32_t smem0, uint32_t sn) {
  PHASE_PROLOGUE
  const int m_tile = maps.id[blockIdx.x][2] & 15, n_tile = maps.id[blockIdx.x][2] >> 4;
  float acc[2][64];
  undef_regs(acc[0]);
  undef_regs(acc[1]);
  uint32_t stage = 0, phase = 0, prev_stage = 0;
  GT(gti++)
  const float* gp = g_gate + m_tile * 128 + warp * 16 + (lane >> 2);
  const float gv[4] = {__ldcg(gp), __ldcg(gp + 8), __ldcg(gp + 64), __ldcg(gp + 72)};
  if (wg == 1) {
    out_side(maps, smem0, gv);
    return sn;
  }
#pragma unroll 1
  for (int kt = 0; kt < O_NK; kt++) {
    uint32_t da = (uint32_t)make_desc(sbase + out_stage(stage), 16, 0, 0);
    uint32_t db = (uint32_t)make_desc(sbase + out_stage(stage) + 16384, 8192, 0, 0);
    asm volatile("" : "+r"(da), "+r"(db));
    mbar_wait(bar + B_OFULL + 8 * stage, phase);
    GT(gti++)
    constexpr int OWAIT = 2;
    constexpr uint64_t DHI = DESC_SW128 | ((uint64_t)(1024 >> 4) << 32);
#pragma unroll
    for (int kk = 0; kk < 4; kk++) {
      wgmma_wait<OWAIT>();
      if (kk == OWAIT)
        mbar_arrive_cluster_if(bar + B_OEMPTY + 8 * prev_stage, wtid >> 6,
                               (wtid & 63) == 32 && kt > 0 && kt - 1 + O_STAGES < O_NK);
      wgmma_fence();
      wgmma_m64n128_ss_tb(acc[0], DHI | (da + kk * 2), DHI | (db + kk * 128), (kt | kk) != 0);
      wgmma_m64n128_ss_tb(acc[1], DHI | (da + 512 + kk * 2), DHI | (db + kk * 128), (kt | kk) != 0);
      wgmma_commit();
    }
    prev_stage = stage;
    if (++stage == O_STAGES) { stage = 0; phase ^= 1; }
  }
  if (tid == 0) { TD(14) }
  st_wait(bar, wg, sn - 1);
  const int st_row = warp * 16 + (lane & 7) + ((lane >> 3) & 1) * 8;
  const uint32_t rowa = sbase + O_X_OFF + st_row * 128;
  wgmma_wait<0>();
  fence_regs(acc[0]);
  fence_regs(acc[1]);
  GT(gti++)
  uint32_t gg[4];
#pragma unroll
  for (int i = 0; i < 4; i++) gg[i] = pack_bf16(gv[i], gv[i]);
  mbar_wait(bar + B_OY + 8, 0);
#pragma unroll
  for (int i = 0; i < 16; i++) {
    const int h = i & 1, j = i & 14;
    const uint32_t addr = rowa + h * 8192 + (j >> 3) * 16384 + ((((j & 7) + (lane >> 4)) ^ (st_row & 7)) << 4);
    uint32_t b0, b1, b2, b3;
    asm volatile("ldmatrix.sync.aligned.m8n8.x4.shared.b16 {%0, %1, %2, %3}, [%4];"
                 : "=r"(b0), "=r"(b1), "=r"(b2), "=r"(b3)
                 : "r"(addr));
    const float* a = acc[h] + 4 * j;
    const uint32_t gg0 = gg[2 * h], gg1 = gg[2 * h + 1];
    stmatrix_x4(addr, add_bf2(mul_bf2(gg0, pack_bf16(a[0], a[1])), b0),
                add_bf2(mul_bf2(gg1, pack_bf16(a[2], a[3])), b1), add_bf2(mul_bf2(gg0, pack_bf16(a[4], a[5])), b2),
                add_bf2(mul_bf2(gg1, pack_bf16(a[6], a[7])), b3));
    if (i == 7) st_post(bar, wg, wtid, sn, ST_BOX1, &maps.oc, sbase + O_X_OFF, n_tile * 128, m_tile * 128, -1);
  }
  fence_proxy_async();
  named_bar_sync(1, 128);
  if (__shfl_sync(0xffffffffu, warp, 0) == 0) {
    if (elect_one()) {
      tma_store_2d(&maps.oc, sbase + O_X_OFF + 16384, n_tile * 128 + 64, m_tile * 128);
      tma_store_commit();
    }
  }
  GT(gti++)
  return sn + 1;
}

__device__ __noinline__ void leave_kernel(int mask) {
  if (!(mask & 4)) return;
  if (atomicAdd(g_cnt + CNT_DONE * 32, 1u) == 2 * gridDim.x - 1) {
    for (int i = 0; i < CNT_N; i++) g_cnt[i * 32] = 0;
  }
}

__device__ __noinline__ void side_jobs(const Maps& maps, uint32_t sbase) {
  const int w12 = __shfl_sync(0xffffffffu, threadIdx.x >> 5, 0);
  gate_rows(maps, sbase, (blockIdx.x - 128) * 12 + w12, w12, threadIdx.x & 31);
  fence_proxy_async();
  __syncthreads();
  if (threadIdx.x == 320) cnt_signal_release(CNT_PREP, 1);
}

__global__ void __launch_bounds__(384, 1) fused_kernel(int mask, const __grid_constant__ Maps maps) {
  extern __shared__ __align__(1024) uint8_t smem_raw[];
  {
    const uint32_t sbase = __shfl_sync(0xffffffffu, smem_u32(smem_raw), 0);
    const uint32_t bar = sbase + BAR_OFF;
    const int tid = threadIdx.x;
    const bool do_qkv = (mask & 1) && blockIdx.x < 128;
    TL(0, 0)
    if (__shfl_sync(0xffffffffu, tid >> 5, 0) == 1 && do_qkv) {
      if (elect_one()) {
        for (int i = 0; i < G_STAGES; i++) mbar_init(bar + B_GFULL + 8 * i, 1);
        fence_barrier_init();
        qkv_producer(maps, sbase, true);
      }
    }
    if (tid == 0) {
      for (int i = 0; i < G_STAGES; i++) {
        mbar_init(bar + B_GEMPTY + 8 * i, 2);
        mbar_init(bar + B_SFULL + 8 * i, 4);
        mbar_init(bar + B_SFREE + 8 * i, 1);
      }
      for (int i = 0; i < 2; i++) {
        mbar_init(bar + B_OFREE + 8 * i, 1);
        mbar_init(bar + B_QFULL + 8 * i, 1);
        mbar_init(bar + B_QEMPTY + 8 * i, 2);
        mbar_init(bar + B_KFULL + 8 * i, 1);
        mbar_init(bar + B_KEMPTY + 8 * i, 2);
        mbar_init(bar + B_VFULL + 8 * i, 1);
        mbar_init(bar + B_VEMPTY + 8 * i, 2);
      }
      for (int i = 0; i < O_STAGES; i++) {
        mbar_init(bar + B_OFULL + 8 * i, 1);
        mbar_init(bar + B_OEMPTY + 8 * i, 2);
      }
      mbar_init(bar + B_OY, 1);
      mbar_init(bar + B_CTX, 1);
      mbar_init(bar + B_OY + 8, 4);
      mbar_init(bar + B_QDONE, 2);
      for (int i = 0; i < 8; i++) mbar_init(bar + B_CFULL + 8 * i, 1);
      for (int i = 0; i < CNT_N; i++) asm volatile("st.shared.u32 [%0], 0;" ::"r"(bar + B_PEND + 4 * i) : "memory");
      fence_barrier_init();
    }
    __syncthreads();
    asm volatile("barrier.cluster.arrive.relaxed.aligned;" ::: "memory");
    if ((mask & 1) && blockIdx.x >= 128) side_jobs(maps, sbase);
  }
  uint32_t smem0 = smem_u32(smem_raw);
  PHASE_PROLOGUE
  const bool do_qkv = (mask & 1) && blockIdx.x < 128, do_out = (mask & 4) && blockIdx.x < 128;
  TL(0, 1)

  if (wg != 2) {
    reg_alloc<232>();
    uint32_t sn = 0;
    float o[64];
    if (do_qkv) {
      sn = qkv_consumer(maps, smem_u32(smem_raw), mask & 2, o);
    } else {
      undef_regs(o);
    }
    TL(0, 2) TL(1, 0) TL(1, 1)
    asm volatile("barrier.cluster.wait.acquire.aligned;" ::: "memory");
    if (mask & 2) {
      sn = attn_consumer(maps, smem_u32(smem_raw), sn, o, mask & 1);
      TL(2, 0)
      if ((mask & 4) && blockIdx.x < 128 && __shfl_sync(0xffffffffu, threadIdx.x, 0) < 128) {
        named_bar_arrive(3, 256);
      } else {
        const uint32_t b2 = blockIdx.x * 2 + (threadIdx.x >> 7);
        const bool fused = mask & 4, mainc = blockIdx.x < 128;
        const uint32_t first = __shfl_sync(0xffffffffu, !fused ? b2 : mainc ? conv_first(maps) : (b2 - 256) * 128, 0);
        conv_consumer(maps, smem_u32(smem_raw), first, !fused ? 264 : mainc ? 16 : 1,
                      !fused ? DM : mainc ? (first | 127) + 1 : first + C_SIDE, fused && !mainc);
      }
      TL(1, 2) TL(2, 1) TL(2, 2)
    }
    TL(3, 0) TL(3, 1)
    if ((mask & 4) && blockIdx.x < 128) sn = out_gemm(maps, smem_u32(smem_raw), sn);
    {
      uint32_t smem0 = smem_u32(smem_raw);
      PHASE_PROLOGUE
      st_wait(bar, wg, sn - 2);
      st_post(bar, wg, wtid, sn, ST_END, nullptr, 0, 0, 0, -1);
      tma_store_wait_read<0>();
    }
  } else {
    reg_dealloc<40>();
    asm volatile("barrier.cluster.wait.acquire.aligned;" ::: "memory");
    const int w = __shfl_sync(0xffffffffu, tid >> 5, 0) - 8;
    if (w < 2) {
      if (do_qkv) prep_agent(maps, sbase, w, lane);
      if (elect_one()) store_agent(bar, w);
      TL2(3, 2)
    } else {
      if (elect_one()) {
        const bool dry = w == 2;
        if (do_qkv && !dry) qkv_producer(maps, sbase, false);
        if (mask & 2) attn_producer(maps, sbase, do_qkv, do_out, dry);
        if (do_out) out_producer(maps, sbase, mask & 2, dry);
        if (dry) { TD(5) }
      }
      __syncwarp();
      if (w == 2) publisher(bar, tid & 31, !(mask & 2) ? 2 : do_out ? 3 : 4, !do_out ? ~0u : mask & 2);
      if ((tid & 31) == 0) leave_kernel(mask);
    }
  }
}

typedef CUresult (*PFN_tmapEncode)(CUtensorMap*, CUtensorMapDataType, cuuint32_t, void*, const cuuint64_t*,
                                   const cuuint64_t*, const cuuint32_t*, const cuuint32_t*, CUtensorMapInterleave,
                                   CUtensorMapSwizzle, CUtensorMapL2promotion, CUtensorMapFloatOOBfill);
static PFN_tmapEncode s_encode = nullptr;

static void make_map_2d(CUtensorMap* m, const void* ptr, int rows, int cols, int box_rows) {
  cuuint64_t dims[2] = {(cuuint64_t)cols, (cuuint64_t)rows};
  cuuint64_t strides[1] = {(cuuint64_t)cols * 2};
  cuuint32_t box[2] = {cols < 64 ? 32u : 64u, (cuuint32_t)box_rows};
  cuuint32_t es[2] = {1, 1};
  s_encode(m, CU_TENSOR_MAP_DATA_TYPE_BFLOAT16, 2, const_cast<void*>(ptr), dims, strides, box, es,
           CU_TENSOR_MAP_INTERLEAVE_NONE, cols < 64 ? CU_TENSOR_MAP_SWIZZLE_64B : CU_TENSOR_MAP_SWIZZLE_128B, CU_TENSOR_MAP_L2_PROMOTION_L2_256B,
           CU_TENSOR_MAP_FLOAT_OOB_FILL_NONE);
}
static void make_map_3d(CUtensorMap* m, const void* ptr, int rows, int cols, int box_rows, int box_chunks) {
  cuuint64_t dims[3] = {64, (cuuint64_t)rows, (cuuint64_t)(cols / 64)};
  cuuint64_t strides[2] = {(cuuint64_t)cols * 2, 128};
  cuuint32_t box[3] = {64, (cuuint32_t)box_rows, (cuuint32_t)box_chunks};
  cuuint32_t es[3] = {1, 1, 1};
  s_encode(m, CU_TENSOR_MAP_DATA_TYPE_BFLOAT16, 3, const_cast<void*>(ptr), dims, strides, box, es,
           CU_TENSOR_MAP_INTERLEAVE_NONE, CU_TENSOR_MAP_SWIZZLE_128B, CU_TENSOR_MAP_L2_PROMOTION_L2_256B,
           CU_TENSOR_MAP_FLOAT_OOB_FILL_NONE);
}

static cudaLaunchConfig_t fused_cfg(cudaLaunchAttribute* at) {
  cudaLaunchConfig_t cfg = {};
  cfg.gridDim = dim3(132);
  cfg.blockDim = dim3(384);
  cfg.dynamicSmemBytes = SMEM_BYTES;
  cfg.stream = cudaStreamPerThread;
  at[0].id = cudaLaunchAttributeClusterDimension;
  at[0].val.clusterDim.x = 2;
  at[0].val.clusterDim.y = 1;
  at[0].val.clusterDim.z = 1;
  cfg.attrs = at;
  cfg.numAttrs = 1;
  return cfg;
}

extern "C" void kernel_launch(void* const* d_in, const int* in_sizes, int n_in, void* d_out, int out_size) {
  const bf16* x = (const bf16*)d_in[0];
  const bf16* ckv = (const bf16*)d_in[1];
  const bf16* wq = (const bf16*)d_in[2];
  const bf16* wuk = (const bf16*)d_in[3];
  const bf16* wuv = (const bf16*)d_in[4];
  const bf16* wo = (const bf16*)d_in[5];
  const bf16* bk = (const bf16*)d_in[7];
  const bf16* bv = (const bf16*)d_in[8];
  const bf16* shift_k = (const bf16*)d_in[9];
  const bf16* ssm_k = (const bf16*)d_in[10];
  const bf16* ssm_D = (const bf16*)d_in[11];
  const bf16* gate_w = (const bf16*)d_in[12];
  bf16* out = (bf16*)d_out;

  static void *pq = nullptr, *pk = nullptr, *pv = nullptr, *pctx = nullptr, *pb = nullptr, *pu = nullptr;
  static int max_clusters = 0;
  if (!s_encode) {
    void* fn = nullptr;
    cudaDriverEntryPointQueryResult qres;
    cudaGetDriverEntryPoint("cuTensorMapEncodeTiled", &fn, cudaEnableDefault, &qres);
    s_encode = (PFN_tmapEncode)fn;
    cudaGetSymbolAddress(&pq, g_q);
    cudaGetSymbolAddress(&pk, g_k);
    cudaGetSymbolAddress(&pv, g_v);
    cudaGetSymbolAddress(&pctx, g_ctx);
    cudaGetSymbolAddress(&pb, g_y2T);
    cudaGetSymbolAddress(&pu, g_kvT);
    cudaFuncSetAttribute(fused_kernel, cudaFuncAttributeMaxDynamicSharedMemorySize, SMEM_BYTES);
    cudaLaunchAttribute at[1];
    cudaLaunchConfig_t cfg = fused_cfg(at);
    if (cudaOccupancyMaxActiveClusters(&max_clusters, fused_kernel, &cfg) != cudaSuccess) max_clusters = 0;
  }

  Maps all = {};
  make_map_2d(&all.a[0], x, S_LEN, DM, 128);
  make_map_2d(&all.a[1], ckv, S_LEN, DC, 128);
  make_map_3d(&all.b[0], wq, DM, HDIM, 64, 4);
  make_map_3d(&all.b[1], wuk, DC, HDIM, 64, 4);
  make_map_3d(&all.b[2], wuv, DC, HDIM, 64, 4);
  make_map_2d(&all.c[0], pq, S_LEN, HDIM, 64);
  make_map_2d(&all.c[1], pk, S_LEN, HDIM, 64);
  make_map_2d(&all.c[2], pv, S_LEN, HDIM, 64);
  make_map_3d(&all.q, pq, S_LEN, HDIM, 128, 2);
  make_map_3d(&all.k, pk, S_LEN, HDIM, 128, 2);
  make_map_3d(&all.v, pv, S_LEN, HDIM, 128, 2);
  make_map_2d(&all.o, pctx, S_LEN, HDIM, 64);
  all.ssm_k = ssm_k;
  all.ssm_D = ssm_D;
  make_map_2d(&all.oa, pctx, S_LEN, HDIM, 128);
  make_map_2d(&all.ob, wo, HDIM, DM, 64);
  make_map_2d(&all.oc, out, S_LEN, DM, 128);
  make_map_2d(&all.y, pb, DM, S_LEN, 128);
  make_map_2d(&all.cu, pu, DM * 64, 32, 64);
  make_map_2d(&all.ch, ssm_k, DM * 64, 32, 64);

  make_map_2d(&all.bk, bk, S_LEN, DM, 35);
  make_map_2d(&all.bv, bv, S_LEN, DM, 32);
  for (int b = 0; b < 128; b++) {
    const int c = b >> 1, r = b & 1;
    const int G = c < 4 ? 0 : c < 36 ? (c - 4) % 8 : 1 + (c - 36) % 7;
    const int i = c < 4 ? 4 + c : c < 36 ? (c - 4) / 8 : 4 + (c - 36) / 7;
    all.id[b][0] = r + 2 * (i & 1) + 4 * (G & 3) + 16 * (i >> 1) + 64 * (G >> 2);
    all.id[b][1] = r + 2 * i + 16 * G;
    all.id[b][2] = r + 2 * G + 16 * i;
  }
  all.shift_k = shift_k;
  all.x = x;
  all.gate_w = gate_w;
  cudaLaunchAttribute at[1];
  cudaLaunchConfig_t cfg = fused_cfg(at);
  if (max_clusters >= 66) {
    cudaLaunchKernelEx(&cfg, fused_kernel, 7, all);
  } else {
    for (int m = 1; m <= 4; m <<= 1) cudaLaunchKernelEx(&cfg, fused_kernel, m, all);
  }
}
```

```cpp
#include <cuda_runtime.h>
#include <cuda_bf16.h>
#include <cuda.h>
#include <stdint.h>

typedef __nv_bfloat16 bf16;
#define INPLACE 3

constexpr int S_LEN = 2048;
constexpr int DM = 1024;
constexpr int NH = 32;
constexpr int HD = 128;
constexpr int DC = 512;
constexpr int HDIM = NH * HD;

__device__ __align__(1024) bf16 g_q[S_LEN * HDIM];
__device__ __align__(1024) bf16 g_k[S_LEN * HDIM];
__device__ __align__(1024) bf16 g_v[S_LEN * HDIM];
#define g_ctx g_q
__device__ __align__(1024) bf16 g_kvT[DM * S_LEN];
#define g_y2T g_kvT
__device__ __align__(1024) float g_gate[S_LEN];
enum { CNT_KV = 0, CNT_PREP = CNT_KV + 2, CNT_CTX, CNT_Y2 = CNT_CTX + 2, CNT_DONE = CNT_Y2 + 2, CNT_N };
__device__ unsigned int g_cnt[CNT_N * 32];

#define TL(k, i)
#define TL2(k, i)
#define TD(i)
#define CT(i)
#define GT(i)
#define GA(i)
#define ST(i)

__device__ __forceinline__ uint32_t smem_u32(const void* p) { return (uint32_t)__cvta_generic_to_shared(p); }

__device__ __forceinline__ void mbar_init(uint32_t bar, uint32_t count) {
  asm volatile("mbarrier.init.shared::cta.b64 [%0], %1;" ::"r"(bar), "r"(count));
}
__device__ __forceinline__ void mbar_expect_tx(uint32_t bar, uint32_t bytes) {
  asm volatile("mbarrier.arrive.expect_tx.shared::cta.b64 _, [%0], %1;" ::"r"(bar), "r"(bytes) : "memory");
}
__device__ __forceinline__ void mbar_arrive(uint32_t bar) {
  asm volatile("mbarrier.arrive.shared::cta.b64 _, [%0];" ::"r"(bar) : "memory");
}
__device__ __forceinline__ void mbar_wait(uint32_t bar, uint32_t parity) {
  uint32_t done;
  uint32_t spins = 0;
  do {
    asm volatile(
        "{\n.reg .pred p;\n"
        "mbarrier.try_wait.parity.shared::cta.b64 p, [%1], %2;\n"
        "selp.u32 %0, 1, 0, p;\n}\n"
        : "=r"(done)
        : "r"(bar), "r"(parity)
        : "memory");
    if (++spins > (1u << 22)) break;
  } while (!done);
}
__device__ __forceinline__ bool mbar_try(uint32_t bar, uint32_t parity) {
  uint32_t done;
  asm volatile(
      "{\n.reg .pred p;\n"
      "mbarrier.try_wait.parity.shared::cta.b64 p, [%1], %2;\n"
      "selp.u32 %0, 1, 0, p;\n}\n"
      : "=r"(done)
      : "r"(bar), "r"(parity)
      : "memory");
  return done != 0;
}
__device__ __forceinline__ bool elect_one() {
  uint32_t pred;
  asm volatile("{\n.reg .pred p;\nelect.sync _|p, 0xffffffff;\nselp.u32 %0, 1, 0, p;\n}\n" : "=r"(pred));
  return pred != 0;
}
__device__ __forceinline__ void mbar_arrive_if(uint32_t bar, bool pred) {
  asm volatile(
      "{\n.reg .pred p;\nsetp.ne.b32 p, %1, 0;\n"
      "@p mbarrier.arrive.shared::cta.b64 _, [%0];\n}\n" ::"r"(bar),
      "r"((uint32_t)pred)
      : "memory");
}
__device__ __forceinline__ void mbar_wait_sleep(uint32_t bar, uint32_t parity) {
  uint32_t done;
  uint32_t spins = 0;
  do {
    asm volatile(
        "{\n.reg .pred p;\n"
        "mbarrier.try_wait.parity.shared::cta.b64 p, [%1], %2, %3;\n"
        "selp.u32 %0, 1, 0, p;\n}\n"
        : "=r"(done)
        : "r"(bar), "r"(parity), "r"(20000u)
        : "memory");
    if (++spins > (1u << 16)) break;
  } while (!done);
}
__device__ __forceinline__ void fence_barrier_init() {
  asm volatile("fence.mbarrier_init.release.cluster;" ::: "memory");
}
__device__ __forceinline__ void fence_proxy_async() {
  asm volatile("fence.proxy.async.shared::cta;" ::: "memory");
}
__device__ __forceinline__ void named_bar_sync(int id, int nthreads) {
  asm volatile("bar.sync %0, %1;" ::"r"(id), "r"(nthreads) : "memory");
}
__device__ __forceinline__ void named_bar_arrive(int id, int nthreads) {
  asm volatile("bar.arrive %0, %1;" ::"r"(id), "r"(nthreads) : "memory");
}
__device__ __forceinline__ void tma_load_2d(uint32_t dst, const CUtensorMap* m, uint32_t bar, int c0, int c1) {
  asm volatile(
      "cp.async.bulk.tensor.2d.shared::cluster.global.mbarrier::complete_tx::bytes [%0], [%1, {%3, %4}], [%2];" ::"r"(dst),
      "l"(reinterpret_cast<uint64_t>(m)), "r"(bar), "r"(c0), "r"(c1)
      : "memory");
}
__device__ __forceinline__ void tma_load_3d(uint32_t dst, const CUtensorMap* m, uint32_t bar, int c0, int c1, int c2) {
  asm volatile(
      "cp.async.bulk.tensor.3d.shared::cluster.global.mbarrier::complete_tx::bytes [%0], [%1, {%3, %4, %5}], [%2];" ::"r"(dst),
      "l"(reinterpret_cast<uint64_t>(m)), "r"(bar), "r"(c0), "r"(c1), "r"(c2)
      : "memory");
}
__device__ __forceinline__ void tma_store_2d(const CUtensorMap* m, uint32_t src, int c0, int c1) {
  asm volatile("cp.async.bulk.tensor.2d.global.shared::cta.bulk_group [%0, {%2, %3}], [%1];" ::"l"(
                   reinterpret_cast<uint64_t>(m)),
               "r"(src), "r"(c0), "r"(c1)
               : "memory");
}
__device__ __forceinline__ void bulk_load(uint32_t dst, const void* src, uint32_t bytes, uint32_t bar) {
  asm volatile("cp.async.bulk.shared::cluster.global.mbarrier::complete_tx::bytes [%0], [%1], %2, [%3];" ::"r"(dst),
               "l"(src), "r"(bytes), "r"(bar)
               : "memory");
}
__device__ __forceinline__ void tma_load_2d_mc(uint32_t dst, const CUtensorMap* m, uint32_t bar, int c0, int c1,
                                               uint16_t mask) {
  asm volatile(
      "cp.async.bulk.tensor.2d.shared::cluster.global.mbarrier::complete_tx::bytes.multicast::cluster [%0], [%1, {%3, "
      "%4}], [%2], %5;" ::"r"(dst),
      "l"(reinterpret_cast<uint64_t>(m)), "r"(bar), "r"(c0), "r"(c1), "h"(mask)
      : "memory");
}
__device__ __forceinline__ void mbar_arrive_cluster_if(uint32_t bar, uint32_t cta, bool pred) {
  asm volatile(
      "{\n.reg .b32 ra;\n.reg .pred p;\nsetp.ne.b32 p, %2, 0;\n"
      "mapa.shared::cluster.u32 ra, %0, %1;\n"
      "@p mbarrier.arrive.shared::cluster.b64 _, [ra];\n}\n" ::"r"(bar),
      "r"(cta), "r"((uint32_t)pred)
      : "memory");
}
__device__ __forceinline__ uint64_t policy_evict_first() {
  uint64_t pol;
  asm volatile("createpolicy.fractional.L2::evict_first.b64 %0, 1.0;" : "=l"(pol));
  return pol;
}
__device__ __forceinline__ void tma_load_2d_hint(uint32_t dst, const CUtensorMap* m, uint32_t bar, int c0, int c1,
                                                 uint64_t pol) {
  asm volatile(
      "cp.async.bulk.tensor.2d.shared::cluster.global.mbarrier::complete_tx::bytes.L2::cache_hint [%0], [%1, {%3, %4}], "
      "[%2], %5;" ::"r"(dst),
      "l"(reinterpret_cast<uint64_t>(m)), "r"(bar), "r"(c0), "r"(c1), "l"(pol)
      : "memory");
}
__device__ __forceinline__ void tma_load_3d_hint(uint32_t dst, const CUtensorMap* m, uint32_t bar, int c0, int c1,
                                                 int c2, uint64_t pol) {
  asm volatile(
      "cp.async.bulk.tensor.3d.shared::cluster.global.mbarrier::complete_tx::bytes.L2::cache_hint [%0], [%1, {%3, %4, "
      "%5}], [%2], %6;" ::"r"(dst),
      "l"(reinterpret_cast<uint64_t>(m)), "r"(bar), "r"(c0), "r"(c1), "r"(c2), "l"(pol)
      : "memory");
}
__device__ __forceinline__ void bulk_load_hint(uint32_t dst, const void* src, uint32_t bytes, uint32_t bar, uint64_t pol) {
  asm volatile(
      "cp.async.bulk.shared::cluster.global.mbarrier::complete_tx::bytes.L2::cache_hint [%0], [%1], %2, [%3], %4;" ::"r"(dst),
      "l"(src), "r"(bytes), "r"(bar), "l"(pol)
      : "memory");
}
__device__ __forceinline__ void cnt_signal_release(int which, uint32_t n) {
  asm volatile("red.release.gpu.global.add.u32 [%0], %1;" ::"l"(g_cnt + which * 32), "r"(n) : "memory");
}
__device__ __forceinline__ void cnt_wait(int which, uint32_t target) {
  uint32_t v, spins = 0;
  while (true) {
    asm volatile("ld.acquire.gpu.global.u32 %0, [%1];" : "=r"(v) : "l"(g_cnt + which * 32) : "memory");
    if (v >= target || ++spins > (1u << 18)) break;
    __nanosleep(64);
  }
  asm volatile("fence.proxy.async.global;" ::: "memory");
}
__device__ __forceinline__ void tma_store_commit() { asm volatile("cp.async.bulk.commit_group;" ::: "memory"); }
template <int N>
__device__ __forceinline__ void tma_store_wait_read() {
  asm volatile("cp.async.bulk.wait_group.read %0;" ::"n"(N) : "memory");
}
template <int N>
__device__ __forceinline__ void tma_store_wait() {
  asm volatile("cp.async.bulk.wait_group %0;" ::"n"(N) : "memory");
}
__device__ __forceinline__ void wgmma_fence() { asm volatile("wgmma.fence.sync.aligned;" ::: "memory"); }
__device__ __forceinline__ void wgmma_commit() { asm volatile("wgmma.commit_group.sync.aligned;" ::: "memory"); }
template <int N>
__device__ __forceinline__ void wgmma_wait() {
  asm volatile("wgmma.wait_group.sync.aligned %0;" ::"n"(N) : "memory");
}
template <int R>
__device__ __forceinline__ void reg_alloc() { asm volatile("setmaxnreg.inc.sync.aligned.u32 %0;" ::"n"(R)); }
template <int R>
__device__ __forceinline__ void reg_dealloc() { asm volatile("setmaxnreg.dec.sync.aligned.u32 %0;" ::"n"(R)); }

__device__ __forceinline__ void stmatrix_x4(uint32_t addr, uint32_t r0, uint32_t r1, uint32_t r2, uint32_t r3) {
  asm volatile("stmatrix.sync.aligned.m8n8.x4.shared.b16 [%0], {%1, %2, %3, %4};" ::"r"(addr), "r"(r0), "r"(r1),
               "r"(r2), "r"(r3)
               : "memory");
}
__device__ __forceinline__ uint32_t pack_bf16(float lo, float hi) {
  uint32_t r;
  asm("cvt.rn.bf16x2.f32 %0, %1, %2;" : "=r"(r) : "f"(hi), "f"(lo));
  return r;
}
__device__ __forceinline__ float bf16_round(float x) { return __bfloat162float(__float2bfloat16_rn(x)); }
__device__ __forceinline__ float bf_lo(uint32_t v) { return __uint_as_float(v << 16); }
__device__ __forceinline__ float bf_hi(uint32_t v) { return __uint_as_float(v & 0xffff0000u); }
__device__ __forceinline__ uint4 lds128(uint32_t a) {
  uint4 v;
  asm volatile("ld.shared.v4.u32 {%0, %1, %2, %3}, [%4];" : "=r"(v.x), "=r"(v.y), "=r"(v.z), "=r"(v.w) : "r"(a));
  return v;
}
__device__ __forceinline__ void sts128(uint32_t a, uint4 v) {
  asm volatile("st.shared.v4.u32 [%0], {%1, %2, %3, %4};" ::"r"(a), "r"(v.x), "r"(v.y), "r"(v.z), "r"(v.w) : "memory");
}
__device__ __forceinline__ uint32_t mul_bf2(uint32_t a, uint32_t b) {
  uint32_t r;
  asm("mul.rn.bf16x2 %0, %1, %2;" : "=r"(r) : "r"(a), "r"(b));
  return r;
}
__device__ __forceinline__ uint32_t add_bf2(uint32_t a, uint32_t b) {
  uint32_t r;
  asm("add.rn.bf16x2 %0, %1, %2;" : "=r"(r) : "r"(a), "r"(b));
  return r;
}
__device__ __forceinline__ float ex2(float x) {
  float y;
  asm("ex2.approx.ftz.f32 %0, %1;" : "=f"(y) : "f"(x));
  return y;
}
__device__ __forceinline__ float rcp(float x) {
  float y;
  asm("rcp.approx.ftz.f32 %0, %1;" : "=f"(y) : "f"(x));
  return y;
}
template <int N>
__device__ __forceinline__ void fence_regs(float (&r)[N]) {
#pragma unroll
  for (int i = 0; i < N; i++) asm volatile("" : "+f"(r[i])::"memory");
}

template <int N>
__device__ __forceinline__ void undef_regs(float (&r)[N]) {
#pragma unroll
  for (int i = 0; i < N; i++) asm volatile("" : "=f"(r[i]));
}
template <int N>
__device__ __forceinline__ void fence_regs_u(uint32_t (&r)[N]) {
#pragma unroll
  for (int i = 0; i < N; i++) asm volatile("" : "+r"(r[i])::"memory");
}

constexpr uint64_t DESC_SW128 = 1ull << 62;
__device__ __forceinline__ uint64_t make_desc(uint32_t addr, uint32_t lbo_bytes, uint32_t sbo_bytes, uint64_t swz) {
  return (uint64_t)((addr & 0x3FFFF) >> 4) | ((uint64_t)((lbo_bytes & 0x3FFFF) >> 4) << 16) |
         ((uint64_t)((sbo_bytes & 0x3FFFF) >> 4) << 32) | swz;
}

__device__ __forceinline__ uint64_t desc_add(uint64_t d, uint32_t off16) {
  return (d & 0xFFFFFFFF00000000ull) | (uint64_t)((uint32_t)d + off16);
}

__device__ __forceinline__ void wgmma_m64n256_ss_tb(float (&d)[128], uint64_t da, uint64_t db, int sd) {
  asm volatile(
    "{\n.reg .pred p;\nsetp.ne.b32 p, %130, 0;\n"
    "wgmma.mma_async.sync.aligned.m64n256k16.f32.bf16.bf16 "
    "{%0, %1, %2, %3, %4, %5, %6, %7, %8, %9, %10, %11, %12, %13, %14, %15, %16, %17, %18, %19, %20, %21, %22, %23, %24, %25, %26, %27, %28, %29, %30, %31, %32, %33, %34, %35, %36, %37, %38, %39, %40, %41, %42, %43, %44, %45, %46, %47, %48, %49, %50, %51, %52, %53, %54, %55, %56, %57, %58, %59, %60, %61, %62, %63, %64, %65, %66, %67, %68, %69, %70, %71, %72, %73, %74, %75, %76, %77, %78, %79, %80, %81, %82, %83, %84, %85, %86, %87, %88, %89, %90, %91, %92, %93, %94, %95, %96, %97, %98, %99, %100, %101, %102, %103, %104, %105, %106, %107, %108, %109, %110, %111, %112, %113, %114, %115, %116, %117, %118, %119, %120, %121, %122, %123, %124, %125, %126, %127}, %128, %129, p, 1, 1, 0, 1;\n}\n"
    : "+f"(d[0]), "+f"(d[1]), "+f"(d[2]), "+f"(d[3]), "+f"(d[4]), "+f"(d[5]), "+f"(d[6]), "+f"(d[7]), "+f"(d[8]), "+f"(d[9]), "+f"(d[10]), "+f"(d[11]), "+f"(d[12]), "+f"(d[13]), "+f"(d[14]), "+f"(d[15]), "+f"(d[16]), "+f"(d[17]), "+f"(d[18]), "+f"(d[19]), "+f"(d[20]), "+f"(d[21]), "+f"(d[22]), "+f"(d[23]), "+f"(d[24]), "+f"(d[25]), "+f"(d[26]), "+f"(d[27]), "+f"(d[28]), "+f"(d[29]), "+f"(d[30]), "+f"(d[31]), "+f"(d[32]), "+f"(d[33]), "+f"(d[34]), "+f"(d[35]), "+f"(d[36]), "+f"(d[37]), "+f"(d[38]), "+f"(d[39]), "+f"(d[40]), "+f"(d[41]), "+f"(d[42]), "+f"(d[43]), "+f"(d[44]), "+f"(d[45]), "+f"(d[46]), "+f"(d[47]), "+f"(d[48]), "+f"(d[49]), "+f"(d[50]), "+f"(d[51]), "+f"(d[52]), "+f"(d[53]), "+f"(d[54]), "+f"(d[55]), "+f"(d[56]), "+f"(d[57]), "+f"(d[58]), "+f"(d[59]), "+f"(d[60]), "+f"(d[61]), "+f"(d[62]), "+f"(d[63]), "+f"(d[64]), "+f"(d[65]), "+f"(d[66]), "+f"(d[67]), "+f"(d[68]), "+f"(d[69]), "+f"(d[70]), "+f"(d[71]), "+f"(d[72]), "+f"(d[73]), "+f"(d[74]), "+f"(d[75]), "+f"(d[76]), "+f"(d[77]), "+f"(d[78]), "+f"(d[79]), "+f"(d[80]), "+f"(d[81]), "+f"(d[82]), "+f"(d[83]), "+f"(d[84]), "+f"(d[85]), "+f"(d[86]), "+f"(d[87]), "+f"(d[88]), "+f"(d[89]), "+f"(d[90]), "+f"(d[91]), "+f"(d[92]), "+f"(d[93]), "+f"(d[94]), "+f"(d[95]), "+f"(d[96]), "+f"(d[97]), "+f"(d[98]), "+f"(d[99]), "+f"(d[100]), "+f"(d[101]), "+f"(d[102]), "+f"(d[103]), "+f"(d[104]), "+f"(d[105]), "+f"(d[106]), "+f"(d[107]), "+f"(d[108]), "+f"(d[109]), "+f"(d[110]), "+f"(d[111]), "+f"(d[112]), "+f"(d[113]), "+f"(d[114]), "+f"(d[115]), "+f"(d[116]), "+f"(d[117]), "+f"(d[118]), "+f"(d[119]), "+f"(d[120]), "+f"(d[121]), "+f"(d[122]), "+f"(d[123]), "+f"(d[124]), "+f"(d[125]), "+f"(d[126]), "+f"(d[127])
    : "l"(da), "l"(db), "r"(sd));
}

__device__ __forceinline__ void wgmma_m64n128_ss(float (&d)[64], uint64_t da, uint64_t db, int sd) {
  asm volatile(
    "{\n.reg .pred p;\nsetp.ne.b32 p, %66, 0;\n"
    "wgmma.mma_async.sync.aligned.m64n128k16.f32.bf16.bf16 "
    "{%0, %1, %2, %3, %4, %5, %6, %7, %8, %9, %10, %11, %12, %13, %14, %15, %16, %17, %18, %19, %20, %21, %22, %23, %24, %25, %26, %27, %28, %29, %30, %31, %32, %33, %34, %35, %36, %37, %38, %39, %40, %41, %42, %43, %44, %45, %46, %47, %48, %49, %50, %51, %52, %53, %54, %55, %56, %57, %58, %59, %60, %61, %62, %63}, %64, %65, p, 1, 1, 0, 0;\n}\n"
    : "+f"(d[0]), "+f"(d[1]), "+f"(d[2]), "+f"(d[3]), "+f"(d[4]), "+f"(d[5]), "+f"(d[6]), "+f"(d[7]), "+f"(d[8]), "+f"(d[9]), "+f"(d[10]), "+f"(d[11]), "+f"(d[12]), "+f"(d[13]), "+f"(d[14]), "+f"(d[15]), "+f"(d[16]), "+f"(d[17]), "+f"(d[18]), "+f"(d[19]), "+f"(d[20]), "+f"(d[21]), "+f"(d[22]), "+f"(d[23]), "+f"(d[24]), "+f"(d[25]), "+f"(d[26]), "+f"(d[27]), "+f"(d[28]), "+f"(d[29]), "+f"(d[30]), "+f"(d[31]), "+f"(d[32]), "+f"(d[33]), "+f"(d[34]), "+f"(d[35]), "+f"(d[36]), "+f"(d[37]), "+f"(d[38]), "+f"(d[39]), "+f"(d[40]), "+f"(d[41]), "+f"(d[42]), "+f"(d[43]), "+f"(d[44]), "+f"(d[45]), "+f"(d[46]), "+f"(d[47]), "+f"(d[48]), "+f"(d[49]), "+f"(d[50]), "+f"(d[51]), "+f"(d[52]), "+f"(d[53]), "+f"(d[54]), "+f"(d[55]), "+f"(d[56]), "+f"(d[57]), "+f"(d[58]), "+f"(d[59]), "+f"(d[60]), "+f"(d[61]), "+f"(d[62]), "+f"(d[63])
    : "l"(da), "l"(db), "r"(sd));
}

__device__ __forceinline__ void wgmma_m64n128_ss_tb(float (&d)[64], uint64_t da, uint64_t db, int sd) {
  asm volatile(
    "{\n.reg .pred p;\nsetp.ne.b32 p, %66, 0;\n"
    "wgmma.mma_async.sync.aligned.m64n128k16.f32.bf16.bf16 "
    "{%0, %1, %2, %3, %4, %5, %6, %7, %8, %9, %10, %11, %12, %13, %14, %15, %16, %17, %18, %19, %20, %21, %22, %23, %24, %25, %26, %27, %28, %29, %30, %31, %32, %33, %34, %35, %36, %37, %38, %39, %40, %41, %42, %43, %44, %45, %46, %47, %48, %49, %50, %51, %52, %53, %54, %55, %56, %57, %58, %59, %60, %61, %62, %63}, %64, %65, p, 1, 1, 0, 1;\n}\n"
    : "+f"(d[0]), "+f"(d[1]), "+f"(d[2]), "+f"(d[3]), "+f"(d[4]), "+f"(d[5]), "+f"(d[6]), "+f"(d[7]), "+f"(d[8]), "+f"(d[9]), "+f"(d[10]), "+f"(d[11]), "+f"(d[12]), "+f"(d[13]), "+f"(d[14]), "+f"(d[15]), "+f"(d[16]), "+f"(d[17]), "+f"(d[18]), "+f"(d[19]), "+f"(d[20]), "+f"(d[21]), "+f"(d[22]), "+f"(d[23]), "+f"(d[24]), "+f"(d[25]), "+f"(d[26]), "+f"(d[27]), "+f"(d[28]), "+f"(d[29]), "+f"(d[30]), "+f"(d[31]), "+f"(d[32]), "+f"(d[33]), "+f"(d[34]), "+f"(d[35]), "+f"(d[36]), "+f"(d[37]), "+f"(d[38]), "+f"(d[39]), "+f"(d[40]), "+f"(d[41]), "+f"(d[42]), "+f"(d[43]), "+f"(d[44]), "+f"(d[45]), "+f"(d[46]), "+f"(d[47]), "+f"(d[48]), "+f"(d[49]), "+f"(d[50]), "+f"(d[51]), "+f"(d[52]), "+f"(d[53]), "+f"(d[54]), "+f"(d[55]), "+f"(d[56]), "+f"(d[57]), "+f"(d[58]), "+f"(d[59]), "+f"(d[60]), "+f"(d[61]), "+f"(d[62]), "+f"(d[63])
    : "l"(da), "l"(db), "r"(sd));
}

__device__ __forceinline__ void wgmma_m64n128_rs_tb(float* d, uint32_t a0, uint32_t a1, uint32_t a2, uint32_t a3, uint64_t db, int sd) {
  asm volatile(
    "{\n.reg .pred p;\nsetp.ne.b32 p, %69, 0;\n"
    "wgmma.mma_async.sync.aligned.m64n128k16.f32.bf16.bf16 "
    "{%0, %1, %2, %3, %4, %5, %6, %7, %8, %9, %10, %11, %12, %13, %14, %15, %16, %17, %18, %19, %20, %21, %22, %23, %24, %25, %26, %27, %28, %29, %30, %31, %32, %33, %34, %35, %36, %37, %38, %39, %40, %41, %42, %43, %44, %45, %46, %47, %48, %49, %50, %51, %52, %53, %54, %55, %56, %57, %58, %59, %60, %61, %62, %63}, {%64, %65, %66, %67}, %68, p, 1, 1, 1;\n}\n"
    : "+f"(d[0]), "+f"(d[1]), "+f"(d[2]), "+f"(d[3]), "+f"(d[4]), "+f"(d[5]), "+f"(d[6]), "+f"(d[7]), "+f"(d[8]), "+f"(d[9]), "+f"(d[10]), "+f"(d[11]), "+f"(d[12]), "+f"(d[13]), "+f"(d[14]), "+f"(d[15]), "+f"(d[16]), "+f"(d[17]), "+f"(d[18]), "+f"(d[19]), "+f"(d[20]), "+f"(d[21]), "+f"(d[22]), "+f"(d[23]), "+f"(d[24]), "+f"(d[25]), "+f"(d[26]), "+f"(d[27]), "+f"(d[28]), "+f"(d[29]), "+f"(d[30]), "+f"(d[31]), "+f"(d[32]), "+f"(d[33]), "+f"(d[34]), "+f"(d[35]), "+f"(d[36]), "+f"(d[37]), "+f"(d[38]), "+f"(d[39]), "+f"(d[40]), "+f"(d[41]), "+f"(d[42]), "+f"(d[43]), "+f"(d[44]), "+f"(d[45]), "+f"(d[46]), "+f"(d[47]), "+f"(d[48]), "+f"(d[49]), "+f"(d[50]), "+f"(d[51]), "+f"(d[52]), "+f"(d[53]), "+f"(d[54]), "+f"(d[55]), "+f"(d[56]), "+f"(d[57]), "+f"(d[58]), "+f"(d[59]), "+f"(d[60]), "+f"(d[61]), "+f"(d[62]), "+f"(d[63])
    : "r"(a0), "r"(a1), "r"(a2), "r"(a3), "l"(db), "r"(sd));
}

__device__ __forceinline__ void wgmma_m64n64_rs_tb(float (&d)[32], const uint32_t (&a)[4], uint64_t db, int sd) {
  asm volatile(
    "{\n.reg .pred p;\nsetp.ne.b32 p, %37, 0;\n"
    "wgmma.mma_async.sync.aligned.m64n64k16.f32.bf16.bf16 "
    "{%0, %1, %2, %3, %4, %5, %6, %7, %8, %9, %10, %11, %12, %13, %14, %15, %16, %17, %18, %19, %20, %21, %22, %23, %24, %25, %26, %27, %28, %29, %30, %31}, {%32, %33, %34, %35}, %36, p, 1, 1, 1;\n}\n"
    : "+f"(d[0]), "+f"(d[1]), "+f"(d[2]), "+f"(d[3]), "+f"(d[4]), "+f"(d[5]), "+f"(d[6]), "+f"(d[7]), "+f"(d[8]), "+f"(d[9]), "+f"(d[10]), "+f"(d[11]), "+f"(d[12]), "+f"(d[13]), "+f"(d[14]), "+f"(d[15]), "+f"(d[16]), "+f"(d[17]), "+f"(d[18]), "+f"(d[19]), "+f"(d[20]), "+f"(d[21]), "+f"(d[22]), "+f"(d[23]), "+f"(d[24]), "+f"(d[25]), "+f"(d[26]), "+f"(d[27]), "+f"(d[28]), "+f"(d[29]), "+f"(d[30]), "+f"(d[31])
    : "r"(a[0]), "r"(a[1]), "r"(a[2]), "r"(a[3]), "l"(db), "r"(sd));
}

__device__ __forceinline__ void wgmma_m64n32_rs_tb(float (&d)[16], const uint32_t (&a)[4], uint64_t db, int sd) {
  asm volatile(
    "{\n.reg .pred p;\nsetp.ne.b32 p, %21, 0;\n"
    "wgmma.mma_async.sync.aligned.m64n32k16.f32.bf16.bf16 "
    "{%0, %1, %2, %3, %4, %5, %6, %7, %8, %9, %10, %11, %12, %13, %14, %15}, {%16, %17, %18, %19}, %20, p, 1, 1, 1;\n}\n"
    : "+f"(d[0]), "+f"(d[1]), "+f"(d[2]), "+f"(d[3]), "+f"(d[4]), "+f"(d[5]), "+f"(d[6]), "+f"(d[7]), "+f"(d[8]), "+f"(d[9]), "+f"(d[10]), "+f"(d[11]), "+f"(d[12]), "+f"(d[13]), "+f"(d[14]), "+f"(d[15])
    : "r"(a[0]), "r"(a[1]), "r"(a[2]), "r"(a[3]), "l"(db), "r"(sd));
}

constexpr int G_STAGES = 4;
constexpr int G_A_BYTES = 128 * 64 * 2;
constexpr int G_B_BYTES = 256 * 64 * 2;
constexpr int G_STAGE_BYTES = G_A_BYTES + G_B_BYTES;
constexpr int G_STG_OFF = G_STAGES * G_STAGE_BYTES;
constexpr int BAR_OFF = G_STG_OFF + 32768 + 2048;
constexpr int SMEM_BYTES = BAR_OFF + 1024;
constexpr int B_GFULL = 0, B_GEMPTY = 32, B_CTX = 64, B_OY2 = 72, B_PFULL = 224;
constexpr int B_KFULL = 80, B_KEMPTY = 96, B_VFULL = 112, B_VEMPTY = 128, B_QFULL = 144, B_QEMPTY = 160,
              B_QDONE = 184;
constexpr int B_CFULL = 192;
constexpr int B_OFREE = 256, B_OFULL = 272, B_OEMPTY = 320, B_OY = 368;
constexpr int B_SFULL = 392, B_SFREE = 424, B_PEND = 456, B_SCMD = 512;

#define PHASE_PROLOGUE                                                                \
  uint32_t tid, rt_zero;                                                              \
  asm volatile("mov.u32 %0, %%tid.x;" : "=r"(tid));                                   \
  asm volatile("mov.u32 %0, %%nctaid.y;" : "=r"(rt_zero));                            \
  asm volatile("" : "+r"(smem0));                                                     \
  rt_zero = __shfl_sync(0xffffffffu, rt_zero >> 8, 0);   \
  const uint32_t sbase = __shfl_sync(0xffffffffu, smem0, 0);                          \
  const uint32_t bar = sbase + BAR_OFF;                                               \
  const int wg = __shfl_sync(0xffffffffu, tid >> 7, 0);                               \
  const int warp = (tid >> 5) & 3, lane = tid & 31, wtid = tid & 127;                 \
  (void)rt_zero; (void)bar; (void)warp; (void)lane; (void)wtid;

enum { ST_END = 0, ST_BOX1, ST_BOX2, ST_BOX2Q, ST_BOX2L };
__device__ __forceinline__ void st_post(uint32_t bar, int wg, int wtid, uint32_t n, int kind, const void* dst,
                                        uint32_t src, int c0, int c1, int sig) {
  if (wtid == 0) {
    const uint32_t c = bar + B_SCMD + wg * 64 + (n & 1) * 32;
    const uint64_t d = reinterpret_cast<uint64_t>(dst);
    sts128(c, make_uint4(kind, src, c0, c1));
    sts128(c + 16, make_uint4((uint32_t)d, (uint32_t)(d >> 32), sig, 0));
  }
  fence_proxy_async();
  __syncwarp();
  mbar_arrive_if(bar + B_SFULL + wg * 16 + (n & 1) * 8, (wtid & 31) == 0);
}
__device__ __forceinline__ void st_wait(uint32_t bar, int wg, uint32_t n) {
  const uint32_t b = bar + B_SFREE + wg * 16 + (n & 1) * 8;
  if (!mbar_try(b, ~(n >> 1) & 1)) mbar_wait(b, ~(n >> 1) & 1);
}
__device__ __forceinline__ void note(uint32_t bar, uint32_t cnt) {
  asm volatile("red.release.cta.shared.add.u32 [%0], 1;" ::"r"(bar + B_PEND + 4 * cnt) : "memory");
}
__device__ __forceinline__ void store_agent(uint32_t bar, int wg) {
  mbar_arrive(bar + B_SFREE + wg * 16);
  mbar_arrive(bar + B_SFREE + wg * 16 + 8);
  bool more = true;
  for (uint32_t n = 0;; n++) {
    mbar_wait_sleep(bar + B_SFULL + wg * 16 + (n & 1) * 8, (n >> 1) & 1);
    const uint4 c = lds128(bar + B_SCMD + wg * 64 + (n & 1) * 32);
    const uint4 d = lds128(bar + B_SCMD + wg * 64 + (n & 1) * 32 + 16);
    if (c.x == ST_END) break;
    const CUtensorMap* dst = reinterpret_cast<const CUtensorMap*>((uint64_t)d.x | ((uint64_t)d.y << 32));
    tma_store_2d(dst, c.y, c.z, c.w);
    if (c.x >= ST_BOX2) tma_store_2d(dst, c.y + 8192, c.z + 64, c.w);
    tma_store_commit();
    tma_store_wait_read<0>();
    mbar_arrive(bar + B_SFREE + wg * 16 + (n & 1) * 8);
    if (c.x == ST_BOX2L) mbar_arrive(bar + B_OFREE + 8 * wg);
    if ((int)d.z >= 0) {
      tma_store_wait<0>();
      if (d.z == 0) { TD(6) }
      asm volatile("fence.proxy.async.global;" ::: "memory");
      if (c.x == ST_BOX2Q) mbar_arrive(bar + B_QDONE);
      else note(bar, d.z);
      if (c.x == ST_BOX2L) {
        note(bar, CNT_DONE);
        more = false;
      }
    }
  }
  if (more) note(bar, CNT_DONE);
}

struct Maps {
  const bf16 *shift_k, *x, *gate_w, *ssm_k, *ssm_D;
  uint8_t id[128][4];
  CUtensorMap a[2];
  CUtensorMap b[3];
  CUtensorMap c[3];
  CUtensorMap bk, bv;
  CUtensorMap q, k, v, o;
  CUtensorMap oa, ob, oc;
  CUtensorMap y, xs;
  CUtensorMap cu, ch;
};

constexpr int P_SLOT = 67 * 128, P_V = 35 * 128, P_TAPS = 2 * P_SLOT;
__device__ __forceinline__ void ldsm4t(uint32_t (&r)[4], uint32_t a) {
  asm volatile("ldmatrix.sync.aligned.m8n8.x4.trans.shared.b16 {%0, %1, %2, %3}, [%4];"
               : "=r"(r[0]), "=r"(r[1]), "=r"(r[2]), "=r"(r[3])
               : "r"(a));
}
__device__ __forceinline__ uint32_t fma_bf2(uint32_t a, uint32_t b, uint32_t c) {
  uint32_t r;
  asm("fma.rn.bf16x2 %0, %1, %2, %3;" : "=r"(r) : "r"(a), "r"(b), "r"(c));
  return r;
}
__device__ __forceinline__ void prep_agent(const Maps& maps, uint32_t sbase, int w, int lane) {
  const uint32_t bar = sbase + BAR_OFF, pb = bar + B_PFULL + w * 16;
  const int d0 = (blockIdx.x >> 3) * 64, t0 = (blockIdx.x & 7) * 256 + w * 128;
  mbar_wait_sleep(bar + B_GFULL + 8 * (G_STAGES - 1), 0);
#pragma unroll 1
  for (int i = -1; i < 4; i++) {
    GA(82 + 2 * i)
    if (i >= 0) mbar_wait_sleep(pb + (i & 1) * 8, i >> 1);
    GA(83 + 2 * i)
    const uint32_t so = sbase + G_STG_OFF + w * (P_TAPS + 512) + (i & 1) * P_SLOT;
    if (i < 3 && elect_one()) {
      const uint32_t b = pb + (~i & 1) * 8, dst = so + (i & 1 ? -P_SLOT : P_SLOT);
      mbar_expect_tx(b, i < 0 ? P_SLOT + 512 : P_SLOT);
      const uint64_t pol = policy_evict_first();
      tma_load_2d_hint(dst, &maps.bk, b, d0, t0 + 32 * i + 29, pol);
      tma_load_2d_hint(dst + P_V, &maps.bv, b, d0, t0 + 32 * i + 32, pol);
      if (i < 0) bulk_load(sbase + G_STG_OFF + P_TAPS, maps.shift_k + d0 * 4, 512, b);
    }
    if (i < 0) continue;
    uint32_t ak[4];
#pragma unroll
    for (int r = 0; r < 4; r++) {
      const uint32_t a = so / 128 + r + 4 * (lane & 6) + (((lane >> 2) ^ lane) & 6) + (lane & 1);
      ak[r] = a * 128 + (a & 7) * 16;
    }
    bf16* dst = g_kvT + (size_t)(d0 + (lane >> 2)) * S_LEN + t0 + ((lane & 3) + 4 * i) * 8;
#pragma unroll 1
    for (int cg = 0; cg < 128; cg += 16) {
      uint32_t t01, t23, k[4][4], v[4];
      asm volatile("ld.shared.v2.u32 {%0, %1}, [%2];"
                   : "=r"(t01), "=r"(t23)
                   : "r"(sbase + G_STG_OFF + P_TAPS + cg * 4 + (lane >> 2) * 8));
#pragma unroll
      for (int r = 0; r < 4; r++) ldsm4t(k[r], ak[r] ^ cg);
      ldsm4t(v, (ak[3] ^ cg) + 4096);
      const uint32_t w0 = __byte_perm(t01, 0, 0x1010), w1 = __byte_perm(t01, 0, 0x3232);
      const uint32_t w2 = __byte_perm(t23, 0, 0x1010), w3 = __byte_perm(t23, 0, 0x3232);
#pragma unroll
      for (int j = 0; j < 4; j++)
        v[j] = mul_bf2(fma_bf2(k[3][j], w0, fma_bf2(k[2][j], w1, fma_bf2(k[1][j], w2, mul_bf2(k[0][j], w3)))), v[j]);
      const bool s1 = lane & 1, s2 = lane & 2;
      const uint32_t a0 = s1 ? v[1] : v[0], a1 = s1 ? v[0] : v[1], a2 = s1 ? v[3] : v[2], a3 = s1 ? v[2] : v[3];
      *reinterpret_cast<uint4*>(dst) = make_uint4(s2 ? a2 : a0, s2 ? a3 : a1, s2 ? a0 : a2, s2 ? a1 : a3);
      dst += 8 * S_LEN;
    }
    fence_proxy_async();
    __syncwarp();
  }
  GA(90)
  if (lane == 0) note(bar, CNT_PREP);
  __syncwarp();
  GA(91)
}

__device__ __forceinline__ void qkv_tile(const Maps& maps, int it, int& which, int& m_tile, int& n_tile) {
  const bool q = it == 0 || it >= 5;
  const int b = maps.id[blockIdx.x][it >= 5];
  which = q ? 0 : 2 - (it & 1);
  m_tile = b & 15;
  n_tile = (b >> 4) * 2 + ((0x19 >> it) & 1);
}

constexpr int G_NTILES = 6;
__device__ __forceinline__ void qkv_producer(const Maps& maps, uint32_t sbase, bool first) {
  const uint32_t bar = sbase + BAR_OFF;
  uint32_t stage = 0, phase = 0;
#pragma unroll 1
  for (int it = 0; it < (first ? 1 : G_NTILES); it++) {
    int which, m_tile, n_tile;
    qkv_tile(maps, it, which, m_tile, n_tile);
    const CUtensorMap* ma = &maps.a[which == 0 ? 0 : 1];
    const CUtensorMap* mb = &maps.b[which];
    const int nk = first ? G_STAGES : which == 0 ? 16 : 8;
#pragma unroll 1
    for (int kt = (it == 0 && !first) ? G_STAGES : 0; kt < nk; kt++) {
      if (!first) mbar_wait_sleep(bar + B_GEMPTY + 8 * stage, phase);
      const uint32_t fb = bar + B_GFULL + 8 * stage;
      const uint32_t sa = sbase + stage * G_STAGE_BYTES;
      mbar_expect_tx(fb, G_STAGE_BYTES);
      tma_load_2d(sa, ma, fb, kt * 64, m_tile * 128);
      tma_load_3d(sa + G_A_BYTES, mb, fb, 0, kt * 64, n_tile * 4);
      if (++stage == G_STAGES) { stage = 0; phase ^= 1; }
      {
        const int b = maps.id[blockIdx.x][1];
        if (it == 2 && kt == (b & 7)) {
          for (int i = 0; i < 2; i++)
            asm volatile("cp.async.bulk.prefetch.tensor.2d.L2.global.tile [%0, {%1, %2}];" ::"l"(&maps.a[0]),
                         "r"((b >> 4) * 128 + i * 64), "r"((b & 15) * 128)
                         : "memory");
        }
        if (it == 3 && kt == (b & 7))
          asm volatile("cp.async.bulk.prefetch.tensor.3d.L2.global.tile [%0, {%1, %2, %3}];" ::"l"(&maps.b[0]), "r"(0),
                       "r"((b & 15) * 64), "r"((b >> 4) * 8)
                       : "memory");
      }
    }
  }
}

__device__ __noinline__ void publisher(uint32_t bar, int lane, uint32_t nsrc, uint32_t poll) {
  uint32_t done = 0;
#pragma unroll 1
  for (uint32_t spins = 0; (done < nsrc || poll <= nsrc) && spins < (1u << 20); spins++) {
    if (done >= poll) {
      uint32_t v;
      asm volatile("ld.acquire.gpu.global.u32 %0, [%1];" : "=r"(v) : "l"(g_cnt + (CNT_CTX + 1) * 32) : "memory");
      if (__all_sync(0xffffffffu, v >= NH * (S_LEN / 128))) {
        asm volatile("fence.proxy.async.global;" ::: "memory");
        mbar_arrive_if(bar + B_CTX, lane == 0);
        poll = ~0u;
      }
    }
    uint32_t v = 0;
    if (lane < CNT_N)
      asm volatile("atom.acquire.cta.shared.exch.b32 %0, [%1], 0;" : "=r"(v) : "r"(bar + B_PEND + 4 * lane) : "memory");
    done += __shfl_sync(0xffffffffu, v, CNT_DONE);
    if (lane == CNT_DONE) v = 0;
    if (done == nsrc && lane < CNT_DONE) {
      uint32_t w;
      asm volatile("atom.acquire.cta.shared.exch.b32 %0, [%1], 0;" : "=r"(w) : "r"(bar + B_PEND + 4 * lane) : "memory");
      v += w;
    }
    if (v && lane == 0) { TD(0) }
    if (v) cnt_signal_release(lane, v);
    if (v && lane == 0) { TD(1) }
    if (!__any_sync(0xffffffffu, v != 0)) __nanosleep(200);
  }
  __threadfence();
  __syncwarp();
}

__device__ __forceinline__ void gate_rows(const Maps& maps, uint32_t sbase, int w48, int w12, int lane) {
  const uint32_t buf = sbase + w12 * 16384, gb = sbase + BAR_OFF + 768 + w12 * 16;
  if (lane == 0) {
    mbar_init(gb, 1);
    mbar_init(gb + 8, 1);
    fence_barrier_init();
    for (int i = 0; i < 2; i++) {
      mbar_expect_tx(gb + 8 * i, 8192);
      bulk_load(buf + i * 8192, maps.x + (size_t)(w48 + 48 * i) * 4 * DM, 8192, gb + 8 * i);
    }
  }
  __syncwarp();
  uint4 wv[4];
#pragma unroll
  for (int i = 0; i < 4; i++) wv[i] = __ldg(reinterpret_cast<const uint4*>(maps.gate_w + (i * 32 + lane) * 8));
  int it = 0;
#pragma unroll 1
  for (int row = w48 * 4; row < S_LEN; row += 48 * 4, it++) {
    mbar_wait(gb + 8 * (it & 1), (it >> 1) & 1);
    uint4 xv[4][4];
#pragma unroll
    for (int r = 0; r < 4; r++)
#pragma unroll
      for (int i = 0; i < 4; i++) xv[r][i] = lds128(buf + (it & 1) * 8192 + r * 2048 + (i * 32 + lane) * 16);
    float d[2][4];
#pragma unroll
    for (int pr = 0; pr < 2; pr++) {
      d[pr][0] = d[pr][1] = d[pr][2] = d[pr][3] = 0.f;
      auto acc = [&](uint32_t a0, uint32_t a2, uint32_t b0, uint32_t b2, uint32_t w0, uint32_t w2) {
        asm volatile(
            "mma.sync.aligned.m16n8k16.row.col.f32.bf16.bf16.f32 {%0, %1, %2, %3}, {%4, %5, %6, %7}, {%8, %8}, "
            "{%0, %1, %2, %3};"
            : "+f"(d[pr][0]), "+f"(d[pr][1]), "+f"(d[pr][2]), "+f"(d[pr][3])
            : "r"(mul_bf2(a0, w0)), "r"(mul_bf2(b0, w0)), "r"(mul_bf2(a2, w2)), "r"(mul_bf2(b2, w2)), "r"(0x3f803f80u));
      };
#pragma unroll
      for (int i = 0; i < 4; i++) {
        acc(xv[2 * pr][i].x, xv[2 * pr][i].y, xv[2 * pr + 1][i].x, xv[2 * pr + 1][i].y, wv[i].x, wv[i].y);
        acc(xv[2 * pr][i].z, xv[2 * pr][i].w, xv[2 * pr + 1][i].z, xv[2 * pr + 1][i].w, wv[i].z, wv[i].w);
      }
    }
    float sum = (lane & 2) ? ((lane & 1) ? d[1][2] : d[1][0]) : ((lane & 1) ? d[0][2] : d[0][0]);
#pragma unroll
    for (int off = 16; off >= 4; off >>= 1) sum += __shfl_xor_sync(0xffffffffu, sum, off);
    if (lane < 4) g_gate[row + lane] = bf16_round(rcp(1.0f + __expf(-bf16_round(sum))));
    if (lane == 0 && row + 2 * 48 * 4 < S_LEN) {
      mbar_expect_tx(gb + 8 * (it & 1), 8192);
      bulk_load(buf + (it & 1) * 8192, maps.x + (size_t)(row + 2 * 48 * 4) * DM, 8192, gb + 8 * (it & 1));
    }
  }
}

constexpr float Q_SCALE = 0.08838834764831845f * 1.4426950408889634f;
__device__ __forceinline__ uint32_t qkv_consumer(const Maps& maps, uint32_t smem0, bool fused, float (&rest)[64]) {
  PHASE_PROLOGUE
  constexpr int NTILES = G_NTILES;
  float acc[128];
  uint32_t stage = 0, phase = 0;
  const uint32_t stg = sbase + G_STG_OFF + wg * 18432;
  const int st_row = warp * 16 + (lane & 7) + ((lane >> 3) & 1) * 8;
  const int st_cb = lane >> 4;
  uint32_t pend[64];
  const CUtensorMap* pend_map = nullptr;
  int pend_c0 = 0, pend_c1 = 0;
  uint32_t sn = 0;
  auto put_box = [&](uint32_t buf, const uint32_t* v) {
#pragma unroll
    for (int jp = 0; jp < 4; jp++) {
      const int chunk = jp * 2 + st_cb;
      const uint32_t addr = buf + st_row * 128 + ((chunk ^ (st_row & 7)) << 4);
      stmatrix_x4(addr, v[jp * 4], v[jp * 4 + 1], v[jp * 4 + 2], v[jp * 4 + 3]);
    }
  };
  GT(gti++)
#pragma unroll 1
  for (int it = 0; it <= NTILES; it++) {
    int which, m_tile, n_tile;
    qkv_tile(maps, it, which, m_tile, n_tile);
    const int nk = (which == 0 && it < NTILES) ? 16 : 8;
    uint32_t prev_stage = 0;
#pragma unroll 1
    for (int kt = 0; kt < nk; kt++) {
      if (it < NTILES) {
        mbar_wait((bar + B_GFULL) + 8 * stage, phase);
        GT(gti++)
        const uint64_t da0 = make_desc(sbase + stage * G_STAGE_BYTES + wg * 8192, 16, 1024, DESC_SW128);
        const uint64_t db0 = make_desc(sbase + stage * G_STAGE_BYTES + G_A_BYTES, 8192, 1024, DESC_SW128);
        wgmma_fence();
#pragma unroll
        for (int kk = 0; kk < 4; kk++) {
          wgmma_m64n256_ss_tb(acc, desc_add(da0, kk * 2), desc_add(db0, kk * 128), (kt | kk) != 0);
        }
        wgmma_commit();
      }
      const uint32_t when = it == 0 ? 0 : it == 5 ? 0x922 << wg : wg ? 0xAA : 0x55;
      if ((when >> kt) & 1) {
        const int c = __popc(when & ~(~0u << kt));
        st_wait(bar, wg, sn - 2);
        const uint32_t buf = stg + (c & 1) * 8192;
        switch (c) {
          case 0: put_box(buf, pend); break;
          case 1: put_box(buf, pend + 16); break;
          case 2: put_box(buf, pend + 32); break;
          default: put_box(buf, pend + 48); break;
        }
        st_post(bar, wg, wtid, sn, ST_BOX1, pend_map, buf, pend_c0 + c * 64, pend_c1, (c == 3 && it > 1) ? CNT_KV + (it > 3) : -1);
        sn++;
      }
      if (it < NTILES) {
        wgmma_wait<1>();
        mbar_arrive_if((bar + B_GEMPTY) + 8 * prev_stage, wtid == 32 && kt > 0);
        prev_stage = stage;
        if (++stage == G_STAGES) { stage = 0; phase ^= 1; }
      }
    }
    wgmma_wait<0>();
    fence_regs(acc);
    if (it == NTILES) break;
    GT(gti++)
    mbar_arrive_if((bar + B_GEMPTY) + 8 * prev_stage, wtid == 32);
    if (it == NTILES - 1 && fused) break;
    if (which == 0) {
#pragma unroll
      for (int j = 0; j < 128; j++) acc[j] *= Q_SCALE;
    }
#pragma unroll
    for (int j = 0; j < 64; j++) pend[j] = pack_bf16(acc[2 * j], acc[2 * j + 1]);
    pend_map = &maps.c[which];
    pend_c0 = n_tile * 256;
    pend_c1 = m_tile * 128 + wg * 64;
  }
  mbar_wait(bar + B_GEMPTY, 1);
#pragma unroll
  for (int j = 0; j < 32; j++) pend[j] = pack_bf16(acc[2 * j] * Q_SCALE, acc[2 * j + 1] * Q_SCALE);
  put_box(sbase + wg * 8192, pend);
  put_box(sbase + 16384 + wg * 8192, pend + 16);
  fence_proxy_async();
#pragma unroll
  for (int j = 0; j < 64; j++) rest[j] = acc[64 + j];
  GT(gti++)
  return sn;
}

constexpr int A_TILE = 128 * 128 * 2;
constexpr int A_Q_OFF = 0;
constexpr int A_K_OFF = 2 * A_TILE;
constexpr int A_V_OFF = 4 * A_TILE;
constexpr int A_O_OFF = 6 * A_TILE;
constexpr int A_ITEMS = NH * (S_LEN / 128);

constexpr uint32_t A_ORDER = 0x3120, A_STEPS = 34;
__device__ __forceinline__ int item_m(uint32_t it) { return it & 15; }
__device__ __forceinline__ int item_h(uint32_t it) { return it >> 4; }

constexpr int C_V = 16384, C_MAT = 24576;
constexpr float C_ALPHA = 0.07874506561842957f;
__device__ __forceinline__ void sincos_turn(int p, float inv, float& c, float& s) {
  const float a = (float)p * (inv * 6.283185307179586f);
  asm("cos.approx.ftz.f32 %0, %1;" : "=f"(c) : "f"(a));
  asm("sin.approx.ftz.f32 %0, %1;" : "=f"(s) : "f"(a));
}

__device__ __forceinline__ uint32_t item_of(const Maps& maps, uint32_t r) {
  const uint32_t b = maps.id[blockIdx.x & 127][1];
  return (b >> 4) * 64 + ((A_ORDER >> (4 * r)) & 3) * 16 + ((b ^ ((r & 1) * 15)) & 15);
}

#define PACE 250
#define C_SIDE 64
__device__ __forceinline__ uint32_t conv_first(const Maps& maps) {
  const uint32_t b = maps.id[blockIdx.x & 127][1];
  return (b >> 4) * 128 + ((b + 15) & 15);
}

__device__ __forceinline__ void conv_consumer(const Maps& maps, uint32_t smem0, uint32_t first, uint32_t step,
                                              uint32_t end, bool pp) {
  PHASE_PROLOGUE
  const uint32_t in_full = bar + B_CFULL + wg * 16;
  const uint32_t ca = sbase + (wg ? A_V_OFF + A_TILE : A_Q_OFF);
  const int w = __shfl_sync(0xffffffffu, warp, 0), g = lane >> 2, c = lane & 3;
  auto fetch = [&](uint32_t ch, uint32_t n) {
    if (w == 2 && ch < end) {
      if (elect_one()) {
        const uint32_t b = in_full + (n & 1) * 8, d = ca + (n & 1) * 8192;
        const uint64_t pol = policy_evict_first();
        mbar_expect_tx(b, 8192);
        tma_load_2d_hint(d, &maps.cu, b, 0, ch * 64, pol);
        tma_load_2d_hint(d + 4096, &maps.ch, b, 0, ch * 64, pol);
      }
    }
  };
  if (wtid == 96 && wg) { TD(15) }
  uint32_t f1[8][4];
  float tt[16], ts[16];
  uint32_t cc[4], ss[4];
#pragma unroll
  for (int i = 0; i < 16; i++) {
    const int k = 2 * (16 * w + g + 8 * (i & 1)) + 1, n = 2 * (8 * (i >> 1) + 2 * c) + 1;
    float c0, s0, c1, s1;
    sincos_turn(((k * n) << 23) >> 23, 1.f / 512, c0, s0);
    sincos_turn(((k * n + 2 * k) << 23) >> 23, 1.f / 512, c1, s1);
    f1[i >> 2][i & 3] = pack_bf16(c0 * C_ALPHA, c1 * C_ALPHA);
    f1[4 + (i >> 2)][i & 3] = pack_bf16(s0 * -C_ALPHA, s1 * -C_ALPHA);
  }
#pragma unroll
  for (int i = 0; i < 16; i++) {
    const int k = 2 * (16 * w + g + 8 * ((i >> 1) & 1)) + 1, n = 16 - (8 * (i >> 2) + 2 * c + (i & 1));
    float cs;
    sincos_turn(k * n, 1.f / 8192, cs, ts[i]);
    tt[i] = ts[i] * rcp(1.f + cs);
  }
#pragma unroll
  for (int j = 0; j < 4; j++) {
    const int k = 8 * w + g, n = 8 * c + 2 * j;
    float c0, s0, c1, s1;
    sincos_turn((int8_t)(k * n * 8), 1.f / 256, c0, s0);
    sincos_turn((int8_t)((k * n + k) * 8), 1.f / 256, c1, s1);
    cc[j] = pack_bf16(c0, c1);
    ss[j] = pack_bf16(s0, s1);
  }
  named_bar_sync(3, 256);
  fetch(first, 0);
  fetch(first + step, 1);
  const uint32_t va = ca + g * 64 + ((c ^ (g >> 1)) << 4);
  {
    const uint32_t a = va + C_MAT + w * 512, m = 0x80008000u;
    sts128(a, make_uint4(cc[0], cc[1], cc[2], cc[3]));
    sts128(a + 2048, make_uint4(ss[0], ss[1], ss[2], ss[3]));
    sts128(a + 4096, make_uint4(ss[0] ^ m, ss[1] ^ m, ss[2] ^ m, ss[3] ^ m));
    sts128(a + 6144, make_uint4(cc[0], cc[1], cc[2], cc[3]));
  }
  fence_proxy_async();
  named_bar_sync(1 + wg, 128);
  constexpr uint64_t DHI = (2ull << 62) | ((uint64_t)(512 >> 4) << 32);
  const uint32_t d0 = (uint32_t)make_desc(ca, 4096, 0, 0);
  float a5[16];
  uint4* const yb = reinterpret_cast<uint4*>(g_y2T) + (16 * w + g) * 4 + c;
  auto issue5 = [&]() {
#pragma unroll
    for (int ks = 0; ks < 8; ks++) wgmma_m64n32_rs_tb(a5, f1[ks], DHI | (d0 + (C_V >> 4) + ks * 64), ks != 0);
    wgmma_commit();
  };
  auto finish = [&](uint32_t ch, bool on) {
    fence_regs(a5);
    uint4* y = yb + (size_t)ch * 256;
    if (on) {
      y[0] = make_uint4(pack_bf16(a5[0], a5[1]), pack_bf16(a5[4], a5[5]), pack_bf16(a5[8], a5[9]), pack_bf16(a5[12], a5[13]));
      y[32] = make_uint4(pack_bf16(a5[2], a5[3]), pack_bf16(a5[6], a5[7]), pack_bf16(a5[10], a5[11]), pack_bf16(a5[14], a5[15]));
    }
  };
  auto dft32 = [&](float (&d)[32], const float* re, const float* im) {
    uint32_t a[4][4];
#pragma unroll
    for (int i = 0; i < 8; i++) {
      a[i >> 2][i & 3] = pack_bf16(re[2 * i], re[2 * i + 1]);
      a[2 + (i >> 2)][i & 3] = pack_bf16(im[2 * i], im[2 * i + 1]);
    }
    wgmma_fence();
#pragma unroll
    for (int ks = 0; ks < 4; ks++) wgmma_m64n64_rs_tb(d, a[ks], DHI | (d0 + (C_MAT >> 4) + ks * 64), ks != 0);
    wgmma_commit();
  };
  auto rot = [&](float* x, float* y) {
#pragma unroll
    for (int i = 0; i < 16; i++) {
      x[i] = fmaf(-tt[i], y[i], x[i]);
      y[i] = fmaf(ts[i], x[i], y[i]);
      x[i] = fmaf(-tt[i], y[i], x[i]);
    }
  };
  auto load_d = [&](uint32_t ch) {
    return __ldg(reinterpret_cast<const unsigned short*>(maps.ssm_D) + ((ch & (DM - 1)) | (lane & rt_zero)));
  };
  uint32_t dn = load_d(first);
  uint32_t n = 0, ch = first;
#pragma unroll 1
  for (; ch < end; n++, ch += step) {
    CT(0)
    float a1[2][32], a2[2][32], a4[32];
    const float dsk = c ? 0.f : __uint_as_float(dn << 16) * C_ALPHA;
    dn = load_d(ch + step);
    mbar_wait(in_full + (n & 1) * 8, (n >> 1) & 1);
    if (pp) named_bar_sync(4 + wg, 256);
    CT(1)
    wgmma_fence();
#pragma unroll
    for (int ks = 0; ks < 8; ks++)
      wgmma_m64n64_rs_tb(a1[ks >> 2], f1[ks], DHI | (d0 + (n & 1) * 512 + (ks & 3) * 64), (ks & 3) != 0);
    wgmma_commit();
    issue5();
    wgmma_wait<1>();
    fence_regs(a1[0]);
    fence_regs(a1[1]);
    CT(2)
    rot(a1[0], a1[1]);
    dft32(a2[0], a1[0], a1[1]);
    rot(a1[0] + 16, a1[1] + 16);
    a1[0][16] += dsk;
    a1[0][18] += dsk;
    dft32(a2[1], a1[0] + 16, a1[1] + 16);
    CT(3)
    wgmma_wait<2>();
    finish(ch - step, n > 0);
    wgmma_wait<0>();
    fence_regs(a2[0]);
    fence_regs(a2[1]);
    CT(4)
    if (pp) named_bar_arrive(5 - wg, 256);
    float re[16], im[16];
#pragma unroll
    for (int i = 0; i < 16; i++) {
      re[i] = a2[0][i] * a2[1][i] - a2[0][16 + i] * a2[1][16 + i];
      im[i] = a2[0][i] * a2[1][16 + i] + a2[0][16 + i] * a2[1][i];
    }
    dft32(a4, im, re);
    wgmma_wait<0>();
    fence_regs(a4);
    CT(5)
    rot(a4, a4 + 16);
#pragma unroll
    for (int i = 0; i < 4; i++) {
      const float* x = a4 + 16 - 16 * (i >> 1) + 2 * (i & 1);
      sts128(va + C_V + w * 1024 + (i >> 1) * 4096 + (i & 1) * 512,
             make_uint4(pack_bf16(x[0], x[1]), pack_bf16(x[4], x[5]), pack_bf16(x[8], x[9]), pack_bf16(x[12], x[13])));
    }
    CT(6)
    fence_proxy_async();
    named_bar_sync(1 + wg, 128);
    fetch(ch + 2 * step, n);
    if (wtid == 96 && n > 0) note(bar, CNT_Y2 + (((ch - step) & 112) == 112));
    CT(7)
  }
  wgmma_fence();
  issue5();
  wgmma_wait<0>();
  finish(ch - step, true);
  named_bar_sync(1 + wg, 128);
  if (wtid == 96 && wg) { TD(8) }
  if (wtid == 96) cnt_signal_release(CNT_Y2 + (((ch - step) & 112) == 112), 1);
  if (wtid == 64) note(bar, CNT_DONE);
  if (wtid == 96 && wg) { TD(9) }
  mbar_wait(bar + B_OFREE, 0);
  mbar_wait(bar + B_OFREE + 8, 0);
}

__device__ __forceinline__ void attn_producer(const Maps& maps, uint32_t sbase, bool after_qkv, bool to_out,
                                              bool dry) {
  const uint32_t bar = sbase + BAR_OFF;
  const uint32_t q_full = bar + B_QFULL, q_empty = bar + B_QEMPTY;
  const uint32_t k_full = bar + B_KFULL, k_empty = bar + B_KEMPTY, v_full = bar + B_VFULL, v_empty = bar + B_VEMPTY;
  int ndrained = after_qkv ? 0 : G_STAGES;
  auto wait = [&](uint32_t b, uint32_t par) {
    if (!dry) mbar_wait_sleep(b, par);
  };
  auto drained = [&](int upto) {
#pragma unroll 1
    for (; ndrained <= upto; ndrained++) wait(bar + B_GEMPTY + 8 * ndrained, 1);
  };
  uint32_t st = 0, ph = 1, vs = 0, vp = 1;
  int pend_j = -1, pend_h = 0;
  int round = -1, m = -1, h = 0;
  bool last = false;
#pragma unroll 1
  for (;; round++) {
    uint32_t nitem = 0;
    const int tpost = m >= 3 ? m - 1 : m;
#pragma unroll 1
    for (int t = m < 0 ? -1 : 0; t <= m; t++) {
      const int j = (t < m && (round & 1)) ? m - 1 - t : t;
      if (t >= 0) {
        drained(1 + st);
        wait(k_empty + 8 * st, ph);
        if (!dry) {
          mbar_expect_tx(k_full + 8 * st, A_TILE);
          tma_load_3d(sbase + A_K_OFF + st * A_TILE, &maps.k, k_full + 8 * st, 0, j * 128, h * 2);
        }
        if (++st == 2) { st = 0; ph ^= 1; }
      }
      if (pend_j >= 0) {
        drained(3);
        wait(v_empty + 8 * vs, vp);
        if (!dry) {
          mbar_expect_tx(v_full + 8 * vs, A_TILE);
          tma_load_3d(sbase + A_V_OFF + vs * A_TILE, &maps.v, v_full + 8 * vs, 0, pend_j * 128, pend_h * 2);
        }
        if (++vs == 2) { vs = 0; vp ^= 1; }
      }
      pend_j = j;
      pend_h = h;
      if (t == tpost && !last) {
        nitem = dry ? 1 : item_of(maps, round + 1);
        if (round == (dry ? 0 : 3) || blockIdx.x >= 128) {
          nitem = A_ITEMS;
          cnt_wait(CNT_PREP, dry ? 0 : 260);
          if (to_out) {
            cnt_wait(CNT_CTX, dry ? 0 : A_ITEMS);
            asm volatile("cp.async.bulk.prefetch.L2.global [%0], 4096;" ::"l"(maps.ssm_k + (size_t)conv_first(maps) * S_LEN));
            if (!dry)
              asm volatile("cp.async.bulk.prefetch.L2.global [%0], 4096;" ::"l"(g_kvT + (size_t)conv_first(maps) * S_LEN));
          }
        }
        const uint32_t qs = (round + 1) & 1;
        wait(q_empty + 8 * qs, (((round + 1) >> 1) & 1) ^ 1);
        if (round == 1 && after_qkv) wait(bar + B_QDONE, 0);
        if (round <= 0 && after_qkv) {
          if (!dry) { TD(2) }
          cnt_wait(CNT_KV + round + 1, dry ? 0 : 512);
          if (!dry) { TD(3) }
        }
        if (nitem >= A_ITEMS || (round < 0 && after_qkv && !dry)) {
          if (!dry) mbar_arrive(q_full + 8 * qs);
        } else {
          drained(qs);
          if (!dry) {
            mbar_expect_tx(q_full + 8 * qs, A_TILE);
            tma_load_3d_hint(sbase + A_Q_OFF + qs * A_TILE, &maps.q, q_full + 8 * qs, 0, item_m(nitem) * 128,
                             item_h(nitem) * 2, policy_evict_first());
          }
        }
      }
    }
    if (last) break;
    last = nitem >= A_ITEMS;
    m = last ? -1 : item_m(nitem);
    h = item_h(nitem);
  }
}

__device__ __forceinline__ uint32_t attn_consumer(const Maps& maps, uint32_t smem0, uint32_t sn,
                                                  float (&rest)[64], bool after_qkv) {
  PHASE_PROLOGUE
  const uint32_t q_full = bar + B_QFULL, q_empty = bar + B_QEMPTY;
  const uint32_t k_full = bar + B_KFULL, k_empty = bar + B_KEMPTY, v_full = bar + B_VFULL;
  float o[64], s[64];
  uint32_t p[32];
  float e[32];
  uint32_t dep = 0;
  constexpr int MIDJ = 5;
  float l0 = 0.f, l1 = 0.f, b0 = 0.f, b1 = 0.f;
  const int sched_own = 4 + wg, sched_other = 5 - wg;
  if (wg == 1) named_bar_arrive(4, 256);

  const uint32_t qd0 = (uint32_t)make_desc(sbase + A_Q_OFF + wg * 8192, 16, 0, 0);
  const uint32_t kd0 = (uint32_t)make_desc(sbase + A_K_OFF, 16, 0, 0);
  const uint32_t vd0 = (uint32_t)make_desc(sbase + A_V_OFF, 16384, 0, 0);
  constexpr uint64_t DHI = DESC_SW128 | ((uint64_t)(1024 >> 4) << 32);
  constexpr uint32_t DST = A_TILE >> 4;
  auto issue_qk = [&](uint32_t qd, uint32_t kd) {
#pragma unroll
    for (int kk = 0; kk < 8; kk++) {
      const uint32_t off = ((kk >> 2) * 16384 + (kk & 3) * 32) >> 4;
      wgmma_m64n128_ss(s, DHI | (qd + off), DHI | (kd + off), kk != 0);
    }
    wgmma_commit();
  };
  auto issue_pv = [&](uint32_t vd, bool accumulate, int nk) {
#pragma unroll
    for (int kk = 0; kk < 8; kk++) {
      if (kk < nk)
        wgmma_m64n128_rs_tb(o, p[4 * kk], p[4 * kk + 1], p[4 * kk + 2], p[4 * kk + 3], DHI | (vd + kk * 128),
                            accumulate || (kk != 0));
    }
    wgmma_commit();
  };
  auto exp_lo = [&](float& a0, float& a1) {
#pragma unroll
    for (int j = 0; j < 8; j++) {
      e[4 * j] = ex2(s[4 * j]);
      e[4 * j + 1] = ex2(s[4 * j + 1]);
      e[4 * j + 2] = ex2(s[4 * j + 2]);
      e[4 * j + 3] = ex2(s[4 * j + 3]);
      a0 += e[4 * j];
      a0 += e[4 * j + 1];
      a1 += e[4 * j + 2];
      a1 += e[4 * j + 3];
      if (j == MIDJ) dep = (__float_as_uint(a0) | __float_as_uint(a1)) & rt_zero;
    }
  };
  auto pack_lo = [&]() {
#pragma unroll
    for (int j = 0; j < 16; j++) p[j] = pack_bf16(e[2 * j], e[2 * j + 1]);
  };
  auto finish_p = [&](float& a0, float& a1) {
    pack_lo();
#pragma unroll
    for (int j = 8; j < 16; j++) {
      const float e0 = ex2(s[4 * j]), e1 = ex2(s[4 * j + 1]), e2 = ex2(s[4 * j + 2]), e3 = ex2(s[4 * j + 3]);
      a0 += e0;
      a0 += e1;
      a1 += e2;
      a1 += e3;
      p[2 * j] = pack_bf16(e0, e1);
      p[2 * j + 1] = pack_bf16(e2, e3);
      if (j == 8 + MIDJ) dep = __float_as_uint(a0) & rt_zero;
    }
  };
  auto quad_sum = [&](float t) {
    t += __shfl_xor_sync(0xffffffffu, t, 1);
    return t + __shfl_xor_sync(0xffffffffu, t, 2);
  };
  auto write_o = [&](float i0, float i1) {
    st_wait(bar, wg, sn - 1);
    const int st_row = warp * 16 + (lane & 7) + ((lane >> 3) & 1) * 8;
    const uint32_t so = sbase + A_O_OFF + wg * 16384 + st_row * 128;
#pragma unroll
    for (int j = 0; j < 16; j += 2)
      stmatrix_x4(so + (j >> 3) * 8192 + ((((j & 7) + (lane >> 4)) ^ (lane & 7)) << 4),
                  pack_bf16(o[4 * j] * i0, o[4 * j + 1] * i0), pack_bf16(o[4 * j + 2] * i1, o[4 * j + 3] * i1),
                  pack_bf16(o[4 * j + 4] * i0, o[4 * j + 5] * i0), pack_bf16(o[4 * j + 6] * i1, o[4 * j + 7] * i1));
  };
  auto store_o = [&](uint32_t r, int kind) {
    const uint32_t it = item_of(maps, r);
    st_post(bar, wg, wtid, sn, kind, (INPLACE & 1) || kind != ST_BOX2Q ? &maps.o : &maps.c[0], sbase + A_O_OFF + wg * 16384, item_h(it) * 128,
            item_m(it) * 128 + wg * 64, CNT_CTX + (r >> 1));
    sn++;
  };
  auto mask_half = [&](float* sh) {
    const int u = warp * 16 + (lane >> 2) - (lane & 3) * 2;
#pragma unroll
    for (int j = 0; j < 8; j++) {
      if (8 * j > u) sh[4 * j] = -INFINITY;
      if (8 * j + 1 > u) sh[4 * j + 1] = -INFINITY;
      if (8 * j - 8 > u) sh[4 * j + 2] = -INFINITY;
      if (8 * j - 7 > u) sh[4 * j + 3] = -INFINITY;
    }
  };
  ST(0)
  mbar_wait(q_full, 0);
  if (blockIdx.x >= 128) {
    mbar_arrive_if(bar + B_OFREE + 8 * wg, wtid == 0);
    return sn;
  }
  mbar_wait(k_full, 0);
  named_bar_sync(sched_own, 256);
  wgmma_fence();
  issue_qk(qd0, kd0);
  named_bar_arrive(sched_other, 256);
  fence_regs(rest);
#pragma unroll
  for (int i = 0; i < 64; i++) o[i] = rest[i] * Q_SCALE;
  fence_regs(o);
  wgmma_wait<0>();
  fence_regs(s);
  mbar_arrive_if(k_empty, wtid == 32);
  uint32_t g = 0;
  uint32_t rnd = 0;
  int rem = item_m(item_of(maps, 0));
  uint32_t first = 1;
  uint32_t fl = 0;
#define redo (fl & 1)
#define shifted (fl & 2)
  float d0 = 0.f, d1 = 0.f;
  float pi0 = 1.f, pi1 = 1.f;
  ST(1)
  for (;;) {
    if (shifted) {
#pragma unroll
      for (int j = 0; j < 16; j++) {
        s[4 * j] -= d0;
        s[4 * j + 1] -= d0;
        s[4 * j + 2] -= d1;
        s[4 * j + 3] -= d1;
      }
    }
    if (rem == 0 && !redo) {
      mbar_arrive_if(q_empty + 8 * (rnd & 1), wtid == 96);
      rnd++;
      if (wg == 0) mask_half(s);
      else mask_half(s + 32);
    }
    for (;;) {
      const bool kill = rem == 0 && wg == 0;
      const uint32_t kd = kd0 + ((g + 1) & 1) * DST, vd = vd0 + (g & 1) * DST;
      float a0 = 0.f, a1 = 0.f;
      exp_lo(a0, a1);
      fence_regs(e);
      const uint32_t kb = k_full + 8 * ((g + 1) & 1);
      const uint32_t kpar = ((((g + 1) >> 1) & 1) ^ (g == A_STEPS - 1 ? 1u : 0u)) | dep;
      if (!mbar_try(kb, kpar)) mbar_wait(kb, kpar | ((__float_as_uint(a0) | __float_as_uint(a1)) & rt_zero));
      wgmma_wait<0>();
      fence_regs(o);
      if (kill) {
        mbar_arrive_if(kb + (B_VEMPTY - B_KFULL), wtid == 64 && !redo && g > 0);
        fence_regs(e);
        pack_lo();
#pragma unroll
        for (int j = 16; j < 32; j++) asm volatile("mov.u32 %0, 0;" : "=r"(p[j]));
        goto check;
      }
#pragma unroll
      for (int i = 32; i < 64; i++) asm volatile("" : "+f"(s[i])::"memory");
      mbar_arrive_if(kb + (B_VEMPTY - B_KFULL), wtid == 64 && !redo && g > 0);
      finish_p(a0, a1);
      if (__any_sync(0xffffffffu, !(mbar_try(v_full + 8 * (g & 1), ((g >> 1) & 1) | dep) &
                                    mbar_try(q_full + 8 * (rnd & 1), ((rnd >> 1) & 1) | dep)) ||
                                      !(a0 + a1 < 1.0995116e12f) || !(fminf(a0, a1) > (first ? 9.094947e-13f : -1.f)))) {
      check:
        bool bad = !(a0 + a1 < 1.0995116e12f);
        if (first) bad |= !(fminf(quad_sum(a0), quad_sum(a1)) > 9.094947e-13f);
        if (!redo && __any_sync(0xffffffffu, bad)) {
          d0 = d1 = first ? -INFINITY : 0.f;
#pragma unroll
          for (int j = 0; j < 16; j++) {
            if (j < 8 || !kill) {
              d0 = fmaxf(d0, fmaxf(s[4 * j], s[4 * j + 1]));
              d1 = fmaxf(d1, fmaxf(s[4 * j + 2], s[4 * j + 3]));
            }
          }
#pragma unroll
          for (int x = 1; x <= 2; x++) {
            d0 = fmaxf(d0, __shfl_xor_sync(0xffffffffu, d0, x));
            d1 = fmaxf(d1, __shfl_xor_sync(0xffffffffu, d1, x));
          }
          b0 += d0;
          b1 += d1;
          if (!first) {
            const float al0 = ex2(-d0), al1 = ex2(-d1);
            l0 *= al0;
            l1 *= al1;
#pragma unroll
            for (int j = 0; j < 16; j++) {
              o[4 * j] *= al0;
              o[4 * j + 1] *= al0;
              o[4 * j + 2] *= al1;
              o[4 * j + 3] *= al1;
            }
          }
          fl = 3;
          break;
        }
        mbar_wait(v_full + 8 * (g & 1), (g >> 1) & 1);
        mbar_wait(q_full + 8 * (rnd & 1), (rnd >> 1) & 1);
      }
      named_bar_sync(sched_own, 256);
      if (g == A_STEPS - 1) {
        if (first) write_o(pi0, pi1);
        fence_regs(o);
        wgmma_fence();
        issue_pv(vd, !first, 8);
        named_bar_arrive(sched_other, 256);
        if (first) store_o(rnd - 2, ST_BOX2);
        pi0 = rcp(quad_sum(l0 + a0));
        pi1 = rcp(quad_sum(l1 + a1));
        goto done;
      }
      wgmma_fence();
      issue_qk(qd0 + (rnd & 1) * DST, kd);
      if (first) write_o(pi0, pi1);
      fence_regs(o);
      if (kill) {
        wgmma_fence();
        issue_pv(vd, !first, 4);
      } else {
        wgmma_fence();
        issue_pv(vd, !first, 8);
      }
      named_bar_arrive(sched_other, 256);
      fl &= 2;
      l0 += a0;
      l1 += a1;
      if (rem == 0 || first) {
        if (first && (g > 0 || after_qkv)) store_o(g ? rnd - (rem == 0 ? 2 : 1) : 2, g ? ST_BOX2 : ST_BOX2Q);
        first = rem == 0;
        if (first) {
          pi0 = rcp(quad_sum(l0));
          pi1 = rcp(quad_sum(l1));
          l0 = l1 = b0 = b1 = 0.f;
          fl = 0;
          rem = item_m(item_of(maps, rnd)) + 1;
        }
      }
      rem--;
      g++;
      wgmma_wait<1>();
      fence_regs(s);
      mbar_arrive_if(kb + (B_KEMPTY - B_KFULL), wtid == 32);
      ST(g + 1)
      if (rem == 0 || shifted) {
        d0 = b0;
        d1 = b1;
        break;
      }
    }
  }
done:
#undef redo
#undef shifted
  wgmma_wait<0>();
  fence_regs(o);
  write_o(pi0, pi1);
  store_o(3, ST_BOX2L);
  ST(35)
  return sn;
}

constexpr int O_STAGES = 5;
constexpr int O_STAGE_BYTES = 32768;
constexpr int O_Y_OFF = 5 * 32768;
constexpr int O_X_OFF = 6 * 32768;
constexpr int O_NK = HDIM / 64;

__device__ __forceinline__ uint32_t out_stage(uint32_t st) { return ((0x43120u >> (4 * st)) & 7) * O_STAGE_BYTES; }

__device__ __forceinline__ void out_producer(const Maps& maps, uint32_t sbase, bool after_attn, bool dry) {
  const uint32_t bar = sbase + BAR_OFF;
  const uint32_t rank = blockIdx.x & 1;
  const int m_tile = maps.id[blockIdx.x][2] & 15, n_tile = maps.id[blockIdx.x][2] >> 4;
  uint32_t stage = 0, phase = 0;
#pragma unroll 1
  for (int ki = 0; ki < (dry ? 1 : O_NK); ki++) {
    const int kt = (ki & 14) * 4 + ((A_ORDER >> ((ki >> 4) * 4)) & 3) * 2 + (ki & 1);
    const uint32_t fb = bar + B_OFULL + 8 * stage, eb = bar + B_OEMPTY + 8 * stage;
    const uint32_t sa = sbase + out_stage(stage);
    if (ki < O_STAGES) {
      constexpr uint32_t LASTB = B_KEMPTY | ((B_QEMPTY + 8) << 8) | ((B_KEMPTY + 8) << 16) | (B_VEMPTY << 24);
      if (ki > 0 && after_attn) mbar_wait_sleep(bar + ((LASTB >> (8 * ki - 8)) & 255), ki == 2);
      mbar_arrive_cluster_if(eb, 0, !dry);
      mbar_arrive_cluster_if(eb, 1, !dry);
    }
    if (ki == 32) mbar_wait_sleep(bar + B_CTX, 0);
    if (!dry) {
      mbar_wait_sleep(eb, phase);
      mbar_expect_tx(fb, O_STAGE_BYTES);
      tma_load_2d_mc(sa + 16384 + rank * 8192, &maps.ob, fb, n_tile * 128 + rank * 64, kt * 64, (uint16_t)3);
      tma_load_2d(sa, &maps.oa, fb, kt * 64, m_tile * 128);
    }
    if (++stage == O_STAGES) { stage = 0; phase ^= 1; }
  }
  if (!dry) mbar_wait_sleep(bar + B_OY2, 0);
}

__device__ __forceinline__ void out_side(const Maps& maps, uint32_t smem0, const float (&gv)[4]) {
  PHASE_PROLOGUE
  const int m_tile = maps.id[blockIdx.x][2] & 15, n_tile = maps.id[blockIdx.x][2] >> 4;
  const bool w0 = __shfl_sync(0xffffffffu, warp, 0) == 0;
  if (w0) {
    if (elect_one()) {
      mbar_expect_tx(bar + B_OY, 65536 - 4096);
#pragma unroll 1
      for (int i = 0; i < 15; i++) {
        if (i == 8) {
          TD(10)
          cnt_wait(CNT_Y2, DM - 128);
          TD(7)
        }
        tma_load_3d(sbase + (i < 8 ? O_X_OFF : O_Y_OFF - 32768) + i * 4096, i < 8 ? &maps.xs : &maps.y, bar + B_OY, 0,
                    i < 8 ? m_tile * 128 + (i & 3) * 32 : n_tile * 128 - 128 + i * 16,
                    i < 8 ? n_tile * 2 + (i >> 2) : m_tile * 2);
        __nanosleep(PACE);
      }
    }
  }
  mbar_wait_sleep(bar + B_OY, 0);
  if (wtid == 0) { TD(12) }
  const int st_row = warp * 16 + (lane & 7) + ((lane >> 3) & 1) * 8;
  const int mrow = (lane & 7) + ((lane >> 4) & 1) * 8;
  const int mchunk = warp * 2 + ((lane >> 3) & 1);
  const uint32_t xrow = sbase + O_X_OFF + st_row * 128;
  const uint32_t yrow = sbase + O_Y_OFF + mrow * 128 + ((mchunk ^ (lane & 7)) << 4);
  uint32_t y[7][4], x[7][4], om[4];
#pragma unroll
  for (int i = 0; i < 4; i++) om[i] = pack_bf16(1.0f - gv[i], 1.0f - gv[i]);
  auto xa = [&](int h, int i) { return xrow + h * 8192 + (i >> 2) * 16384 + ((((i & 3) * 2 + (lane >> 4)) ^ (lane & 7)) << 4); };
  auto load = [&](int r, int h, int i) {
    ldsm4t(y[r], yrow + h * 2048 + i * 4096);
    asm volatile("ldmatrix.sync.aligned.m8n8.x4.shared.b16 {%0, %1, %2, %3}, [%4];"
                 : "=r"(x[r][0]), "=r"(x[r][1]), "=r"(x[r][2]), "=r"(x[r][3])
                 : "r"(xa(h, i)));
  };
  auto store = [&](int r, int h, int i, uint32_t om0, uint32_t om1) {
    stmatrix_x4(xa(h, i), mul_bf2(om0, mul_bf2(x[r][0], y[r][0])), mul_bf2(om1, mul_bf2(x[r][1], y[r][1])),
                mul_bf2(om0, mul_bf2(x[r][2], y[r][2])), mul_bf2(om1, mul_bf2(x[r][3], y[r][3])));
  };
#pragma unroll 1
  for (int h = 0; h < 2; h++) {
#pragma unroll
    for (int i = 0; i < 7; i++) load(i, h, i);
#pragma unroll
    for (int i = 0; i < 7; i++) store(i, h, i, h ? om[2] : om[0], h ? om[3] : om[1]);
  }
  if (w0) {
    if (elect_one()) {
      mbar_expect_tx(bar + B_OY2, 4096);
      cnt_wait(CNT_Y2 + 1, 128);
      TD(11)
      tma_load_3d(sbase + O_Y_OFF + 7 * 4096, &maps.y, bar + B_OY2, 0, n_tile * 128 + 112, m_tile * 2);
    }
  }
  mbar_wait_sleep(bar + B_OY2, 0);
  load(0, 0, 7);
  load(1, 1, 7);
  store(0, 0, 7, om[0], om[1]);
  store(1, 1, 7, om[2], om[3]);
  __syncwarp();
  mbar_arrive_if(bar + B_OY + 8, lane == 0);
  if (wtid == 0) { TD(13) }
}

__device__ __forceinline__ uint32_t out_gemm(const Maps& maps, uint32_t smem0, uint32_t sn) {
  PHASE_PROLOGUE
  const int m_tile = maps.id[blockIdx.x][2] & 15, n_tile = maps.id[blockIdx.x][2] >> 4;
  float acc[2][64];
  undef_regs(acc[0]);
  undef_regs(acc[1]);
  uint32_t stage = 0, phase = 0, prev_stage = 0;
  GT(gti++)
  const float* gp = g_gate + m_tile * 128 + warp * 16 + (lane >> 2);
  const float gv[4] = {__ldcg(gp), __ldcg(gp + 8), __ldcg(gp + 64), __ldcg(gp + 72)};
  if (wg == 1) {
    out_side(maps, smem0, gv);
    return sn;
  }
#pragma unroll 1
  for (int kt = 0; kt < O_NK; kt++) {
    uint32_t da = (uint32_t)make_desc(sbase + out_stage(stage), 16, 0, 0);
    uint32_t db = (uint32_t)make_desc(sbase + out_stage(stage) + 16384, 8192, 0, 0);
    asm volatile("" : "+r"(da), "+r"(db));
    mbar_wait(bar + B_OFULL + 8 * stage, phase);
    GT(gti++)
    constexpr int OWAIT = 2;
    constexpr uint64_t DHI = DESC_SW128 | ((uint64_t)(1024 >> 4) << 32);
#pragma unroll
    for (int kk = 0; kk < 4; kk++) {
      wgmma_wait<OWAIT>();
      if (kk == OWAIT)
        mbar_arrive_cluster_if(bar + B_OEMPTY + 8 * prev_stage, wtid >> 6,
                               (wtid & 63) == 32 && kt > 0 && kt - 1 + O_STAGES < O_NK);
      wgmma_fence();
      wgmma_m64n128_ss_tb(acc[0], DHI | (da + kk * 2), DHI | (db + kk * 128), (kt | kk) != 0);
      wgmma_m64n128_ss_tb(acc[1], DHI | (da + 512 + kk * 2), DHI | (db + kk * 128), (kt | kk) != 0);
      wgmma_commit();
    }
    prev_stage = stage;
    if (++stage == O_STAGES) { stage = 0; phase ^= 1; }
  }
  if (tid == 0) { TD(14) }
  st_wait(bar, wg, sn - 1);
  const int st_row = warp * 16 + (lane & 7) + ((lane >> 3) & 1) * 8;
  const uint32_t rowa = sbase + O_X_OFF + st_row * 128;
  wgmma_wait<0>();
  fence_regs(acc[0]);
  fence_regs(acc[1]);
  GT(gti++)
  uint32_t gg[4];
#pragma unroll
  for (int i = 0; i < 4; i++) gg[i] = pack_bf16(gv[i], gv[i]);
  mbar_wait(bar + B_OY + 8, 0);
#pragma unroll
  for (int i = 0; i < 16; i++) {
    const int h = i & 1, j = i & 14;
    const uint32_t addr = rowa + h * 8192 + (j >> 3) * 16384 + ((((j & 7) + (lane >> 4)) ^ (st_row & 7)) << 4);
    uint32_t b0, b1, b2, b3;
    asm volatile("ldmatrix.sync.aligned.m8n8.x4.shared.b16 {%0, %1, %2, %3}, [%4];"
                 : "=r"(b0), "=r"(b1), "=r"(b2), "=r"(b3)
                 : "r"(addr));
    const float* a = acc[h] + 4 * j;
    const uint32_t gg0 = gg[2 * h], gg1 = gg[2 * h + 1];
    stmatrix_x4(addr, add_bf2(mul_bf2(gg0, pack_bf16(a[0], a[1])), b0),
                add_bf2(mul_bf2(gg1, pack_bf16(a[2], a[3])), b1), add_bf2(mul_bf2(gg0, pack_bf16(a[4], a[5])), b2),
                add_bf2(mul_bf2(gg1, pack_bf16(a[6], a[7])), b3));
    if (i == 7) st_post(bar, wg, wtid, sn, ST_BOX1, &maps.oc, sbase + O_X_OFF, n_tile * 128, m_tile * 128, -1);
  }
  fence_proxy_async();
  named_bar_sync(1, 128);
  if (__shfl_sync(0xffffffffu, warp, 0) == 0) {
    if (elect_one()) {
      tma_store_2d(&maps.oc, sbase + O_X_OFF + 16384, n_tile * 128 + 64, m_tile * 128);
      tma_store_commit();
    }
  }
  GT(gti++)
  return sn + 1;
}

__device__ __noinline__ void leave_kernel(int mask) {
  if (!(mask & 4)) return;
  if (atomicAdd(g_cnt + CNT_DONE * 32, 1u) == 2 * gridDim.x - 1) {
    for (int i = 0; i < CNT_N; i++) g_cnt[i * 32] = 0;
  }
}

__device__ __noinline__ void side_jobs(const Maps& maps, uint32_t sbase) {
  const int w12 = __shfl_sync(0xffffffffu, threadIdx.x >> 5, 0);
  gate_rows(maps, sbase, (blockIdx.x - 128) * 12 + w12, w12, threadIdx.x & 31);
  fence_proxy_async();
  __syncthreads();
  if (threadIdx.x == 320) cnt_signal_release(CNT_PREP, 1);
}

__global__ void __launch_bounds__(384, 1) fused_kernel(int mask, const __grid_constant__ Maps maps) {
  extern __shared__ __align__(1024) uint8_t smem_raw[];
  {
    const uint32_t sbase = __shfl_sync(0xffffffffu, smem_u32(smem_raw), 0);
    const uint32_t bar = sbase + BAR_OFF;
    const int tid = threadIdx.x;
    const bool do_qkv = (mask & 1) && blockIdx.x < 128;
    TL(0, 0)
    if (__shfl_sync(0xffffffffu, tid >> 5, 0) == 1 && do_qkv) {
      if (elect_one()) {
        for (int i = 0; i < G_STAGES; i++) mbar_init(bar + B_GFULL + 8 * i, 1);
        fence_barrier_init();
        qkv_producer(maps, sbase, true);
      }
    }
    if (tid == 0) {
      for (int i = 0; i < G_STAGES; i++) {
        mbar_init(bar + B_GEMPTY + 8 * i, 2);
        mbar_init(bar + B_SFULL + 8 * i, 4);
        mbar_init(bar + B_SFREE + 8 * i, 1);
      }
      for (int i = 0; i < 2; i++) {
        mbar_init(bar + B_OFREE + 8 * i, 1);
        mbar_init(bar + B_QFULL + 8 * i, 1);
        mbar_init(bar + B_QEMPTY + 8 * i, 2);
        mbar_init(bar + B_KFULL + 8 * i, 1);
        mbar_init(bar + B_KEMPTY + 8 * i, 2);
        mbar_init(bar + B_VFULL + 8 * i, 1);
        mbar_init(bar + B_VEMPTY + 8 * i, 2);
      }
      for (int i = 0; i < O_STAGES; i++) {
        mbar_init(bar + B_OFULL + 8 * i, 1);
        mbar_init(bar + B_OEMPTY + 8 * i, 2);
      }
      mbar_init(bar + B_OY, 1);
      mbar_init(bar + B_CTX, 1);
      mbar_init(bar + B_OY2, 1);
      mbar_init(bar + B_OY + 8, 4);
      mbar_init(bar + B_QDONE, 2);
      for (int i = 0; i < 8; i++) mbar_init(bar + B_CFULL + 8 * i, 1);
      for (int i = 0; i < CNT_N; i++) asm volatile("st.shared.u32 [%0], 0;" ::"r"(bar + B_PEND + 4 * i) : "memory");
      fence_barrier_init();
    }
    __syncthreads();
    asm volatile("barrier.cluster.arrive.relaxed.aligned;" ::: "memory");
    if ((mask & 1) && blockIdx.x >= 128) side_jobs(maps, sbase);
  }
  uint32_t smem0 = smem_u32(smem_raw);
  PHASE_PROLOGUE
  const bool do_qkv = (mask & 1) && blockIdx.x < 128, do_out = (mask & 4) && blockIdx.x < 128;
  TL(0, 1)

  if (wg != 2) {
    reg_alloc<232>();
    uint32_t sn = 0;
    float o[64];
    if (do_qkv) {
      sn = qkv_consumer(maps, smem_u32(smem_raw), mask & 2, o);
    } else {
      undef_regs(o);
    }
    TL(0, 2) TL(1, 0) TL(1, 1)
    asm volatile("barrier.cluster.wait.acquire.aligned;" ::: "memory");
    if (mask & 2) {
      sn = attn_consumer(maps, smem_u32(smem_raw), sn, o, mask & 1);
      TL(2, 0)
      if ((mask & 4) && blockIdx.x < 128 && __shfl_sync(0xffffffffu, threadIdx.x, 0) < 128) {
        named_bar_arrive(3, 256);
      } else {
        const uint32_t b2 = blockIdx.x * 2 + (threadIdx.x >> 7);
        const bool fused = mask & 4, mainc = blockIdx.x < 128;
        const uint32_t first = __shfl_sync(0xffffffffu, !fused ? b2 : mainc ? conv_first(maps) : (b2 - 255) * 128 - C_SIDE, 0);
        conv_consumer(maps, smem_u32(smem_raw), first, !fused ? 264 : mainc ? 16 : 1,
                      !fused ? DM : mainc ? (first | 127) + 1 - C_SIDE : first + C_SIDE, fused && !mainc);
      }
      TL(1, 2) TL(2, 1) TL(2, 2)
    }
    TL(3, 0) TL(3, 1)
    if ((mask & 4) && blockIdx.x < 128) sn = out_gemm(maps, smem_u32(smem_raw), sn);
    {
      uint32_t smem0 = smem_u32(smem_raw);
      PHASE_PROLOGUE
      st_wait(bar, wg, sn - 2);
      st_post(bar, wg, wtid, sn, ST_END, nullptr, 0, 0, 0, -1);
      tma_store_wait_read<0>();
    }
  } else {
    reg_dealloc<40>();
    asm volatile("barrier.cluster.wait.acquire.aligned;" ::: "memory");
    const int w = __shfl_sync(0xffffffffu, tid >> 5, 0) - 8;
    if (w < 2) {
      if (do_qkv) prep_agent(maps, sbase, w, lane);
      if (elect_one()) store_agent(bar, w);
      TL2(3, 2)
    } else {
      if (elect_one()) {
        const bool dry = w == 2;
        if (do_qkv && !dry) qkv_producer(maps, sbase, false);
        if (mask & 2) attn_producer(maps, sbase, do_qkv, do_out, dry);
        if (do_out) out_producer(maps, sbase, mask & 2, dry);
        if (dry) { TD(5) }
      }
      __syncwarp();
      if (w == 2) publisher(bar, tid & 31, !(mask & 2) ? 2 : do_out ? 3 : 4, !do_out ? ~0u : mask & 2);
      if ((tid & 31) == 0) leave_kernel(mask);
    }
  }
}

typedef CUresult (*PFN_tmapEncode)(CUtensorMap*, CUtensorMapDataType, cuuint32_t, void*, const cuuint64_t*,
                                   const cuuint64_t*, const cuuint32_t*, const cuuint32_t*, CUtensorMapInterleave,
                                   CUtensorMapSwizzle, CUtensorMapL2promotion, CUtensorMapFloatOOBfill);
static PFN_tmapEncode s_encode = nullptr;

static void make_map_2d(CUtensorMap* m, const void* ptr, int rows, int cols, int box_rows) {
  cuuint64_t dims[2] = {(cuuint64_t)cols, (cuuint64_t)rows};
  cuuint64_t strides[1] = {(cuuint64_t)cols * 2};
  cuuint32_t box[2] = {cols < 64 ? 32u : 64u, (cuuint32_t)box_rows};
  cuuint32_t es[2] = {1, 1};
  s_encode(m, CU_TENSOR_MAP_DATA_TYPE_BFLOAT16, 2, const_cast<void*>(ptr), dims, strides, box, es,
           CU_TENSOR_MAP_INTERLEAVE_NONE, cols < 64 ? CU_TENSOR_MAP_SWIZZLE_64B : CU_TENSOR_MAP_SWIZZLE_128B, CU_TENSOR_MAP_L2_PROMOTION_L2_256B,
           CU_TENSOR_MAP_FLOAT_OOB_FILL_NONE);
}
static void make_map_3d(CUtensorMap* m, const void* ptr, int rows, int cols, int box_rows, int box_chunks) {
  cuuint64_t dims[3] = {64, (cuuint64_t)rows, (cuuint64_t)(cols / 64)};
  cuuint64_t strides[2] = {(cuuint64_t)cols * 2, 128};
  cuuint32_t box[3] = {64, (cuuint32_t)box_rows, (cuuint32_t)box_chunks};
  cuuint32_t es[3] = {1, 1, 1};
  s_encode(m, CU_TENSOR_MAP_DATA_TYPE_BFLOAT16, 3, const_cast<void*>(ptr), dims, strides, box, es,
           CU_TENSOR_MAP_INTERLEAVE_NONE, CU_TENSOR_MAP_SWIZZLE_128B, CU_TENSOR_MAP_L2_PROMOTION_L2_256B,
           CU_TENSOR_MAP_FLOAT_OOB_FILL_NONE);
}

static cudaLaunchConfig_t fused_cfg(cudaLaunchAttribute* at) {
  cudaLaunchConfig_t cfg = {};
  cfg.gridDim = dim3(132);
  cfg.blockDim = dim3(384);
  cfg.dynamicSmemBytes = SMEM_BYTES;
  cfg.stream = cudaStreamPerThread;
  at[0].id = cudaLaunchAttributeClusterDimension;
  at[0].val.clusterDim.x = 2;
  at[0].val.clusterDim.y = 1;
  at[0].val.clusterDim.z = 1;
  cfg.attrs = at;
  cfg.numAttrs = 1;
  return cfg;
}

extern "C" void kernel_launch(void* const* d_in, const int* in_sizes, int n_in, void* d_out, int out_size) {
  const bf16* x = (const bf16*)d_in[0];
  const bf16* ckv = (const bf16*)d_in[1];
  const bf16* wq = (const bf16*)d_in[2];
  const bf16* wuk = (const bf16*)d_in[3];
  const bf16* wuv = (const bf16*)d_in[4];
  const bf16* wo = (const bf16*)d_in[5];
  const bf16* bk = (const bf16*)d_in[7];
  const bf16* bv = (const bf16*)d_in[8];
  const bf16* shift_k = (const bf16*)d_in[9];
  const bf16* ssm_k = (const bf16*)d_in[10];
  const bf16* ssm_D = (const bf16*)d_in[11];
  const bf16* gate_w = (const bf16*)d_in[12];
  bf16* out = (bf16*)d_out;

  static void *pq = nullptr, *pk = nullptr, *pv = nullptr, *pctx = nullptr, *pb = nullptr, *pu = nullptr;
  static int max_clusters = 0;
  if (!s_encode) {
    void* fn = nullptr;
    cudaDriverEntryPointQueryResult qres;
    cudaGetDriverEntryPoint("cuTensorMapEncodeTiled", &fn, cudaEnableDefault, &qres);
    s_encode = (PFN_tmapEncode)fn;
    cudaGetSymbolAddress(&pq, g_q);
    cudaGetSymbolAddress(&pk, g_k);
    cudaGetSymbolAddress(&pv, g_v);
    cudaGetSymbolAddress(&pctx, g_ctx);
    cudaGetSymbolAddress(&pb, g_y2T);
    cudaGetSymbolAddress(&pu, g_kvT);
    cudaFuncSetAttribute(fused_kernel, cudaFuncAttributeMaxDynamicSharedMemorySize, SMEM_BYTES);
    cudaLaunchAttribute at[1];
    cudaLaunchConfig_t cfg = fused_cfg(at);
    if (cudaOccupancyMaxActiveClusters(&max_clusters, fused_kernel, &cfg) != cudaSuccess) max_clusters = 0;
  }

  Maps all = {};
  make_map_2d(&all.a[0], x, S_LEN, DM, 128);
  make_map_2d(&all.a[1], ckv, S_LEN, DC, 128);
  make_map_3d(&all.b[0], wq, DM, HDIM, 64, 4);
  make_map_3d(&all.b[1], wuk, DC, HDIM, 64, 4);
  make_map_3d(&all.b[2], wuv, DC, HDIM, 64, 4);
  make_map_2d(&all.c[0], pq, S_LEN, HDIM, 64);
  make_map_2d(&all.c[1], pk, S_LEN, HDIM, 64);
  make_map_2d(&all.c[2], pv, S_LEN, HDIM, 64);
  make_map_3d(&all.q, pq, S_LEN, HDIM, 128, 2);
  make_map_3d(&all.k, pk, S_LEN, HDIM, 128, 2);
  make_map_3d(&all.v, pv, S_LEN, HDIM, 128, 2);
  make_map_2d(&all.o, pctx, S_LEN, HDIM, 64);
  all.ssm_k = ssm_k;
  all.ssm_D = ssm_D;
  make_map_2d(&all.oa, pctx, S_LEN, HDIM, 128);
  make_map_2d(&all.ob, wo, HDIM, DM, 64);
  make_map_2d(&all.oc, out, S_LEN, DM, 128);
  make_map_3d(&all.y, pb, DM, S_LEN, 16, 2);
  make_map_3d(&all.xs, x, S_LEN, DM, 32, 1);
  make_map_2d(&all.cu, pu, DM * 64, 32, 64);
  make_map_2d(&all.ch, ssm_k, DM * 64, 32, 64);

  make_map_2d(&all.bk, bk, S_LEN, DM, 35);
  make_map_2d(&all.bv, bv, S_LEN, DM, 32);
  for (int b = 0; b < 128; b++) {
    const int c = b >> 1, r = b & 1;
    const int G = c < 4 ? 0 : c < 36 ? (c - 4) % 8 : 1 + (c - 36) % 7;
    const int i = c < 4 ? 4 + c : c < 36 ? (c - 4) / 8 : 4 + (c - 36) / 7;
    all.id[b][0] = r + 2 * (i & 1) + 4 * (G & 3) + 16 * (i >> 1) + 64 * (G >> 2);
    all.id[b][1] = r + 2 * i + 16 * G;
    all.id[b][2] = r + 2 * G + 16 * i;
  }
  all.shift_k = shift_k;
  all.x = x;
  all.gate_w = gate_w;
  cudaLaunchAttribute at[1];
  cudaLaunchConfig_t cfg = fused_cfg(at);
  if (max_clusters >= 66) {
    cudaLaunchKernelEx(&cfg, fused_kernel, 7, all);
  } else {
    for (int m = 1; m <= 4; m <<= 1) cudaLaunchKernelEx(&cfg, fused_kernel, m, all);
  }
}
```

```cpp
#include <cuda_runtime.h>
#include <cuda_bf16.h>
#include <cuda.h>
#include <stdint.h>

typedef __nv_bfloat16 bf16;
#define INPLACE 3

constexpr int S_LEN = 2048;
constexpr int DM = 1024;
constexpr int NH = 32;
constexpr int HD = 128;
constexpr int DC = 512;
constexpr int HDIM = NH * HD;

__device__ __align__(1024) bf16 g_q[S_LEN * HDIM];
__device__ __align__(1024) bf16 g_k[S_LEN * HDIM];
__device__ __align__(1024) bf16 g_v[S_LEN * HDIM];
#define g_ctx g_q
__device__ __align__(1024) bf16 g_kvT[DM * S_LEN];
#define g_y2T g_kvT
__device__ __align__(1024) float g_gate[S_LEN];
enum { CNT_KV = 0, CNT_PREP = CNT_KV + 2, CNT_CTX, CNT_Y2 = CNT_CTX + 2, CNT_DONE = CNT_Y2 + 2, CNT_N };
__device__ unsigned int g_cnt[CNT_N * 32];

#define TL(k, i)
#define TL2(k, i)
#define TD(i)
#define CT(i)
#define GT(i)
#define GA(i)
#define ST(i)

__device__ __forceinline__ uint32_t smem_u32(const void* p) { return (uint32_t)__cvta_generic_to_shared(p); }

__device__ __forceinline__ void mbar_init(uint32_t bar, uint32_t count) {
  asm volatile("mbarrier.init.shared::cta.b64 [%0], %1;" ::"r"(bar), "r"(count));
}
__device__ __forceinline__ void mbar_expect_tx(uint32_t bar, uint32_t bytes) {
  asm volatile("mbarrier.arrive.expect_tx.shared::cta.b64 _, [%0], %1;" ::"r"(bar), "r"(bytes) : "memory");
}
__device__ __forceinline__ void mbar_arrive(uint32_t bar) {
  asm volatile("mbarrier.arrive.shared::cta.b64 _, [%0];" ::"r"(bar) : "memory");
}
__device__ __forceinline__ void mbar_wait(uint32_t bar, uint32_t parity) {
  uint32_t done;
  uint32_t spins = 0;
  do {
    asm volatile(
        "{\n.reg .pred p;\n"
        "mbarrier.try_wait.parity.shared::cta.b64 p, [%1], %2;\n"
        "selp.u32 %0, 1, 0, p;\n}\n"
        : "=r"(done)
        : "r"(bar), "r"(parity)
        : "memory");
    if (++spins > (1u << 22)) break;
  } while (!done);
}
__device__ __forceinline__ bool mbar_try(uint32_t bar, uint32_t parity) {
  uint32_t done;
  asm volatile(
      "{\n.reg .pred p;\n"
      "mbarrier.try_wait.parity.shared::cta.b64 p, [%1], %2;\n"
      "selp.u32 %0, 1, 0, p;\n}\n"
      : "=r"(done)
      : "r"(bar), "r"(parity)
      : "memory");
  return done != 0;
}
__device__ __forceinline__ bool elect_one() {
  uint32_t pred;
  asm volatile("{\n.reg .pred p;\nelect.sync _|p, 0xffffffff;\nselp.u32 %0, 1, 0, p;\n}\n" : "=r"(pred));
  return pred != 0;
}
__device__ __forceinline__ void mbar_arrive_if(uint32_t bar, bool pred) {
  asm volatile(
      "{\n.reg .pred p;\nsetp.ne.b32 p, %1, 0;\n"
      "@p mbarrier.arrive.shared::cta.b64 _, [%0];\n}\n" ::"r"(bar),
      "r"((uint32_t)pred)
      : "memory");
}
__device__ __forceinline__ void mbar_wait_sleep(uint32_t bar, uint32_t parity) {
  uint32_t done;
  uint32_t spins = 0;
  do {
    asm volatile(
        "{\n.reg .pred p;\n"
        "mbarrier.try_wait.parity.shared::cta.b64 p, [%1], %2, %3;\n"
        "selp.u32 %0, 1, 0, p;\n}\n"
        : "=r"(done)
        : "r"(bar), "r"(parity), "r"(20000u)
        : "memory");
    if (++spins > (1u << 16)) break;
  } while (!done);
}
__device__ __forceinline__ void fence_barrier_init() {
  asm volatile("fence.mbarrier_init.release.cluster;" ::: "memory");
}
__device__ __forceinline__ void fence_proxy_async() {
  asm volatile("fence.proxy.async.shared::cta;" ::: "memory");
}
__device__ __forceinline__ void named_bar_sync(int id, int nthreads) {
  asm volatile("bar.sync %0, %1;" ::"r"(id), "r"(nthreads) : "memory");
}
__device__ __forceinline__ void named_bar_arrive(int id, int nthreads) {
  asm volatile("bar.arrive %0, %1;" ::"r"(id), "r"(nthreads) : "memory");
}
__device__ __forceinline__ void tma_load_2d(uint32_t dst, const CUtensorMap* m, uint32_t bar, int c0, int c1) {
  asm volatile(
      "cp.async.bulk.tensor.2d.shared::cluster.global.mbarrier::complete_tx::bytes [%0], [%1, {%3, %4}], [%2];" ::"r"(dst),
      "l"(reinterpret_cast<uint64_t>(m)), "r"(bar), "r"(c0), "r"(c1)
      : "memory");
}
__device__ __forceinline__ void tma_load_3d(uint32_t dst, const CUtensorMap* m, uint32_t bar, int c0, int c1, int c2) {
  asm volatile(
      "cp.async.bulk.tensor.3d.shared::cluster.global.mbarrier::complete_tx::bytes [%0], [%1, {%3, %4, %5}], [%2];" ::"r"(dst),
      "l"(reinterpret_cast<uint64_t>(m)), "r"(bar), "r"(c0), "r"(c1), "r"(c2)
      : "memory");
}
__device__ __forceinline__ void tma_store_2d(const CUtensorMap* m, uint32_t src, int c0, int c1) {
  asm volatile("cp.async.bulk.tensor.2d.global.shared::cta.bulk_group [%0, {%2, %3}], [%1];" ::"l"(
                   reinterpret_cast<uint64_t>(m)),
               "r"(src), "r"(c0), "r"(c1)
               : "memory");
}
__device__ __forceinline__ void bulk_load(uint32_t dst, const void* src, uint32_t bytes, uint32_t bar) {
  asm volatile("cp.async.bulk.shared::cluster.global.mbarrier::complete_tx::bytes [%0], [%1], %2, [%3];" ::"r"(dst),
               "l"(src), "r"(bytes), "r"(bar)
               : "memory");
}
__device__ __forceinline__ void tma_load_2d_mc(uint32_t dst, const CUtensorMap* m, uint32_t bar, int c0, int c1,
                                               uint16_t mask) {
  asm volatile(
      "cp.async.bulk.tensor.2d.shared::cluster.global.mbarrier::complete_tx::bytes.multicast::cluster [%0], [%1, {%3, "
      "%4}], [%2], %5;" ::"r"(dst),
      "l"(reinterpret_cast<uint64_t>(m)), "r"(bar), "r"(c0), "r"(c1), "h"(mask)
      : "memory");
}
__device__ __forceinline__ void mbar_arrive_cluster_if(uint32_t bar, uint32_t cta, bool pred) {
  asm volatile(
      "{\n.reg .b32 ra;\n.reg .pred p;\nsetp.ne.b32 p, %2, 0;\n"
      "mapa.shared::cluster.u32 ra, %0, %1;\n"
      "@p mbarrier.arrive.shared::cluster.b64 _, [ra];\n}\n" ::"r"(bar),
      "r"(cta), "r"((uint32_t)pred)
      : "memory");
}
__device__ __forceinline__ uint64_t policy_evict_first() {
  uint64_t pol;
  asm volatile("createpolicy.fractional.L2::evict_first.b64 %0, 1.0;" : "=l"(pol));
  return pol;
}
__device__ __forceinline__ void tma_load_2d_hint(uint32_t dst, const CUtensorMap* m, uint32_t bar, int c0, int c1,
                                                 uint64_t pol) {
  asm volatile(
      "cp.async.bulk.tensor.2d.shared::cluster.global.mbarrier::complete_tx::bytes.L2::cache_hint [%0], [%1, {%3, %4}], "
      "[%2], %5;" ::"r"(dst),
      "l"(reinterpret_cast<uint64_t>(m)), "r"(bar), "r"(c0), "r"(c1), "l"(pol)
      : "memory");
}
__device__ __forceinline__ void tma_load_3d_hint(uint32_t dst, const CUtensorMap* m, uint32_t bar, int c0, int c1,
                                                 int c2, uint64_t pol) {
  asm volatile(
      "cp.async.bulk.tensor.3d.shared::cluster.global.mbarrier::complete_tx::bytes.L2::cache_hint [%0], [%1, {%3, %4, "
      "%5}], [%2], %6;" ::"r"(dst),
      "l"(reinterpret_cast<uint64_t>(m)), "r"(bar), "r"(c0), "r"(c1), "r"(c2), "l"(pol)
      : "memory");
}
__device__ __forceinline__ void bulk_load_hint(uint32_t dst, const void* src, uint32_t bytes, uint32_t bar, uint64_t pol) {
  asm volatile(
      "cp.async.bulk.shared::cluster.global.mbarrier::complete_tx::bytes.L2::cache_hint [%0], [%1], %2, [%3], %4;" ::"r"(dst),
      "l"(src), "r"(bytes), "r"(bar), "l"(pol)
      : "memory");
}
__device__ __forceinline__ void cnt_signal_release(int which, uint32_t n) {
  asm volatile("red.release.gpu.global.add.u32 [%0], %1;" ::"l"(g_cnt + which * 32), "r"(n) : "memory");
}
__device__ __forceinline__ void cnt_wait(int which, uint32_t target) {
  uint32_t v, spins = 0;
  while (true) {
    asm volatile("ld.acquire.gpu.global.u32 %0, [%1];" : "=r"(v) : "l"(g_cnt + which * 32) : "memory");
    if (v >= target || ++spins > (1u << 18)) break;
    __nanosleep(64);
  }
  asm volatile("fence.proxy.async.global;" ::: "memory");
}
__device__ __forceinline__ void tma_store_commit() { asm volatile("cp.async.bulk.commit_group;" ::: "memory"); }
template <int N>
__device__ __forceinline__ void tma_store_wait_read() {
  asm volatile("cp.async.bulk.wait_group.read %0;" ::"n"(N) : "memory");
}
template <int N>
__device__ __forceinline__ void tma_store_wait() {
  asm volatile("cp.async.bulk.wait_group %0;" ::"n"(N) : "memory");
}
__device__ __forceinline__ void wgmma_fence() { asm volatile("wgmma.fence.sync.aligned;" ::: "memory"); }
__device__ __forceinline__ void wgmma_commit() { asm volatile("wgmma.commit_group.sync.aligned;" ::: "memory"); }
template <int N>
__device__ __forceinline__ void wgmma_wait() {
  asm volatile("wgmma.wait_group.sync.aligned %0;" ::"n"(N) : "memory");
}
template <int R>
__device__ __forceinline__ void reg_alloc() { asm volatile("setmaxnreg.inc.sync.aligned.u32 %0;" ::"n"(R)); }
template <int R>
__device__ __forceinline__ void reg_dealloc() { asm volatile("setmaxnreg.dec.sync.aligned.u32 %0;" ::"n"(R)); }

__device__ __forceinline__ void stmatrix_x4(uint32_t addr, uint32_t r0, uint32_t r1, uint32_t r2, uint32_t r3) {
  asm volatile("stmatrix.sync.aligned.m8n8.x4.shared.b16 [%0], {%1, %2, %3, %4};" ::"r"(addr), "r"(r0), "r"(r1),
               "r"(r2), "r"(r3)
               : "memory");
}
__device__ __forceinline__ uint32_t pack_bf16(float lo, float hi) {
  uint32_t r;
  asm("cvt.rn.bf16x2.f32 %0, %1, %2;" : "=r"(r) : "f"(hi), "f"(lo));
  return r;
}
__device__ __forceinline__ float bf16_round(float x) { return __bfloat162float(__float2bfloat16_rn(x)); }
__device__ __forceinline__ float bf_lo(uint32_t v) { return __uint_as_float(v << 16); }
__device__ __forceinline__ float bf_hi(uint32_t v) { return __uint_as_float(v & 0xffff0000u); }
__device__ __forceinline__ uint4 lds128(uint32_t a) {
  uint4 v;
  asm volatile("ld.shared.v4.u32 {%0, %1, %2, %3}, [%4];" : "=r"(v.x), "=r"(v.y), "=r"(v.z), "=r"(v.w) : "r"(a));
  return v;
}
__device__ __forceinline__ void sts128(uint32_t a, uint4 v) {
  asm volatile("st.shared.v4.u32 [%0], {%1, %2, %3, %4};" ::"r"(a), "r"(v.x), "r"(v.y), "r"(v.z), "r"(v.w) : "memory");
}
__device__ __forceinline__ uint32_t mul_bf2(uint32_t a, uint32_t b) {
  uint32_t r;
  asm("mul.rn.bf16x2 %0, %1, %2;" : "=r"(r) : "r"(a), "r"(b));
  return r;
}
__device__ __forceinline__ uint32_t add_bf2(uint32_t a, uint32_t b) {
  uint32_t r;
  asm("add.rn.bf16x2 %0, %1, %2;" : "=r"(r) : "r"(a), "r"(b));
  return r;
}
__device__ __forceinline__ float ex2(float x) {
  float y;
  asm("ex2.approx.ftz.f32 %0, %1;" : "=f"(y) : "f"(x));
  return y;
}
__device__ __forceinline__ float rcp(float x) {
  float y;
  asm("rcp.approx.ftz.f32 %0, %1;" : "=f"(y) : "f"(x));
  return y;
}
template <int N>
__device__ __forceinline__ void fence_regs(float (&r)[N]) {
#pragma unroll
  for (int i = 0; i < N; i++) asm volatile("" : "+f"(r[i])::"memory");
}

template <int N>
__device__ __forceinline__ void undef_regs(float (&r)[N]) {
#pragma unroll
  for (int i = 0; i < N; i++) asm volatile("" : "=f"(r[i]));
}
template <int N>
__device__ __forceinline__ void fence_regs_u(uint32_t (&r)[N]) {
#pragma unroll
  for (int i = 0; i < N; i++) asm volatile("" : "+r"(r[i])::"memory");
}

constexpr uint64_t DESC_SW128 = 1ull << 62;
__device__ __forceinline__ uint64_t make_desc(uint32_t addr, uint32_t lbo_bytes, uint32_t sbo_bytes, uint64_t swz) {
  return (uint64_t)((addr & 0x3FFFF) >> 4) | ((uint64_t)((lbo_bytes & 0x3FFFF) >> 4) << 16) |
         ((uint64_t)((sbo_bytes & 0x3FFFF) >> 4) << 32) | swz;
}

__device__ __forceinline__ uint64_t desc_add(uint64_t d, uint32_t off16) {
  return (d & 0xFFFFFFFF00000000ull) | (uint64_t)((uint32_t)d + off16);
}

__device__ __forceinline__ void wgmma_m64n256_ss_tb(float (&d)[128], uint64_t da, uint64_t db, int sd) {
  asm volatile(
    "{\n.reg .pred p;\nsetp.ne.b32 p, %130, 0;\n"
    "wgmma.mma_async.sync.aligned.m64n256k16.f32.bf16.bf16 "
    "{%0, %1, %2, %3, %4, %5, %6, %7, %8, %9, %10, %11, %12, %13, %14, %15, %16, %17, %18, %19, %20, %21, %22, %23, %24, %25, %26, %27, %28, %29, %30, %31, %32, %33, %34, %35, %36, %37, %38, %39, %40, %41, %42, %43, %44, %45, %46, %47, %48, %49, %50, %51, %52, %53, %54, %55, %56, %57, %58, %59, %60, %61, %62, %63, %64, %65, %66, %67, %68, %69, %70, %71, %72, %73, %74, %75, %76, %77, %78, %79, %80, %81, %82, %83, %84, %85, %86, %87, %88, %89, %90, %91, %92, %93, %94, %95, %96, %97, %98, %99, %100, %101, %102, %103, %104, %105, %106, %107, %108, %109, %110, %111, %112, %113, %114, %115, %116, %117, %118, %119, %120, %121, %122, %123, %124, %125, %126, %127}, %128, %129, p, 1, 1, 0, 1;\n}\n"
    : "+f"(d[0]), "+f"(d[1]), "+f"(d[2]), "+f"(d[3]), "+f"(d[4]), "+f"(d[5]), "+f"(d[6]), "+f"(d[7]), "+f"(d[8]), "+f"(d[9]), "+f"(d[10]), "+f"(d[11]), "+f"(d[12]), "+f"(d[13]), "+f"(d[14]), "+f"(d[15]), "+f"(d[16]), "+f"(d[17]), "+f"(d[18]), "+f"(d[19]), "+f"(d[20]), "+f"(d[21]), "+f"(d[22]), "+f"(d[23]), "+f"(d[24]), "+f"(d[25]), "+f"(d[26]), "+f"(d[27]), "+f"(d[28]), "+f"(d[29]), "+f"(d[30]), "+f"(d[31]), "+f"(d[32]), "+f"(d[33]), "+f"(d[34]), "+f"(d[35]), "+f"(d[36]), "+f"(d[37]), "+f"(d[38]), "+f"(d[39]), "+f"(d[40]), "+f"(d[41]), "+f"(d[42]), "+f"(d[43]), "+f"(d[44]), "+f"(d[45]), "+f"(d[46]), "+f"(d[47]), "+f"(d[48]), "+f"(d[49]), "+f"(d[50]), "+f"(d[51]), "+f"(d[52]), "+f"(d[53]), "+f"(d[54]), "+f"(d[55]), "+f"(d[56]), "+f"(d[57]), "+f"(d[58]), "+f"(d[59]), "+f"(d[60]), "+f"(d[61]), "+f"(d[62]), "+f"(d[63]), "+f"(d[64]), "+f"(d[65]), "+f"(d[66]), "+f"(d[67]), "+f"(d[68]), "+f"(d[69]), "+f"(d[70]), "+f"(d[71]), "+f"(d[72]), "+f"(d[73]), "+f"(d[74]), "+f"(d[75]), "+f"(d[76]), "+f"(d[77]), "+f"(d[78]), "+f"(d[79]), "+f"(d[80]), "+f"(d[81]), "+f"(d[82]), "+f"(d[83]), "+f"(d[84]), "+f"(d[85]), "+f"(d[86]), "+f"(d[87]), "+f"(d[88]), "+f"(d[89]), "+f"(d[90]), "+f"(d[91]), "+f"(d[92]), "+f"(d[93]), "+f"(d[94]), "+f"(d[95]), "+f"(d[96]), "+f"(d[97]), "+f"(d[98]), "+f"(d[99]), "+f"(d[100]), "+f"(d[101]), "+f"(d[102]), "+f"(d[103]), "+f"(d[104]), "+f"(d[105]), "+f"(d[106]), "+f"(d[107]), "+f"(d[108]), "+f"(d[109]), "+f"(d[110]), "+f"(d[111]), "+f"(d[112]), "+f"(d[113]), "+f"(d[114]), "+f"(d[115]), "+f"(d[116]), "+f"(d[117]), "+f"(d[118]), "+f"(d[119]), "+f"(d[120]), "+f"(d[121]), "+f"(d[122]), "+f"(d[123]), "+f"(d[124]), "+f"(d[125]), "+f"(d[126]), "+f"(d[127])
    : "l"(da), "l"(db), "r"(sd));
}

__device__ __forceinline__ void wgmma_m64n128_ss(float (&d)[64], uint64_t da, uint64_t db, int sd) {
  asm volatile(
    "{\n.reg .pred p;\nsetp.ne.b32 p, %66, 0;\n"
    "wgmma.mma_async.sync.aligned.m64n128k16.f32.bf16.bf16 "
    "{%0, %1, %2, %3, %4, %5, %6, %7, %8, %9, %10, %11, %12, %13, %14, %15, %16, %17, %18, %19, %20, %21, %22, %23, %24, %25, %26, %27, %28, %29, %30, %31, %32, %33, %34, %35, %36, %37, %38, %39, %40, %41, %42, %43, %44, %45, %46, %47, %48, %49, %50, %51, %52, %53, %54, %55, %56, %57, %58, %59, %60, %61, %62, %63}, %64, %65, p, 1, 1, 0, 0;\n}\n"
    : "+f"(d[0]), "+f"(d[1]), "+f"(d[2]), "+f"(d[3]), "+f"(d[4]), "+f"(d[5]), "+f"(d[6]), "+f"(d[7]), "+f"(d[8]), "+f"(d[9]), "+f"(d[10]), "+f"(d[11]), "+f"(d[12]), "+f"(d[13]), "+f"(d[14]), "+f"(d[15]), "+f"(d[16]), "+f"(d[17]), "+f"(d[18]), "+f"(d[19]), "+f"(d[20]), "+f"(d[21]), "+f"(d[22]), "+f"(d[23]), "+f"(d[24]), "+f"(d[25]), "+f"(d[26]), "+f"(d[27]), "+f"(d[28]), "+f"(d[29]), "+f"(d[30]), "+f"(d[31]), "+f"(d[32]), "+f"(d[33]), "+f"(d[34]), "+f"(d[35]), "+f"(d[36]), "+f"(d[37]), "+f"(d[38]), "+f"(d[39]), "+f"(d[40]), "+f"(d[41]), "+f"(d[42]), "+f"(d[43]), "+f"(d[44]), "+f"(d[45]), "+f"(d[46]), "+f"(d[47]), "+f"(d[48]), "+f"(d[49]), "+f"(d[50]), "+f"(d[51]), "+f"(d[52]), "+f"(d[53]), "+f"(d[54]), "+f"(d[55]), "+f"(d[56]), "+f"(d[57]), "+f"(d[58]), "+f"(d[59]), "+f"(d[60]), "+f"(d[61]), "+f"(d[62]), "+f"(d[63])
    : "l"(da), "l"(db), "r"(sd));
}

__device__ __forceinline__ void wgmma_m64n128_ss_tb(float (&d)[64], uint64_t da, uint64_t db, int sd) {
  asm volatile(
    "{\n.reg .pred p;\nsetp.ne.b32 p, %66, 0;\n"
    "wgmma.mma_async.sync.aligned.m64n128k16.f32.bf16.bf16 "
    "{%0, %1, %2, %3, %4, %5, %6, %7, %8, %9, %10, %11, %12, %13, %14, %15, %16, %17, %18, %19, %20, %21, %22, %23, %24, %25, %26, %27, %28, %29, %30, %31, %32, %33, %34, %35, %36, %37, %38, %39, %40, %41, %42, %43, %44, %45, %46, %47, %48, %49, %50, %51, %52, %53, %54, %55, %56, %57, %58, %59, %60, %61, %62, %63}, %64, %65, p, 1, 1, 0, 1;\n}\n"
    : "+f"(d[0]), "+f"(d[1]), "+f"(d[2]), "+f"(d[3]), "+f"(d[4]), "+f"(d[5]), "+f"(d[6]), "+f"(d[7]), "+f"(d[8]), "+f"(d[9]), "+f"(d[10]), "+f"(d[11]), "+f"(d[12]), "+f"(d[13]), "+f"(d[14]), "+f"(d[15]), "+f"(d[16]), "+f"(d[17]), "+f"(d[18]), "+f"(d[19]), "+f"(d[20]), "+f"(d[21]), "+f"(d[22]), "+f"(d[23]), "+f"(d[24]), "+f"(d[25]), "+f"(d[26]), "+f"(d[27]), "+f"(d[28]), "+f"(d[29]), "+f"(d[30]), "+f"(d[31]), "+f"(d[32]), "+f"(d[33]), "+f"(d[34]), "+f"(d[35]), "+f"(d[36]), "+f"(d[37]), "+f"(d[38]), "+f"(d[39]), "+f"(d[40]), "+f"(d[41]), "+f"(d[42]), "+f"(d[43]), "+f"(d[44]), "+f"(d[45]), "+f"(d[46]), "+f"(d[47]), "+f"(d[48]), "+f"(d[49]), "+f"(d[50]), "+f"(d[51]), "+f"(d[52]), "+f"(d[53]), "+f"(d[54]), "+f"(d[55]), "+f"(d[56]), "+f"(d[57]), "+f"(d[58]), "+f"(d[59]), "+f"(d[60]), "+f"(d[61]), "+f"(d[62]), "+f"(d[63])
    : "l"(da), "l"(db), "r"(sd));
}

__device__ __forceinline__ void wgmma_m64n128_rs_tb(float* d, uint32_t a0, uint32_t a1, uint32_t a2, uint32_t a3, uint64_t db, int sd) {
  asm volatile(
    "{\n.reg .pred p;\nsetp.ne.b32 p, %69, 0;\n"
    "wgmma.mma_async.sync.aligned.m64n128k16.f32.bf16.bf16 "
    "{%0, %1, %2, %3, %4, %5, %6, %7, %8, %9, %10, %11, %12, %13, %14, %15, %16, %17, %18, %19, %20, %21, %22, %23, %24, %25, %26, %27, %28, %29, %30, %31, %32, %33, %34, %35, %36, %37, %38, %39, %40, %41, %42, %43, %44, %45, %46, %47, %48, %49, %50, %51, %52, %53, %54, %55, %56, %57, %58, %59, %60, %61, %62, %63}, {%64, %65, %66, %67}, %68, p, 1, 1, 1;\n}\n"
    : "+f"(d[0]), "+f"(d[1]), "+f"(d[2]), "+f"(d[3]), "+f"(d[4]), "+f"(d[5]), "+f"(d[6]), "+f"(d[7]), "+f"(d[8]), "+f"(d[9]), "+f"(d[10]), "+f"(d[11]), "+f"(d[12]), "+f"(d[13]), "+f"(d[14]), "+f"(d[15]), "+f"(d[16]), "+f"(d[17]), "+f"(d[18]), "+f"(d[19]), "+f"(d[20]), "+f"(d[21]), "+f"(d[22]), "+f"(d[23]), "+f"(d[24]), "+f"(d[25]), "+f"(d[26]), "+f"(d[27]), "+f"(d[28]), "+f"(d[29]), "+f"(d[30]), "+f"(d[31]), "+f"(d[32]), "+f"(d[33]), "+f"(d[34]), "+f"(d[35]), "+f"(d[36]), "+f"(d[37]), "+f"(d[38]), "+f"(d[39]), "+f"(d[40]), "+f"(d[41]), "+f"(d[42]), "+f"(d[43]), "+f"(d[44]), "+f"(d[45]), "+f"(d[46]), "+f"(d[47]), "+f"(d[48]), "+f"(d[49]), "+f"(d[50]), "+f"(d[51]), "+f"(d[52]), "+f"(d[53]), "+f"(d[54]), "+f"(d[55]), "+f"(d[56]), "+f"(d[57]), "+f"(d[58]), "+f"(d[59]), "+f"(d[60]), "+f"(d[61]), "+f"(d[62]), "+f"(d[63])
    : "r"(a0), "r"(a1), "r"(a2), "r"(a3), "l"(db), "r"(sd));
}

__device__ __forceinline__ void wgmma_m64n64_rs_tb(float (&d)[32], const uint32_t (&a)[4], uint64_t db, int sd) {
  asm volatile(
    "{\n.reg .pred p;\nsetp.ne.b32 p, %37, 0;\n"
    "wgmma.mma_async.sync.aligned.m64n64k16.f32.bf16.bf16 "
    "{%0, %1, %2, %3, %4, %5, %6, %7, %8, %9, %10, %11, %12, %13, %14, %15, %16, %17, %18, %19, %20, %21, %22, %23, %24, %25, %26, %27, %28, %29, %30, %31}, {%32, %33, %34, %35}, %36, p, 1, 1, 1;\n}\n"
    : "+f"(d[0]), "+f"(d[1]), "+f"(d[2]), "+f"(d[3]), "+f"(d[4]), "+f"(d[5]), "+f"(d[6]), "+f"(d[7]), "+f"(d[8]), "+f"(d[9]), "+f"(d[10]), "+f"(d[11]), "+f"(d[12]), "+f"(d[13]), "+f"(d[14]), "+f"(d[15]), "+f"(d[16]), "+f"(d[17]), "+f"(d[18]), "+f"(d[19]), "+f"(d[20]), "+f"(d[21]), "+f"(d[22]), "+f"(d[23]), "+f"(d[24]), "+f"(d[25]), "+f"(d[26]), "+f"(d[27]), "+f"(d[28]), "+f"(d[29]), "+f"(d[30]), "+f"(d[31])
    : "r"(a[0]), "r"(a[1]), "r"(a[2]), "r"(a[3]), "l"(db), "r"(sd));
}

__device__ __forceinline__ void wgmma_m64n32_rs_tb(float (&d)[16], const uint32_t (&a)[4], uint64_t db, int sd) {
  asm volatile(
    "{\n.reg .pred p;\nsetp.ne.b32 p, %21, 0;\n"
    "wgmma.mma_async.sync.aligned.m64n32k16.f32.bf16.bf16 "
    "{%0, %1, %2, %3, %4, %5, %6, %7, %8, %9, %10, %11, %12, %13, %14, %15}, {%16, %17, %18, %19}, %20, p, 1, 1, 1;\n}\n"
    : "+f"(d[0]), "+f"(d[1]), "+f"(d[2]), "+f"(d[3]), "+f"(d[4]), "+f"(d[5]), "+f"(d[6]), "+f"(d[7]), "+f"(d[8]), "+f"(d[9]), "+f"(d[10]), "+f"(d[11]), "+f"(d[12]), "+f"(d[13]), "+f"(d[14]), "+f"(d[15])
    : "r"(a[0]), "r"(a[1]), "r"(a[2]), "r"(a[3]), "l"(db), "r"(sd));
}

constexpr int G_STAGES = 4;
constexpr int G_A_BYTES = 128 * 64 * 2;
constexpr int G_B_BYTES = 256 * 64 * 2;
constexpr int G_STAGE_BYTES = G_A_BYTES + G_B_BYTES;
constexpr int G_STG_OFF = G_STAGES * G_STAGE_BYTES;
constexpr int BAR_OFF = G_STG_OFF + 32768 + 2048;
constexpr int SMEM_BYTES = BAR_OFF + 1024;
constexpr int B_GFULL = 0, B_GEMPTY = 32, B_CTX = 64, B_OY2 = 72, B_PFULL = 224;
constexpr int B_KFULL = 80, B_KEMPTY = 96, B_VFULL = 112, B_VEMPTY = 128, B_QFULL = 144, B_QEMPTY = 160,
              B_QDONE = 184;
constexpr int B_CFULL = 192;
constexpr int B_OFREE = 256, B_OFULL = 272, B_OEMPTY = 320, B_OY = 368;
constexpr int B_SFULL = 392, B_SFREE = 424, B_PEND = 456, B_SCMD = 512;

#define PHASE_PROLOGUE                                                                \
  uint32_t tid, rt_zero;                                                              \
  asm volatile("mov.u32 %0, %%tid.x;" : "=r"(tid));                                   \
  asm volatile("mov.u32 %0, %%nctaid.y;" : "=r"(rt_zero));                            \
  asm volatile("" : "+r"(smem0));                                                     \
  rt_zero = __shfl_sync(0xffffffffu, rt_zero >> 8, 0);   \
  const uint32_t sbase = __shfl_sync(0xffffffffu, smem0, 0);                          \
  const uint32_t bar = sbase + BAR_OFF;                                               \
  const int wg = __shfl_sync(0xffffffffu, tid >> 7, 0);                               \
  const int warp = (tid >> 5) & 3, lane = tid & 31, wtid = tid & 127;                 \
  (void)rt_zero; (void)bar; (void)warp; (void)lane; (void)wtid;

enum { ST_END = 0, ST_BOX1, ST_BOX2, ST_BOX2Q, ST_BOX2L };
__device__ __forceinline__ void st_post(uint32_t bar, int wg, int wtid, uint32_t n, int kind, const void* dst,
                                        uint32_t src, int c0, int c1, int sig) {
  if (wtid == 0) {
    const uint32_t c = bar + B_SCMD + wg * 64 + (n & 1) * 32;
    const uint64_t d = reinterpret_cast<uint64_t>(dst);
    sts128(c, make_uint4(kind, src, c0, c1));
    sts128(c + 16, make_uint4((uint32_t)d, (uint32_t)(d >> 32), sig, 0));
  }
  fence_proxy_async();
  __syncwarp();
  mbar_arrive_if(bar + B_SFULL + wg * 16 + (n & 1) * 8, (wtid & 31) == 0);
}
__device__ __forceinline__ void st_wait(uint32_t bar, int wg, uint32_t n) {
  const uint32_t b = bar + B_SFREE + wg * 16 + (n & 1) * 8;
  if (!mbar_try(b, ~(n >> 1) & 1)) mbar_wait(b, ~(n >> 1) & 1);
}
__device__ __forceinline__ void note(uint32_t bar, uint32_t cnt) {
  asm volatile("red.release.cta.shared.add.u32 [%0], 1;" ::"r"(bar + B_PEND + 4 * cnt) : "memory");
}
__device__ __forceinline__ void store_agent(uint32_t bar, int wg) {
  mbar_arrive(bar + B_SFREE + wg * 16);
  mbar_arrive(bar + B_SFREE + wg * 16 + 8);
  bool more = true;
  for (uint32_t n = 0;; n++) {
    mbar_wait_sleep(bar + B_SFULL + wg * 16 + (n & 1) * 8, (n >> 1) & 1);
    const uint4 c = lds128(bar + B_SCMD + wg * 64 + (n & 1) * 32);
    const uint4 d = lds128(bar + B_SCMD + wg * 64 + (n & 1) * 32 + 16);
    if (c.x == ST_END) break;
    const CUtensorMap* dst = reinterpret_cast<const CUtensorMap*>((uint64_t)d.x | ((uint64_t)d.y << 32));
    tma_store_2d(dst, c.y, c.z, c.w);
    if (c.x >= ST_BOX2) tma_store_2d(dst, c.y + 8192, c.z + 64, c.w);
    tma_store_commit();
    tma_store_wait_read<0>();
    mbar_arrive(bar + B_SFREE + wg * 16 + (n & 1) * 8);
    if (c.x == ST_BOX2L) mbar_arrive(bar + B_OFREE + 8 * wg);
    if ((int)d.z >= 0) {
      tma_store_wait<0>();
      if (d.z == 0) { TD(6) }
      asm volatile("fence.proxy.async.global;" ::: "memory");
      if (c.x == ST_BOX2Q) mbar_arrive(bar + B_QDONE);
      else note(bar, d.z);
      if (c.x == ST_BOX2L) {
        note(bar, CNT_DONE);
        more = false;
      }
    }
  }
  if (more) note(bar, CNT_DONE);
}

struct Maps {
  const bf16 *shift_k, *x, *gate_w, *ssm_k, *ssm_D;
  uint8_t id[128][4];
  CUtensorMap a[2];
  CUtensorMap b[3];
  CUtensorMap c[3];
  CUtensorMap bk, bv;
  CUtensorMap q, k, v, o;
  CUtensorMap oa, ob, oc;
  CUtensorMap y, xs;
  CUtensorMap cu, ch;
};

constexpr int P_SLOT = 67 * 128, P_V = 35 * 128, P_TAPS = 2 * P_SLOT;
__device__ __forceinline__ void ldsm4t(uint32_t (&r)[4], uint32_t a) {
  asm volatile("ldmatrix.sync.aligned.m8n8.x4.trans.shared.b16 {%0, %1, %2, %3}, [%4];"
               : "=r"(r[0]), "=r"(r[1]), "=r"(r[2]), "=r"(r[3])
               : "r"(a));
}
__device__ __forceinline__ uint32_t fma_bf2(uint32_t a, uint32_t b, uint32_t c) {
  uint32_t r;
  asm("fma.rn.bf16x2 %0, %1, %2, %3;" : "=r"(r) : "r"(a), "r"(b), "r"(c));
  return r;
}
__device__ __forceinline__ void prep_agent(const Maps& maps, uint32_t sbase, int w, int lane) {
  const uint32_t bar = sbase + BAR_OFF, pb = bar + B_PFULL + w * 16;
  const int d0 = (blockIdx.x >> 3) * 64, t0 = (blockIdx.x & 7) * 256 + w * 128;
  mbar_wait_sleep(bar + B_GFULL + 8 * (G_STAGES - 1), 0);
#pragma unroll 1
  for (int i = -1; i < 4; i++) {
    GA(82 + 2 * i)
    if (i >= 0) mbar_wait_sleep(pb + (i & 1) * 8, i >> 1);
    GA(83 + 2 * i)
    const uint32_t so = sbase + G_STG_OFF + w * (P_TAPS + 512) + (i & 1) * P_SLOT;
    if (i < 3 && elect_one()) {
      const uint32_t b = pb + (~i & 1) * 8, dst = so + (i & 1 ? -P_SLOT : P_SLOT);
      mbar_expect_tx(b, i < 0 ? P_SLOT + 512 : P_SLOT);
      const uint64_t pol = policy_evict_first();
      tma_load_2d_hint(dst, &maps.bk, b, d0, t0 + 32 * i + 29, pol);
      tma_load_2d_hint(dst + P_V, &maps.bv, b, d0, t0 + 32 * i + 32, pol);
      if (i < 0) bulk_load(sbase + G_STG_OFF + P_TAPS, maps.shift_k + d0 * 4, 512, b);
    }
    if (i < 0) continue;
    uint32_t ak[4];
#pragma unroll
    for (int r = 0; r < 4; r++) {
      const uint32_t a = so / 128 + r + 4 * (lane & 6) + (((lane >> 2) ^ lane) & 6) + (lane & 1);
      ak[r] = a * 128 + (a & 7) * 16;
    }
    bf16* dst = g_kvT + (size_t)(d0 + (lane >> 2)) * S_LEN + t0 + ((lane & 3) + 4 * i) * 8;
#pragma unroll 1
    for (int cg = 0; cg < 128; cg += 16) {
      uint32_t t01, t23, k[4][4], v[4];
      asm volatile("ld.shared.v2.u32 {%0, %1}, [%2];"
                   : "=r"(t01), "=r"(t23)
                   : "r"(sbase + G_STG_OFF + P_TAPS + cg * 4 + (lane >> 2) * 8));
#pragma unroll
      for (int r = 0; r < 4; r++) ldsm4t(k[r], ak[r] ^ cg);
      ldsm4t(v, (ak[3] ^ cg) + 4096);
      const uint32_t w0 = __byte_perm(t01, 0, 0x1010), w1 = __byte_perm(t01, 0, 0x3232);
      const uint32_t w2 = __byte_perm(t23, 0, 0x1010), w3 = __byte_perm(t23, 0, 0x3232);
#pragma unroll
      for (int j = 0; j < 4; j++)
        v[j] = mul_bf2(fma_bf2(k[3][j], w0, fma_bf2(k[2][j], w1, fma_bf2(k[1][j], w2, mul_bf2(k[0][j], w3)))), v[j]);
      const bool s1 = lane & 1, s2 = lane & 2;
      const uint32_t a0 = s1 ? v[1] : v[0], a1 = s1 ? v[0] : v[1], a2 = s1 ? v[3] : v[2], a3 = s1 ? v[2] : v[3];
      *reinterpret_cast<uint4*>(dst) = make_uint4(s2 ? a2 : a0, s2 ? a3 : a1, s2 ? a0 : a2, s2 ? a1 : a3);
      dst += 8 * S_LEN;
    }
    fence_proxy_async();
    __syncwarp();
  }
  GA(90)
  if (lane == 0) note(bar, CNT_PREP);
  __syncwarp();
  GA(91)
}

__device__ __forceinline__ void qkv_tile(const Maps& maps, int it, int& which, int& m_tile, int& n_tile) {
  const bool q = it == 0 || it >= 5;
  const int b = maps.id[blockIdx.x][it >= 5];
  which = q ? 0 : 2 - (it & 1);
  m_tile = b & 15;
  n_tile = (b >> 4) * 2 + ((0x19 >> it) & 1);
}

constexpr int G_NTILES = 6;
__device__ __forceinline__ void qkv_producer(const Maps& maps, uint32_t sbase, bool first) {
  const uint32_t bar = sbase + BAR_OFF;
  uint32_t stage = 0, phase = 0;
#pragma unroll 1
  for (int it = 0; it < (first ? 1 : G_NTILES); it++) {
    int which, m_tile, n_tile;
    qkv_tile(maps, it, which, m_tile, n_tile);
    const CUtensorMap* ma = &maps.a[which == 0 ? 0 : 1];
    const CUtensorMap* mb = &maps.b[which];
    const int nk = first ? G_STAGES : which == 0 ? 16 : 8;
#pragma unroll 1
    for (int kt = (it == 0 && !first) ? G_STAGES : 0; kt < nk; kt++) {
      if (!first) mbar_wait_sleep(bar + B_GEMPTY + 8 * stage, phase);
      const uint32_t fb = bar + B_GFULL + 8 * stage;
      const uint32_t sa = sbase + stage * G_STAGE_BYTES;
      mbar_expect_tx(fb, G_STAGE_BYTES);
      tma_load_2d(sa, ma, fb, kt * 64, m_tile * 128);
      tma_load_3d(sa + G_A_BYTES, mb, fb, 0, kt * 64, n_tile * 4);
      if (++stage == G_STAGES) { stage = 0; phase ^= 1; }
      {
        const int b = maps.id[blockIdx.x][1];
        if (it == 2 && kt == (b & 7)) {
          for (int i = 0; i < 2; i++)
            asm volatile("cp.async.bulk.prefetch.tensor.2d.L2.global.tile [%0, {%1, %2}];" ::"l"(&maps.a[0]),
                         "r"((b >> 4) * 128 + i * 64), "r"((b & 15) * 128)
                         : "memory");
        }
        if (it == 3 && kt == (b & 7))
          asm volatile("cp.async.bulk.prefetch.tensor.3d.L2.global.tile [%0, {%1, %2, %3}];" ::"l"(&maps.b[0]), "r"(0),
                       "r"((b & 15) * 64), "r"((b >> 4) * 8)
                       : "memory");
      }
    }
  }
}

__device__ __noinline__ void publisher(uint32_t bar, int lane, uint32_t nsrc, uint32_t poll) {
  uint32_t done = 0;
#pragma unroll 1
  for (uint32_t spins = 0; (done < nsrc || poll <= nsrc) && spins < (1u << 20); spins++) {
    if (done >= poll) {
      uint32_t v;
      asm volatile("ld.acquire.gpu.global.u32 %0, [%1];" : "=r"(v) : "l"(g_cnt + (CNT_CTX + 1) * 32) : "memory");
      if (__all_sync(0xffffffffu, v >= NH * (S_LEN / 128))) {
        asm volatile("fence.proxy.async.global;" ::: "memory");
        mbar_arrive_if(bar + B_CTX, lane == 0);
        poll = ~0u;
      }
    }
    uint32_t v = 0;
    if (lane < CNT_N)
      asm volatile("atom.acquire.cta.shared.exch.b32 %0, [%1], 0;" : "=r"(v) : "r"(bar + B_PEND + 4 * lane) : "memory");
    done += __shfl_sync(0xffffffffu, v, CNT_DONE);
    if (lane == CNT_DONE) v = 0;
    if (done == nsrc && lane < CNT_DONE) {
      uint32_t w;
      asm volatile("atom.acquire.cta.shared.exch.b32 %0, [%1], 0;" : "=r"(w) : "r"(bar + B_PEND + 4 * lane) : "memory");
      v += w;
    }
    if (v && lane == 0) { TD(0) }
    if (v) cnt_signal_release(lane, v);
    if (v && lane == 0) { TD(1) }
    if (!__any_sync(0xffffffffu, v != 0)) __nanosleep(200);
  }
  __threadfence();
  __syncwarp();
}

__device__ __forceinline__ void gate_rows(const Maps& maps, uint32_t sbase, int w48, int w12, int lane) {
  const uint32_t buf = sbase + w12 * 16384, gb = sbase + BAR_OFF + 768 + w12 * 16;
  if (lane == 0) {
    mbar_init(gb, 1);
    mbar_init(gb + 8, 1);
    fence_barrier_init();
    for (int i = 0; i < 2; i++) {
      mbar_expect_tx(gb + 8 * i, 8192);
      bulk_load(buf + i * 8192, maps.x + (size_t)(w48 + 48 * i) * 4 * DM, 8192, gb + 8 * i);
    }
  }
  __syncwarp();
  uint4 wv[4];
#pragma unroll
  for (int i = 0; i < 4; i++) wv[i] = __ldg(reinterpret_cast<const uint4*>(maps.gate_w + (i * 32 + lane) * 8));
  int it = 0;
#pragma unroll 1
  for (int row = w48 * 4; row < S_LEN; row += 48 * 4, it++) {
    mbar_wait(gb + 8 * (it & 1), (it >> 1) & 1);
    uint4 xv[4][4];
#pragma unroll
    for (int r = 0; r < 4; r++)
#pragma unroll
      for (int i = 0; i < 4; i++) xv[r][i] = lds128(buf + (it & 1) * 8192 + r * 2048 + (i * 32 + lane) * 16);
    float d[2][4];
#pragma unroll
    for (int pr = 0; pr < 2; pr++) {
      d[pr][0] = d[pr][1] = d[pr][2] = d[pr][3] = 0.f;
      auto acc = [&](uint32_t a0, uint32_t a2, uint32_t b0, uint32_t b2, uint32_t w0, uint32_t w2) {
        asm volatile(
            "mma.sync.aligned.m16n8k16.row.col.f32.bf16.bf16.f32 {%0, %1, %2, %3}, {%4, %5, %6, %7}, {%8, %8}, "
            "{%0, %1, %2, %3};"
            : "+f"(d[pr][0]), "+f"(d[pr][1]), "+f"(d[pr][2]), "+f"(d[pr][3])
            : "r"(mul_bf2(a0, w0)), "r"(mul_bf2(b0, w0)), "r"(mul_bf2(a2, w2)), "r"(mul_bf2(b2, w2)), "r"(0x3f803f80u));
      };
#pragma unroll
      for (int i = 0; i < 4; i++) {
        acc(xv[2 * pr][i].x, xv[2 * pr][i].y, xv[2 * pr + 1][i].x, xv[2 * pr + 1][i].y, wv[i].x, wv[i].y);
        acc(xv[2 * pr][i].z, xv[2 * pr][i].w, xv[2 * pr + 1][i].z, xv[2 * pr + 1][i].w, wv[i].z, wv[i].w);
      }
    }
    float sum = (lane & 2) ? ((lane & 1) ? d[1][2] : d[1][0]) : ((lane & 1) ? d[0][2] : d[0][0]);
#pragma unroll
    for (int off = 16; off >= 4; off >>= 1) sum += __shfl_xor_sync(0xffffffffu, sum, off);
    if (lane < 4) g_gate[row + lane] = bf16_round(rcp(1.0f + __expf(-bf16_round(sum))));
    if (lane == 0 && row + 2 * 48 * 4 < S_LEN) {
      mbar_expect_tx(gb + 8 * (it & 1), 8192);
      bulk_load(buf + (it & 1) * 8192, maps.x + (size_t)(row + 2 * 48 * 4) * DM, 8192, gb + 8 * (it & 1));
    }
  }
}

constexpr float Q_SCALE = 0.08838834764831845f * 1.4426950408889634f;
__device__ __forceinline__ uint32_t qkv_consumer(const Maps& maps, uint32_t smem0, bool fused, float (&rest)[64]) {
  PHASE_PROLOGUE
  constexpr int NTILES = G_NTILES;
  float acc[128];
  uint32_t stage = 0, phase = 0;
  const uint32_t stg = sbase + G_STG_OFF + wg * 18432;
  const int st_row = warp * 16 + (lane & 7) + ((lane >> 3) & 1) * 8;
  const int st_cb = lane >> 4;
  uint32_t pend[64];
  const CUtensorMap* pend_map = nullptr;
  int pend_c0 = 0, pend_c1 = 0;
  uint32_t sn = 0;
  auto put_box = [&](uint32_t buf, const uint32_t* v) {
#pragma unroll
    for (int jp = 0; jp < 4; jp++) {
      const int chunk = jp * 2 + st_cb;
      const uint32_t addr = buf + st_row * 128 + ((chunk ^ (st_row & 7)) << 4);
      stmatrix_x4(addr, v[jp * 4], v[jp * 4 + 1], v[jp * 4 + 2], v[jp * 4 + 3]);
    }
  };
  GT(gti++)
#pragma unroll 1
  for (int it = 0; it <= NTILES; it++) {
    int which, m_tile, n_tile;
    qkv_tile(maps, it, which, m_tile, n_tile);
    const int nk = (which == 0 && it < NTILES) ? 16 : 8;
    uint32_t prev_stage = 0;
#pragma unroll 1
    for (int kt = 0; kt < nk; kt++) {
      if (it < NTILES) {
        mbar_wait((bar + B_GFULL) + 8 * stage, phase);
        GT(gti++)
        const uint64_t da0 = make_desc(sbase + stage * G_STAGE_BYTES + wg * 8192, 16, 1024, DESC_SW128);
        const uint64_t db0 = make_desc(sbase + stage * G_STAGE_BYTES + G_A_BYTES, 8192, 1024, DESC_SW128);
        wgmma_fence();
#pragma unroll
        for (int kk = 0; kk < 4; kk++) {
          wgmma_m64n256_ss_tb(acc, desc_add(da0, kk * 2), desc_add(db0, kk * 128), (kt | kk) != 0);
        }
        wgmma_commit();
      }
      const uint32_t when = it == 0 ? 0 : it == 5 ? 0x922 << wg : wg ? 0xAA : 0x55;
      if ((when >> kt) & 1) {
        const int c = __popc(when & ~(~0u << kt));
        st_wait(bar, wg, sn - 2);
        const uint32_t buf = stg + (c & 1) * 8192;
        switch (c) {
          case 0: put_box(buf, pend); break;
          case 1: put_box(buf, pend + 16); break;
          case 2: put_box(buf, pend + 32); break;
          default: put_box(buf, pend + 48); break;
        }
        st_post(bar, wg, wtid, sn, ST_BOX1, pend_map, buf, pend_c0 + c * 64, pend_c1, (c == 3 && it > 1) ? CNT_KV + (it > 3) : -1);
        sn++;
      }
      if (it < NTILES) {
        wgmma_wait<1>();
        mbar_arrive_if((bar + B_GEMPTY) + 8 * prev_stage, wtid == 32 && kt > 0);
        prev_stage = stage;
        if (++stage == G_STAGES) { stage = 0; phase ^= 1; }
      }
    }
    wgmma_wait<0>();
    fence_regs(acc);
    if (it == NTILES) break;
    GT(gti++)
    mbar_arrive_if((bar + B_GEMPTY) + 8 * prev_stage, wtid == 32);
    if (it == NTILES - 1 && fused) break;
    if (which == 0) {
#pragma unroll
      for (int j = 0; j < 128; j++) acc[j] *= Q_SCALE;
    }
#pragma unroll
    for (int j = 0; j < 64; j++) pend[j] = pack_bf16(acc[2 * j], acc[2 * j + 1]);
    pend_map = &maps.c[which];
    pend_c0 = n_tile * 256;
    pend_c1 = m_tile * 128 + wg * 64;
  }
  mbar_wait(bar + B_GEMPTY, 1);
#pragma unroll
  for (int j = 0; j < 32; j++) pend[j] = pack_bf16(acc[2 * j] * Q_SCALE, acc[2 * j + 1] * Q_SCALE);
  put_box(sbase + wg * 8192, pend);
  put_box(sbase + 16384 + wg * 8192, pend + 16);
  fence_proxy_async();
#pragma unroll
  for (int j = 0; j < 64; j++) rest[j] = acc[64 + j];
  GT(gti++)
  return sn;
}

constexpr int A_TILE = 128 * 128 * 2;
constexpr int A_Q_OFF = 0;
constexpr int A_K_OFF = 2 * A_TILE;
constexpr int A_V_OFF = 4 * A_TILE;
constexpr int A_O_OFF = 6 * A_TILE;
constexpr int A_ITEMS = NH * (S_LEN / 128);

constexpr uint32_t A_ORDER = 0x3120, A_STEPS = 34;
__device__ __forceinline__ int item_m(uint32_t it) { return it & 15; }
__device__ __forceinline__ int item_h(uint32_t it) { return it >> 4; }

constexpr int C_V = 16384, C_MAT = 24576;
constexpr float C_ALPHA = 0.07874506561842957f;
__device__ __forceinline__ void sincos_turn(int p, float inv, float& c, float& s) {
  const float a = (float)p * (inv * 6.283185307179586f);
  asm("cos.approx.ftz.f32 %0, %1;" : "=f"(c) : "f"(a));
  asm("sin.approx.ftz.f32 %0, %1;" : "=f"(s) : "f"(a));
}

__device__ __forceinline__ uint32_t item_of(const Maps& maps, uint32_t r) {
  const uint32_t b = maps.id[blockIdx.x & 127][1];
  return (b >> 4) * 64 + ((A_ORDER >> (4 * r)) & 3) * 16 + ((b ^ ((r & 1) * 15)) & 15);
}

#define PACE 250
#define C_SIDE 64
__device__ __forceinline__ uint32_t conv_first(const Maps& maps) {
  const uint32_t b = maps.id[blockIdx.x & 127][1];
  return (b >> 4) * 128 + ((b + 15) & 15);
}

__device__ __forceinline__ void conv_consumer(const Maps& maps, uint32_t smem0, uint32_t first, uint32_t step,
                                              uint32_t end, bool pp) {
  PHASE_PROLOGUE
  const uint32_t in_full = bar + B_CFULL + wg * 16;
  const uint32_t ca = sbase + (wg ? A_V_OFF + A_TILE : A_Q_OFF);
  const int w = __shfl_sync(0xffffffffu, warp, 0), g = lane >> 2, c = lane & 3;
  auto fetch = [&](uint32_t ch, uint32_t n) {
    if (w == 2 && ch < end) {
      if (elect_one()) {
        const uint32_t b = in_full + (n & 1) * 8, d = ca + (n & 1) * 8192;
        const uint64_t pol = policy_evict_first();
        mbar_expect_tx(b, 8192);
        tma_load_2d_hint(d, &maps.cu, b, 0, ch * 64, pol);
        tma_load_2d_hint(d + 4096, &maps.ch, b, 0, ch * 64, pol);
      }
    }
  };
  if (wtid == 96 && wg) { TD(15) }
  {
    const uint32_t b = maps.id[blockIdx.x & 127][2];
    const bf16* xp = maps.x + ((b & 15) * 128 + wtid) * DM + (b >> 4) * 128;
    asm volatile("prefetch.global.L2 [%0];" ::"l"(xp));
    asm volatile("prefetch.global.L2 [%0];" ::"l"(xp + 64));
  }
  uint32_t f1[8][4];
  float tt[16], ts[16];
  uint32_t cc[4], ss[4];
#pragma unroll
  for (int i = 0; i < 16; i++) {
    const int k = 2 * (16 * w + g + 8 * (i & 1)) + 1, n = 2 * (8 * (i >> 1) + 2 * c) + 1;
    float c0, s0, c1, s1;
    sincos_turn(((k * n) << 23) >> 23, 1.f / 512, c0, s0);
    sincos_turn(((k * n + 2 * k) << 23) >> 23, 1.f / 512, c1, s1);
    f1[i >> 2][i & 3] = pack_bf16(c0 * C_ALPHA, c1 * C_ALPHA);
    f1[4 + (i >> 2)][i & 3] = pack_bf16(s0 * -C_ALPHA, s1 * -C_ALPHA);
  }
#pragma unroll
  for (int i = 0; i < 16; i++) {
    const int k = 2 * (16 * w + g + 8 * ((i >> 1) & 1)) + 1, n = 16 - (8 * (i >> 2) + 2 * c + (i & 1));
    float cs;
    sincos_turn(k * n, 1.f / 8192, cs, ts[i]);
    tt[i] = ts[i] * rcp(1.f + cs);
  }
#pragma unroll
  for (int j = 0; j < 4; j++) {
    const int k = 8 * w + g, n = 8 * c + 2 * j;
    float c0, s0, c1, s1;
    sincos_turn((int8_t)(k * n * 8), 1.f / 256, c0, s0);
    sincos_turn((int8_t)((k * n + k) * 8), 1.f / 256, c1, s1);
    cc[j] = pack_bf16(c0, c1);
    ss[j] = pack_bf16(s0, s1);
  }
  named_bar_sync(3, 256);
  fetch(first, 0);
  fetch(first + step, 1);
  const uint32_t va = ca + g * 64 + ((c ^ (g >> 1)) << 4);
  {
    const uint32_t a = va + C_MAT + w * 512, m = 0x80008000u;
    sts128(a, make_uint4(cc[0], cc[1], cc[2], cc[3]));
    sts128(a + 2048, make_uint4(ss[0], ss[1], ss[2], ss[3]));
    sts128(a + 4096, make_uint4(ss[0] ^ m, ss[1] ^ m, ss[2] ^ m, ss[3] ^ m));
    sts128(a + 6144, make_uint4(cc[0], cc[1], cc[2], cc[3]));
  }
  fence_proxy_async();
  named_bar_sync(1 + wg, 128);
  constexpr uint64_t DHI = (2ull << 62) | ((uint64_t)(512 >> 4) << 32);
  const uint32_t d0 = (uint32_t)make_desc(ca, 4096, 0, 0);
  float a5[16];
  uint4* const yb = reinterpret_cast<uint4*>(g_y2T) + (16 * w + g) * 4 + c;
  auto issue5 = [&]() {
#pragma unroll
    for (int ks = 0; ks < 8; ks++) wgmma_m64n32_rs_tb(a5, f1[ks], DHI | (d0 + (C_V >> 4) + ks * 64), ks != 0);
    wgmma_commit();
  };
  auto finish = [&](uint32_t ch, bool on) {
    fence_regs(a5);
    uint4* y = yb + (size_t)ch * 256;
    if (on) {
      y[0] = make_uint4(pack_bf16(a5[0], a5[1]), pack_bf16(a5[4], a5[5]), pack_bf16(a5[8], a5[9]), pack_bf16(a5[12], a5[13]));
      y[32] = make_uint4(pack_bf16(a5[2], a5[3]), pack_bf16(a5[6], a5[7]), pack_bf16(a5[10], a5[11]), pack_bf16(a5[14], a5[15]));
    }
  };
  auto dft32 = [&](float (&d)[32], const float* re, const float* im) {
    uint32_t a[4][4];
#pragma unroll
    for (int i = 0; i < 8; i++) {
      a[i >> 2][i & 3] = pack_bf16(re[2 * i], re[2 * i + 1]);
      a[2 + (i >> 2)][i & 3] = pack_bf16(im[2 * i], im[2 * i + 1]);
    }
    wgmma_fence();
#pragma unroll
    for (int ks = 0; ks < 4; ks++) wgmma_m64n64_rs_tb(d, a[ks], DHI | (d0 + (C_MAT >> 4) + ks * 64), ks != 0);
    wgmma_commit();
  };
  auto rot = [&](float* x, float* y) {
#pragma unroll
    for (int i = 0; i < 16; i++) {
      x[i] = fmaf(-tt[i], y[i], x[i]);
      y[i] = fmaf(ts[i], x[i], y[i]);
      x[i] = fmaf(-tt[i], y[i], x[i]);
    }
  };
  auto load_d = [&](uint32_t ch) {
    return __ldg(reinterpret_cast<const unsigned short*>(maps.ssm_D) + ((ch & (DM - 1)) | (lane & rt_zero)));
  };
  uint32_t dn = load_d(first);
  uint32_t n = 0, ch = first;
#pragma unroll 1
  for (; ch < end; n++, ch += step) {
    CT(0)
    float a1[2][32], a2[2][32], a4[32];
    const float dsk = c ? 0.f : __uint_as_float(dn << 16) * C_ALPHA;
    dn = load_d(ch + step);
    mbar_wait(in_full + (n & 1) * 8, (n >> 1) & 1);
    if (pp) named_bar_sync(4 + wg, 256);
    CT(1)
    wgmma_fence();
#pragma unroll
    for (int ks = 0; ks < 8; ks++)
      wgmma_m64n64_rs_tb(a1[ks >> 2], f1[ks], DHI | (d0 + (n & 1) * 512 + (ks & 3) * 64), (ks & 3) != 0);
    wgmma_commit();
    issue5();
    wgmma_wait<1>();
    fence_regs(a1[0]);
    fence_regs(a1[1]);
    CT(2)
    rot(a1[0], a1[1]);
    dft32(a2[0], a1[0], a1[1]);
    rot(a1[0] + 16, a1[1] + 16);
    a1[0][16] += dsk;
    a1[0][18] += dsk;
    dft32(a2[1], a1[0] + 16, a1[1] + 16);
    CT(3)
    wgmma_wait<2>();
    finish(ch - step, n > 0);
    wgmma_wait<0>();
    fence_regs(a2[0]);
    fence_regs(a2[1]);
    CT(4)
    if (pp) named_bar_arrive(5 - wg, 256);
    float re[16], im[16];
#pragma unroll
    for (int i = 0; i < 16; i++) {
      re[i] = a2[0][i] * a2[1][i] - a2[0][16 + i] * a2[1][16 + i];
      im[i] = a2[0][i] * a2[1][16 + i] + a2[0][16 + i] * a2[1][i];
    }
    dft32(a4, im, re);
    wgmma_wait<0>();
    fence_regs(a4);
    CT(5)
    rot(a4, a4 + 16);
#pragma unroll
    for (int i = 0; i < 4; i++) {
      const float* x = a4 + 16 - 16 * (i >> 1) + 2 * (i & 1);
      sts128(va + C_V + w * 1024 + (i >> 1) * 4096 + (i & 1) * 512,
             make_uint4(pack_bf16(x[0], x[1]), pack_bf16(x[4], x[5]), pack_bf16(x[8], x[9]), pack_bf16(x[12], x[13])));
    }
    CT(6)
    fence_proxy_async();
    named_bar_sync(1 + wg, 128);
    fetch(ch + 2 * step, n);
    if (wtid == 96 && n > 0) note(bar, CNT_Y2 + (((ch - step) & 112) == 112));
    CT(7)
  }
  wgmma_fence();
  issue5();
  wgmma_wait<0>();
  finish(ch - step, true);
  named_bar_sync(1 + wg, 128);
  if (wtid == 96 && wg) { TD(8) }
  if (wtid == 96) cnt_signal_release(CNT_Y2 + (((ch - step) & 112) == 112), 1);
  if (wtid == 64) note(bar, CNT_DONE);
  if (wtid == 96 && wg) { TD(9) }
  mbar_wait(bar + B_OFREE, 0);
  mbar_wait(bar + B_OFREE + 8, 0);
}

__device__ __forceinline__ void attn_producer(const Maps& maps, uint32_t sbase, bool after_qkv, bool to_out,
                                              bool dry) {
  const uint32_t bar = sbase + BAR_OFF;
  const uint32_t q_full = bar + B_QFULL, q_empty = bar + B_QEMPTY;
  const uint32_t k_full = bar + B_KFULL, k_empty = bar + B_KEMPTY, v_full = bar + B_VFULL, v_empty = bar + B_VEMPTY;
  int ndrained = after_qkv ? 0 : G_STAGES;
  auto wait = [&](uint32_t b, uint32_t par) {
    if (!dry) mbar_wait_sleep(b, par);
  };
  auto drained = [&](int upto) {
#pragma unroll 1
    for (; ndrained <= upto; ndrained++) wait(bar + B_GEMPTY + 8 * ndrained, 1);
  };
  uint32_t st = 0, ph = 1, vs = 0, vp = 1;
  int pend_j = -1, pend_h = 0;
  int round = -1, m = -1, h = 0;
  bool last = false;
#pragma unroll 1
  for (;; round++) {
    uint32_t nitem = 0;
    const int tpost = m >= 3 ? m - 1 : m;
#pragma unroll 1
    for (int t = m < 0 ? -1 : 0; t <= m; t++) {
      const int j = (t < m && (round & 1)) ? m - 1 - t : t;
      if (t >= 0) {
        drained(1 + st);
        wait(k_empty + 8 * st, ph);
        if (!dry) {
          mbar_expect_tx(k_full + 8 * st, A_TILE);
          tma_load_3d(sbase + A_K_OFF + st * A_TILE, &maps.k, k_full + 8 * st, 0, j * 128, h * 2);
        }
        if (++st == 2) { st = 0; ph ^= 1; }
      }
      if (pend_j >= 0) {
        drained(3);
        wait(v_empty + 8 * vs, vp);
        if (!dry) {
          mbar_expect_tx(v_full + 8 * vs, A_TILE);
          tma_load_3d(sbase + A_V_OFF + vs * A_TILE, &maps.v, v_full + 8 * vs, 0, pend_j * 128, pend_h * 2);
        }
        if (++vs == 2) { vs = 0; vp ^= 1; }
      }
      pend_j = j;
      pend_h = h;
      if (t == tpost && !last) {
        nitem = dry ? 1 : item_of(maps, round + 1);
        if (round == (dry ? 0 : 3) || blockIdx.x >= 128) {
          nitem = A_ITEMS;
          cnt_wait(CNT_PREP, dry ? 0 : 260);
          if (to_out) {
            cnt_wait(CNT_CTX, dry ? 0 : A_ITEMS);
            asm volatile("cp.async.bulk.prefetch.L2.global [%0], 4096;" ::"l"(maps.ssm_k + (size_t)conv_first(maps) * S_LEN));
            if (!dry)
              asm volatile("cp.async.bulk.prefetch.L2.global [%0], 4096;" ::"l"(g_kvT + (size_t)conv_first(maps) * S_LEN));
          }
        }
        const uint32_t qs = (round + 1) & 1;
        wait(q_empty + 8 * qs, (((round + 1) >> 1) & 1) ^ 1);
        if (round == 1 && after_qkv) wait(bar + B_QDONE, 0);
        if (round <= 0 && after_qkv) {
          if (!dry) { TD(2) }
          cnt_wait(CNT_KV + round + 1, dry ? 0 : 512);
          if (!dry) { TD(3) }
        }
        if (nitem >= A_ITEMS || (round < 0 && after_qkv && !dry)) {
          if (!dry) mbar_arrive(q_full + 8 * qs);
        } else {
          drained(qs);
          if (!dry) {
            mbar_expect_tx(q_full + 8 * qs, A_TILE);
            tma_load_3d_hint(sbase + A_Q_OFF + qs * A_TILE, &maps.q, q_full + 8 * qs, 0, item_m(nitem) * 128,
                             item_h(nitem) * 2, policy_evict_first());
          }
        }
      }
    }
    if (last) break;
    last = nitem >= A_ITEMS;
    m = last ? -1 : item_m(nitem);
    h = item_h(nitem);
  }
}

__device__ __forceinline__ uint32_t attn_consumer(const Maps& maps, uint32_t smem0, uint32_t sn,
                                                  float (&rest)[64], bool after_qkv) {
  PHASE_PROLOGUE
  const uint32_t q_full = bar + B_QFULL, q_empty = bar + B_QEMPTY;
  const uint32_t k_full = bar + B_KFULL, k_empty = bar + B_KEMPTY, v_full = bar + B_VFULL;
  float o[64], s[64];
  uint32_t p[32];
  float e[32];
  uint32_t dep = 0;
  constexpr int MIDJ = 5;
  float l0 = 0.f, l1 = 0.f, b0 = 0.f, b1 = 0.f;
  const int sched_own = 4 + wg, sched_other = 5 - wg;
  if (wg == 1) named_bar_arrive(4, 256);

  const uint32_t qd0 = (uint32_t)make_desc(sbase + A_Q_OFF + wg * 8192, 16, 0, 0);
  const uint32_t kd0 = (uint32_t)make_desc(sbase + A_K_OFF, 16, 0, 0);
  const uint32_t vd0 = (uint32_t)make_desc(sbase + A_V_OFF, 16384, 0, 0);
  constexpr uint64_t DHI = DESC_SW128 | ((uint64_t)(1024 >> 4) << 32);
  constexpr uint32_t DST = A_TILE >> 4;
  auto issue_qk = [&](uint32_t qd, uint32_t kd) {
#pragma unroll
    for (int kk = 0; kk < 8; kk++) {
      const uint32_t off = ((kk >> 2) * 16384 + (kk & 3) * 32) >> 4;
      wgmma_m64n128_ss(s, DHI | (qd + off), DHI | (kd + off), kk != 0);
    }
    wgmma_commit();
  };
  auto issue_pv = [&](uint32_t vd, bool accumulate, int nk) {
#pragma unroll
    for (int kk = 0; kk < 8; kk++) {
      if (kk < nk)
        wgmma_m64n128_rs_tb(o, p[4 * kk], p[4 * kk + 1], p[4 * kk + 2], p[4 * kk + 3], DHI | (vd + kk * 128),
                            accumulate || (kk != 0));
    }
    wgmma_commit();
  };
  auto exp_lo = [&](float& a0, float& a1) {
#pragma unroll
    for (int j = 0; j < 8; j++) {
      e[4 * j] = ex2(s[4 * j]);
      e[4 * j + 1] = ex2(s[4 * j + 1]);
      e[4 * j + 2] = ex2(s[4 * j + 2]);
      e[4 * j + 3] = ex2(s[4 * j + 3]);
      a0 += e[4 * j];
      a0 += e[4 * j + 1];
      a1 += e[4 * j + 2];
      a1 += e[4 * j + 3];
      if (j == MIDJ) dep = (__float_as_uint(a0) | __float_as_uint(a1)) & rt_zero;
    }
  };
  auto pack_lo = [&]() {
#pragma unroll
    for (int j = 0; j < 16; j++) p[j] = pack_bf16(e[2 * j], e[2 * j + 1]);
  };
  auto finish_p = [&](float& a0, float& a1) {
    pack_lo();
#pragma unroll
    for (int j = 8; j < 16; j++) {
      const float e0 = ex2(s[4 * j]), e1 = ex2(s[4 * j + 1]), e2 = ex2(s[4 * j + 2]), e3 = ex2(s[4 * j + 3]);
      a0 += e0;
      a0 += e1;
      a1 += e2;
      a1 += e3;
      p[2 * j] = pack_bf16(e0, e1);
      p[2 * j + 1] = pack_bf16(e2, e3);
      if (j == 8 + MIDJ) dep = __float_as_uint(a0) & rt_zero;
    }
  };
  auto quad_sum = [&](float t) {
    t += __shfl_xor_sync(0xffffffffu, t, 1);
    return t + __shfl_xor_sync(0xffffffffu, t, 2);
  };
  auto write_o = [&](float i0, float i1) {
    st_wait(bar, wg, sn - 1);
    const int st_row = warp * 16 + (lane & 7) + ((lane >> 3) & 1) * 8;
    const uint32_t so = sbase + A_O_OFF + wg * 16384 + st_row * 128;
#pragma unroll
    for (int j = 0; j < 16; j += 2)
      stmatrix_x4(so + (j >> 3) * 8192 + ((((j & 7) + (lane >> 4)) ^ (lane & 7)) << 4),
                  pack_bf16(o[4 * j] * i0, o[4 * j + 1] * i0), pack_bf16(o[4 * j + 2] * i1, o[4 * j + 3] * i1),
                  pack_bf16(o[4 * j + 4] * i0, o[4 * j + 5] * i0), pack_bf16(o[4 * j + 6] * i1, o[4 * j + 7] * i1));
  };
  auto store_o = [&](uint32_t r, int kind) {
    const uint32_t it = item_of(maps, r);
    st_post(bar, wg, wtid, sn, kind, (INPLACE & 1) || kind != ST_BOX2Q ? &maps.o : &maps.c[0], sbase + A_O_OFF + wg * 16384, item_h(it) * 128,
            item_m(it) * 128 + wg * 64, CNT_CTX + (r >> 1));
    sn++;
  };
  auto mask_half = [&](float* sh) {
    const int u = warp * 16 + (lane >> 2) - (lane & 3) * 2;
#pragma unroll
    for (int j = 0; j < 8; j++) {
      if (8 * j > u) sh[4 * j] = -INFINITY;
      if (8 * j + 1 > u) sh[4 * j + 1] = -INFINITY;
      if (8 * j - 8 > u) sh[4 * j + 2] = -INFINITY;
      if (8 * j - 7 > u) sh[4 * j + 3] = -INFINITY;
    }
  };
  ST(0)
  mbar_wait(q_full, 0);
  if (blockIdx.x >= 128) {
    mbar_arrive_if(bar + B_OFREE + 8 * wg, wtid == 0);
    return sn;
  }
  mbar_wait(k_full, 0);
  named_bar_sync(sched_own, 256);
  wgmma_fence();
  issue_qk(qd0, kd0);
  named_bar_arrive(sched_other, 256);
  fence_regs(rest);
#pragma unroll
  for (int i = 0; i < 64; i++) o[i] = rest[i] * Q_SCALE;
  fence_regs(o);
  wgmma_wait<0>();
  fence_regs(s);
  mbar_arrive_if(k_empty, wtid == 32);
  uint32_t g = 0;
  uint32_t rnd = 0;
  int rem = item_m(item_of(maps, 0));
  uint32_t first = 1;
  uint32_t fl = 0;
#define redo (fl & 1)
#define shifted (fl & 2)
  float d0 = 0.f, d1 = 0.f;
  float pi0 = 1.f, pi1 = 1.f;
  ST(1)
  for (;;) {
    if (shifted) {
#pragma unroll
      for (int j = 0; j < 16; j++) {
        s[4 * j] -= d0;
        s[4 * j + 1] -= d0;
        s[4 * j + 2] -= d1;
        s[4 * j + 3] -= d1;
      }
    }
    if (rem == 0 && !redo) {
      mbar_arrive_if(q_empty + 8 * (rnd & 1), wtid == 96);
      rnd++;
      if (wg == 0) mask_half(s);
      else mask_half(s + 32);
    }
    for (;;) {
      const bool kill = rem == 0 && wg == 0;
      const uint32_t kd = kd0 + ((g + 1) & 1) * DST, vd = vd0 + (g & 1) * DST;
      float a0 = 0.f, a1 = 0.f;
      exp_lo(a0, a1);
      fence_regs(e);
      const uint32_t kb = k_full + 8 * ((g + 1) & 1);
      const uint32_t kpar = ((((g + 1) >> 1) & 1) ^ (g == A_STEPS - 1 ? 1u : 0u)) | dep;
      if (!mbar_try(kb, kpar)) mbar_wait(kb, kpar | ((__float_as_uint(a0) | __float_as_uint(a1)) & rt_zero));
      wgmma_wait<0>();
      fence_regs(o);
      if (kill) {
        mbar_arrive_if(kb + (B_VEMPTY - B_KFULL), wtid == 64 && !redo && g > 0);
        fence_regs(e);
        pack_lo();
#pragma unroll
        for (int j = 16; j < 32; j++) asm volatile("mov.u32 %0, 0;" : "=r"(p[j]));
        goto check;
      }
#pragma unroll
      for (int i = 32; i < 64; i++) asm volatile("" : "+f"(s[i])::"memory");
      mbar_arrive_if(kb + (B_VEMPTY - B_KFULL), wtid == 64 && !redo && g > 0);
      finish_p(a0, a1);
      if (__any_sync(0xffffffffu, !(mbar_try(v_full + 8 * (g & 1), ((g >> 1) & 1) | dep) &
                                    mbar_try(q_full + 8 * (rnd & 1), ((rnd >> 1) & 1) | dep)) ||
                                      !(a0 + a1 < 1.0995116e12f) || !(fminf(a0, a1) > (first ? 9.094947e-13f : -1.f)))) {
      check:
        bool bad = !(a0 + a1 < 1.0995116e12f);
        if (first) bad |= !(fminf(quad_sum(a0), quad_sum(a1)) > 9.094947e-13f);
        if (!redo && __any_sync(0xffffffffu, bad)) {
          d0 = d1 = first ? -INFINITY : 0.f;
#pragma unroll
          for (int j = 0; j < 16; j++) {
            if (j < 8 || !kill) {
              d0 = fmaxf(d0, fmaxf(s[4 * j], s[4 * j + 1]));
              d1 = fmaxf(d1, fmaxf(s[4 * j + 2], s[4 * j + 3]));
            }
          }
#pragma unroll
          for (int x = 1; x <= 2; x++) {
            d0 = fmaxf(d0, __shfl_xor_sync(0xffffffffu, d0, x));
            d1 = fmaxf(d1, __shfl_xor_sync(0xffffffffu, d1, x));
          }
          b0 += d0;
          b1 += d1;
          if (!first) {
            const float al0 = ex2(-d0), al1 = ex2(-d1);
            l0 *= al0;
            l1 *= al1;
#pragma unroll
            for (int j = 0; j < 16; j++) {
              o[4 * j] *= al0;
              o[4 * j + 1] *= al0;
              o[4 * j + 2] *= al1;
              o[4 * j + 3] *= al1;
            }
          }
          fl = 3;
          break;
        }
        mbar_wait(v_full + 8 * (g & 1), (g >> 1) & 1);
        mbar_wait(q_full + 8 * (rnd & 1), (rnd >> 1) & 1);
      }
      named_bar_sync(sched_own, 256);
      if (g == A_STEPS - 1) {
        if (first) write_o(pi0, pi1);
        fence_regs(o);
        wgmma_fence();
        issue_pv(vd, !first, 8);
        named_bar_arrive(sched_other, 256);
        if (first) store_o(rnd - 2, ST_BOX2);
        pi0 = rcp(quad_sum(l0 + a0));
        pi1 = rcp(quad_sum(l1 + a1));
        goto done;
      }
      wgmma_fence();
      issue_qk(qd0 + (rnd & 1) * DST, kd);
      if (first) write_o(pi0, pi1);
      fence_regs(o);
      if (kill) {
        wgmma_fence();
        issue_pv(vd, !first, 4);
      } else {
        wgmma_fence();
        issue_pv(vd, !first, 8);
      }
      named_bar_arrive(sched_other, 256);
      fl &= 2;
      l0 += a0;
      l1 += a1;
      if (rem == 0 || first) {
        if (first && (g > 0 || after_qkv)) store_o(g ? rnd - (rem == 0 ? 2 : 1) : 2, g ? ST_BOX2 : ST_BOX2Q);
        first = rem == 0;
        if (first) {
          pi0 = rcp(quad_sum(l0));
          pi1 = rcp(quad_sum(l1));
          l0 = l1 = b0 = b1 = 0.f;
          fl = 0;
          rem = item_m(item_of(maps, rnd)) + 1;
        }
      }
      rem--;
      g++;
      wgmma_wait<1>();
      fence_regs(s);
      mbar_arrive_if(kb + (B_KEMPTY - B_KFULL), wtid == 32);
      ST(g + 1)
      if (rem == 0 || shifted) {
        d0 = b0;
        d1 = b1;
        break;
      }
    }
  }
done:
#undef redo
#undef shifted
  wgmma_wait<0>();
  fence_regs(o);
  write_o(pi0, pi1);
  store_o(3, ST_BOX2L);
  ST(35)
  return sn;
}

constexpr int O_STAGES = 5;
constexpr int O_STAGE_BYTES = 32768;
constexpr int O_Y_OFF = 5 * 32768;
constexpr int O_X_OFF = 6 * 32768;
constexpr int O_NK = HDIM / 64;

__device__ __forceinline__ uint32_t out_stage(uint32_t st) { return ((0x43120u >> (4 * st)) & 7) * O_STAGE_BYTES; }

__device__ __forceinline__ void out_producer(const Maps& maps, uint32_t sbase, bool after_attn, bool dry) {
  const uint32_t bar = sbase + BAR_OFF;
  const uint32_t rank = blockIdx.x & 1;
  const int m_tile = maps.id[blockIdx.x][2] & 15, n_tile = maps.id[blockIdx.x][2] >> 4;
  uint32_t stage = 0, phase = 0;
#pragma unroll 1
  for (int ki = 0; ki < (dry ? 1 : O_NK); ki++) {
    const int kt = (ki & 14) * 4 + ((A_ORDER >> ((ki >> 4) * 4)) & 3) * 2 + (ki & 1);
    const uint32_t fb = bar + B_OFULL + 8 * stage, eb = bar + B_OEMPTY + 8 * stage;
    const uint32_t sa = sbase + out_stage(stage);
    if (ki < O_STAGES) {
      constexpr uint32_t LASTB = B_KEMPTY | ((B_QEMPTY + 8) << 8) | ((B_KEMPTY + 8) << 16) | (B_VEMPTY << 24);
      if (ki > 0 && after_attn) mbar_wait_sleep(bar + ((LASTB >> (8 * ki - 8)) & 255), ki == 2);
      mbar_arrive_cluster_if(eb, 0, !dry);
      mbar_arrive_cluster_if(eb, 1, !dry);
    }
    if (ki == 32) mbar_wait_sleep(bar + B_CTX, 0);
    if (!dry) {
      mbar_wait_sleep(eb, phase);
      mbar_expect_tx(fb, O_STAGE_BYTES);
      tma_load_2d_mc(sa + 16384 + rank * 8192, &maps.ob, fb, n_tile * 128 + rank * 64, kt * 64, (uint16_t)3);
      tma_load_2d(sa, &maps.oa, fb, kt * 64, m_tile * 128);
    }
    if (++stage == O_STAGES) { stage = 0; phase ^= 1; }
  }
  if (!dry) mbar_wait_sleep(bar + B_OY2, 0);
}

__device__ __forceinline__ void out_side(const Maps& maps, uint32_t smem0, const float (&gv)[4]) {
  PHASE_PROLOGUE
  const int m_tile = maps.id[blockIdx.x][2] & 15, n_tile = maps.id[blockIdx.x][2] >> 4;
  const bool w0 = __shfl_sync(0xffffffffu, warp, 0) == 0;
  if (w0) {
    if (elect_one()) {
      mbar_expect_tx(bar + B_OY, 65536 - 4096);
#pragma unroll 1
      for (int i = 0; i < 15; i++) {
        if (i == 8) {
          TD(10)
          cnt_wait(CNT_Y2, DM - 128);
          TD(7)
        }
        tma_load_3d(sbase + (i < 8 ? O_X_OFF : O_Y_OFF - 32768) + i * 4096, i < 8 ? &maps.xs : &maps.y, bar + B_OY, 0,
                    i < 8 ? m_tile * 128 + (i & 3) * 32 : n_tile * 128 - 128 + i * 16,
                    i < 8 ? n_tile * 2 + (i >> 2) : m_tile * 2);
        __nanosleep(PACE);
      }
    }
  }
  mbar_wait_sleep(bar + B_OY, 0);
  if (wtid == 0) { TD(12) }
  const int st_row = warp * 16 + (lane & 7) + ((lane >> 3) & 1) * 8;
  const int mrow = (lane & 7) + ((lane >> 4) & 1) * 8;
  const int mchunk = warp * 2 + ((lane >> 3) & 1);
  const uint32_t xrow = sbase + O_X_OFF + st_row * 128;
  const uint32_t yrow = sbase + O_Y_OFF + mrow * 128 + ((mchunk ^ (lane & 7)) << 4);
  uint32_t y[7][4], x[7][4], om[4];
#pragma unroll
  for (int i = 0; i < 4; i++) om[i] = pack_bf16(1.0f - gv[i], 1.0f - gv[i]);
  auto xa = [&](int h, int i) { return xrow + h * 8192 + (i >> 2) * 16384 + ((((i & 3) * 2 + (lane >> 4)) ^ (lane & 7)) << 4); };
  auto load = [&](int r, int h, int i) {
    ldsm4t(y[r], yrow + h * 2048 + i * 4096);
    asm volatile("ldmatrix.sync.aligned.m8n8.x4.shared.b16 {%0, %1, %2, %3}, [%4];"
                 : "=r"(x[r][0]), "=r"(x[r][1]), "=r"(x[r][2]), "=r"(x[r][3])
                 : "r"(xa(h, i)));
  };
  auto store = [&](int r, int h, int i, uint32_t om0, uint32_t om1) {
    stmatrix_x4(xa(h, i), mul_bf2(om0, mul_bf2(x[r][0], y[r][0])), mul_bf2(om1, mul_bf2(x[r][1], y[r][1])),
                mul_bf2(om0, mul_bf2(x[r][2], y[r][2])), mul_bf2(om1, mul_bf2(x[r][3], y[r][3])));
  };
#pragma unroll 1
  for (int h = 0; h < 2; h++) {
#pragma unroll
    for (int i = 0; i < 7; i++) load(i, h, i);
#pragma unroll
    for (int i = 0; i < 7; i++) store(i, h, i, h ? om[2] : om[0], h ? om[3] : om[1]);
  }
  if (w0) {
    if (elect_one()) {
      mbar_expect_tx(bar + B_OY2, 4096);
      cnt_wait(CNT_Y2 + 1, 128);
      TD(11)
      tma_load_3d(sbase + O_Y_OFF + 7 * 4096, &maps.y, bar + B_OY2, 0, n_tile * 128 + 112, m_tile * 2);
    }
  }
  mbar_wait_sleep(bar + B_OY2, 0);
  load(0, 0, 7);
  load(1, 1, 7);
  store(0, 0, 7, om[0], om[1]);
  store(1, 1, 7, om[2], om[3]);
  __syncwarp();
  mbar_arrive_if(bar + B_OY + 8, lane == 0);
  if (wtid == 0) { TD(13) }
}

__device__ __forceinline__ uint32_t out_gemm(const Maps& maps, uint32_t smem0, uint32_t sn) {
  PHASE_PROLOGUE
  const int m_tile = maps.id[blockIdx.x][2] & 15, n_tile = maps.id[blockIdx.x][2] >> 4;
  float acc[2][64];
  undef_regs(acc[0]);
  undef_regs(acc[1]);
  uint32_t stage = 0, phase = 0, prev_stage = 0;
  GT(gti++)
  const float* gp = g_gate + m_tile * 128 + warp * 16 + (lane >> 2);
  const float gv[4] = {__ldcg(gp), __ldcg(gp + 8), __ldcg(gp + 64), __ldcg(gp + 72)};
  if (wg == 1) {
    out_side(maps, smem0, gv);
    return sn;
  }
#pragma unroll 1
  for (int kt = 0; kt < O_NK; kt++) {
    uint32_t da = (uint32_t)make_desc(sbase + out_stage(stage), 16, 0, 0);
    uint32_t db = (uint32_t)make_desc(sbase + out_stage(stage) + 16384, 8192, 0, 0);
    asm volatile("" : "+r"(da), "+r"(db));
    mbar_wait(bar + B_OFULL + 8 * stage, phase);
    GT(gti++)
    constexpr int OWAIT = 2;
    constexpr uint64_t DHI = DESC_SW128 | ((uint64_t)(1024 >> 4) << 32);
#pragma unroll
    for (int kk = 0; kk < 4; kk++) {
      wgmma_wait<OWAIT>();
      if (kk == OWAIT)
        mbar_arrive_cluster_if(bar + B_OEMPTY + 8 * prev_stage, wtid >> 6,
                               (wtid & 63) == 32 && kt > 0 && kt - 1 + O_STAGES < O_NK);
      wgmma_fence();
      wgmma_m64n128_ss_tb(acc[0], DHI | (da + kk * 2), DHI | (db + kk * 128), (kt | kk) != 0);
      wgmma_m64n128_ss_tb(acc[1], DHI | (da + 512 + kk * 2), DHI | (db + kk * 128), (kt | kk) != 0);
      wgmma_commit();
    }
    prev_stage = stage;
    if (++stage == O_STAGES) { stage = 0; phase ^= 1; }
  }
  if (tid == 0) { TD(14) }
  st_wait(bar, wg, sn - 1);
  const int st_row = warp * 16 + (lane & 7) + ((lane >> 3) & 1) * 8;
  const uint32_t rowa = sbase + O_X_OFF + st_row * 128;
  wgmma_wait<0>();
  fence_regs(acc[0]);
  fence_regs(acc[1]);
  GT(gti++)
  uint32_t gg[4];
#pragma unroll
  for (int i = 0; i < 4; i++) gg[i] = pack_bf16(gv[i], gv[i]);
  mbar_wait(bar + B_OY + 8, 0);
#pragma unroll
  for (int i = 0; i < 16; i++) {
    const int h = i & 1, j = i & 14;
    const uint32_t addr = rowa + h * 8192 + (j >> 3) * 16384 + ((((j & 7) + (lane >> 4)) ^ (st_row & 7)) << 4);
    uint32_t b0, b1, b2, b3;
    asm volatile("ldmatrix.sync.aligned.m8n8.x4.shared.b16 {%0, %1, %2, %3}, [%4];"
                 : "=r"(b0), "=r"(b1), "=r"(b2), "=r"(b3)
                 : "r"(addr));
    const float* a = acc[h] + 4 * j;
    const uint32_t gg0 = gg[2 * h], gg1 = gg[2 * h + 1];
    stmatrix_x4(addr, add_bf2(mul_bf2(gg0, pack_bf16(a[0], a[1])), b0),
                add_bf2(mul_bf2(gg1, pack_bf16(a[2], a[3])), b1), add_bf2(mul_bf2(gg0, pack_bf16(a[4], a[5])), b2),
                add_bf2(mul_bf2(gg1, pack_bf16(a[6], a[7])), b3));
    if (i == 7) st_post(bar, wg, wtid, sn, ST_BOX1, &maps.oc, sbase + O_X_OFF, n_tile * 128, m_tile * 128, -1);
  }
  fence_proxy_async();
  named_bar_sync(1, 128);
  if (__shfl_sync(0xffffffffu, warp, 0) == 0) {
    if (elect_one()) {
      tma_store_2d(&maps.oc, sbase + O_X_OFF + 16384, n_tile * 128 + 64, m_tile * 128);
      tma_store_commit();
    }
  }
  GT(gti++)
  return sn + 1;
}

__device__ __noinline__ void leave_kernel(int mask) {
  if (!(mask & 4)) return;
  if (atomicAdd(g_cnt + CNT_DONE * 32, 1u) == 2 * gridDim.x - 1) {
    for (int i = 0; i < CNT_N; i++) g_cnt[i * 32] = 0;
  }
}

__device__ __noinline__ void side_jobs(const Maps& maps, uint32_t sbase) {
  const int w12 = __shfl_sync(0xffffffffu, threadIdx.x >> 5, 0);
  gate_rows(maps, sbase, (blockIdx.x - 128) * 12 + w12, w12, threadIdx.x & 31);
  fence_proxy_async();
  __syncthreads();
  if (threadIdx.x == 320) cnt_signal_release(CNT_PREP, 1);
}

__global__ void __launch_bounds__(384, 1) fused_kernel(int mask, const __grid_constant__ Maps maps) {
  extern __shared__ __align__(1024) uint8_t smem_raw[];
  {
    const uint32_t sbase = __shfl_sync(0xffffffffu, smem_u32(smem_raw), 0);
    const uint32_t bar = sbase + BAR_OFF;
    const int tid = threadIdx.x;
    const bool do_qkv = (mask & 1) && blockIdx.x < 128;
    TL(0, 0)
    if (__shfl_sync(0xffffffffu, tid >> 5, 0) == 1 && do_qkv) {
      if (elect_one()) {
        for (int i = 0; i < G_STAGES; i++) mbar_init(bar + B_GFULL + 8 * i, 1);
        fence_barrier_init();
        qkv_producer(maps, sbase, true);
      }
    }
    if (tid == 0) {
      for (int i = 0; i < G_STAGES; i++) {
        mbar_init(bar + B_GEMPTY + 8 * i, 2);
        mbar_init(bar + B_SFULL + 8 * i, 4);
        mbar_init(bar + B_SFREE + 8 * i, 1);
      }
      for (int i = 0; i < 2; i++) {
        mbar_init(bar + B_OFREE + 8 * i, 1);
        mbar_init(bar + B_QFULL + 8 * i, 1);
        mbar_init(bar + B_QEMPTY + 8 * i, 2);
        mbar_init(bar + B_KFULL + 8 * i, 1);
        mbar_init(bar + B_KEMPTY + 8 * i, 2);
        mbar_init(bar + B_VFULL + 8 * i, 1);
        mbar_init(bar + B_VEMPTY + 8 * i, 2);
      }
      for (int i = 0; i < O_STAGES; i++) {
        mbar_init(bar + B_OFULL + 8 * i, 1);
        mbar_init(bar + B_OEMPTY + 8 * i, 2);
      }
      mbar_init(bar + B_OY, 1);
      mbar_init(bar + B_CTX, 1);
      mbar_init(bar + B_OY2, 1);
      mbar_init(bar + B_OY + 8, 4);
      mbar_init(bar + B_QDONE, 2);
      for (int i = 0; i < 8; i++) mbar_init(bar + B_CFULL + 8 * i, 1);
      for (int i = 0; i < CNT_N; i++) asm volatile("st.shared.u32 [%0], 0;" ::"r"(bar + B_PEND + 4 * i) : "memory");
      fence_barrier_init();
    }
    __syncthreads();
    asm volatile("barrier.cluster.arrive.relaxed.aligned;" ::: "memory");
    if ((mask & 1) && blockIdx.x >= 128) side_jobs(maps, sbase);
  }
  uint32_t smem0 = smem_u32(smem_raw);
  PHASE_PROLOGUE
  const bool do_qkv = (mask & 1) && blockIdx.x < 128, do_out = (mask & 4) && blockIdx.x < 128;
  TL(0, 1)

  if (wg != 2) {
    reg_alloc<232>();
    uint32_t sn = 0;
    float o[64];
    if (do_qkv) {
      sn = qkv_consumer(maps, smem_u32(smem_raw), mask & 2, o);
    } else {
      undef_regs(o);
    }
    TL(0, 2) TL(1, 0) TL(1, 1)
    asm volatile("barrier.cluster.wait.acquire.aligned;" ::: "memory");
    if (mask & 2) {
      sn = attn_consumer(maps, smem_u32(smem_raw), sn, o, mask & 1);
      TL(2, 0)
      if ((mask & 4) && blockIdx.x < 128 && __shfl_sync(0xffffffffu, threadIdx.x, 0) < 128) {
        named_bar_arrive(3, 256);
      } else {
        const uint32_t b2 = blockIdx.x * 2 + (threadIdx.x >> 7);
        const bool fused = mask & 4, mainc = blockIdx.x < 128;
        const uint32_t first = __shfl_sync(0xffffffffu, !fused ? b2 : mainc ? conv_first(maps) : (b2 - 255) * 128 - C_SIDE, 0);
        conv_consumer(maps, smem_u32(smem_raw), first, !fused ? 264 : mainc ? 16 : 1,
                      !fused ? DM : mainc ? (first | 127) + 1 - C_SIDE : first + C_SIDE, fused && !mainc);
      }
      TL(1, 2) TL(2, 1) TL(2, 2)
    }
    TL(3, 0) TL(3, 1)
    if ((mask & 4) && blockIdx.x < 128) sn = out_gemm(maps, smem_u32(smem_raw), sn);
    {
      uint32_t smem0 = smem_u32(smem_raw);
      PHASE_PROLOGUE
      st_wait(bar, wg, sn - 2);
      st_post(bar, wg, wtid, sn, ST_END, nullptr, 0, 0, 0, -1);
      tma_store_wait_read<0>();
    }
  } else {
    reg_dealloc<40>();
    asm volatile("barrier.cluster.wait.acquire.aligned;" ::: "memory");
    const int w = __shfl_sync(0xffffffffu, tid >> 5, 0) - 8;
    if (w < 2) {
      if (do_qkv) prep_agent(maps, sbase, w, lane);
      if (elect_one()) store_agent(bar, w);
      TL2(3, 2)
    } else {
      if (elect_one()) {
        const bool dry = w == 2;
        if (do_qkv && !dry) qkv_producer(maps, sbase, false);
        if (mask & 2) attn_producer(maps, sbase, do_qkv, do_out, dry);
        if (do_out) out_producer(maps, sbase, mask & 2, dry);
        if (dry) { TD(5) }
      }
      __syncwarp();
      if (w == 2) publisher(bar, tid & 31, !(mask & 2) ? 2 : do_out ? 3 : 4, !do_out ? ~0u : mask & 2);
      if ((tid & 31) == 0) leave_kernel(mask);
    }
  }
}

typedef CUresult (*PFN_tmapEncode)(CUtensorMap*, CUtensorMapDataType, cuuint32_t, void*, const cuuint64_t*,
                                   const cuuint64_t*, const cuuint32_t*, const cuuint32_t*, CUtensorMapInterleave,
                                   CUtensorMapSwizzle, CUtensorMapL2promotion, CUtensorMapFloatOOBfill);
static PFN_tmapEncode s_encode = nullptr;

static void make_map_2d(CUtensorMap* m, const void* ptr, int rows, int cols, int box_rows) {
  cuuint64_t dims[2] = {(cuuint64_t)cols, (cuuint64_t)rows};
  cuuint64_t strides[1] = {(cuuint64_t)cols * 2};
  cuuint32_t box[2] = {cols < 64 ? 32u : 64u, (cuuint32_t)box_rows};
  cuuint32_t es[2] = {1, 1};
  s_encode(m, CU_TENSOR_MAP_DATA_TYPE_BFLOAT16, 2, const_cast<void*>(ptr), dims, strides, box, es,
           CU_TENSOR_MAP_INTERLEAVE_NONE, cols < 64 ? CU_TENSOR_MAP_SWIZZLE_64B : CU_TENSOR_MAP_SWIZZLE_128B, CU_TENSOR_MAP_L2_PROMOTION_L2_256B,
           CU_TENSOR_MAP_FLOAT_OOB_FILL_NONE);
}
static void make_map_3d(CUtensorMap* m, const void* ptr, int rows, int cols, int box_rows, int box_chunks) {
  cuuint64_t dims[3] = {64, (cuuint64_t)rows, (cuuint64_t)(cols / 64)};
  cuuint64_t strides[2] = {(cuuint64_t)cols * 2, 128};
  cuuint32_t box[3] = {64, (cuuint32_t)box_rows, (cuuint32_t)box_chunks};
  cuuint32_t es[3] = {1, 1, 1};
  s_encode(m, CU_TENSOR_MAP_DATA_TYPE_BFLOAT16, 3, const_cast<void*>(ptr), dims, strides, box, es,
           CU_TENSOR_MAP_INTERLEAVE_NONE, CU_TENSOR_MAP_SWIZZLE_128B, CU_TENSOR_MAP_L2_PROMOTION_L2_256B,
           CU_TENSOR_MAP_FLOAT_OOB_FILL_NONE);
}

static cudaLaunchConfig_t fused_cfg(cudaLaunchAttribute* at) {
  cudaLaunchConfig_t cfg = {};
  cfg.gridDim = dim3(132);
  cfg.blockDim = dim3(384);
  cfg.dynamicSmemBytes = SMEM_BYTES;
  cfg.stream = cudaStreamPerThread;
  at[0].id = cudaLaunchAttributeClusterDimension;
  at[0].val.clusterDim.x = 2;
  at[0].val.clusterDim.y = 1;
  at[0].val.clusterDim.z = 1;
  cfg.attrs = at;
  cfg.numAttrs = 1;
  return cfg;
}

extern "C" void kernel_launch(void* const* d_in, const int* in_sizes, int n_in, void* d_out, int out_size) {
  const bf16* x = (const bf16*)d_in[0];
  const bf16* ckv = (const bf16*)d_in[1];
  const bf16* wq = (const bf16*)d_in[2];
  const bf16* wuk = (const bf16*)d_in[3];
  const bf16* wuv = (const bf16*)d_in[4];
  const bf16* wo = (const bf16*)d_in[5];
  const bf16* bk = (const bf16*)d_in[7];
  const bf16* bv = (const bf16*)d_in[8];
  const bf16* shift_k = (const bf16*)d_in[9];
  const bf16* ssm_k = (const bf16*)d_in[10];
  const bf16* ssm_D = (const bf16*)d_in[11];
  const bf16* gate_w = (const bf16*)d_in[12];
  bf16* out = (bf16*)d_out;

  static void *pq = nullptr, *pk = nullptr, *pv = nullptr, *pctx = nullptr, *pb = nullptr, *pu = nullptr;
  static int max_clusters = 0;
  if (!s_encode) {
    void* fn = nullptr;
    cudaDriverEntryPointQueryResult qres;
    cudaGetDriverEntryPoint("cuTensorMapEncodeTiled", &fn, cudaEnableDefault, &qres);
    s_encode = (PFN_tmapEncode)fn;
    cudaGetSymbolAddress(&pq, g_q);
    cudaGetSymbolAddress(&pk, g_k);
    cudaGetSymbolAddress(&pv, g_v);
    cudaGetSymbolAddress(&pctx, g_ctx);
    cudaGetSymbolAddress(&pb, g_y2T);
    cudaGetSymbolAddress(&pu, g_kvT);
    cudaFuncSetAttribute(fused_kernel, cudaFuncAttributeMaxDynamicSharedMemorySize, SMEM_BYTES);
    cudaLaunchAttribute at[1];
    cudaLaunchConfig_t cfg = fused_cfg(at);
    if (cudaOccupancyMaxActiveClusters(&max_clusters, fused_kernel, &cfg) != cudaSuccess) max_clusters = 0;
  }

  Maps all = {};
  make_map_2d(&all.a[0], x, S_LEN, DM, 128);
  make_map_2d(&all.a[1], ckv, S_LEN, DC, 128);
  make_map_3d(&all.b[0], wq, DM, HDIM, 64, 4);
  make_map_3d(&all.b[1], wuk, DC, HDIM, 64, 4);
  make_map_3d(&all.b[2], wuv, DC, HDIM, 64, 4);
  make_map_2d(&all.c[0], pq, S_LEN, HDIM, 64);
  make_map_2d(&all.c[1], pk, S_LEN, HDIM, 64);
  make_map_2d(&all.c[2], pv, S_LEN, HDIM, 64);
  make_map_3d(&all.q, pq, S_LEN, HDIM, 128, 2);
  make_map_3d(&all.k, pk, S_LEN, HDIM, 128, 2);
  make_map_3d(&all.v, pv, S_LEN, HDIM, 128, 2);
  make_map_2d(&all.o, pctx, S_LEN, HDIM, 64);
  all.ssm_k = ssm_k;
  all.ssm_D = ssm_D;
  make_map_2d(&all.oa, pctx, S_LEN, HDIM, 128);
  make_map_2d(&all.ob, wo, HDIM, DM, 64);
  make_map_2d(&all.oc, out, S_LEN, DM, 128);
  make_map_3d(&all.y, pb, DM, S_LEN, 16, 2);
  make_map_3d(&all.xs, x, S_LEN, DM, 32, 1);
  make_map_2d(&all.cu, pu, DM * 64, 32, 64);
  make_map_2d(&all.ch, ssm_k, DM * 64, 32, 64);

  make_map_2d(&all.bk, bk, S_LEN, DM, 35);
  make_map_2d(&all.bv, bv, S_LEN, DM, 32);
  for (int b = 0; b < 128; b++) {
    const int c = b >> 1, r = b & 1;
    const int G = c < 4 ? 0 : c < 36 ? (c - 4) % 8 : 1 + (c - 36) % 7;
    const int i = c < 4 ? 4 + c : c < 36 ? (c - 4) / 8 : 4 + (c - 36) / 7;
    all.id[b][0] = r + 2 * (i & 1) + 4 * (G & 3) + 16 * (i >> 1) + 64 * (G >> 2);
    all.id[b][1] = r + 2 * i + 16 * G;
    all.id[b][2] = r + 2 * G + 16 * i;
  }
  all.shift_k = shift_k;
  all.x = x;
  all.gate_w = gate_w;
  cudaLaunchAttribute at[1];
  cudaLaunchConfig_t cfg = fused_cfg(at);
  if (max_clusters >= 66) {
    cudaLaunchKernelEx(&cfg, fused_kernel, 7, all);
  } else {
    for (int m = 1; m <= 4; m <<= 1) cudaLaunchKernelEx(&cfg, fused_kernel, m, all);
  }
}
```

```cpp
#include <cuda_runtime.h>
#include <cuda_bf16.h>
#include <cuda.h>
#include <stdint.h>

typedef __nv_bfloat16 bf16;
#define INPLACE 3

constexpr int S_LEN = 2048;
constexpr int DM = 1024;
constexpr int NH = 32;
constexpr int HD = 128;
constexpr int DC = 512;
constexpr int HDIM = NH * HD;

__device__ __align__(1024) bf16 g_q[S_LEN * HDIM];
__device__ __align__(1024) bf16 g_k[S_LEN * HDIM];
__device__ __align__(1024) bf16 g_v[S_LEN * HDIM];
#define g_ctx g_q
__device__ __align__(1024) bf16 g_kvT[DM * S_LEN];
#define g_y2T g_kvT
__device__ __align__(1024) float g_gate[S_LEN];
enum { CNT_KV = 0, CNT_PREP = CNT_KV + 2, CNT_CTX, CNT_Y2 = CNT_CTX + 2, CNT_DONE = CNT_Y2 + 2, CNT_N };
__device__ unsigned int g_cnt[CNT_N * 32];

#define TL(k, i)
#define TL2(k, i)
#define TD(i)
#define CT(i)
#define GT(i)
#define GA(i)
#define ST(i)

__device__ __forceinline__ uint32_t smem_u32(const void* p) { return (uint32_t)__cvta_generic_to_shared(p); }

__device__ __forceinline__ void mbar_init(uint32_t bar, uint32_t count) {
  asm volatile("mbarrier.init.shared::cta.b64 [%0], %1;" ::"r"(bar), "r"(count));
}
__device__ __forceinline__ void mbar_expect_tx(uint32_t bar, uint32_t bytes) {
  asm volatile("mbarrier.arrive.expect_tx.shared::cta.b64 _, [%0], %1;" ::"r"(bar), "r"(bytes) : "memory");
}
__device__ __forceinline__ void mbar_arrive(uint32_t bar) {
  asm volatile("mbarrier.arrive.shared::cta.b64 _, [%0];" ::"r"(bar) : "memory");
}
__device__ __forceinline__ void mbar_wait(uint32_t bar, uint32_t parity) {
  uint32_t done;
  uint32_t spins = 0;
  do {
    asm volatile(
        "{\n.reg .pred p;\n"
        "mbarrier.try_wait.parity.shared::cta.b64 p, [%1], %2;\n"
        "selp.u32 %0, 1, 0, p;\n}\n"
        : "=r"(done)
        : "r"(bar), "r"(parity)
        : "memory");
    if (++spins > (1u << 22)) break;
  } while (!done);
}
__device__ __forceinline__ bool mbar_try(uint32_t bar, uint32_t parity) {
  uint32_t done;
  asm volatile(
      "{\n.reg .pred p;\n"
      "mbarrier.try_wait.parity.shared::cta.b64 p, [%1], %2;\n"
      "selp.u32 %0, 1, 0, p;\n}\n"
      : "=r"(done)
      : "r"(bar), "r"(parity)
      : "memory");
  return done != 0;
}
__device__ __forceinline__ bool elect_one() {
  uint32_t pred;
  asm volatile("{\n.reg .pred p;\nelect.sync _|p, 0xffffffff;\nselp.u32 %0, 1, 0, p;\n}\n" : "=r"(pred));
  return pred != 0;
}
__device__ __forceinline__ void mbar_arrive_if(uint32_t bar, bool pred) {
  asm volatile(
      "{\n.reg .pred p;\nsetp.ne.b32 p, %1, 0;\n"
      "@p mbarrier.arrive.shared::cta.b64 _, [%0];\n}\n" ::"r"(bar),
      "r"((uint32_t)pred)
      : "memory");
}
__device__ __forceinline__ void mbar_wait_sleep(uint32_t bar, uint32_t parity) {
  uint32_t done;
  uint32_t spins = 0;
  do {
    asm volatile(
        "{\n.reg .pred p;\n"
        "mbarrier.try_wait.parity.shared::cta.b64 p, [%1], %2, %3;\n"
        "selp.u32 %0, 1, 0, p;\n}\n"
        : "=r"(done)
        : "r"(bar), "r"(parity), "r"(20000u)
        : "memory");
    if (++spins > (1u << 16)) break;
  } while (!done);
}
__device__ __forceinline__ void fence_barrier_init() {
  asm volatile("fence.mbarrier_init.release.cluster;" ::: "memory");
}
__device__ __forceinline__ void fence_proxy_async() {
  asm volatile("fence.proxy.async.shared::cta;" ::: "memory");
}
__device__ __forceinline__ void named_bar_sync(int id, int nthreads) {
  asm volatile("bar.sync %0, %1;" ::"r"(id), "r"(nthreads) : "memory");
}
__device__ __forceinline__ void named_bar_arrive(int id, int nthreads) {
  asm volatile("bar.arrive %0, %1;" ::"r"(id), "r"(nthreads) : "memory");
}
__device__ __forceinline__ void tma_load_2d(uint32_t dst, const CUtensorMap* m, uint32_t bar, int c0, int c1) {
  asm volatile(
      "cp.async.bulk.tensor.2d.shared::cluster.global.mbarrier::complete_tx::bytes [%0], [%1, {%3, %4}], [%2];" ::"r"(dst),
      "l"(reinterpret_cast<uint64_t>(m)), "r"(bar), "r"(c0), "r"(c1)
      : "memory");
}
__device__ __forceinline__ void tma_load_3d(uint32_t dst, const CUtensorMap* m, uint32_t bar, int c0, int c1, int c2) {
  asm volatile(
      "cp.async.bulk.tensor.3d.shared::cluster.global.mbarrier::complete_tx::bytes [%0], [%1, {%3, %4, %5}], [%2];" ::"r"(dst),
      "l"(reinterpret_cast<uint64_t>(m)), "r"(bar), "r"(c0), "r"(c1), "r"(c2)
      : "memory");
}
__device__ __forceinline__ void tma_store_2d(const CUtensorMap* m, uint32_t src, int c0, int c1) {
  asm volatile("cp.async.bulk.tensor.2d.global.shared::cta.bulk_group [%0, {%2, %3}], [%1];" ::"l"(
                   reinterpret_cast<uint64_t>(m)),
               "r"(src), "r"(c0), "r"(c1)
               : "memory");
}
__device__ __forceinline__ void bulk_load(uint32_t dst, const void* src, uint32_t bytes, uint32_t bar) {
  asm volatile("cp.async.bulk.shared::cluster.global.mbarrier::complete_tx::bytes [%0], [%1], %2, [%3];" ::"r"(dst),
               "l"(src), "r"(bytes), "r"(bar)
               : "memory");
}
__device__ __forceinline__ void tma_load_2d_mc(uint32_t dst, const CUtensorMap* m, uint32_t bar, int c0, int c1,
                                               uint16_t mask) {
  asm volatile(
      "cp.async.bulk.tensor.2d.shared::cluster.global.mbarrier::complete_tx::bytes.multicast::cluster [%0], [%1, {%3, "
      "%4}], [%2], %5;" ::"r"(dst),
      "l"(reinterpret_cast<uint64_t>(m)), "r"(bar), "r"(c0), "r"(c1), "h"(mask)
      : "memory");
}
__device__ __forceinline__ void mbar_arrive_cluster_if(uint32_t bar, uint32_t cta, bool pred) {
  asm volatile(
      "{\n.reg .b32 ra;\n.reg .pred p;\nsetp.ne.b32 p, %2, 0;\n"
      "mapa.shared::cluster.u32 ra, %0, %1;\n"
      "@p mbarrier.arrive.shared::cluster.b64 _, [ra];\n}\n" ::"r"(bar),
      "r"(cta), "r"((uint32_t)pred)
      : "memory");
}
__device__ __forceinline__ uint64_t policy_evict_first() {
  uint64_t pol;
  asm volatile("createpolicy.fractional.L2::evict_first.b64 %0, 1.0;" : "=l"(pol));
  return pol;
}
__device__ __forceinline__ void tma_load_2d_hint(uint32_t dst, const CUtensorMap* m, uint32_t bar, int c0, int c1,
                                                 uint64_t pol) {
  asm volatile(
      "cp.async.bulk.tensor.2d.shared::cluster.global.mbarrier::complete_tx::bytes.L2::cache_hint [%0], [%1, {%3, %4}], "
      "[%2], %5;" ::"r"(dst),
      "l"(reinterpret_cast<uint64_t>(m)), "r"(bar), "r"(c0), "r"(c1), "l"(pol)
      : "memory");
}
__device__ __forceinline__ void tma_load_3d_hint(uint32_t dst, const CUtensorMap* m, uint32_t bar, int c0, int c1,
                                                 int c2, uint64_t pol) {
  asm volatile(
      "cp.async.bulk.tensor.3d.shared::cluster.global.mbarrier::complete_tx::bytes.L2::cache_hint [%0], [%1, {%3, %4, "
      "%5}], [%2], %6;" ::"r"(dst),
      "l"(reinterpret_cast<uint64_t>(m)), "r"(bar), "r"(c0), "r"(c1), "r"(c2), "l"(pol)
      : "memory");
}
__device__ __forceinline__ void bulk_load_hint(uint32_t dst, const void* src, uint32_t bytes, uint32_t bar, uint64_t pol) {
  asm volatile(
      "cp.async.bulk.shared::cluster.global.mbarrier::complete_tx::bytes.L2::cache_hint [%0], [%1], %2, [%3], %4;" ::"r"(dst),
      "l"(src), "r"(bytes), "r"(bar), "l"(pol)
      : "memory");
}
__device__ __forceinline__ void cnt_signal_release(int which, uint32_t n) {
  asm volatile("red.release.gpu.global.add.u32 [%0], %1;" ::"l"(g_cnt + which * 32), "r"(n) : "memory");
}
__device__ __forceinline__ void cnt_wait(int which, uint32_t target) {
  uint32_t v, spins = 0;
  while (true) {
    asm volatile("ld.acquire.gpu.global.u32 %0, [%1];" : "=r"(v) : "l"(g_cnt + which * 32) : "memory");
    if (v >= target || ++spins > (1u << 18)) break;
    __nanosleep(64);
  }
  asm volatile("fence.proxy.async.global;" ::: "memory");
}
__device__ __forceinline__ void tma_store_commit() { asm volatile("cp.async.bulk.commit_group;" ::: "memory"); }
template <int N>
__device__ __forceinline__ void tma_store_wait_read() {
  asm volatile("cp.async.bulk.wait_group.read %0;" ::"n"(N) : "memory");
}
template <int N>
__device__ __forceinline__ void tma_store_wait() {
  asm volatile("cp.async.bulk.wait_group %0;" ::"n"(N) : "memory");
}
__device__ __forceinline__ void wgmma_fence() { asm volatile("wgmma.fence.sync.aligned;" ::: "memory"); }
__device__ __forceinline__ void wgmma_commit() { asm volatile("wgmma.commit_group.sync.aligned;" ::: "memory"); }
template <int N>
__device__ __forceinline__ void wgmma_wait() {
  asm volatile("wgmma.wait_group.sync.aligned %0;" ::"n"(N) : "memory");
}
template <int R>
__device__ __forceinline__ void reg_alloc() { asm volatile("setmaxnreg.inc.sync.aligned.u32 %0;" ::"n"(R)); }
template <int R>
__device__ __forceinline__ void reg_dealloc() { asm volatile("setmaxnreg.dec.sync.aligned.u32 %0;" ::"n"(R)); }

__device__ __forceinline__ void stmatrix_x4(uint32_t addr, uint32_t r0, uint32_t r1, uint32_t r2, uint32_t r3) {
  asm volatile("stmatrix.sync.aligned.m8n8.x4.shared.b16 [%0], {%1, %2, %3, %4};" ::"r"(addr), "r"(r0), "r"(r1),
               "r"(r2), "r"(r3)
               : "memory");
}
__device__ __forceinline__ uint32_t pack_bf16(float lo, float hi) {
  uint32_t r;
  asm("cvt.rn.bf16x2.f32 %0, %1, %2;" : "=r"(r) : "f"(hi), "f"(lo));
  return r;
}
__device__ __forceinline__ float bf16_round(float x) { return __bfloat162float(__float2bfloat16_rn(x)); }
__device__ __forceinline__ float bf_lo(uint32_t v) { return __uint_as_float(v << 16); }
__device__ __forceinline__ float bf_hi(uint32_t v) { return __uint_as_float(v & 0xffff0000u); }
__device__ __forceinline__ uint4 lds128(uint32_t a) {
  uint4 v;
  asm volatile("ld.shared.v4.u32 {%0, %1, %2, %3}, [%4];" : "=r"(v.x), "=r"(v.y), "=r"(v.z), "=r"(v.w) : "r"(a));
  return v;
}
__device__ __forceinline__ void sts128(uint32_t a, uint4 v) {
  asm volatile("st.shared.v4.u32 [%0], {%1, %2, %3, %4};" ::"r"(a), "r"(v.x), "r"(v.y), "r"(v.z), "r"(v.w) : "memory");
}
__device__ __forceinline__ uint32_t mul_bf2(uint32_t a, uint32_t b) {
  uint32_t r;
  asm("mul.rn.bf16x2 %0, %1, %2;" : "=r"(r) : "r"(a), "r"(b));
  return r;
}
__device__ __forceinline__ uint32_t add_bf2(uint32_t a, uint32_t b) {
  uint32_t r;
  asm("add.rn.bf16x2 %0, %1, %2;" : "=r"(r) : "r"(a), "r"(b));
  return r;
}
__device__ __forceinline__ float ex2(float x) {
  float y;
  asm("ex2.approx.ftz.f32 %0, %1;" : "=f"(y) : "f"(x));
  return y;
}
__device__ __forceinline__ float rcp(float x) {
  float y;
  asm("rcp.approx.ftz.f32 %0, %1;" : "=f"(y) : "f"(x));
  return y;
}
template <int N>
__device__ __forceinline__ void fence_regs(float (&r)[N]) {
#pragma unroll
  for (int i = 0; i < N; i++) asm volatile("" : "+f"(r[i])::"memory");
}

template <int N>
__device__ __forceinline__ void undef_regs(float (&r)[N]) {
#pragma unroll
  for (int i = 0; i < N; i++) asm volatile("" : "=f"(r[i]));
}
template <int N>
__device__ __forceinline__ void fence_regs_u(uint32_t (&r)[N]) {
#pragma unroll
  for (int i = 0; i < N; i++) asm volatile("" : "+r"(r[i])::"memory");
}

constexpr uint64_t DESC_SW128 = 1ull << 62;
__device__ __forceinline__ uint64_t make_desc(uint32_t addr, uint32_t lbo_bytes, uint32_t sbo_bytes, uint64_t swz) {
  return (uint64_t)((addr & 0x3FFFF) >> 4) | ((uint64_t)((lbo_bytes & 0x3FFFF) >> 4) << 16) |
         ((uint64_t)((sbo_bytes & 0x3FFFF) >> 4) << 32) | swz;
}

__device__ __forceinline__ uint64_t desc_add(uint64_t d, uint32_t off16) {
  return (d & 0xFFFFFFFF00000000ull) | (uint64_t)((uint32_t)d + off16);
}

__device__ __forceinline__ void wgmma_m64n256_ss_tb(float (&d)[128], uint64_t da, uint64_t db, int sd) {
  asm volatile(
    "{\n.reg .pred p;\nsetp.ne.b32 p, %130, 0;\n"
    "wgmma.mma_async.sync.aligned.m64n256k16.f32.bf16.bf16 "
    "{%0, %1, %2, %3, %4, %5, %6, %7, %8, %9, %10, %11, %12, %13, %14, %15, %16, %17, %18, %19, %20, %21, %22, %23, %24, %25, %26, %27, %28, %29, %30, %31, %32, %33, %34, %35, %36, %37, %38, %39, %40, %41, %42, %43, %44, %45, %46, %47, %48, %49, %50, %51, %52, %53, %54, %55, %56, %57, %58, %59, %60, %61, %62, %63, %64, %65, %66, %67, %68, %69, %70, %71, %72, %73, %74, %75, %76, %77, %78, %79, %80, %81, %82, %83, %84, %85, %86, %87, %88, %89, %90, %91, %92, %93, %94, %95, %96, %97, %98, %99, %100, %101, %102, %103, %104, %105, %106, %107, %108, %109, %110, %111, %112, %113, %114, %115, %116, %117, %118, %119, %120, %121, %122, %123, %124, %125, %126, %127}, %128, %129, p, 1, 1, 0, 1;\n}\n"
    : "+f"(d[0]), "+f"(d[1]), "+f"(d[2]), "+f"(d[3]), "+f"(d[4]), "+f"(d[5]), "+f"(d[6]), "+f"(d[7]), "+f"(d[8]), "+f"(d[9]), "+f"(d[10]), "+f"(d[11]), "+f"(d[12]), "+f"(d[13]), "+f"(d[14]), "+f"(d[15]), "+f"(d[16]), "+f"(d[17]), "+f"(d[18]), "+f"(d[19]), "+f"(d[20]), "+f"(d[21]), "+f"(d[22]), "+f"(d[23]), "+f"(d[24]), "+f"(d[25]), "+f"(d[26]), "+f"(d[27]), "+f"(d[28]), "+f"(d[29]), "+f"(d[30]), "+f"(d[31]), "+f"(d[32]), "+f"(d[33]), "+f"(d[34]), "+f"(d[35]), "+f"(d[36]), "+f"(d[37]), "+f"(d[38]), "+f"(d[39]), "+f"(d[40]), "+f"(d[41]), "+f"(d[42]), "+f"(d[43]), "+f"(d[44]), "+f"(d[45]), "+f"(d[46]), "+f"(d[47]), "+f"(d[48]), "+f"(d[49]), "+f"(d[50]), "+f"(d[51]), "+f"(d[52]), "+f"(d[53]), "+f"(d[54]), "+f"(d[55]), "+f"(d[56]), "+f"(d[57]), "+f"(d[58]), "+f"(d[59]), "+f"(d[60]), "+f"(d[61]), "+f"(d[62]), "+f"(d[63]), "+f"(d[64]), "+f"(d[65]), "+f"(d[66]), "+f"(d[67]), "+f"(d[68]), "+f"(d[69]), "+f"(d[70]), "+f"(d[71]), "+f"(d[72]), "+f"(d[73]), "+f"(d[74]), "+f"(d[75]), "+f"(d[76]), "+f"(d[77]), "+f"(d[78]), "+f"(d[79]), "+f"(d[80]), "+f"(d[81]), "+f"(d[82]), "+f"(d[83]), "+f"(d[84]), "+f"(d[85]), "+f"(d[86]), "+f"(d[87]), "+f"(d[88]), "+f"(d[89]), "+f"(d[90]), "+f"(d[91]), "+f"(d[92]), "+f"(d[93]), "+f"(d[94]), "+f"(d[95]), "+f"(d[96]), "+f"(d[97]), "+f"(d[98]), "+f"(d[99]), "+f"(d[100]), "+f"(d[101]), "+f"(d[102]), "+f"(d[103]), "+f"(d[104]), "+f"(d[105]), "+f"(d[106]), "+f"(d[107]), "+f"(d[108]), "+f"(d[109]), "+f"(d[110]), "+f"(d[111]), "+f"(d[112]), "+f"(d[113]), "+f"(d[114]), "+f"(d[115]), "+f"(d[116]), "+f"(d[117]), "+f"(d[118]), "+f"(d[119]), "+f"(d[120]), "+f"(d[121]), "+f"(d[122]), "+f"(d[123]), "+f"(d[124]), "+f"(d[125]), "+f"(d[126]), "+f"(d[127])
    : "l"(da), "l"(db), "r"(sd));
}

__device__ __forceinline__ void wgmma_m64n128_ss(float (&d)[64], uint64_t da, uint64_t db, int sd) {
  asm volatile(
    "{\n.reg .pred p;\nsetp.ne.b32 p, %66, 0;\n"
    "wgmma.mma_async.sync.aligned.m64n128k16.f32.bf16.bf16 "
    "{%0, %1, %2, %3, %4, %5, %6, %7, %8, %9, %10, %11, %12, %13, %14, %15, %16, %17, %18, %19, %20, %21, %22, %23, %24, %25, %26, %27, %28, %29, %30, %31, %32, %33, %34, %35, %36, %37, %38, %39, %40, %41, %42, %43, %44, %45, %46, %47, %48, %49, %50, %51, %52, %53, %54, %55, %56, %57, %58, %59, %60, %61, %62, %63}, %64, %65, p, 1, 1, 0, 0;\n}\n"
    : "+f"(d[0]), "+f"(d[1]), "+f"(d[2]), "+f"(d[3]), "+f"(d[4]), "+f"(d[5]), "+f"(d[6]), "+f"(d[7]), "+f"(d[8]), "+f"(d[9]), "+f"(d[10]), "+f"(d[11]), "+f"(d[12]), "+f"(d[13]), "+f"(d[14]), "+f"(d[15]), "+f"(d[16]), "+f"(d[17]), "+f"(d[18]), "+f"(d[19]), "+f"(d[20]), "+f"(d[21]), "+f"(d[22]), "+f"(d[23]), "+f"(d[24]), "+f"(d[25]), "+f"(d[26]), "+f"(d[27]), "+f"(d[28]), "+f"(d[29]), "+f"(d[30]), "+f"(d[31]), "+f"(d[32]), "+f"(d[33]), "+f"(d[34]), "+f"(d[35]), "+f"(d[36]), "+f"(d[37]), "+f"(d[38]), "+f"(d[39]), "+f"(d[40]), "+f"(d[41]), "+f"(d[42]), "+f"(d[43]), "+f"(d[44]), "+f"(d[45]), "+f"(d[46]), "+f"(d[47]), "+f"(d[48]), "+f"(d[49]), "+f"(d[50]), "+f"(d[51]), "+f"(d[52]), "+f"(d[53]), "+f"(d[54]), "+f"(d[55]), "+f"(d[56]), "+f"(d[57]), "+f"(d[58]), "+f"(d[59]), "+f"(d[60]), "+f"(d[61]), "+f"(d[62]), "+f"(d[63])
    : "l"(da), "l"(db), "r"(sd));
}

__device__ __forceinline__ void wgmma_m64n128_ss_tb(float (&d)[64], uint64_t da, uint64_t db, int sd) {
  asm volatile(
    "{\n.reg .pred p;\nsetp.ne.b32 p, %66, 0;\n"
    "wgmma.mma_async.sync.aligned.m64n128k16.f32.bf16.bf16 "
    "{%0, %1, %2, %3, %4, %5, %6, %7, %8, %9, %10, %11, %12, %13, %14, %15, %16, %17, %18, %19, %20, %21, %22, %23, %24, %25, %26, %27, %28, %29, %30, %31, %32, %33, %34, %35, %36, %37, %38, %39, %40, %41, %42, %43, %44, %45, %46, %47, %48, %49, %50, %51, %52, %53, %54, %55, %56, %57, %58, %59, %60, %61, %62, %63}, %64, %65, p, 1, 1, 0, 1;\n}\n"
    : "+f"(d[0]), "+f"(d[1]), "+f"(d[2]), "+f"(d[3]), "+f"(d[4]), "+f"(d[5]), "+f"(d[6]), "+f"(d[7]), "+f"(d[8]), "+f"(d[9]), "+f"(d[10]), "+f"(d[11]), "+f"(d[12]), "+f"(d[13]), "+f"(d[14]), "+f"(d[15]), "+f"(d[16]), "+f"(d[17]), "+f"(d[18]), "+f"(d[19]), "+f"(d[20]), "+f"(d[21]), "+f"(d[22]), "+f"(d[23]), "+f"(d[24]), "+f"(d[25]), "+f"(d[26]), "+f"(d[27]), "+f"(d[28]), "+f"(d[29]), "+f"(d[30]), "+f"(d[31]), "+f"(d[32]), "+f"(d[33]), "+f"(d[34]), "+f"(d[35]), "+f"(d[36]), "+f"(d[37]), "+f"(d[38]), "+f"(d[39]), "+f"(d[40]), "+f"(d[41]), "+f"(d[42]), "+f"(d[43]), "+f"(d[44]), "+f"(d[45]), "+f"(d[46]), "+f"(d[47]), "+f"(d[48]), "+f"(d[49]), "+f"(d[50]), "+f"(d[51]), "+f"(d[52]), "+f"(d[53]), "+f"(d[54]), "+f"(d[55]), "+f"(d[56]), "+f"(d[57]), "+f"(d[58]), "+f"(d[59]), "+f"(d[60]), "+f"(d[61]), "+f"(d[62]), "+f"(d[63])
    : "l"(da), "l"(db), "r"(sd));
}

__device__ __forceinline__ void wgmma_m64n128_rs_tb(float* d, uint32_t a0, uint32_t a1, uint32_t a2, uint32_t a3, uint64_t db, int sd) {
  asm volatile(
    "{\n.reg .pred p;\nsetp.ne.b32 p, %69, 0;\n"
    "wgmma.mma_async.sync.aligned.m64n128k16.f32.bf16.bf16 "
    "{%0, %1, %2, %3, %4, %5, %6, %7, %8, %9, %10, %11, %12, %13, %14, %15, %16, %17, %18, %19, %20, %21, %22, %23, %24, %25, %26, %27, %28, %29, %30, %31, %32, %33, %34, %35, %36, %37, %38, %39, %40, %41, %42, %43, %44, %45, %46, %47, %48, %49, %50, %51, %52, %53, %54, %55, %56, %57, %58, %59, %60, %61, %62, %63}, {%64, %65, %66, %67}, %68, p, 1, 1, 1;\n}\n"
    : "+f"(d[0]), "+f"(d[1]), "+f"(d[2]), "+f"(d[3]), "+f"(d[4]), "+f"(d[5]), "+f"(d[6]), "+f"(d[7]), "+f"(d[8]), "+f"(d[9]), "+f"(d[10]), "+f"(d[11]), "+f"(d[12]), "+f"(d[13]), "+f"(d[14]), "+f"(d[15]), "+f"(d[16]), "+f"(d[17]), "+f"(d[18]), "+f"(d[19]), "+f"(d[20]), "+f"(d[21]), "+f"(d[22]), "+f"(d[23]), "+f"(d[24]), "+f"(d[25]), "+f"(d[26]), "+f"(d[27]), "+f"(d[28]), "+f"(d[29]), "+f"(d[30]), "+f"(d[31]), "+f"(d[32]), "+f"(d[33]), "+f"(d[34]), "+f"(d[35]), "+f"(d[36]), "+f"(d[37]), "+f"(d[38]), "+f"(d[39]), "+f"(d[40]), "+f"(d[41]), "+f"(d[42]), "+f"(d[43]), "+f"(d[44]), "+f"(d[45]), "+f"(d[46]), "+f"(d[47]), "+f"(d[48]), "+f"(d[49]), "+f"(d[50]), "+f"(d[51]), "+f"(d[52]), "+f"(d[53]), "+f"(d[54]), "+f"(d[55]), "+f"(d[56]), "+f"(d[57]), "+f"(d[58]), "+f"(d[59]), "+f"(d[60]), "+f"(d[61]), "+f"(d[62]), "+f"(d[63])
    : "r"(a0), "r"(a1), "r"(a2), "r"(a3), "l"(db), "r"(sd));
}

__device__ __forceinline__ void wgmma_m64n64_rs_tb(float (&d)[32], const uint32_t (&a)[4], uint64_t db, int sd) {
  asm volatile(
    "{\n.reg .pred p;\nsetp.ne.b32 p, %37, 0;\n"
    "wgmma.mma_async.sync.aligned.m64n64k16.f32.bf16.bf16 "
    "{%0, %1, %2, %3, %4, %5, %6, %7, %8, %9, %10, %11, %12, %13, %14, %15, %16, %17, %18, %19, %20, %21, %22, %23, %24, %25, %26, %27, %28, %29, %30, %31}, {%32, %33, %34, %35}, %36, p, 1, 1, 1;\n}\n"
    : "+f"(d[0]), "+f"(d[1]), "+f"(d[2]), "+f"(d[3]), "+f"(d[4]), "+f"(d[5]), "+f"(d[6]), "+f"(d[7]), "+f"(d[8]), "+f"(d[9]), "+f"(d[10]), "+f"(d[11]), "+f"(d[12]), "+f"(d[13]), "+f"(d[14]), "+f"(d[15]), "+f"(d[16]), "+f"(d[17]), "+f"(d[18]), "+f"(d[19]), "+f"(d[20]), "+f"(d[21]), "+f"(d[22]), "+f"(d[23]), "+f"(d[24]), "+f"(d[25]), "+f"(d[26]), "+f"(d[27]), "+f"(d[28]), "+f"(d[29]), "+f"(d[30]), "+f"(d[31])
    : "r"(a[0]), "r"(a[1]), "r"(a[2]), "r"(a[3]), "l"(db), "r"(sd));
}

__device__ __forceinline__ void wgmma_m64n32_rs_tb(float (&d)[16], const uint32_t (&a)[4], uint64_t db, int sd) {
  asm volatile(
    "{\n.reg .pred p;\nsetp.ne.b32 p, %21, 0;\n"
    "wgmma.mma_async.sync.aligned.m64n32k16.f32.bf16.bf16 "
    "{%0, %1, %2, %3, %4, %5, %6, %7, %8, %9, %10, %11, %12, %13, %14, %15}, {%16, %17, %18, %19}, %20, p, 1, 1, 1;\n}\n"
    : "+f"(d[0]), "+f"(d[1]), "+f"(d[2]), "+f"(d[3]), "+f"(d[4]), "+f"(d[5]), "+f"(d[6]), "+f"(d[7]), "+f"(d[8]), "+f"(d[9]), "+f"(d[10]), "+f"(d[11]), "+f"(d[12]), "+f"(d[13]), "+f"(d[14]), "+f"(d[15])
    : "r"(a[0]), "r"(a[1]), "r"(a[2]), "r"(a[3]), "l"(db), "r"(sd));
}

constexpr int G_STAGES = 4;
constexpr int G_A_BYTES = 128 * 64 * 2;
constexpr int G_B_BYTES = 256 * 64 * 2;
constexpr int G_STAGE_BYTES = G_A_BYTES + G_B_BYTES;
constexpr int G_STG_OFF = G_STAGES * G_STAGE_BYTES;
constexpr int BAR_OFF = G_STG_OFF + 32768 + 2048;
constexpr int SMEM_BYTES = BAR_OFF + 1024;
constexpr int B_GFULL = 0, B_GEMPTY = 32, B_CTX = 64, B_OY2 = 72, B_PFULL = 224;
constexpr int B_KFULL = 80, B_KEMPTY = 96, B_VFULL = 112, B_VEMPTY = 128, B_QFULL = 144, B_QEMPTY = 160,
              B_QDONE = 184;
constexpr int B_CFULL = 192;
constexpr int B_OFREE = 256, B_OFULL = 272, B_OEMPTY = 320, B_OY = 368;
constexpr int B_SFULL = 392, B_SFREE = 424, B_PEND = 456, B_SCMD = 512;

#define PHASE_PROLOGUE                                                                \
  uint32_t tid, rt_zero;                                                              \
  asm volatile("mov.u32 %0, %%tid.x;" : "=r"(tid));                                   \
  asm volatile("mov.u32 %0, %%nctaid.y;" : "=r"(rt_zero));                            \
  asm volatile("" : "+r"(smem0));                                                     \
  rt_zero = __shfl_sync(0xffffffffu, rt_zero >> 8, 0);   \
  const uint32_t sbase = __shfl_sync(0xffffffffu, smem0, 0);                          \
  const uint32_t bar = sbase + BAR_OFF;                                               \
  const int wg = __shfl_sync(0xffffffffu, tid >> 7, 0);                               \
  const int warp = (tid >> 5) & 3, lane = tid & 31, wtid = tid & 127;                 \
  (void)rt_zero; (void)bar; (void)warp; (void)lane; (void)wtid;

enum { ST_END = 0, ST_BOX1, ST_BOX2, ST_BOX2Q, ST_BOX2L };
__device__ __forceinline__ void st_post(uint32_t bar, int wg, int wtid, uint32_t n, int kind, const void* dst,
                                        uint32_t src, int c0, int c1, int sig) {
  if (wtid == 0) {
    const uint32_t c = bar + B_SCMD + wg * 64 + (n & 1) * 32;
    const uint64_t d = reinterpret_cast<uint64_t>(dst);
    sts128(c, make_uint4(kind, src, c0, c1));
    sts128(c + 16, make_uint4((uint32_t)d, (uint32_t)(d >> 32), sig, 0));
  }
  fence_proxy_async();
  __syncwarp();
  mbar_arrive_if(bar + B_SFULL + wg * 16 + (n & 1) * 8, (wtid & 31) == 0);
}
__device__ __forceinline__ void st_wait(uint32_t bar, int wg, uint32_t n) {
  const uint32_t b = bar + B_SFREE + wg * 16 + (n & 1) * 8;
  if (!mbar_try(b, ~(n >> 1) & 1)) mbar_wait(b, ~(n >> 1) & 1);
}
__device__ __forceinline__ void note(uint32_t bar, uint32_t cnt) {
  asm volatile("red.release.cta.shared.add.u32 [%0], 1;" ::"r"(bar + B_PEND + 4 * cnt) : "memory");
}
__device__ __forceinline__ void store_agent(uint32_t bar, int wg) {
  mbar_arrive(bar + B_SFREE + wg * 16);
  mbar_arrive(bar + B_SFREE + wg * 16 + 8);
  bool more = true;
  for (uint32_t n = 0;; n++) {
    mbar_wait_sleep(bar + B_SFULL + wg * 16 + (n & 1) * 8, (n >> 1) & 1);
    const uint4 c = lds128(bar + B_SCMD + wg * 64 + (n & 1) * 32);
    const uint4 d = lds128(bar + B_SCMD + wg * 64 + (n & 1) * 32 + 16);
    if (c.x == ST_END) break;
    const CUtensorMap* dst = reinterpret_cast<const CUtensorMap*>((uint64_t)d.x | ((uint64_t)d.y << 32));
    tma_store_2d(dst, c.y, c.z, c.w);
    if (c.x >= ST_BOX2) tma_store_2d(dst, c.y + 8192, c.z + 64, c.w);
    tma_store_commit();
    tma_store_wait_read<0>();
    mbar_arrive(bar + B_SFREE + wg * 16 + (n & 1) * 8);
    if (c.x == ST_BOX2L) mbar_arrive(bar + B_OFREE + 8 * wg);
    if ((int)d.z >= 0) {
      tma_store_wait<0>();
      if (d.z == 0) { TD(6) }
      asm volatile("fence.proxy.async.global;" ::: "memory");
      if (c.x == ST_BOX2Q) mbar_arrive(bar + B_QDONE);
      else note(bar, d.z);
      if (c.x == ST_BOX2L) {
        note(bar, CNT_DONE);
        more = false;
      }
    }
  }
  if (more) note(bar, CNT_DONE);
}

struct Maps {
  const bf16 *shift_k, *x, *gate_w, *ssm_k, *ssm_D;
  uint8_t id[128][4];
  CUtensorMap a[2];
  CUtensorMap b[3];
  CUtensorMap c[3];
  CUtensorMap bk, bv;
  CUtensorMap q, k, v, o;
  CUtensorMap oa, ob, oc;
  CUtensorMap y, xs;
  CUtensorMap cu, ch;
};

constexpr int P_SLOT = 67 * 128, P_V = 35 * 128, P_TAPS = 2 * P_SLOT;
__device__ __forceinline__ void ldsm4t(uint32_t (&r)[4], uint32_t a) {
  asm volatile("ldmatrix.sync.aligned.m8n8.x4.trans.shared.b16 {%0, %1, %2, %3}, [%4];"
               : "=r"(r[0]), "=r"(r[1]), "=r"(r[2]), "=r"(r[3])
               : "r"(a));
}
__device__ __forceinline__ uint32_t fma_bf2(uint32_t a, uint32_t b, uint32_t c) {
  uint32_t r;
  asm("fma.rn.bf16x2 %0, %1, %2, %3;" : "=r"(r) : "r"(a), "r"(b), "r"(c));
  return r;
}
__device__ __forceinline__ void prep_agent(const Maps& maps, uint32_t sbase, int w, int lane) {
  const uint32_t bar = sbase + BAR_OFF, pb = bar + B_PFULL + w * 16;
  const int d0 = (blockIdx.x >> 3) * 64, t0 = (blockIdx.x & 7) * 256 + w * 128;
  mbar_wait_sleep(bar + B_GFULL + 8 * (G_STAGES - 1), 0);
#pragma unroll 1
  for (int i = -1; i < 4; i++) {
    GA(82 + 2 * i)
    if (i >= 0) mbar_wait_sleep(pb + (i & 1) * 8, i >> 1);
    GA(83 + 2 * i)
    const uint32_t so = sbase + G_STG_OFF + w * (P_TAPS + 512) + (i & 1) * P_SLOT;
    if (i < 3 && elect_one()) {
      const uint32_t b = pb + (~i & 1) * 8, dst = so + (i & 1 ? -P_SLOT : P_SLOT);
      mbar_expect_tx(b, i < 0 ? P_SLOT + 512 : P_SLOT);
      const uint64_t pol = policy_evict_first();
      tma_load_2d_hint(dst, &maps.bk, b, d0, t0 + 32 * i + 29, pol);
      tma_load_2d_hint(dst + P_V, &maps.bv, b, d0, t0 + 32 * i + 32, pol);
      if (i < 0) bulk_load(sbase + G_STG_OFF + P_TAPS, maps.shift_k + d0 * 4, 512, b);
    }
    if (i < 0) continue;
    uint32_t ak[4];
#pragma unroll
    for (int r = 0; r < 4; r++) {
      const uint32_t a = so / 128 + r + 4 * (lane & 6) + (((lane >> 2) ^ lane) & 6) + (lane & 1);
      ak[r] = a * 128 + (a & 7) * 16;
    }
    bf16* dst = g_kvT + (size_t)(d0 + (lane >> 2)) * S_LEN + t0 + ((lane & 3) + 4 * i) * 8;
#pragma unroll 1
    for (int cg = 0; cg < 128; cg += 16) {
      uint32_t t01, t23, k[4][4], v[4];
      asm volatile("ld.shared.v2.u32 {%0, %1}, [%2];"
                   : "=r"(t01), "=r"(t23)
                   : "r"(sbase + G_STG_OFF + P_TAPS + cg * 4 + (lane >> 2) * 8));
#pragma unroll
      for (int r = 0; r < 4; r++) ldsm4t(k[r], ak[r] ^ cg);
      ldsm4t(v, (ak[3] ^ cg) + 4096);
      const uint32_t w0 = __byte_perm(t01, 0, 0x1010), w1 = __byte_perm(t01, 0, 0x3232);
      const uint32_t w2 = __byte_perm(t23, 0, 0x1010), w3 = __byte_perm(t23, 0, 0x3232);
#pragma unroll
      for (int j = 0; j < 4; j++)
        v[j] = mul_bf2(fma_bf2(k[3][j], w0, fma_bf2(k[2][j], w1, fma_bf2(k[1][j], w2, mul_bf2(k[0][j], w3)))), v[j]);
      const bool s1 = lane & 1, s2 = lane & 2;
      const uint32_t a0 = s1 ? v[1] : v[0], a1 = s1 ? v[0] : v[1], a2 = s1 ? v[3] : v[2], a3 = s1 ? v[2] : v[3];
      *reinterpret_cast<uint4*>(dst) = make_uint4(s2 ? a2 : a0, s2 ? a3 : a1, s2 ? a0 : a2, s2 ? a1 : a3);
      dst += 8 * S_LEN;
    }
    fence_proxy_async();
    __syncwarp();
  }
  GA(90)
  if (lane == 0) note(bar, CNT_PREP);
  __syncwarp();
  GA(91)
}

__device__ __forceinline__ void qkv_tile(const Maps& maps, int it, int& which, int& m_tile, int& n_tile) {
  const bool q = it == 0 || it >= 5;
  const int b = maps.id[blockIdx.x][it >= 5];
  which = q ? 0 : 2 - (it & 1);
  m_tile = b & 15;
  n_tile = (b >> 4) * 2 + ((0x19 >> it) & 1);
}

constexpr int G_NTILES = 6;
__device__ __forceinline__ void qkv_producer(const Maps& maps, uint32_t sbase, bool first) {
  const uint32_t bar = sbase + BAR_OFF;
  uint32_t stage = 0, phase = 0;
#pragma unroll 1
  for (int it = 0; it < (first ? 1 : G_NTILES); it++) {
    int which, m_tile, n_tile;
    qkv_tile(maps, it, which, m_tile, n_tile);
    const CUtensorMap* ma = &maps.a[which == 0 ? 0 : 1];
    const CUtensorMap* mb = &maps.b[which];
    const int nk = first ? G_STAGES : which == 0 ? 16 : 8;
#pragma unroll 1
    for (int kt = (it == 0 && !first) ? G_STAGES : 0; kt < nk; kt++) {
      if (!first) mbar_wait_sleep(bar + B_GEMPTY + 8 * stage, phase);
      const uint32_t fb = bar + B_GFULL + 8 * stage;
      const uint32_t sa = sbase + stage * G_STAGE_BYTES;
      mbar_expect_tx(fb, G_STAGE_BYTES);
      tma_load_2d(sa, ma, fb, kt * 64, m_tile * 128);
      tma_load_3d(sa + G_A_BYTES, mb, fb, 0, kt * 64, n_tile * 4);
      if (++stage == G_STAGES) { stage = 0; phase ^= 1; }
      {
        const int b = maps.id[blockIdx.x][1];
        if (it == 2 && kt == (b & 7)) {
          for (int i = 0; i < 2; i++)
            asm volatile("cp.async.bulk.prefetch.tensor.2d.L2.global.tile [%0, {%1, %2}];" ::"l"(&maps.a[0]),
                         "r"((b >> 4) * 128 + i * 64), "r"((b & 15) * 128)
                         : "memory");
        }
        if (it == 3 && kt == (b & 7))
          asm volatile("cp.async.bulk.prefetch.tensor.3d.L2.global.tile [%0, {%1, %2, %3}];" ::"l"(&maps.b[0]), "r"(0),
                       "r"((b & 15) * 64), "r"((b >> 4) * 8)
                       : "memory");
      }
    }
  }
}

__device__ __noinline__ void publisher(uint32_t bar, int lane, uint32_t nsrc, uint32_t poll) {
  uint32_t done = 0;
#pragma unroll 1
  for (uint32_t spins = 0; (done < nsrc || poll <= nsrc) && spins < (1u << 20); spins++) {
    if (done >= poll) {
      uint32_t v;
      asm volatile("ld.acquire.gpu.global.u32 %0, [%1];" : "=r"(v) : "l"(g_cnt + (CNT_CTX + 1) * 32) : "memory");
      if (__all_sync(0xffffffffu, v >= NH * (S_LEN / 128))) {
        asm volatile("fence.proxy.async.global;" ::: "memory");
        mbar_arrive_if(bar + B_CTX, lane == 0);
        poll = ~0u;
      }
    }
    uint32_t v = 0;
    if (lane < CNT_N)
      asm volatile("atom.acquire.cta.shared.exch.b32 %0, [%1], 0;" : "=r"(v) : "r"(bar + B_PEND + 4 * lane) : "memory");
    done += __shfl_sync(0xffffffffu, v, CNT_DONE);
    if (lane == CNT_DONE) v = 0;
    if (done == nsrc && lane < CNT_DONE) {
      uint32_t w;
      asm volatile("atom.acquire.cta.shared.exch.b32 %0, [%1], 0;" : "=r"(w) : "r"(bar + B_PEND + 4 * lane) : "memory");
      v += w;
    }
    if (v && lane == 0) { TD(0) }
    if (v) cnt_signal_release(lane, v);
    if (v && lane == 0) { TD(1) }
    if (!__any_sync(0xffffffffu, v != 0)) __nanosleep(200);
  }
  __threadfence();
  __syncwarp();
}

__device__ __forceinline__ void gate_rows(const Maps& maps, uint32_t sbase, int w48, int w12, int lane) {
  const uint32_t buf = sbase + w12 * 16384, gb = sbase + BAR_OFF + 768 + w12 * 16;
  if (lane == 0) {
    mbar_init(gb, 1);
    mbar_init(gb + 8, 1);
    fence_barrier_init();
    for (int i = 0; i < 2; i++) {
      mbar_expect_tx(gb + 8 * i, 8192);
      bulk_load(buf + i * 8192, maps.x + (size_t)(w48 + 48 * i) * 4 * DM, 8192, gb + 8 * i);
    }
  }
  __syncwarp();
  uint4 wv[4];
#pragma unroll
  for (int i = 0; i < 4; i++) wv[i] = __ldg(reinterpret_cast<const uint4*>(maps.gate_w + (i * 32 + lane) * 8));
  int it = 0;
#pragma unroll 1
  for (int row = w48 * 4; row < S_LEN; row += 48 * 4, it++) {
    mbar_wait(gb + 8 * (it & 1), (it >> 1) & 1);
    uint4 xv[4][4];
#pragma unroll
    for (int r = 0; r < 4; r++)
#pragma unroll
      for (int i = 0; i < 4; i++) xv[r][i] = lds128(buf + (it & 1) * 8192 + r * 2048 + (i * 32 + lane) * 16);
    float d[2][4];
#pragma unroll
    for (int pr = 0; pr < 2; pr++) {
      d[pr][0] = d[pr][1] = d[pr][2] = d[pr][3] = 0.f;
      auto acc = [&](uint32_t a0, uint32_t a2, uint32_t b0, uint32_t b2, uint32_t w0, uint32_t w2) {
        asm volatile(
            "mma.sync.aligned.m16n8k16.row.col.f32.bf16.bf16.f32 {%0, %1, %2, %3}, {%4, %5, %6, %7}, {%8, %8}, "
            "{%0, %1, %2, %3};"
            : "+f"(d[pr][0]), "+f"(d[pr][1]), "+f"(d[pr][2]), "+f"(d[pr][3])
            : "r"(mul_bf2(a0, w0)), "r"(mul_bf2(b0, w0)), "r"(mul_bf2(a2, w2)), "r"(mul_bf2(b2, w2)), "r"(0x3f803f80u));
      };
#pragma unroll
      for (int i = 0; i < 4; i++) {
        acc(xv[2 * pr][i].x, xv[2 * pr][i].y, xv[2 * pr + 1][i].x, xv[2 * pr + 1][i].y, wv[i].x, wv[i].y);
        acc(xv[2 * pr][i].z, xv[2 * pr][i].w, xv[2 * pr + 1][i].z, xv[2 * pr + 1][i].w, wv[i].z, wv[i].w);
      }
    }
    float sum = (lane & 2) ? ((lane & 1) ? d[1][2] : d[1][0]) : ((lane & 1) ? d[0][2] : d[0][0]);
#pragma unroll
    for (int off = 16; off >= 4; off >>= 1) sum += __shfl_xor_sync(0xffffffffu, sum, off);
    if (lane < 4) g_gate[row + lane] = bf16_round(rcp(1.0f + __expf(-bf16_round(sum))));
    if (lane == 0 && row + 2 * 48 * 4 < S_LEN) {
      mbar_expect_tx(gb + 8 * (it & 1), 8192);
      bulk_load(buf + (it & 1) * 8192, maps.x + (size_t)(row + 2 * 48 * 4) * DM, 8192, gb + 8 * (it & 1));
    }
  }
}

constexpr float Q_SCALE = 0.08838834764831845f * 1.4426950408889634f;
__device__ __forceinline__ uint32_t qkv_consumer(const Maps& maps, uint32_t smem0, bool fused, float (&rest)[64]) {
  PHASE_PROLOGUE
  constexpr int NTILES = G_NTILES;
  float acc[128];
  uint32_t stage = 0, phase = 0;
  const uint32_t stg = sbase + G_STG_OFF + wg * 18432;
  const int st_row = warp * 16 + (lane & 7) + ((lane >> 3) & 1) * 8;
  const int st_cb = lane >> 4;
  uint32_t pend[64];
  const CUtensorMap* pend_map = nullptr;
  int pend_c0 = 0, pend_c1 = 0;
  uint32_t sn = 0;
  auto put_box = [&](uint32_t buf, const uint32_t* v) {
#pragma unroll
    for (int jp = 0; jp < 4; jp++) {
      const int chunk = jp * 2 + st_cb;
      const uint32_t addr = buf + st_row * 128 + ((chunk ^ (st_row & 7)) << 4);
      stmatrix_x4(addr, v[jp * 4], v[jp * 4 + 1], v[jp * 4 + 2], v[jp * 4 + 3]);
    }
  };
  GT(gti++)
#pragma unroll 1
  for (int it = 0; it <= NTILES; it++) {
    int which, m_tile, n_tile;
    qkv_tile(maps, it, which, m_tile, n_tile);
    const int nk = (which == 0 && it < NTILES) ? 16 : 8;
    uint32_t prev_stage = 0;
#pragma unroll 1
    for (int kt = 0; kt < nk; kt++) {
      if (it < NTILES) {
        mbar_wait((bar + B_GFULL) + 8 * stage, phase);
        GT(gti++)
        const uint64_t da0 = make_desc(sbase + stage * G_STAGE_BYTES + wg * 8192, 16, 1024, DESC_SW128);
        const uint64_t db0 = make_desc(sbase + stage * G_STAGE_BYTES + G_A_BYTES, 8192, 1024, DESC_SW128);
        wgmma_fence();
#pragma unroll
        for (int kk = 0; kk < 4; kk++) {
          wgmma_m64n256_ss_tb(acc, desc_add(da0, kk * 2), desc_add(db0, kk * 128), (kt | kk) != 0);
        }
        wgmma_commit();
      }
      const uint32_t when = it == 0 ? 0 : it == 5 ? 0x922 << wg : wg ? 0xAA : 0x55;
      if ((when >> kt) & 1) {
        const int c = __popc(when & ~(~0u << kt));
        st_wait(bar, wg, sn - 2);
        const uint32_t buf = stg + (c & 1) * 8192;
        switch (c) {
          case 0: put_box(buf, pend); break;
          case 1: put_box(buf, pend + 16); break;
          case 2: put_box(buf, pend + 32); break;
          default: put_box(buf, pend + 48); break;
        }
        st_post(bar, wg, wtid, sn, ST_BOX1, pend_map, buf, pend_c0 + c * 64, pend_c1, (c == 3 && it > 1) ? CNT_KV + (it > 3) : -1);
        sn++;
      }
      if (it < NTILES) {
        wgmma_wait<1>();
        mbar_arrive_if((bar + B_GEMPTY) + 8 * prev_stage, wtid == 32 && kt > 0);
        prev_stage = stage;
        if (++stage == G_STAGES) { stage = 0; phase ^= 1; }
      }
    }
    wgmma_wait<0>();
    fence_regs(acc);
    if (it == NTILES) break;
    GT(gti++)
    mbar_arrive_if((bar + B_GEMPTY) + 8 * prev_stage, wtid == 32);
    if (it == NTILES - 1 && fused) break;
    if (which == 0) {
#pragma unroll
      for (int j = 0; j < 128; j++) acc[j] *= Q_SCALE;
    }
#pragma unroll
    for (int j = 0; j < 64; j++) pend[j] = pack_bf16(acc[2 * j], acc[2 * j + 1]);
    pend_map = &maps.c[which];
    pend_c0 = n_tile * 256;
    pend_c1 = m_tile * 128 + wg * 64;
  }
  mbar_wait(bar + B_GEMPTY, 1);
#pragma unroll
  for (int j = 0; j < 32; j++) pend[j] = pack_bf16(acc[2 * j] * Q_SCALE, acc[2 * j + 1] * Q_SCALE);
  put_box(sbase + wg * 8192, pend);
  put_box(sbase + 16384 + wg * 8192, pend + 16);
  fence_proxy_async();
#pragma unroll
  for (int j = 0; j < 64; j++) rest[j] = acc[64 + j];
  GT(gti++)
  return sn;
}

constexpr int A_TILE = 128 * 128 * 2;
constexpr int A_Q_OFF = 0;
constexpr int A_K_OFF = 2 * A_TILE;
constexpr int A_V_OFF = 4 * A_TILE;
constexpr int A_O_OFF = 6 * A_TILE;
constexpr int A_ITEMS = NH * (S_LEN / 128);

constexpr uint32_t A_ORDER = 0x3120, A_STEPS = 34;
__device__ __forceinline__ int item_m(uint32_t it) { return it & 15; }
__device__ __forceinline__ int item_h(uint32_t it) { return it >> 4; }

constexpr int C_V = 16384, C_MAT = 24576;
constexpr float C_ALPHA = 0.07874506561842957f;
__device__ __forceinline__ void sincos_turn(int p, float inv, float& c, float& s) {
  const float a = (float)p * (inv * 6.283185307179586f);
  asm("cos.approx.ftz.f32 %0, %1;" : "=f"(c) : "f"(a));
  asm("sin.approx.ftz.f32 %0, %1;" : "=f"(s) : "f"(a));
}

__device__ __forceinline__ uint32_t item_of(const Maps& maps, uint32_t r) {
  const uint32_t b = maps.id[blockIdx.x & 127][1];
  return (b >> 4) * 64 + ((A_ORDER >> (4 * r)) & 3) * 16 + ((b ^ ((r & 1) * 15)) & 15);
}

#define PACE 250
#define XMASK 3
#define XFIRST 4
#define C_SIDE 64
__device__ __forceinline__ uint32_t conv_first(const Maps& maps) {
  const uint32_t b = maps.id[blockIdx.x & 127][1];
  return (b >> 4) * 128 + ((b + 15) & 15);
}

__device__ __forceinline__ void conv_consumer(const Maps& maps, uint32_t smem0, uint32_t first, uint32_t step,
                                              uint32_t end, bool pp) {
  PHASE_PROLOGUE
  const uint32_t in_full = bar + B_CFULL + wg * 16;
  const uint32_t ca = sbase + (wg ? A_V_OFF + A_TILE : A_Q_OFF);
  const int w = __shfl_sync(0xffffffffu, warp, 0), g = lane >> 2, c = lane & 3;
  auto fetch = [&](uint32_t ch, uint32_t n) {
    if (w == 2 && ch < end) {
      if (elect_one()) {
        const uint32_t b = in_full + (n & 1) * 8, d = ca + (n & 1) * 8192;
        const uint64_t pol = policy_evict_first();
        mbar_expect_tx(b, 8192);
        tma_load_2d_hint(d, &maps.cu, b, 0, ch * 64, pol);
        tma_load_2d_hint(d + 4096, &maps.ch, b, 0, ch * 64, pol);
      }
    }
  };
  if (wtid == 96 && wg) { TD(15) }
  uint32_t f1[8][4];
  float tt[16], ts[16];
  uint32_t cc[4], ss[4];
#pragma unroll
  for (int i = 0; i < 16; i++) {
    const int k = 2 * (16 * w + g + 8 * (i & 1)) + 1, n = 2 * (8 * (i >> 1) + 2 * c) + 1;
    float c0, s0, c1, s1;
    sincos_turn(((k * n) << 23) >> 23, 1.f / 512, c0, s0);
    sincos_turn(((k * n + 2 * k) << 23) >> 23, 1.f / 512, c1, s1);
    f1[i >> 2][i & 3] = pack_bf16(c0 * C_ALPHA, c1 * C_ALPHA);
    f1[4 + (i >> 2)][i & 3] = pack_bf16(s0 * -C_ALPHA, s1 * -C_ALPHA);
  }
#pragma unroll
  for (int i = 0; i < 16; i++) {
    const int k = 2 * (16 * w + g + 8 * ((i >> 1) & 1)) + 1, n = 16 - (8 * (i >> 2) + 2 * c + (i & 1));
    float cs;
    sincos_turn(k * n, 1.f / 8192, cs, ts[i]);
    tt[i] = ts[i] * rcp(1.f + cs);
  }
#pragma unroll
  for (int j = 0; j < 4; j++) {
    const int k = 8 * w + g, n = 8 * c + 2 * j;
    float c0, s0, c1, s1;
    sincos_turn((int8_t)(k * n * 8), 1.f / 256, c0, s0);
    sincos_turn((int8_t)((k * n + k) * 8), 1.f / 256, c1, s1);
    cc[j] = pack_bf16(c0, c1);
    ss[j] = pack_bf16(s0, s1);
  }
  named_bar_sync(3, 256);
  fetch(first, 0);
  fetch(first + step, 1);
  const uint32_t va = ca + g * 64 + ((c ^ (g >> 1)) << 4);
  {
    const uint32_t a = va + C_MAT + w * 512, m = 0x80008000u;
    sts128(a, make_uint4(cc[0], cc[1], cc[2], cc[3]));
    sts128(a + 2048, make_uint4(ss[0], ss[1], ss[2], ss[3]));
    sts128(a + 4096, make_uint4(ss[0] ^ m, ss[1] ^ m, ss[2] ^ m, ss[3] ^ m));
    sts128(a + 6144, make_uint4(cc[0], cc[1], cc[2], cc[3]));
  }
  fence_proxy_async();
  named_bar_sync(1 + wg, 128);
  constexpr uint64_t DHI = (2ull << 62) | ((uint64_t)(512 >> 4) << 32);
  const uint32_t d0 = (uint32_t)make_desc(ca, 4096, 0, 0);
  float a5[16];
  uint4* const yb = reinterpret_cast<uint4*>(g_y2T) + (16 * w + g) * 4 + c;
  auto issue5 = [&]() {
#pragma unroll
    for (int ks = 0; ks < 8; ks++) wgmma_m64n32_rs_tb(a5, f1[ks], DHI | (d0 + (C_V >> 4) + ks * 64), ks != 0);
    wgmma_commit();
  };
  auto finish = [&](uint32_t ch, bool on) {
    fence_regs(a5);
    uint4* y = yb + (size_t)ch * 256;
    if (on) {
      y[0] = make_uint4(pack_bf16(a5[0], a5[1]), pack_bf16(a5[4], a5[5]), pack_bf16(a5[8], a5[9]), pack_bf16(a5[12], a5[13]));
      y[32] = make_uint4(pack_bf16(a5[2], a5[3]), pack_bf16(a5[6], a5[7]), pack_bf16(a5[10], a5[11]), pack_bf16(a5[14], a5[15]));
    }
  };
  auto dft32 = [&](float (&d)[32], const float* re, const float* im) {
    uint32_t a[4][4];
#pragma unroll
    for (int i = 0; i < 8; i++) {
      a[i >> 2][i & 3] = pack_bf16(re[2 * i], re[2 * i + 1]);
      a[2 + (i >> 2)][i & 3] = pack_bf16(im[2 * i], im[2 * i + 1]);
    }
    wgmma_fence();
#pragma unroll
    for (int ks = 0; ks < 4; ks++) wgmma_m64n64_rs_tb(d, a[ks], DHI | (d0 + (C_MAT >> 4) + ks * 64), ks != 0);
    wgmma_commit();
  };
  auto rot = [&](float* x, float* y) {
#pragma unroll
    for (int i = 0; i < 16; i++) {
      x[i] = fmaf(-tt[i], y[i], x[i]);
      y[i] = fmaf(ts[i], x[i], y[i]);
      x[i] = fmaf(-tt[i], y[i], x[i]);
    }
  };
  auto load_d = [&](uint32_t ch) {
    return __ldg(reinterpret_cast<const unsigned short*>(maps.ssm_D) + ((ch & (DM - 1)) | (lane & rt_zero)));
  };
  uint32_t dn = load_d(first);
  uint32_t n = 0, ch = first;
#pragma unroll 1
  for (; ch < end; n++, ch += step) {
    CT(0)
    float a1[2][32], a2[2][32], a4[32];
    const float dsk = c ? 0.f : __uint_as_float(dn << 16) * C_ALPHA;
    dn = load_d(ch + step);
    mbar_wait(in_full + (n & 1) * 8, (n >> 1) & 1);
    if (pp) named_bar_sync(4 + wg, 256);
    CT(1)
    wgmma_fence();
#pragma unroll
    for (int ks = 0; ks < 8; ks++)
      wgmma_m64n64_rs_tb(a1[ks >> 2], f1[ks], DHI | (d0 + (n & 1) * 512 + (ks & 3) * 64), (ks & 3) != 0);
    wgmma_commit();
    issue5();
    wgmma_wait<1>();
    fence_regs(a1[0]);
    fence_regs(a1[1]);
    CT(2)
    rot(a1[0], a1[1]);
    dft32(a2[0], a1[0], a1[1]);
    rot(a1[0] + 16, a1[1] + 16);
    a1[0][16] += dsk;
    a1[0][18] += dsk;
    dft32(a2[1], a1[0] + 16, a1[1] + 16);
    CT(3)
    wgmma_wait<2>();
    finish(ch - step, n > 0);
    wgmma_wait<0>();
    fence_regs(a2[0]);
    fence_regs(a2[1]);
    CT(4)
    if (pp) named_bar_arrive(5 - wg, 256);
    float re[16], im[16];
#pragma unroll
    for (int i = 0; i < 16; i++) {
      re[i] = a2[0][i] * a2[1][i] - a2[0][16 + i] * a2[1][16 + i];
      im[i] = a2[0][i] * a2[1][16 + i] + a2[0][16 + i] * a2[1][i];
    }
    dft32(a4, im, re);
    wgmma_wait<0>();
    fence_regs(a4);
    CT(5)
    rot(a4, a4 + 16);
#pragma unroll
    for (int i = 0; i < 4; i++) {
      const float* x = a4 + 16 - 16 * (i >> 1) + 2 * (i & 1);
      sts128(va + C_V + w * 1024 + (i >> 1) * 4096 + (i & 1) * 512,
             make_uint4(pack_bf16(x[0], x[1]), pack_bf16(x[4], x[5]), pack_bf16(x[8], x[9]), pack_bf16(x[12], x[13])));
    }
    CT(6)
    fence_proxy_async();
    named_bar_sync(1 + wg, 128);
    fetch(ch + 2 * step, n);
    if (wtid == 96 && n > 0) note(bar, CNT_Y2 + (((ch - step) & 112) == 112));
    CT(7)
  }
  wgmma_fence();
  issue5();
  wgmma_wait<0>();
  finish(ch - step, true);
  named_bar_sync(1 + wg, 128);
  if (wtid == 96 && wg) { TD(8) }
  if (wtid == 96) cnt_signal_release(CNT_Y2 + (((ch - step) & 112) == 112), 1);
  if (wtid == 64) note(bar, CNT_DONE);
  if (wtid == 96 && wg) { TD(9) }
}

__device__ __forceinline__ void attn_producer(const Maps& maps, uint32_t sbase, bool after_qkv, bool to_out,
                                              bool dry) {
  const uint32_t bar = sbase + BAR_OFF;
  const uint32_t q_full = bar + B_QFULL, q_empty = bar + B_QEMPTY;
  const uint32_t k_full = bar + B_KFULL, k_empty = bar + B_KEMPTY, v_full = bar + B_VFULL, v_empty = bar + B_VEMPTY;
  int ndrained = after_qkv ? 0 : G_STAGES;
  auto wait = [&](uint32_t b, uint32_t par) {
    if (!dry) mbar_wait_sleep(b, par);
  };
  auto drained = [&](int upto) {
#pragma unroll 1
    for (; ndrained <= upto; ndrained++) wait(bar + B_GEMPTY + 8 * ndrained, 1);
  };
  uint32_t st = 0, ph = 1, vs = 0, vp = 1;
  int pend_j = -1, pend_h = 0;
  int round = -1, m = -1, h = 0;
  bool last = false;
#pragma unroll 1
  for (;; round++) {
    uint32_t nitem = 0;
    const int tpost = m >= 3 ? m - 1 : m;
#pragma unroll 1
    for (int t = m < 0 ? -1 : 0; t <= m; t++) {
      const int j = (t < m && (round & 1)) ? m - 1 - t : t;
      if (t >= 0) {
        drained(1 + st);
        wait(k_empty + 8 * st, ph);
        if (!dry) {
          mbar_expect_tx(k_full + 8 * st, A_TILE);
          tma_load_3d(sbase + A_K_OFF + st * A_TILE, &maps.k, k_full + 8 * st, 0, j * 128, h * 2);
        }
        if (++st == 2) { st = 0; ph ^= 1; }
      }
      if (pend_j >= 0) {
        drained(3);
        wait(v_empty + 8 * vs, vp);
        if (!dry) {
          mbar_expect_tx(v_full + 8 * vs, A_TILE);
          tma_load_3d(sbase + A_V_OFF + vs * A_TILE, &maps.v, v_full + 8 * vs, 0, pend_j * 128, pend_h * 2);
        }
        if (++vs == 2) { vs = 0; vp ^= 1; }
      }
      pend_j = j;
      pend_h = h;
      if (t == tpost && !last) {
        nitem = dry ? 1 : item_of(maps, round + 1);
        if (round == (dry ? 0 : 3) || blockIdx.x >= 128) {
          nitem = A_ITEMS;
          cnt_wait(CNT_PREP, dry ? 0 : 260);
          if (to_out) {
            cnt_wait(CNT_CTX, dry ? 0 : A_ITEMS);
            asm volatile("cp.async.bulk.prefetch.L2.global [%0], 4096;" ::"l"(maps.ssm_k + (size_t)conv_first(maps) * S_LEN));
            if (!dry)
              asm volatile("cp.async.bulk.prefetch.L2.global [%0], 4096;" ::"l"(g_kvT + (size_t)conv_first(maps) * S_LEN));
          }
        }
        const uint32_t qs = (round + 1) & 1;
        wait(q_empty + 8 * qs, (((round + 1) >> 1) & 1) ^ 1);
        if (round == 1 && after_qkv) wait(bar + B_QDONE, 0);
        if (round <= 0 && after_qkv) {
          if (!dry) { TD(2) }
          cnt_wait(CNT_KV + round + 1, dry ? 0 : 512);
          if (!dry) { TD(3) }
        }
        if (nitem >= A_ITEMS || (round < 0 && after_qkv && !dry)) {
          if (!dry) mbar_arrive(q_full + 8 * qs);
        } else {
          drained(qs);
          if (!dry) {
            mbar_expect_tx(q_full + 8 * qs, A_TILE);
            tma_load_3d_hint(sbase + A_Q_OFF + qs * A_TILE, &maps.q, q_full + 8 * qs, 0, item_m(nitem) * 128,
                             item_h(nitem) * 2, policy_evict_first());
          }
        }
      }
    }
    if (last) break;
    last = nitem >= A_ITEMS;
    m = last ? -1 : item_m(nitem);
    h = item_h(nitem);
  }
}

__device__ __forceinline__ uint32_t attn_consumer(const Maps& maps, uint32_t smem0, uint32_t sn,
                                                  float (&rest)[64], bool after_qkv) {
  PHASE_PROLOGUE
  const uint32_t q_full = bar + B_QFULL, q_empty = bar + B_QEMPTY;
  const uint32_t k_full = bar + B_KFULL, k_empty = bar + B_KEMPTY, v_full = bar + B_VFULL;
  float o[64], s[64];
  uint32_t p[32];
  float e[32];
  uint32_t dep = 0;
  constexpr int MIDJ = 5;
  float l0 = 0.f, l1 = 0.f, b0 = 0.f, b1 = 0.f;
  const int sched_own = 4 + wg, sched_other = 5 - wg;
  if (wg == 1) named_bar_arrive(4, 256);

  const uint32_t qd0 = (uint32_t)make_desc(sbase + A_Q_OFF + wg * 8192, 16, 0, 0);
  const uint32_t kd0 = (uint32_t)make_desc(sbase + A_K_OFF, 16, 0, 0);
  const uint32_t vd0 = (uint32_t)make_desc(sbase + A_V_OFF, 16384, 0, 0);
  constexpr uint64_t DHI = DESC_SW128 | ((uint64_t)(1024 >> 4) << 32);
  constexpr uint32_t DST = A_TILE >> 4;
  auto issue_qk = [&](uint32_t qd, uint32_t kd) {
#pragma unroll
    for (int kk = 0; kk < 8; kk++) {
      const uint32_t off = ((kk >> 2) * 16384 + (kk & 3) * 32) >> 4;
      wgmma_m64n128_ss(s, DHI | (qd + off), DHI | (kd + off), kk != 0);
    }
    wgmma_commit();
  };
  auto issue_pv = [&](uint32_t vd, bool accumulate, int nk) {
#pragma unroll
    for (int kk = 0; kk < 8; kk++) {
      if (kk < nk)
        wgmma_m64n128_rs_tb(o, p[4 * kk], p[4 * kk + 1], p[4 * kk + 2], p[4 * kk + 3], DHI | (vd + kk * 128),
                            accumulate || (kk != 0));
    }
    wgmma_commit();
  };
  auto exp_lo = [&](float& a0, float& a1) {
#pragma unroll
    for (int j = 0; j < 8; j++) {
      e[4 * j] = ex2(s[4 * j]);
      e[4 * j + 1] = ex2(s[4 * j + 1]);
      e[4 * j + 2] = ex2(s[4 * j + 2]);
      e[4 * j + 3] = ex2(s[4 * j + 3]);
      a0 += e[4 * j];
      a0 += e[4 * j + 1];
      a1 += e[4 * j + 2];
      a1 += e[4 * j + 3];
      if (j == MIDJ) dep = (__float_as_uint(a0) | __float_as_uint(a1)) & rt_zero;
    }
  };
  auto pack_lo = [&]() {
#pragma unroll
    for (int j = 0; j < 16; j++) p[j] = pack_bf16(e[2 * j], e[2 * j + 1]);
  };
  auto finish_p = [&](float& a0, float& a1) {
    pack_lo();
#pragma unroll
    for (int j = 8; j < 16; j++) {
      const float e0 = ex2(s[4 * j]), e1 = ex2(s[4 * j + 1]), e2 = ex2(s[4 * j + 2]), e3 = ex2(s[4 * j + 3]);
      a0 += e0;
      a0 += e1;
      a1 += e2;
      a1 += e3;
      p[2 * j] = pack_bf16(e0, e1);
      p[2 * j + 1] = pack_bf16(e2, e3);
      if (j == 8 + MIDJ) dep = __float_as_uint(a0) & rt_zero;
    }
  };
  auto quad_sum = [&](float t) {
    t += __shfl_xor_sync(0xffffffffu, t, 1);
    return t + __shfl_xor_sync(0xffffffffu, t, 2);
  };
  auto write_o = [&](float i0, float i1) {
    st_wait(bar, wg, sn - 1);
    const int st_row = warp * 16 + (lane & 7) + ((lane >> 3) & 1) * 8;
    const uint32_t so = sbase + A_O_OFF + wg * 16384 + st_row * 128;
#pragma unroll
    for (int j = 0; j < 16; j += 2)
      stmatrix_x4(so + (j >> 3) * 8192 + ((((j & 7) + (lane >> 4)) ^ (lane & 7)) << 4),
                  pack_bf16(o[4 * j] * i0, o[4 * j + 1] * i0), pack_bf16(o[4 * j + 2] * i1, o[4 * j + 3] * i1),
                  pack_bf16(o[4 * j + 4] * i0, o[4 * j + 5] * i0), pack_bf16(o[4 * j + 6] * i1, o[4 * j + 7] * i1));
  };
  auto store_o = [&](uint32_t r, int kind) {
    const uint32_t it = item_of(maps, r);
    st_post(bar, wg, wtid, sn, kind, (INPLACE & 1) || kind != ST_BOX2Q ? &maps.o : &maps.c[0], sbase + A_O_OFF + wg * 16384, item_h(it) * 128,
            item_m(it) * 128 + wg * 64, CNT_CTX + (r >> 1));
    sn++;
  };
  auto mask_half = [&](float* sh) {
    const int u = warp * 16 + (lane >> 2) - (lane & 3) * 2;
#pragma unroll
    for (int j = 0; j < 8; j++) {
      if (8 * j > u) sh[4 * j] = -INFINITY;
      if (8 * j + 1 > u) sh[4 * j + 1] = -INFINITY;
      if (8 * j - 8 > u) sh[4 * j + 2] = -INFINITY;
      if (8 * j - 7 > u) sh[4 * j + 3] = -INFINITY;
    }
  };
  ST(0)
  mbar_wait(q_full, 0);
  if (blockIdx.x >= 128) {
    return sn;
  }
  mbar_wait(k_full, 0);
  named_bar_sync(sched_own, 256);
  wgmma_fence();
  issue_qk(qd0, kd0);
  named_bar_arrive(sched_other, 256);
  fence_regs(rest);
#pragma unroll
  for (int i = 0; i < 64; i++) o[i] = rest[i] * Q_SCALE;
  fence_regs(o);
  wgmma_wait<0>();
  fence_regs(s);
  mbar_arrive_if(k_empty, wtid == 32);
  uint32_t g = 0;
  uint32_t rnd = 0;
  int rem = item_m(item_of(maps, 0));
  uint32_t first = 1;
  uint32_t fl = 0;
#define redo (fl & 1)
#define shifted (fl & 2)
  float d0 = 0.f, d1 = 0.f;
  float pi0 = 1.f, pi1 = 1.f;
  ST(1)
  for (;;) {
    if (shifted) {
#pragma unroll
      for (int j = 0; j < 16; j++) {
        s[4 * j] -= d0;
        s[4 * j + 1] -= d0;
        s[4 * j + 2] -= d1;
        s[4 * j + 3] -= d1;
      }
    }
    if (rem == 0 && !redo) {
      mbar_arrive_if(q_empty + 8 * (rnd & 1), wtid == 96);
      rnd++;
      if (wg == 0) mask_half(s);
      else mask_half(s + 32);
    }
    for (;;) {
      const bool kill = rem == 0 && wg == 0;
      const uint32_t kd = kd0 + ((g + 1) & 1) * DST, vd = vd0 + (g & 1) * DST;
      float a0 = 0.f, a1 = 0.f;
      exp_lo(a0, a1);
      fence_regs(e);
      const uint32_t kb = k_full + 8 * ((g + 1) & 1);
      const uint32_t kpar = ((((g + 1) >> 1) & 1) ^ (g == A_STEPS - 1 ? 1u : 0u)) | dep;
      if (!mbar_try(kb, kpar)) mbar_wait(kb, kpar | ((__float_as_uint(a0) | __float_as_uint(a1)) & rt_zero));
      wgmma_wait<0>();
      fence_regs(o);
      if (kill) {
        mbar_arrive_if(kb + (B_VEMPTY - B_KFULL), wtid == 64 && !redo && g > 0);
        fence_regs(e);
        pack_lo();
#pragma unroll
        for (int j = 16; j < 32; j++) asm volatile("mov.u32 %0, 0;" : "=r"(p[j]));
        goto check;
      }
#pragma unroll
      for (int i = 32; i < 64; i++) asm volatile("" : "+f"(s[i])::"memory");
      mbar_arrive_if(kb + (B_VEMPTY - B_KFULL), wtid == 64 && !redo && g > 0);
      finish_p(a0, a1);
      if (__any_sync(0xffffffffu, !(mbar_try(v_full + 8 * (g & 1), ((g >> 1) & 1) | dep) &
                                    mbar_try(q_full + 8 * (rnd & 1), ((rnd >> 1) & 1) | dep)) ||
                                      !(a0 + a1 < 1.0995116e12f) || !(fminf(a0, a1) > (first ? 9.094947e-13f : -1.f)))) {
      check:
        bool bad = !(a0 + a1 < 1.0995116e12f);
        if (first) bad |= !(fminf(quad_sum(a0), quad_sum(a1)) > 9.094947e-13f);
        if (!redo && __any_sync(0xffffffffu, bad)) {
          d0 = d1 = first ? -INFINITY : 0.f;
#pragma unroll
          for (int j = 0; j < 16; j++) {
            if (j < 8 || !kill) {
              d0 = fmaxf(d0, fmaxf(s[4 * j], s[4 * j + 1]));
              d1 = fmaxf(d1, fmaxf(s[4 * j + 2], s[4 * j + 3]));
            }
          }
#pragma unroll
          for (int x = 1; x <= 2; x++) {
            d0 = fmaxf(d0, __shfl_xor_sync(0xffffffffu, d0, x));
            d1 = fmaxf(d1, __shfl_xor_sync(0xffffffffu, d1, x));
          }
          b0 += d0;
          b1 += d1;
          if (!first) {
            const float al0 = ex2(-d0), al1 = ex2(-d1);
            l0 *= al0;
            l1 *= al1;
#pragma unroll
            for (int j = 0; j < 16; j++) {
              o[4 * j] *= al0;
              o[4 * j + 1] *= al0;
              o[4 * j + 2] *= al1;
              o[4 * j + 3] *= al1;
            }
          }
          fl = 3;
          break;
        }
        mbar_wait(v_full + 8 * (g & 1), (g >> 1) & 1);
        mbar_wait(q_full + 8 * (rnd & 1), (rnd >> 1) & 1);
      }
      named_bar_sync(sched_own, 256);
      if (g == A_STEPS - 1) {
        if (first) write_o(pi0, pi1);
        fence_regs(o);
        wgmma_fence();
        issue_pv(vd, !first, 8);
        named_bar_arrive(sched_other, 256);
        if (first) store_o(rnd - 2, ST_BOX2);
        pi0 = rcp(quad_sum(l0 + a0));
        pi1 = rcp(quad_sum(l1 + a1));
        goto done;
      }
      wgmma_fence();
      issue_qk(qd0 + (rnd & 1) * DST, kd);
      if (first) write_o(pi0, pi1);
      fence_regs(o);
      if (kill) {
        wgmma_fence();
        issue_pv(vd, !first, 4);
      } else {
        wgmma_fence();
        issue_pv(vd, !first, 8);
      }
      named_bar_arrive(sched_other, 256);
      fl &= 2;
      l0 += a0;
      l1 += a1;
      if (rem == 0 || first) {
        if (first && (g > 0 || after_qkv)) store_o(g ? rnd - (rem == 0 ? 2 : 1) : 2, g ? ST_BOX2 : ST_BOX2Q);
        first = rem == 0;
        if (first) {
          pi0 = rcp(quad_sum(l0));
          pi1 = rcp(quad_sum(l1));
          l0 = l1 = b0 = b1 = 0.f;
          fl = 0;
          rem = item_m(item_of(maps, rnd)) + 1;
        }
      }
      rem--;
      g++;
      wgmma_wait<1>();
      fence_regs(s);
      mbar_arrive_if(kb + (B_KEMPTY - B_KFULL), wtid == 32);
      ST(g + 1)
      if (rem == 0 || shifted) {
        d0 = b0;
        d1 = b1;
        break;
      }
    }
  }
done:
#undef redo
#undef shifted
  wgmma_wait<0>();
  fence_regs(o);
  write_o(pi0, pi1);
  store_o(3, ST_BOX2L);
  ST(35)
  return sn;
}

constexpr int O_STAGES = 5;
constexpr int O_STAGE_BYTES = 32768;
constexpr int O_Y_OFF = 5 * 32768;
constexpr int O_X_OFF = 6 * 32768;
constexpr int O_NK = HDIM / 64;

__device__ __forceinline__ uint32_t out_stage(uint32_t st) { return ((0x43120u >> (4 * st)) & 7) * O_STAGE_BYTES; }

__device__ __forceinline__ void out_producer(const Maps& maps, uint32_t sbase, bool after_attn, bool dry) {
  const uint32_t bar = sbase + BAR_OFF;
  const uint32_t rank = blockIdx.x & 1;
  const int m_tile = maps.id[blockIdx.x][2] & 15, n_tile = maps.id[blockIdx.x][2] >> 4;
  uint32_t stage = 0, phase = 0, xi = 0;
#pragma unroll 1
  for (int ki = 0; ki < (dry ? 1 : O_NK); ki++) {
    const int kt = (ki & 14) * 4 + ((A_ORDER >> ((ki >> 4) * 4)) & 3) * 2 + (ki & 1);
    const uint32_t fb = bar + B_OFULL + 8 * stage, eb = bar + B_OEMPTY + 8 * stage;
    const uint32_t sa = sbase + out_stage(stage);
    if (ki < O_STAGES) {
      constexpr uint32_t LASTB = B_KEMPTY | ((B_QEMPTY + 8) << 8) | ((B_KEMPTY + 8) << 16) | (B_VEMPTY << 24);
      if (ki > 0 && after_attn) mbar_wait_sleep(bar + ((LASTB >> (8 * ki - 8)) & 255), ki == 2);
      mbar_arrive_cluster_if(eb, 0, !dry);
      mbar_arrive_cluster_if(eb, 1, !dry);
    }
    if (ki == 32) mbar_wait_sleep(bar + B_CTX, 0);
    if (!dry) {
      mbar_wait_sleep(eb, phase);
      mbar_expect_tx(fb, O_STAGE_BYTES);
      tma_load_2d_mc(sa + 16384 + rank * 8192, &maps.ob, fb, n_tile * 128 + rank * 64, kt * 64, (uint16_t)3);
      tma_load_2d(sa, &maps.oa, fb, kt * 64, m_tile * 128);
    }
    if (++stage == O_STAGES) { stage = 0; phase ^= 1; }
    if ((ki & XMASK) == XMASK && ki >= XFIRST && xi < 8) {
      if (after_attn && xi < 2) mbar_wait_sleep(bar + B_OFREE + 8 * xi, 0);
      tma_load_3d(sbase + O_X_OFF + (xi & 1) * 16384 + (xi >> 1) * 4096, &maps.xs, bar + B_OY, 0,
                  m_tile * 128 + (xi >> 1) * 32, n_tile * 2 + (xi & 1));
      xi++;
    }
  }
  if (!dry) mbar_wait_sleep(bar + B_OY2, 0);
}

__device__ __forceinline__ void out_side(const Maps& maps, uint32_t smem0, const float (&gv)[4]) {
  PHASE_PROLOGUE
  const int m_tile = maps.id[blockIdx.x][2] & 15, n_tile = maps.id[blockIdx.x][2] >> 4;
  const bool w0 = __shfl_sync(0xffffffffu, warp, 0) == 0;
  if (w0) {
    if (elect_one()) {
      mbar_expect_tx(bar + B_OY, 65536 - 4096);
      TD(10)
      cnt_wait(CNT_Y2, DM - 128);
      TD(7)
#pragma unroll 1
      for (int i = 0; i < 7; i++) {
        tma_load_3d(sbase + O_Y_OFF + i * 4096, &maps.y, bar + B_OY, 0, n_tile * 128 + i * 16, m_tile * 2);
        __nanosleep(PACE);
      }
    }
  }
  mbar_wait_sleep(bar + B_OY, 0);
  if (wtid == 0) { TD(12) }
  const int st_row = warp * 16 + (lane & 7) + ((lane >> 3) & 1) * 8;
  const int mrow = (lane & 7) + ((lane >> 4) & 1) * 8;
  const int mchunk = warp * 2 + ((lane >> 3) & 1);
  const uint32_t xrow = sbase + O_X_OFF + st_row * 128;
  const uint32_t yrow = sbase + O_Y_OFF + mrow * 128 + ((mchunk ^ (lane & 7)) << 4);
  uint32_t y[7][4], x[7][4], om[4];
#pragma unroll
  for (int i = 0; i < 4; i++) om[i] = pack_bf16(1.0f - gv[i], 1.0f - gv[i]);
  auto xa = [&](int h, int i) { return xrow + h * 8192 + (i >> 2) * 16384 + ((((i & 3) * 2 + (lane >> 4)) ^ (lane & 7)) << 4); };
  auto load = [&](int r, int h, int i) {
    ldsm4t(y[r], yrow + h * 2048 + i * 4096);
    asm volatile("ldmatrix.sync.aligned.m8n8.x4.shared.b16 {%0, %1, %2, %3}, [%4];"
                 : "=r"(x[r][0]), "=r"(x[r][1]), "=r"(x[r][2]), "=r"(x[r][3])
                 : "r"(xa(h, i)));
  };
  auto store = [&](int r, int h, int i, uint32_t om0, uint32_t om1) {
    stmatrix_x4(xa(h, i), mul_bf2(om0, mul_bf2(x[r][0], y[r][0])), mul_bf2(om1, mul_bf2(x[r][1], y[r][1])),
                mul_bf2(om0, mul_bf2(x[r][2], y[r][2])), mul_bf2(om1, mul_bf2(x[r][3], y[r][3])));
  };
#pragma unroll 1
  for (int h = 0; h < 2; h++) {
#pragma unroll
    for (int i = 0; i < 7; i++) load(i, h, i);
#pragma unroll
    for (int i = 0; i < 7; i++) store(i, h, i, h ? om[2] : om[0], h ? om[3] : om[1]);
  }
  if (w0) {
    if (elect_one()) {
      mbar_expect_tx(bar + B_OY2, 4096);
      cnt_wait(CNT_Y2 + 1, 128);
      TD(11)
      tma_load_3d(sbase + O_Y_OFF + 7 * 4096, &maps.y, bar + B_OY2, 0, n_tile * 128 + 112, m_tile * 2);
    }
  }
  mbar_wait_sleep(bar + B_OY2, 0);
  load(0, 0, 7);
  load(1, 1, 7);
  store(0, 0, 7, om[0], om[1]);
  store(1, 1, 7, om[2], om[3]);
  __syncwarp();
  mbar_arrive_if(bar + B_OY + 8, lane == 0);
  if (wtid == 0) { TD(13) }
}

__device__ __forceinline__ uint32_t out_gemm(const Maps& maps, uint32_t smem0, uint32_t sn) {
  PHASE_PROLOGUE
  const int m_tile = maps.id[blockIdx.x][2] & 15, n_tile = maps.id[blockIdx.x][2] >> 4;
  float acc[2][64];
  undef_regs(acc[0]);
  undef_regs(acc[1]);
  uint32_t stage = 0, phase = 0, prev_stage = 0;
  GT(gti++)
  const float* gp = g_gate + m_tile * 128 + warp * 16 + (lane >> 2);
  const float gv[4] = {__ldcg(gp), __ldcg(gp + 8), __ldcg(gp + 64), __ldcg(gp + 72)};
  if (wg == 1) {
    out_side(maps, smem0, gv);
    return sn;
  }
#pragma unroll 1
  for (int kt = 0; kt < O_NK; kt++) {
    uint32_t da = (uint32_t)make_desc(sbase + out_stage(stage), 16, 0, 0);
    uint32_t db = (uint32_t)make_desc(sbase + out_stage(stage) + 16384, 8192, 0, 0);
    asm volatile("" : "+r"(da), "+r"(db));
    mbar_wait(bar + B_OFULL + 8 * stage, phase);
    GT(gti++)
    constexpr int OWAIT = 2;
    constexpr uint64_t DHI = DESC_SW128 | ((uint64_t)(1024 >> 4) << 32);
#pragma unroll
    for (int kk = 0; kk < 4; kk++) {
      wgmma_wait<OWAIT>();
      if (kk == OWAIT)
        mbar_arrive_cluster_if(bar + B_OEMPTY + 8 * prev_stage, wtid >> 6,
                               (wtid & 63) == 32 && kt > 0 && kt - 1 + O_STAGES < O_NK);
      wgmma_fence();
      wgmma_m64n128_ss_tb(acc[0], DHI | (da + kk * 2), DHI | (db + kk * 128), (kt | kk) != 0);
      wgmma_m64n128_ss_tb(acc[1], DHI | (da + 512 + kk * 2), DHI | (db + kk * 128), (kt | kk) != 0);
      wgmma_commit();
    }
    prev_stage = stage;
    if (++stage == O_STAGES) { stage = 0; phase ^= 1; }
  }
  if (tid == 0) { TD(14) }
  st_wait(bar, wg, sn - 1);
  const int st_row = warp * 16 + (lane & 7) + ((lane >> 3) & 1) * 8;
  const uint32_t rowa = sbase + O_X_OFF + st_row * 128;
  wgmma_wait<0>();
  fence_regs(acc[0]);
  fence_regs(acc[1]);
  GT(gti++)
  uint32_t gg[4];
#pragma unroll
  for (int i = 0; i < 4; i++) gg[i] = pack_bf16(gv[i], gv[i]);
  mbar_wait(bar + B_OY + 8, 0);
#pragma unroll
  for (int i = 0; i < 16; i++) {
    const int h = i & 1, j = i & 14;
    const uint32_t addr = rowa + h * 8192 + (j >> 3) * 16384 + ((((j & 7) + (lane >> 4)) ^ (st_row & 7)) << 4);
    uint32_t b0, b1, b2, b3;
    asm volatile("ldmatrix.sync.aligned.m8n8.x4.shared.b16 {%0, %1, %2, %3}, [%4];"
                 : "=r"(b0), "=r"(b1), "=r"(b2), "=r"(b3)
                 : "r"(addr));
    const float* a = acc[h] + 4 * j;
    const uint32_t gg0 = gg[2 * h], gg1 = gg[2 * h + 1];
    stmatrix_x4(addr, add_bf2(mul_bf2(gg0, pack_bf16(a[0], a[1])), b0),
                add_bf2(mul_bf2(gg1, pack_bf16(a[2], a[3])), b1), add_bf2(mul_bf2(gg0, pack_bf16(a[4], a[5])), b2),
                add_bf2(mul_bf2(gg1, pack_bf16(a[6], a[7])), b3));
    if (i == 7) st_post(bar, wg, wtid, sn, ST_BOX1, &maps.oc, sbase + O_X_OFF, n_tile * 128, m_tile * 128, -1);
  }
  fence_proxy_async();
  named_bar_sync(1, 128);
  if (__shfl_sync(0xffffffffu, warp, 0) == 0) {
    if (elect_one()) {
      tma_store_2d(&maps.oc, sbase + O_X_OFF + 16384, n_tile * 128 + 64, m_tile * 128);
      tma_store_commit();
    }
  }
  GT(gti++)
  return sn + 1;
}

__device__ __noinline__ void leave_kernel(int mask) {
  if (!(mask & 4)) return;
  if (atomicAdd(g_cnt + CNT_DONE * 32, 1u) == 2 * gridDim.x - 1) {
    for (int i = 0; i < CNT_N; i++) g_cnt[i * 32] = 0;
  }
}

__device__ __noinline__ void side_jobs(const Maps& maps, uint32_t sbase) {
  const int w12 = __shfl_sync(0xffffffffu, threadIdx.x >> 5, 0);
  gate_rows(maps, sbase, (blockIdx.x - 128) * 12 + w12, w12, threadIdx.x & 31);
  fence_proxy_async();
  __syncthreads();
  if (threadIdx.x == 320) cnt_signal_release(CNT_PREP, 1);
}

__global__ void __launch_bounds__(384, 1) fused_kernel(int mask, const __grid_constant__ Maps maps) {
  extern __shared__ __align__(1024) uint8_t smem_raw[];
  {
    const uint32_t sbase = __shfl_sync(0xffffffffu, smem_u32(smem_raw), 0);
    const uint32_t bar = sbase + BAR_OFF;
    const int tid = threadIdx.x;
    const bool do_qkv = (mask & 1) && blockIdx.x < 128;
    TL(0, 0)
    if (__shfl_sync(0xffffffffu, tid >> 5, 0) == 1 && do_qkv) {
      if (elect_one()) {
        for (int i = 0; i < G_STAGES; i++) mbar_init(bar + B_GFULL + 8 * i, 1);
        fence_barrier_init();
        qkv_producer(maps, sbase, true);
      }
    }
    if (tid == 0) {
      for (int i = 0; i < G_STAGES; i++) {
        mbar_init(bar + B_GEMPTY + 8 * i, 2);
        mbar_init(bar + B_SFULL + 8 * i, 4);
        mbar_init(bar + B_SFREE + 8 * i, 1);
      }
      for (int i = 0; i < 2; i++) {
        mbar_init(bar + B_OFREE + 8 * i, 1);
        mbar_init(bar + B_QFULL + 8 * i, 1);
        mbar_init(bar + B_QEMPTY + 8 * i, 2);
        mbar_init(bar + B_KFULL + 8 * i, 1);
        mbar_init(bar + B_KEMPTY + 8 * i, 2);
        mbar_init(bar + B_VFULL + 8 * i, 1);
        mbar_init(bar + B_VEMPTY + 8 * i, 2);
      }
      for (int i = 0; i < O_STAGES; i++) {
        mbar_init(bar + B_OFULL + 8 * i, 1);
        mbar_init(bar + B_OEMPTY + 8 * i, 2);
      }
      mbar_init(bar + B_OY, 1);
      mbar_init(bar + B_CTX, 1);
      mbar_init(bar + B_OY2, 1);
      mbar_init(bar + B_OY + 8, 4);
      mbar_init(bar + B_QDONE, 2);
      for (int i = 0; i < 8; i++) mbar_init(bar + B_CFULL + 8 * i, 1);
      for (int i = 0; i < CNT_N; i++) asm volatile("st.shared.u32 [%0], 0;" ::"r"(bar + B_PEND + 4 * i) : "memory");
      fence_barrier_init();
    }
    __syncthreads();
    asm volatile("barrier.cluster.arrive.relaxed.aligned;" ::: "memory");
    if ((mask & 1) && blockIdx.x >= 128) side_jobs(maps, sbase);
  }
  uint32_t smem0 = smem_u32(smem_raw);
  PHASE_PROLOGUE
  const bool do_qkv = (mask & 1) && blockIdx.x < 128, do_out = (mask & 4) && blockIdx.x < 128;
  TL(0, 1)

  if (wg != 2) {
    reg_alloc<232>();
    uint32_t sn = 0;
    float o[64];
    if (do_qkv) {
      sn = qkv_consumer(maps, smem_u32(smem_raw), mask & 2, o);
    } else {
      undef_regs(o);
    }
    TL(0, 2) TL(1, 0) TL(1, 1)
    asm volatile("barrier.cluster.wait.acquire.aligned;" ::: "memory");
    if (mask & 2) {
      sn = attn_consumer(maps, smem_u32(smem_raw), sn, o, mask & 1);
      TL(2, 0)
      if ((mask & 4) && blockIdx.x < 128 && __shfl_sync(0xffffffffu, threadIdx.x, 0) < 128) {
        named_bar_arrive(3, 256);
      } else {
        const uint32_t b2 = blockIdx.x * 2 + (threadIdx.x >> 7);
        const bool fused = mask & 4, mainc = blockIdx.x < 128;
        const uint32_t first = __shfl_sync(0xffffffffu, !fused ? b2 : mainc ? conv_first(maps) : (b2 - 255) * 128 - C_SIDE, 0);
        conv_consumer(maps, smem_u32(smem_raw), first, !fused ? 264 : mainc ? 16 : 1,
                      !fused ? DM : mainc ? (first | 127) + 1 - C_SIDE : first + C_SIDE, fused && !mainc);
      }
      TL(1, 2) TL(2, 1) TL(2, 2)
    }
    TL(3, 0) TL(3, 1)
    if ((mask & 4) && blockIdx.x < 128) sn = out_gemm(maps, smem_u32(smem_raw), sn);
    {
      uint32_t smem0 = smem_u32(smem_raw);
      PHASE_PROLOGUE
      st_wait(bar, wg, sn - 2);
      st_post(bar, wg, wtid, sn, ST_END, nullptr, 0, 0, 0, -1);
      tma_store_wait_read<0>();
    }
  } else {
    reg_dealloc<40>();
    asm volatile("barrier.cluster.wait.acquire.aligned;" ::: "memory");
    const int w = __shfl_sync(0xffffffffu, tid >> 5, 0) - 8;
    if (w < 2) {
      if (do_qkv) prep_agent(maps, sbase, w, lane);
      if (elect_one()) store_agent(bar, w);
      TL2(3, 2)
    } else {
      if (elect_one()) {
        const bool dry = w == 2;
        if (do_qkv && !dry) qkv_producer(maps, sbase, false);
        if (mask & 2) attn_producer(maps, sbase, do_qkv, do_out, dry);
        if (do_out) out_producer(maps, sbase, mask & 2, dry);
        if (dry) { TD(5) }
      }
      __syncwarp();
      if (w == 2) publisher(bar, tid & 31, !(mask & 2) ? 2 : do_out ? 3 : 4, !do_out ? ~0u : mask & 2);
      if ((tid & 31) == 0) leave_kernel(mask);
    }
  }
}

typedef CUresult (*PFN_tmapEncode)(CUtensorMap*, CUtensorMapDataType, cuuint32_t, void*, const cuuint64_t*,
                                   const cuuint64_t*, const cuuint32_t*, const cuuint32_t*, CUtensorMapInterleave,
                                   CUtensorMapSwizzle, CUtensorMapL2promotion, CUtensorMapFloatOOBfill);
static PFN_tmapEncode s_encode = nullptr;

static void make_map_2d(CUtensorMap* m, const void* ptr, int rows, int cols, int box_rows) {
  cuuint64_t dims[2] = {(cuuint64_t)cols, (cuuint64_t)rows};
  cuuint64_t strides[1] = {(cuuint64_t)cols * 2};
  cuuint32_t box[2] = {cols < 64 ? 32u : 64u, (cuuint32_t)box_rows};
  cuuint32_t es[2] = {1, 1};
  s_encode(m, CU_TENSOR_MAP_DATA_TYPE_BFLOAT16, 2, const_cast<void*>(ptr), dims, strides, box, es,
           CU_TENSOR_MAP_INTERLEAVE_NONE, cols < 64 ? CU_TENSOR_MAP_SWIZZLE_64B : CU_TENSOR_MAP_SWIZZLE_128B, CU_TENSOR_MAP_L2_PROMOTION_L2_256B,
           CU_TENSOR_MAP_FLOAT_OOB_FILL_NONE);
}
static void make_map_3d(CUtensorMap* m, const void* ptr, int rows, int cols, int box_rows, int box_chunks) {
  cuuint64_t dims[3] = {64, (cuuint64_t)rows, (cuuint64_t)(cols / 64)};
  cuuint64_t strides[2] = {(cuuint64_t)cols * 2, 128};
  cuuint32_t box[3] = {64, (cuuint32_t)box_rows, (cuuint32_t)box_chunks};
  cuuint32_t es[3] = {1, 1, 1};
  s_encode(m, CU_TENSOR_MAP_DATA_TYPE_BFLOAT16, 3, const_cast<void*>(ptr), dims, strides, box, es,
           CU_TENSOR_MAP_INTERLEAVE_NONE, CU_TENSOR_MAP_SWIZZLE_128B, CU_TENSOR_MAP_L2_PROMOTION_L2_256B,
           CU_TENSOR_MAP_FLOAT_OOB_FILL_NONE);
}

static cudaLaunchConfig_t fused_cfg(cudaLaunchAttribute* at) {
  cudaLaunchConfig_t cfg = {};
  cfg.gridDim = dim3(132);
  cfg.blockDim = dim3(384);
  cfg.dynamicSmemBytes = SMEM_BYTES;
  cfg.stream = cudaStreamPerThread;
  at[0].id = cudaLaunchAttributeClusterDimension;
  at[0].val.clusterDim.x = 2;
  at[0].val.clusterDim.y = 1;
  at[0].val.clusterDim.z = 1;
  cfg.attrs = at;
  cfg.numAttrs = 1;
  return cfg;
}

extern "C" void kernel_launch(void* const* d_in, const int* in_sizes, int n_in, void* d_out, int out_size) {
  const bf16* x = (const bf16*)d_in[0];
  const bf16* ckv = (const bf16*)d_in[1];
  const bf16* wq = (const bf16*)d_in[2];
  const bf16* wuk = (const bf16*)d_in[3];
  const bf16* wuv = (const bf16*)d_in[4];
  const bf16* wo = (const bf16*)d_in[5];
  const bf16* bk = (const bf16*)d_in[7];
  const bf16* bv = (const bf16*)d_in[8];
  const bf16* shift_k = (const bf16*)d_in[9];
  const bf16* ssm_k = (const bf16*)d_in[10];
  const bf16* ssm_D = (const bf16*)d_in[11];
  const bf16* gate_w = (const bf16*)d_in[12];
  bf16* out = (bf16*)d_out;

  static void *pq = nullptr, *pk = nullptr, *pv = nullptr, *pctx = nullptr, *pb = nullptr, *pu = nullptr;
  static int max_clusters = 0;
  if (!s_encode) {
    void* fn = nullptr;
    cudaDriverEntryPointQueryResult qres;
    cudaGetDriverEntryPoint("cuTensorMapEncodeTiled", &fn, cudaEnableDefault, &qres);
    s_encode = (PFN_tmapEncode)fn;
    cudaGetSymbolAddress(&pq, g_q);
    cudaGetSymbolAddress(&pk, g_k);
    cudaGetSymbolAddress(&pv, g_v);
    cudaGetSymbolAddress(&pctx, g_ctx);
    cudaGetSymbolAddress(&pb, g_y2T);
    cudaGetSymbolAddress(&pu, g_kvT);
    cudaFuncSetAttribute(fused_kernel, cudaFuncAttributeMaxDynamicSharedMemorySize, SMEM_BYTES);
    cudaLaunchAttribute at[1];
    cudaLaunchConfig_t cfg = fused_cfg(at);
    if (cudaOccupancyMaxActiveClusters(&max_clusters, fused_kernel, &cfg) != cudaSuccess) max_clusters = 0;
  }

  Maps all = {};
  make_map_2d(&all.a[0], x, S_LEN, DM, 128);
  make_map_2d(&all.a[1], ckv, S_LEN, DC, 128);
  make_map_3d(&all.b[0], wq, DM, HDIM, 64, 4);
  make_map_3d(&all.b[1], wuk, DC, HDIM, 64, 4);
  make_map_3d(&all.b[2], wuv, DC, HDIM, 64, 4);
  make_map_2d(&all.c[0], pq, S_LEN, HDIM, 64);
  make_map_2d(&all.c[1], pk, S_LEN, HDIM, 64);
  make_map_2d(&all.c[2], pv, S_LEN, HDIM, 64);
  make_map_3d(&all.q, pq, S_LEN, HDIM, 128, 2);
  make_map_3d(&all.k, pk, S_LEN, HDIM, 128, 2);
  make_map_3d(&all.v, pv, S_LEN, HDIM, 128, 2);
  make_map_2d(&all.o, pctx, S_LEN, HDIM, 64);
  all.ssm_k = ssm_k;
  all.ssm_D = ssm_D;
  make_map_2d(&all.oa, pctx, S_LEN, HDIM, 128);
  make_map_2d(&all.ob, wo, HDIM, DM, 64);
  make_map_2d(&all.oc, out, S_LEN, DM, 128);
  make_map_3d(&all.y, pb, DM, S_LEN, 16, 2);
  make_map_3d(&all.xs, x, S_LEN, DM, 32, 1);
  make_map_2d(&all.cu, pu, DM * 64, 32, 64);
  make_map_2d(&all.ch, ssm_k, DM * 64, 32, 64);

  make_map_2d(&all.bk, bk, S_LEN, DM, 35);
  make_map_2d(&all.bv, bv, S_LEN, DM, 32);
  for (int b = 0; b < 128; b++) {
    const int c = b >> 1, r = b & 1;
    const int G = c < 4 ? 0 : c < 36 ? (c - 4) % 8 : 1 + (c - 36) % 7;
    const int i = c < 4 ? 4 + c : c < 36 ? (c - 4) / 8 : 4 + (c - 36) / 7;
    all.id[b][0] = r + 2 * (i & 1) + 4 * (G & 3) + 16 * (i >> 1) + 64 * (G >> 2);
    all.id[b][1] = r + 2 * i + 16 * G;
    all.id[b][2] = r + 2 * G + 16 * i;
  }
  all.shift_k = shift_k;
  all.x = x;
  all.gate_w = gate_w;
  cudaLaunchAttribute at[1];
  cudaLaunchConfig_t cfg = fused_cfg(at);
  if (max_clusters >= 66) {
    cudaLaunchKernelEx(&cfg, fused_kernel, 7, all);
  } else {
    for (int m = 1; m <= 4; m <<= 1) cudaLaunchKernelEx(&cfg, fused_kernel, m, all);
  }
}
```

```cpp
#include <cuda_runtime.h>
#include <cuda_bf16.h>
#include <cuda.h>
#include <stdint.h>

typedef __nv_bfloat16 bf16;
#define INPLACE 3

constexpr int S_LEN = 2048;
constexpr int DM = 1024;
constexpr int NH = 32;
constexpr int HD = 128;
constexpr int DC = 512;
constexpr int HDIM = NH * HD;

__device__ __align__(1024) bf16 g_q[S_LEN * HDIM];
__device__ __align__(1024) bf16 g_k[S_LEN * HDIM];
__device__ __align__(1024) bf16 g_v[S_LEN * HDIM];
#define g_ctx g_q
__device__ __align__(1024) bf16 g_kvT[DM * S_LEN];
#define g_y2T g_kvT
__device__ __align__(1024) float g_gate[S_LEN];
enum { CNT_KV = 0, CNT_PREP = CNT_KV + 2, CNT_CTX, CNT_Y2 = CNT_CTX + 2, CNT_DONE = CNT_Y2 + 2, CNT_N };
__device__ unsigned int g_cnt[CNT_N * 32];

#define TL(k, i)
#define TL2(k, i)
#define TD(i)
#define CT(i)
#define GT(i)
#define GA(i)
#define ST(i)

__device__ __forceinline__ uint32_t smem_u32(const void* p) { return (uint32_t)__cvta_generic_to_shared(p); }

__device__ __forceinline__ void mbar_init(uint32_t bar, uint32_t count) {
  asm volatile("mbarrier.init.shared::cta.b64 [%0], %1;" ::"r"(bar), "r"(count));
}
__device__ __forceinline__ void mbar_expect_tx(uint32_t bar, uint32_t bytes) {
  asm volatile("mbarrier.arrive.expect_tx.shared::cta.b64 _, [%0], %1;" ::"r"(bar), "r"(bytes) : "memory");
}
__device__ __forceinline__ void mbar_arrive(uint32_t bar) {
  asm volatile("mbarrier.arrive.shared::cta.b64 _, [%0];" ::"r"(bar) : "memory");
}
__device__ __forceinline__ void mbar_wait(uint32_t bar, uint32_t parity) {
  uint32_t done;
  uint32_t spins = 0;
  do {
    asm volatile(
        "{\n.reg .pred p;\n"
        "mbarrier.try_wait.parity.shared::cta.b64 p, [%1], %2;\n"
        "selp.u32 %0, 1, 0, p;\n}\n"
        : "=r"(done)
        : "r"(bar), "r"(parity)
        : "memory");
    if (++spins > (1u << 22)) break;
  } while (!done);
}
__device__ __forceinline__ bool mbar_try(uint32_t bar, uint32_t parity) {
  uint32_t done;
  asm volatile(
      "{\n.reg .pred p;\n"
      "mbarrier.try_wait.parity.shared::cta.b64 p, [%1], %2;\n"
      "selp.u32 %0, 1, 0, p;\n}\n"
      : "=r"(done)
      : "r"(bar), "r"(parity)
      : "memory");
  return done != 0;
}
__device__ __forceinline__ bool elect_one() {
  uint32_t pred;
  asm volatile("{\n.reg .pred p;\nelect.sync _|p, 0xffffffff;\nselp.u32 %0, 1, 0, p;\n}\n" : "=r"(pred));
  return pred != 0;
}
__device__ __forceinline__ void mbar_arrive_if(uint32_t bar, bool pred) {
  asm volatile(
      "{\n.reg .pred p;\nsetp.ne.b32 p, %1, 0;\n"
      "@p mbarrier.arrive.shared::cta.b64 _, [%0];\n}\n" ::"r"(bar),
      "r"((uint32_t)pred)
      : "memory");
}
__device__ __forceinline__ void mbar_wait_sleep(uint32_t bar, uint32_t parity) {
  uint32_t done;
  uint32_t spins = 0;
  do {
    asm volatile(
        "{\n.reg .pred p;\n"
        "mbarrier.try_wait.parity.shared::cta.b64 p, [%1], %2, %3;\n"
        "selp.u32 %0, 1, 0, p;\n}\n"
        : "=r"(done)
        : "r"(bar), "r"(parity), "r"(20000u)
        : "memory");
    if (++spins > (1u << 16)) break;
  } while (!done);
}
__device__ __forceinline__ void fence_barrier_init() {
  asm volatile("fence.mbarrier_init.release.cluster;" ::: "memory");
}
__device__ __forceinline__ void fence_proxy_async() {
  asm volatile("fence.proxy.async.shared::cta;" ::: "memory");
}
__device__ __forceinline__ void named_bar_sync(int id, int nthreads) {
  asm volatile("bar.sync %0, %1;" ::"r"(id), "r"(nthreads) : "memory");
}
__device__ __forceinline__ void named_bar_arrive(int id, int nthreads) {
  asm volatile("bar.arrive %0, %1;" ::"r"(id), "r"(nthreads) : "memory");
}
__device__ __forceinline__ void tma_load_2d(uint32_t dst, const CUtensorMap* m, uint32_t bar, int c0, int c1) {
  asm volatile(
      "cp.async.bulk.tensor.2d.shared::cluster.global.mbarrier::complete_tx::bytes [%0], [%1, {%3, %4}], [%2];" ::"r"(dst),
      "l"(reinterpret_cast<uint64_t>(m)), "r"(bar), "r"(c0), "r"(c1)
      : "memory");
}
__device__ __forceinline__ void tma_load_3d(uint32_t dst, const CUtensorMap* m, uint32_t bar, int c0, int c1, int c2) {
  asm volatile(
      "cp.async.bulk.tensor.3d.shared::cluster.global.mbarrier::complete_tx::bytes [%0], [%1, {%3, %4, %5}], [%2];" ::"r"(dst),
      "l"(reinterpret_cast<uint64_t>(m)), "r"(bar), "r"(c0), "r"(c1), "r"(c2)
      : "memory");
}
__device__ __forceinline__ void tma_store_2d(const CUtensorMap* m, uint32_t src, int c0, int c1) {
  asm volatile("cp.async.bulk.tensor.2d.global.shared::cta.bulk_group [%0, {%2, %3}], [%1];" ::"l"(
                   reinterpret_cast<uint64_t>(m)),
               "r"(src), "r"(c0), "r"(c1)
               : "memory");
}
__device__ __forceinline__ void bulk_load(uint32_t dst, const void* src, uint32_t bytes, uint32_t bar) {
  asm volatile("cp.async.bulk.shared::cluster.global.mbarrier::complete_tx::bytes [%0], [%1], %2, [%3];" ::"r"(dst),
               "l"(src), "r"(bytes), "r"(bar)
               : "memory");
}
__device__ __forceinline__ void tma_load_2d_mc(uint32_t dst, const CUtensorMap* m, uint32_t bar, int c0, int c1,
                                               uint16_t mask) {
  asm volatile(
      "cp.async.bulk.tensor.2d.shared::cluster.global.mbarrier::complete_tx::bytes.multicast::cluster [%0], [%1, {%3, "
      "%4}], [%2], %5;" ::"r"(dst),
      "l"(reinterpret_cast<uint64_t>(m)), "r"(bar), "r"(c0), "r"(c1), "h"(mask)
      : "memory");
}
__device__ __forceinline__ void mbar_arrive_cluster_if(uint32_t bar, uint32_t cta, bool pred) {
  asm volatile(
      "{\n.reg .b32 ra;\n.reg .pred p;\nsetp.ne.b32 p, %2, 0;\n"
      "mapa.shared::cluster.u32 ra, %0, %1;\n"
      "@p mbarrier.arrive.shared::cluster.b64 _, [ra];\n}\n" ::"r"(bar),
      "r"(cta), "r"((uint32_t)pred)
      : "memory");
}
__device__ __forceinline__ uint64_t policy_evict_first() {
  uint64_t pol;
  asm volatile("createpolicy.fractional.L2::evict_first.b64 %0, 1.0;" : "=l"(pol));
  return pol;
}
__device__ __forceinline__ void tma_load_2d_hint(uint32_t dst, const CUtensorMap* m, uint32_t bar, int c0, int c1,
                                                 uint64_t pol) {
  asm volatile(
      "cp.async.bulk.tensor.2d.shared::cluster.global.mbarrier::complete_tx::bytes.L2::cache_hint [%0], [%1, {%3, %4}], "
      "[%2], %5;" ::"r"(dst),
      "l"(reinterpret_cast<uint64_t>(m)), "r"(bar), "r"(c0), "r"(c1), "l"(pol)
      : "memory");
}
__device__ __forceinline__ void tma_load_3d_hint(uint32_t dst, const CUtensorMap* m, uint32_t bar, int c0, int c1,
                                                 int c2, uint64_t pol) {
  asm volatile(
      "cp.async.bulk.tensor.3d.shared::cluster.global.mbarrier::complete_tx::bytes.L2::cache_hint [%0], [%1, {%3, %4, "
      "%5}], [%2], %6;" ::"r"(dst),
      "l"(reinterpret_cast<uint64_t>(m)), "r"(bar), "r"(c0), "r"(c1), "r"(c2), "l"(pol)
      : "memory");
}
__device__ __forceinline__ void bulk_load_hint(uint32_t dst, const void* src, uint32_t bytes, uint32_t bar, uint64_t pol) {
  asm volatile(
      "cp.async.bulk.shared::cluster.global.mbarrier::complete_tx::bytes.L2::cache_hint [%0], [%1], %2, [%3], %4;" ::"r"(dst),
      "l"(src), "r"(bytes), "r"(bar), "l"(pol)
      : "memory");
}
__device__ __forceinline__ void cnt_signal_release(int which, uint32_t n) {
  asm volatile("red.release.gpu.global.add.u32 [%0], %1;" ::"l"(g_cnt + which * 32), "r"(n) : "memory");
}
__device__ __forceinline__ void cnt_wait(int which, uint32_t target) {
  uint32_t v, spins = 0;
  while (true) {
    asm volatile("ld.acquire.gpu.global.u32 %0, [%1];" : "=r"(v) : "l"(g_cnt + which * 32) : "memory");
    if (v >= target || ++spins > (1u << 18)) break;
    __nanosleep(64);
  }
  asm volatile("fence.proxy.async.global;" ::: "memory");
}
__device__ __forceinline__ void tma_store_commit() { asm volatile("cp.async.bulk.commit_group;" ::: "memory"); }
template <int N>
__device__ __forceinline__ void tma_store_wait_read() {
  asm volatile("cp.async.bulk.wait_group.read %0;" ::"n"(N) : "memory");
}
template <int N>
__device__ __forceinline__ void tma_store_wait() {
  asm volatile("cp.async.bulk.wait_group %0;" ::"n"(N) : "memory");
}
__device__ __forceinline__ void wgmma_fence() { asm volatile("wgmma.fence.sync.aligned;" ::: "memory"); }
__device__ __forceinline__ void wgmma_commit() { asm volatile("wgmma.commit_group.sync.aligned;" ::: "memory"); }
template <int N>
__device__ __forceinline__ void wgmma_wait() {
  asm volatile("wgmma.wait_group.sync.aligned %0;" ::"n"(N) : "memory");
}
template <int R>
__device__ __forceinline__ void reg_alloc() { asm volatile("setmaxnreg.inc.sync.aligned.u32 %0;" ::"n"(R)); }
template <int R>
__device__ __forceinline__ void reg_dealloc() { asm volatile("setmaxnreg.dec.sync.aligned.u32 %0;" ::"n"(R)); }

__device__ __forceinline__ void stmatrix_x4(uint32_t addr, uint32_t r0, uint32_t r1, uint32_t r2, uint32_t r3) {
  asm volatile("stmatrix.sync.aligned.m8n8.x4.shared.b16 [%0], {%1, %2, %3, %4};" ::"r"(addr), "r"(r0), "r"(r1),
               "r"(r2), "r"(r3)
               : "memory");
}
__device__ __forceinline__ uint32_t pack_bf16(float lo, float hi) {
  uint32_t r;
  asm("cvt.rn.bf16x2.f32 %0, %1, %2;" : "=r"(r) : "f"(hi), "f"(lo));
  return r;
}
__device__ __forceinline__ float bf16_round(float x) { return __bfloat162float(__float2bfloat16_rn(x)); }
__device__ __forceinline__ float bf_lo(uint32_t v) { return __uint_as_float(v << 16); }
__device__ __forceinline__ float bf_hi(uint32_t v) { return __uint_as_float(v & 0xffff0000u); }
__device__ __forceinline__ uint4 lds128(uint32_t a) {
  uint4 v;
  asm volatile("ld.shared.v4.u32 {%0, %1, %2, %3}, [%4];" : "=r"(v.x), "=r"(v.y), "=r"(v.z), "=r"(v.w) : "r"(a));
  return v;
}
__device__ __forceinline__ void sts128(uint32_t a, uint4 v) {
  asm volatile("st.shared.v4.u32 [%0], {%1, %2, %3, %4};" ::"r"(a), "r"(v.x), "r"(v.y), "r"(v.z), "r"(v.w) : "memory");
}
__device__ __forceinline__ uint32_t mul_bf2(uint32_t a, uint32_t b) {
  uint32_t r;
  asm("mul.rn.bf16x2 %0, %1, %2;" : "=r"(r) : "r"(a), "r"(b));
  return r;
}
__device__ __forceinline__ uint32_t add_bf2(uint32_t a, uint32_t b) {
  uint32_t r;
  asm("add.rn.bf16x2 %0, %1, %2;" : "=r"(r) : "r"(a), "r"(b));
  return r;
}
__device__ __forceinline__ float ex2(float x) {
  float y;
  asm("ex2.approx.ftz.f32 %0, %1;" : "=f"(y) : "f"(x));
  return y;
}
__device__ __forceinline__ float rcp(float x) {
  float y;
  asm("rcp.approx.ftz.f32 %0, %1;" : "=f"(y) : "f"(x));
  return y;
}
template <int N>
__device__ __forceinline__ void fence_regs(float (&r)[N]) {
#pragma unroll
  for (int i = 0; i < N; i++) asm volatile("" : "+f"(r[i])::"memory");
}

template <int N>
__device__ __forceinline__ void undef_regs(float (&r)[N]) {
#pragma unroll
  for (int i = 0; i < N; i++) asm volatile("" : "=f"(r[i]));
}
template <int N>
__device__ __forceinline__ void fence_regs_u(uint32_t (&r)[N]) {
#pragma unroll
  for (int i = 0; i < N; i++) asm volatile("" : "+r"(r[i])::"memory");
}

constexpr uint64_t DESC_SW128 = 1ull << 62;
__device__ __forceinline__ uint64_t make_desc(uint32_t addr, uint32_t lbo_bytes, uint32_t sbo_bytes, uint64_t swz) {
  return (uint64_t)((addr & 0x3FFFF) >> 4) | ((uint64_t)((lbo_bytes & 0x3FFFF) >> 4) << 16) |
         ((uint64_t)((sbo_bytes & 0x3FFFF) >> 4) << 32) | swz;
}

__device__ __forceinline__ uint64_t desc_add(uint64_t d, uint32_t off16) {
  return (d & 0xFFFFFFFF00000000ull) | (uint64_t)((uint32_t)d + off16);
}

__device__ __forceinline__ void wgmma_m64n256_ss_tb(float (&d)[128], uint64_t da, uint64_t db, int sd) {
  asm volatile(
    "{\n.reg .pred p;\nsetp.ne.b32 p, %130, 0;\n"
    "wgmma.mma_async.sync.aligned.m64n256k16.f32.bf16.bf16 "
    "{%0, %1, %2, %3, %4, %5, %6, %7, %8, %9, %10, %11, %12, %13, %14, %15, %16, %17, %18, %19, %20, %21, %22, %23, %24, %25, %26, %27, %28, %29, %30, %31, %32, %33, %34, %35, %36, %37, %38, %39, %40, %41, %42, %43, %44, %45, %46, %47, %48, %49, %50, %51, %52, %53, %54, %55, %56, %57, %58, %59, %60, %61, %62, %63, %64, %65, %66, %67, %68, %69, %70, %71, %72, %73, %74, %75, %76, %77, %78, %79, %80, %81, %82, %83, %84, %85, %86, %87, %88, %89, %90, %91, %92, %93, %94, %95, %96, %97, %98, %99, %100, %101, %102, %103, %104, %105, %106, %107, %108, %109, %110, %111, %112, %113, %114, %115, %116, %117, %118, %119, %120, %121, %122, %123, %124, %125, %126, %127}, %128, %129, p, 1, 1, 0, 1;\n}\n"
    : "+f"(d[0]), "+f"(d[1]), "+f"(d[2]), "+f"(d[3]), "+f"(d[4]), "+f"(d[5]), "+f"(d[6]), "+f"(d[7]), "+f"(d[8]), "+f"(d[9]), "+f"(d[10]), "+f"(d[11]), "+f"(d[12]), "+f"(d[13]), "+f"(d[14]), "+f"(d[15]), "+f"(d[16]), "+f"(d[17]), "+f"(d[18]), "+f"(d[19]), "+f"(d[20]), "+f"(d[21]), "+f"(d[22]), "+f"(d[23]), "+f"(d[24]), "+f"(d[25]), "+f"(d[26]), "+f"(d[27]), "+f"(d[28]), "+f"(d[29]), "+f"(d[30]), "+f"(d[31]), "+f"(d[32]), "+f"(d[33]), "+f"(d[34]), "+f"(d[35]), "+f"(d[36]), "+f"(d[37]), "+f"(d[38]), "+f"(d[39]), "+f"(d[40]), "+f"(d[41]), "+f"(d[42]), "+f"(d[43]), "+f"(d[44]), "+f"(d[45]), "+f"(d[46]), "+f"(d[47]), "+f"(d[48]), "+f"(d[49]), "+f"(d[50]), "+f"(d[51]), "+f"(d[52]), "+f"(d[53]), "+f"(d[54]), "+f"(d[55]), "+f"(d[56]), "+f"(d[57]), "+f"(d[58]), "+f"(d[59]), "+f"(d[60]), "+f"(d[61]), "+f"(d[62]), "+f"(d[63]), "+f"(d[64]), "+f"(d[65]), "+f"(d[66]), "+f"(d[67]), "+f"(d[68]), "+f"(d[69]), "+f"(d[70]), "+f"(d[71]), "+f"(d[72]), "+f"(d[73]), "+f"(d[74]), "+f"(d[75]), "+f"(d[76]), "+f"(d[77]), "+f"(d[78]), "+f"(d[79]), "+f"(d[80]), "+f"(d[81]), "+f"(d[82]), "+f"(d[83]), "+f"(d[84]), "+f"(d[85]), "+f"(d[86]), "+f"(d[87]), "+f"(d[88]), "+f"(d[89]), "+f"(d[90]), "+f"(d[91]), "+f"(d[92]), "+f"(d[93]), "+f"(d[94]), "+f"(d[95]), "+f"(d[96]), "+f"(d[97]), "+f"(d[98]), "+f"(d[99]), "+f"(d[100]), "+f"(d[101]), "+f"(d[102]), "+f"(d[103]), "+f"(d[104]), "+f"(d[105]), "+f"(d[106]), "+f"(d[107]), "+f"(d[108]), "+f"(d[109]), "+f"(d[110]), "+f"(d[111]), "+f"(d[112]), "+f"(d[113]), "+f"(d[114]), "+f"(d[115]), "+f"(d[116]), "+f"(d[117]), "+f"(d[118]), "+f"(d[119]), "+f"(d[120]), "+f"(d[121]), "+f"(d[122]), "+f"(d[123]), "+f"(d[124]), "+f"(d[125]), "+f"(d[126]), "+f"(d[127])
    : "l"(da), "l"(db), "r"(sd));
}

__device__ __forceinline__ void wgmma_m64n128_ss(float (&d)[64], uint64_t da, uint64_t db, int sd) {
  asm volatile(
    "{\n.reg .pred p;\nsetp.ne.b32 p, %66, 0;\n"
    "wgmma.mma_async.sync.aligned.m64n128k16.f32.bf16.bf16 "
    "{%0, %1, %2, %3, %4, %5, %6, %7, %8, %9, %10, %11, %12, %13, %14, %15, %16, %17, %18, %19, %20, %21, %22, %23, %24, %25, %26, %27, %28, %29, %30, %31, %32, %33, %34, %35, %36, %37, %38, %39, %40, %41, %42, %43, %44, %45, %46, %47, %48, %49, %50, %51, %52, %53, %54, %55, %56, %57, %58, %59, %60, %61, %62, %63}, %64, %65, p, 1, 1, 0, 0;\n}\n"
    : "+f"(d[0]), "+f"(d[1]), "+f"(d[2]), "+f"(d[3]), "+f"(d[4]), "+f"(d[5]), "+f"(d[6]), "+f"(d[7]), "+f"(d[8]), "+f"(d[9]), "+f"(d[10]), "+f"(d[11]), "+f"(d[12]), "+f"(d[13]), "+f"(d[14]), "+f"(d[15]), "+f"(d[16]), "+f"(d[17]), "+f"(d[18]), "+f"(d[19]), "+f"(d[20]), "+f"(d[21]), "+f"(d[22]), "+f"(d[23]), "+f"(d[24]), "+f"(d[25]), "+f"(d[26]), "+f"(d[27]), "+f"(d[28]), "+f"(d[29]), "+f"(d[30]), "+f"(d[31]), "+f"(d[32]), "+f"(d[33]), "+f"(d[34]), "+f"(d[35]), "+f"(d[36]), "+f"(d[37]), "+f"(d[38]), "+f"(d[39]), "+f"(d[40]), "+f"(d[41]), "+f"(d[42]), "+f"(d[43]), "+f"(d[44]), "+f"(d[45]), "+f"(d[46]), "+f"(d[47]), "+f"(d[48]), "+f"(d[49]), "+f"(d[50]), "+f"(d[51]), "+f"(d[52]), "+f"(d[53]), "+f"(d[54]), "+f"(d[55]), "+f"(d[56]), "+f"(d[57]), "+f"(d[58]), "+f"(d[59]), "+f"(d[60]), "+f"(d[61]), "+f"(d[62]), "+f"(d[63])
    : "l"(da), "l"(db), "r"(sd));
}

__device__ __forceinline__ void wgmma_m64n128_ss_tb(float (&d)[64], uint64_t da, uint64_t db, int sd) {
  asm volatile(
    "{\n.reg .pred p;\nsetp.ne.b32 p, %66, 0;\n"
    "wgmma.mma_async.sync.aligned.m64n128k16.f32.bf16.bf16 "
    "{%0, %1, %2, %3, %4, %5, %6, %7, %8, %9, %10, %11, %12, %13, %14, %15, %16, %17, %18, %19, %20, %21, %22, %23, %24, %25, %26, %27, %28, %29, %30, %31, %32, %33, %34, %35, %36, %37, %38, %39, %40, %41, %42, %43, %44, %45, %46, %47, %48, %49, %50, %51, %52, %53, %54, %55, %56, %57, %58, %59, %60, %61, %62, %63}, %64, %65, p, 1, 1, 0, 1;\n}\n"
    : "+f"(d[0]), "+f"(d[1]), "+f"(d[2]), "+f"(d[3]), "+f"(d[4]), "+f"(d[5]), "+f"(d[6]), "+f"(d[7]), "+f"(d[8]), "+f"(d[9]), "+f"(d[10]), "+f"(d[11]), "+f"(d[12]), "+f"(d[13]), "+f"(d[14]), "+f"(d[15]), "+f"(d[16]), "+f"(d[17]), "+f"(d[18]), "+f"(d[19]), "+f"(d[20]), "+f"(d[21]), "+f"(d[22]), "+f"(d[23]), "+f"(d[24]), "+f"(d[25]), "+f"(d[26]), "+f"(d[27]), "+f"(d[28]), "+f"(d[29]), "+f"(d[30]), "+f"(d[31]), "+f"(d[32]), "+f"(d[33]), "+f"(d[34]), "+f"(d[35]), "+f"(d[36]), "+f"(d[37]), "+f"(d[38]), "+f"(d[39]), "+f"(d[40]), "+f"(d[41]), "+f"(d[42]), "+f"(d[43]), "+f"(d[44]), "+f"(d[45]), "+f"(d[46]), "+f"(d[47]), "+f"(d[48]), "+f"(d[49]), "+f"(d[50]), "+f"(d[51]), "+f"(d[52]), "+f"(d[53]), "+f"(d[54]), "+f"(d[55]), "+f"(d[56]), "+f"(d[57]), "+f"(d[58]), "+f"(d[59]), "+f"(d[60]), "+f"(d[61]), "+f"(d[62]), "+f"(d[63])
    : "l"(da), "l"(db), "r"(sd));
}

__device__ __forceinline__ void wgmma_m64n128_rs_tb(float* d, uint32_t a0, uint32_t a1, uint32_t a2, uint32_t a3, uint64_t db, int sd) {
  asm volatile(
    "{\n.reg .pred p;\nsetp.ne.b32 p, %69, 0;\n"
    "wgmma.mma_async.sync.aligned.m64n128k16.f32.bf16.bf16 "
    "{%0, %1, %2, %3, %4, %5, %6, %7, %8, %9, %10, %11, %12, %13, %14, %15, %16, %17, %18, %19, %20, %21, %22, %23, %24, %25, %26, %27, %28, %29, %30, %31, %32, %33, %34, %35, %36, %37, %38, %39, %40, %41, %42, %43, %44, %45, %46, %47, %48, %49, %50, %51, %52, %53, %54, %55, %56, %57, %58, %59, %60, %61, %62, %63}, {%64, %65, %66, %67}, %68, p, 1, 1, 1;\n}\n"
    : "+f"(d[0]), "+f"(d[1]), "+f"(d[2]), "+f"(d[3]), "+f"(d[4]), "+f"(d[5]), "+f"(d[6]), "+f"(d[7]), "+f"(d[8]), "+f"(d[9]), "+f"(d[10]), "+f"(d[11]), "+f"(d[12]), "+f"(d[13]), "+f"(d[14]), "+f"(d[15]), "+f"(d[16]), "+f"(d[17]), "+f"(d[18]), "+f"(d[19]), "+f"(d[20]), "+f"(d[21]), "+f"(d[22]), "+f"(d[23]), "+f"(d[24]), "+f"(d[25]), "+f"(d[26]), "+f"(d[27]), "+f"(d[28]), "+f"(d[29]), "+f"(d[30]), "+f"(d[31]), "+f"(d[32]), "+f"(d[33]), "+f"(d[34]), "+f"(d[35]), "+f"(d[36]), "+f"(d[37]), "+f"(d[38]), "+f"(d[39]), "+f"(d[40]), "+f"(d[41]), "+f"(d[42]), "+f"(d[43]), "+f"(d[44]), "+f"(d[45]), "+f"(d[46]), "+f"(d[47]), "+f"(d[48]), "+f"(d[49]), "+f"(d[50]), "+f"(d[51]), "+f"(d[52]), "+f"(d[53]), "+f"(d[54]), "+f"(d[55]), "+f"(d[56]), "+f"(d[57]), "+f"(d[58]), "+f"(d[59]), "+f"(d[60]), "+f"(d[61]), "+f"(d[62]), "+f"(d[63])
    : "r"(a0), "r"(a1), "r"(a2), "r"(a3), "l"(db), "r"(sd));
}

__device__ __forceinline__ void wgmma_m64n64_rs_tb(float (&d)[32], const uint32_t (&a)[4], uint64_t db, int sd) {
  asm volatile(
    "{\n.reg .pred p;\nsetp.ne.b32 p, %37, 0;\n"
    "wgmma.mma_async.sync.aligned.m64n64k16.f32.bf16.bf16 "
    "{%0, %1, %2, %3, %4, %5, %6, %7, %8, %9, %10, %11, %12, %13, %14, %15, %16, %17, %18, %19, %20, %21, %22, %23, %24, %25, %26, %27, %28, %29, %30, %31}, {%32, %33, %34, %35}, %36, p, 1, 1, 1;\n}\n"
    : "+f"(d[0]), "+f"(d[1]), "+f"(d[2]), "+f"(d[3]), "+f"(d[4]), "+f"(d[5]), "+f"(d[6]), "+f"(d[7]), "+f"(d[8]), "+f"(d[9]), "+f"(d[10]), "+f"(d[11]), "+f"(d[12]), "+f"(d[13]), "+f"(d[14]), "+f"(d[15]), "+f"(d[16]), "+f"(d[17]), "+f"(d[18]), "+f"(d[19]), "+f"(d[20]), "+f"(d[21]), "+f"(d[22]), "+f"(d[23]), "+f"(d[24]), "+f"(d[25]), "+f"(d[26]), "+f"(d[27]), "+f"(d[28]), "+f"(d[29]), "+f"(d[30]), "+f"(d[31])
    : "r"(a[0]), "r"(a[1]), "r"(a[2]), "r"(a[3]), "l"(db), "r"(sd));
}

__device__ __forceinline__ void wgmma_m64n32_rs_tb(float (&d)[16], const uint32_t (&a)[4], uint64_t db, int sd) {
  asm volatile(
    "{\n.reg .pred p;\nsetp.ne.b32 p, %21, 0;\n"
    "wgmma.mma_async.sync.aligned.m64n32k16.f32.bf16.bf16 "
    "{%0, %1, %2, %3, %4, %5, %6, %7, %8, %9, %10, %11, %12, %13, %14, %15}, {%16, %17, %18, %19}, %20, p, 1, 1, 1;\n}\n"
    : "+f"(d[0]), "+f"(d[1]), "+f"(d[2]), "+f"(d[3]), "+f"(d[4]), "+f"(d[5]), "+f"(d[6]), "+f"(d[7]), "+f"(d[8]), "+f"(d[9]), "+f"(d[10]), "+f"(d[11]), "+f"(d[12]), "+f"(d[13]), "+f"(d[14]), "+f"(d[15])
    : "r"(a[0]), "r"(a[1]), "r"(a[2]), "r"(a[3]), "l"(db), "r"(sd));
}

constexpr int G_STAGES = 4;
constexpr int G_A_BYTES = 128 * 64 * 2;
constexpr int G_B_BYTES = 256 * 64 * 2;
constexpr int G_STAGE_BYTES = G_A_BYTES + G_B_BYTES;
constexpr int G_STG_OFF = G_STAGES * G_STAGE_BYTES;
constexpr int BAR_OFF = G_STG_OFF + 32768 + 2048;
constexpr int SMEM_BYTES = BAR_OFF + 1024;
constexpr int B_GFULL = 0, B_GEMPTY = 32, B_SEEN = 64, B_PFULL = 224;
constexpr int B_KFULL = 80, B_KEMPTY = 96, B_VFULL = 112, B_VEMPTY = 128, B_QFULL = 144, B_QEMPTY = 160,
              B_QDONE = 184;
constexpr int B_CFULL = 192;
constexpr int B_OFREE = 256, B_OFULL = 272, B_OEMPTY = 320, B_OY = 368, B_OY2 = 384;
constexpr int B_SFULL = 392, B_SFREE = 424, B_PEND = 456, B_SCMD = 512;

#define PHASE_PROLOGUE                                                                \
  uint32_t tid, rt_zero;                                                              \
  asm volatile("mov.u32 %0, %%tid.x;" : "=r"(tid));                                   \
  asm volatile("mov.u32 %0, %%nctaid.y;" : "=r"(rt_zero));                            \
  asm volatile("" : "+r"(smem0));                                                     \
  rt_zero = __shfl_sync(0xffffffffu, rt_zero >> 8, 0);   \
  const uint32_t sbase = __shfl_sync(0xffffffffu, smem0, 0);                          \
  const uint32_t bar = sbase + BAR_OFF;                                               \
  const int wg = __shfl_sync(0xffffffffu, tid >> 7, 0);                               \
  const int warp = (tid >> 5) & 3, lane = tid & 31, wtid = tid & 127;                 \
  (void)rt_zero; (void)bar; (void)warp; (void)lane; (void)wtid;

enum { ST_END = 0, ST_BOX1, ST_BOX2, ST_BOX2Q, ST_BOX2L };
__device__ __forceinline__ void st_post(uint32_t bar, int wg, int wtid, uint32_t n, int kind, const void* dst,
                                        uint32_t src, int c0, int c1, int sig) {
  if (wtid == 0) {
    const uint32_t c = bar + B_SCMD + wg * 64 + (n & 1) * 32;
    const uint64_t d = reinterpret_cast<uint64_t>(dst);
    sts128(c, make_uint4(kind, src, c0, c1));
    sts128(c + 16, make_uint4((uint32_t)d, (uint32_t)(d >> 32), sig, 0));
  }
  fence_proxy_async();
  __syncwarp();
  mbar_arrive_if(bar + B_SFULL + wg * 16 + (n & 1) * 8, (wtid & 31) == 0);
}
__device__ __forceinline__ void st_wait(uint32_t bar, int wg, uint32_t n) {
  const uint32_t b = bar + B_SFREE + wg * 16 + (n & 1) * 8;
  if (!mbar_try(b, ~(n >> 1) & 1)) mbar_wait(b, ~(n >> 1) & 1);
}
__device__ __forceinline__ void note(uint32_t bar, uint32_t cnt) {
  asm volatile("red.release.cta.shared.add.u32 [%0], 1;" ::"r"(bar + B_PEND + 4 * cnt) : "memory");
}
__device__ __forceinline__ void store_agent(uint32_t bar, int wg) {
  mbar_arrive(bar + B_SFREE + wg * 16);
  mbar_arrive(bar + B_SFREE + wg * 16 + 8);
  bool more = true;
  for (uint32_t n = 0;; n++) {
    mbar_wait_sleep(bar + B_SFULL + wg * 16 + (n & 1) * 8, (n >> 1) & 1);
    const uint4 c = lds128(bar + B_SCMD + wg * 64 + (n & 1) * 32);
    const uint4 d = lds128(bar + B_SCMD + wg * 64 + (n & 1) * 32 + 16);
    if (c.x == ST_END) break;
    const CUtensorMap* dst = reinterpret_cast<const CUtensorMap*>((uint64_t)d.x | ((uint64_t)d.y << 32));
    tma_store_2d(dst, c.y, c.z, c.w);
    if (c.x >= ST_BOX2) tma_store_2d(dst, c.y + 8192, c.z + 64, c.w);
    tma_store_commit();
    tma_store_wait_read<0>();
    mbar_arrive(bar + B_SFREE + wg * 16 + (n & 1) * 8);
    if (c.x == ST_BOX2L) mbar_arrive(bar + B_OFREE + 8 * wg);
    if ((int)d.z >= 0) {
      tma_store_wait<0>();
      if (d.z == 0) { TD(6) }
      asm volatile("fence.proxy.async.global;" ::: "memory");
      if (c.x == ST_BOX2Q) mbar_arrive(bar + B_QDONE);
      else note(bar, d.z);
      if (c.x == ST_BOX2L) {
        note(bar, CNT_DONE);
        more = false;
      }
    }
  }
  if (more) note(bar, CNT_DONE);
}

struct Maps {
  const bf16 *shift_k, *x, *gate_w, *ssm_k, *ssm_D;
  uint8_t id[128][4];
  CUtensorMap a[2];
  CUtensorMap b[3];
  CUtensorMap c[3];
  CUtensorMap bk, bv;
  CUtensorMap q, k, v, o;
  CUtensorMap oa, ob, oc;
  CUtensorMap y, xs;
  CUtensorMap cu, ch;
};

constexpr int P_SLOT = 67 * 128, P_V = 35 * 128, P_TAPS = 2 * P_SLOT;
__device__ __forceinline__ void ldsm4t(uint32_t (&r)[4], uint32_t a) {
  asm volatile("ldmatrix.sync.aligned.m8n8.x4.trans.shared.b16 {%0, %1, %2, %3}, [%4];"
               : "=r"(r[0]), "=r"(r[1]), "=r"(r[2]), "=r"(r[3])
               : "r"(a));
}
__device__ __forceinline__ uint32_t fma_bf2(uint32_t a, uint32_t b, uint32_t c) {
  uint32_t r;
  asm("fma.rn.bf16x2 %0, %1, %2, %3;" : "=r"(r) : "r"(a), "r"(b), "r"(c));
  return r;
}
__device__ __forceinline__ void prep_agent(const Maps& maps, uint32_t sbase, int w, int lane) {
  const uint32_t bar = sbase + BAR_OFF, pb = bar + B_PFULL + w * 16;
  const int d0 = (blockIdx.x >> 3) * 64, t0 = (blockIdx.x & 7) * 256 + w * 128;
  mbar_wait_sleep(bar + B_GFULL + 8 * (G_STAGES - 1), 0);
#pragma unroll 1
  for (int i = -1; i < 4; i++) {
    GA(82 + 2 * i)
    if (i >= 0) mbar_wait_sleep(pb + (i & 1) * 8, i >> 1);
    GA(83 + 2 * i)
    const uint32_t so = sbase + G_STG_OFF + w * (P_TAPS + 512) + (i & 1) * P_SLOT;
    if (i < 3 && elect_one()) {
      const uint32_t b = pb + (~i & 1) * 8, dst = so + (i & 1 ? -P_SLOT : P_SLOT);
      mbar_expect_tx(b, i < 0 ? P_SLOT + 512 : P_SLOT);
      const uint64_t pol = policy_evict_first();
      tma_load_2d_hint(dst, &maps.bk, b, d0, t0 + 32 * i + 29, pol);
      tma_load_2d_hint(dst + P_V, &maps.bv, b, d0, t0 + 32 * i + 32, pol);
      if (i < 0) bulk_load(sbase + G_STG_OFF + P_TAPS, maps.shift_k + d0 * 4, 512, b);
    }
    if (i < 0) continue;
    uint32_t ak[4];
#pragma unroll
    for (int r = 0; r < 4; r++) {
      const uint32_t a = so / 128 + r + 4 * (lane & 6) + (((lane >> 2) ^ lane) & 6) + (lane & 1);
      ak[r] = a * 128 + (a & 7) * 16;
    }
    bf16* dst = g_kvT + (size_t)(d0 + (lane >> 2)) * S_LEN + t0 + ((lane & 3) + 4 * i) * 8;
#pragma unroll 1
    for (int cg = 0; cg < 128; cg += 16) {
      uint32_t t01, t23, k[4][4], v[4];
      asm volatile("ld.shared.v2.u32 {%0, %1}, [%2];"
                   : "=r"(t01), "=r"(t23)
                   : "r"(sbase + G_STG_OFF + P_TAPS + cg * 4 + (lane >> 2) * 8));
#pragma unroll
      for (int r = 0; r < 4; r++) ldsm4t(k[r], ak[r] ^ cg);
      ldsm4t(v, (ak[3] ^ cg) + 4096);
      const uint32_t w0 = __byte_perm(t01, 0, 0x1010), w1 = __byte_perm(t01, 0, 0x3232);
      const uint32_t w2 = __byte_perm(t23, 0, 0x1010), w3 = __byte_perm(t23, 0, 0x3232);
#pragma unroll
      for (int j = 0; j < 4; j++)
        v[j] = mul_bf2(fma_bf2(k[3][j], w0, fma_bf2(k[2][j], w1, fma_bf2(k[1][j], w2, mul_bf2(k[0][j], w3)))), v[j]);
      const bool s1 = lane & 1, s2 = lane & 2;
      const uint32_t a0 = s1 ? v[1] : v[0], a1 = s1 ? v[0] : v[1], a2 = s1 ? v[3] : v[2], a3 = s1 ? v[2] : v[3];
      *reinterpret_cast<uint4*>(dst) = make_uint4(s2 ? a2 : a0, s2 ? a3 : a1, s2 ? a0 : a2, s2 ? a1 : a3);
      dst += 8 * S_LEN;
    }
    fence_proxy_async();
    __syncwarp();
  }
  GA(90)
  if (lane == 0) note(bar, CNT_PREP);
  __syncwarp();
  GA(91)
}

__device__ __forceinline__ void qkv_tile(const Maps& maps, int it, int& which, int& m_tile, int& n_tile) {
  const bool q = it == 0 || it >= 5;
  const int b = maps.id[blockIdx.x][it >= 5];
  which = q ? 0 : 2 - (it & 1);
  m_tile = b & 15;
  n_tile = (b >> 4) * 2 + ((0x19 >> it) & 1);
}

constexpr int G_NTILES = 6;
__device__ __forceinline__ void qkv_producer(const Maps& maps, uint32_t sbase, bool first) {
  const uint32_t bar = sbase + BAR_OFF;
  uint32_t stage = 0, phase = 0;
#pragma unroll 1
  for (int it = 0; it < (first ? 1 : G_NTILES); it++) {
    int which, m_tile, n_tile;
    qkv_tile(maps, it, which, m_tile, n_tile);
    const CUtensorMap* ma = &maps.a[which == 0 ? 0 : 1];
    const CUtensorMap* mb = &maps.b[which];
    const int nk = first ? G_STAGES : which == 0 ? 16 : 8;
#pragma unroll 1
    for (int kt = (it == 0 && !first) ? G_STAGES : 0; kt < nk; kt++) {
      if (!first) mbar_wait_sleep(bar + B_GEMPTY + 8 * stage, phase);
      const uint32_t fb = bar + B_GFULL + 8 * stage;
      const uint32_t sa = sbase + stage * G_STAGE_BYTES;
      mbar_expect_tx(fb, G_STAGE_BYTES);
      tma_load_2d(sa, ma, fb, kt * 64, m_tile * 128);
      tma_load_3d(sa + G_A_BYTES, mb, fb, 0, kt * 64, n_tile * 4);
      if (++stage == G_STAGES) { stage = 0; phase ^= 1; }
      {
        const int b = maps.id[blockIdx.x][1];
        if (it == 2 && kt == (b & 7)) {
          for (int i = 0; i < 2; i++)
            asm volatile("cp.async.bulk.prefetch.tensor.2d.L2.global.tile [%0, {%1, %2}];" ::"l"(&maps.a[0]),
                         "r"((b >> 4) * 128 + i * 64), "r"((b & 15) * 128)
                         : "memory");
        }
        if (it == 3 && kt == (b & 7))
          asm volatile("cp.async.bulk.prefetch.tensor.3d.L2.global.tile [%0, {%1, %2, %3}];" ::"l"(&maps.b[0]), "r"(0),
                       "r"((b & 15) * 64), "r"((b >> 4) * 8)
                       : "memory");
      }
    }
  }
}

__device__ __forceinline__ uint32_t seen_bar(uint32_t item) { return B_SEEN + ((0x700800u >> (8 * item)) & 255); }
__device__ __noinline__ void publisher(uint32_t bar, int lane, uint32_t nsrc, uint32_t item, uint32_t mine) {
  uint32_t done = 0, tot = 0;
#pragma unroll 1
  for (uint32_t spins = 0; (done < nsrc || item < 3) && spins < (1u << 20); spins++) {
    const uint32_t cnt = item ? CNT_CTX - 1 + item : CNT_KV + 1;
    if (item < 3 && __shfl_sync(0xffffffffu, tot, cnt) >= mine) {
      uint32_t v;
      asm volatile("ld.acquire.gpu.global.u32 %0, [%1];" : "=r"(v) : "l"(g_cnt + (lane ? cnt : CNT_PREP) * 32) : "memory");
      if (__all_sync(0xffffffffu, v >= (lane ? 512 : 260))) {
        asm volatile("fence.proxy.async.global;" ::: "memory");
        mbar_arrive_if(bar + seen_bar(item), lane == 0);
        item++;
      }
    }
    uint32_t v = 0;
    if (lane < CNT_N)
      asm volatile("atom.acquire.cta.shared.exch.b32 %0, [%1], 0;" : "=r"(v) : "r"(bar + B_PEND + 4 * lane) : "memory");
    done += __shfl_sync(0xffffffffu, v, CNT_DONE);
    if (lane == CNT_DONE) v = 0;
    if (done == nsrc && lane < CNT_DONE) {
      uint32_t w;
      asm volatile("atom.acquire.cta.shared.exch.b32 %0, [%1], 0;" : "=r"(w) : "r"(bar + B_PEND + 4 * lane) : "memory");
      v += w;
    }
    if (v && lane == 0) { TD(0) }
    if (v) cnt_signal_release(lane, v);
    tot += v;
    if (v && lane == 0) { TD(1) }
    if (!__any_sync(0xffffffffu, v != 0)) __nanosleep(200);
  }
  __threadfence();
  __syncwarp();
}

__device__ __forceinline__ void gate_rows(const Maps& maps, uint32_t sbase, int w48, int w12, int lane) {
  const uint32_t buf = sbase + w12 * 16384, gb = sbase + BAR_OFF + 768 + w12 * 16;
  if (lane == 0) {
    mbar_init(gb, 1);
    mbar_init(gb + 8, 1);
    fence_barrier_init();
    for (int i = 0; i < 2; i++) {
      mbar_expect_tx(gb + 8 * i, 8192);
      bulk_load(buf + i * 8192, maps.x + (size_t)(w48 + 48 * i) * 4 * DM, 8192, gb + 8 * i);
    }
  }
  __syncwarp();
  uint4 wv[4];
#pragma unroll
  for (int i = 0; i < 4; i++) wv[i] = __ldg(reinterpret_cast<const uint4*>(maps.gate_w + (i * 32 + lane) * 8));
  int it = 0;
#pragma unroll 1
  for (int row = w48 * 4; row < S_LEN; row += 48 * 4, it++) {
    mbar_wait(gb + 8 * (it & 1), (it >> 1) & 1);
    uint4 xv[4][4];
#pragma unroll
    for (int r = 0; r < 4; r++)
#pragma unroll
      for (int i = 0; i < 4; i++) xv[r][i] = lds128(buf + (it & 1) * 8192 + r * 2048 + (i * 32 + lane) * 16);
    float d[2][4];
#pragma unroll
    for (int pr = 0; pr < 2; pr++) {
      d[pr][0] = d[pr][1] = d[pr][2] = d[pr][3] = 0.f;
      auto acc = [&](uint32_t a0, uint32_t a2, uint32_t b0, uint32_t b2, uint32_t w0, uint32_t w2) {
        asm volatile(
            "mma.sync.aligned.m16n8k16.row.col.f32.bf16.bf16.f32 {%0, %1, %2, %3}, {%4, %5, %6, %7}, {%8, %8}, "
            "{%0, %1, %2, %3};"
            : "+f"(d[pr][0]), "+f"(d[pr][1]), "+f"(d[pr][2]), "+f"(d[pr][3])
            : "r"(mul_bf2(a0, w0)), "r"(mul_bf2(b0, w0)), "r"(mul_bf2(a2, w2)), "r"(mul_bf2(b2, w2)), "r"(0x3f803f80u));
      };
#pragma unroll
      for (int i = 0; i < 4; i++) {
        acc(xv[2 * pr][i].x, xv[2 * pr][i].y, xv[2 * pr + 1][i].x, xv[2 * pr + 1][i].y, wv[i].x, wv[i].y);
        acc(xv[2 * pr][i].z, xv[2 * pr][i].w, xv[2 * pr + 1][i].z, xv[2 * pr + 1][i].w, wv[i].z, wv[i].w);
      }
    }
    float sum = (lane & 2) ? ((lane & 1) ? d[1][2] : d[1][0]) : ((lane & 1) ? d[0][2] : d[0][0]);
#pragma unroll
    for (int off = 16; off >= 4; off >>= 1) sum += __shfl_xor_sync(0xffffffffu, sum, off);
    if (lane < 4) g_gate[row + lane] = bf16_round(rcp(1.0f + __expf(-bf16_round(sum))));
    if (lane == 0 && row + 2 * 48 * 4 < S_LEN) {
      mbar_expect_tx(gb + 8 * (it & 1), 8192);
      bulk_load(buf + (it & 1) * 8192, maps.x + (size_t)(row + 2 * 48 * 4) * DM, 8192, gb + 8 * (it & 1));
    }
  }
}

constexpr float Q_SCALE = 0.08838834764831845f * 1.4426950408889634f;
__device__ __forceinline__ uint32_t qkv_consumer(const Maps& maps, uint32_t smem0, bool fused, float (&rest)[64]) {
  PHASE_PROLOGUE
  constexpr int NTILES = G_NTILES;
  float acc[128];
  uint32_t stage = 0, phase = 0;
  const uint32_t stg = sbase + G_STG_OFF + wg * 18432;
  const int st_row = warp * 16 + (lane & 7) + ((lane >> 3) & 1) * 8;
  const int st_cb = lane >> 4;
  uint32_t pend[64];
  const CUtensorMap* pend_map = nullptr;
  int pend_c0 = 0, pend_c1 = 0;
  uint32_t sn = 0;
  auto put_box = [&](uint32_t buf, const uint32_t* v) {
#pragma unroll
    for (int jp = 0; jp < 4; jp++) {
      const int chunk = jp * 2 + st_cb;
      const uint32_t addr = buf + st_row * 128 + ((chunk ^ (st_row & 7)) << 4);
      stmatrix_x4(addr, v[jp * 4], v[jp * 4 + 1], v[jp * 4 + 2], v[jp * 4 + 3]);
    }
  };
  GT(gti++)
#pragma unroll 1
  for (int it = 0; it <= NTILES; it++) {
    int which, m_tile, n_tile;
    qkv_tile(maps, it, which, m_tile, n_tile);
    const int nk = (which == 0 && it < NTILES) ? 16 : 8;
    uint32_t prev_stage = 0;
#pragma unroll 1
    for (int kt = 0; kt < nk; kt++) {
      if (it < NTILES) {
        mbar_wait((bar + B_GFULL) + 8 * stage, phase);
        GT(gti++)
        const uint64_t da0 = make_desc(sbase + stage * G_STAGE_BYTES + wg * 8192, 16, 1024, DESC_SW128);
        const uint64_t db0 = make_desc(sbase + stage * G_STAGE_BYTES + G_A_BYTES, 8192, 1024, DESC_SW128);
        wgmma_fence();
#pragma unroll
        for (int kk = 0; kk < 4; kk++) {
          wgmma_m64n256_ss_tb(acc, desc_add(da0, kk * 2), desc_add(db0, kk * 128), (kt | kk) != 0);
        }
        wgmma_commit();
      }
      const uint32_t when = it == 0 ? 0 : it == 5 ? 0x922 << wg : wg ? 0xAA : 0x55;
      if ((when >> kt) & 1) {
        const int c = __popc(when & ~(~0u << kt));
        st_wait(bar, wg, sn - 2);
        const uint32_t buf = stg + (c & 1) * 8192;
        switch (c) {
          case 0: put_box(buf, pend); break;
          case 1: put_box(buf, pend + 16); break;
          case 2: put_box(buf, pend + 32); break;
          default: put_box(buf, pend + 48); break;
        }
        st_post(bar, wg, wtid, sn, ST_BOX1, pend_map, buf, pend_c0 + c * 64, pend_c1, (c == 3 && it > 1) ? CNT_KV + (it > 3) : -1);
        sn++;
      }
      if (it < NTILES) {
        wgmma_wait<1>();
        mbar_arrive_if((bar + B_GEMPTY) + 8 * prev_stage, wtid == 32 && kt > 0);
        prev_stage = stage;
        if (++stage == G_STAGES) { stage = 0; phase ^= 1; }
      }
    }
    wgmma_wait<0>();
    fence_regs(acc);
    if (it == NTILES) break;
    GT(gti++)
    mbar_arrive_if((bar + B_GEMPTY) + 8 * prev_stage, wtid == 32);
    if (it == NTILES - 1 && fused) break;
    if (which == 0) {
#pragma unroll
      for (int j = 0; j < 128; j++) acc[j] *= Q_SCALE;
    }
#pragma unroll
    for (int j = 0; j < 64; j++) pend[j] = pack_bf16(acc[2 * j], acc[2 * j + 1]);
    pend_map = &maps.c[which];
    pend_c0 = n_tile * 256;
    pend_c1 = m_tile * 128 + wg * 64;
  }
  mbar_wait(bar + B_GEMPTY, 1);
#pragma unroll
  for (int j = 0; j < 32; j++) pend[j] = pack_bf16(acc[2 * j] * Q_SCALE, acc[2 * j + 1] * Q_SCALE);
  put_box(sbase + wg * 8192, pend);
  put_box(sbase + 16384 + wg * 8192, pend + 16);
  fence_proxy_async();
#pragma unroll
  for (int j = 0; j < 64; j++) rest[j] = acc[64 + j];
  GT(gti++)
  return sn;
}

constexpr int A_TILE = 128 * 128 * 2;
constexpr int A_Q_OFF = 0;
constexpr int A_K_OFF = 2 * A_TILE;
constexpr int A_V_OFF = 4 * A_TILE;
constexpr int A_O_OFF = 6 * A_TILE;
constexpr int A_ITEMS = NH * (S_LEN / 128);

constexpr uint32_t A_ORDER = 0x3120, A_STEPS = 34;
__device__ __forceinline__ int item_m(uint32_t it) { return it & 15; }
__device__ __forceinline__ int item_h(uint32_t it) { return it >> 4; }

constexpr int C_V = 16384, C_MAT = 24576;
constexpr float C_ALPHA = 0.07874506561842957f;
__device__ __forceinline__ void sincos_turn(int p, float inv, float& c, float& s) {
  const float a = (float)p * (inv * 6.283185307179586f);
  asm("cos.approx.ftz.f32 %0, %1;" : "=f"(c) : "f"(a));
  asm("sin.approx.ftz.f32 %0, %1;" : "=f"(s) : "f"(a));
}

__device__ __forceinline__ uint32_t item_of(const Maps& maps, uint32_t r) {
  const uint32_t b = maps.id[blockIdx.x & 127][1];
  return (b >> 4) * 64 + ((A_ORDER >> (4 * r)) & 3) * 16 + ((b ^ ((r & 1) * 15)) & 15);
}

#define PACE 250
#define XMASK 3
#define XFIRST 4
#define C_SIDE 64
__device__ __forceinline__ uint32_t conv_first(const Maps& maps) {
  const uint32_t b = maps.id[blockIdx.x & 127][1];
  return (b >> 4) * 128 + ((b + 15) & 15);
}

__device__ __forceinline__ void conv_consumer(const Maps& maps, uint32_t smem0, uint32_t first, uint32_t step,
                                              uint32_t end, bool pp) {
  PHASE_PROLOGUE
  const uint32_t in_full = bar + B_CFULL + wg * 16;
  const uint32_t ca = sbase + (wg ? A_V_OFF + A_TILE : A_Q_OFF);
  const int w = __shfl_sync(0xffffffffu, warp, 0), g = lane >> 2, c = lane & 3;
  auto fetch = [&](uint32_t ch, uint32_t n) {
    if (w == 2 && ch < end) {
      if (elect_one()) {
        const uint32_t b = in_full + (n & 1) * 8, d = ca + (n & 1) * 8192;
        const uint64_t pol = policy_evict_first();
        mbar_expect_tx(b, 8192);
        tma_load_2d_hint(d, &maps.cu, b, 0, ch * 64, pol);
        tma_load_2d_hint(d + 4096, &maps.ch, b, 0, ch * 64, pol);
      }
    }
  };
  if (wtid == 96 && wg) { TD(15) }
  uint32_t f1[8][4];
  float tt[16], ts[16];
  uint32_t cc[4], ss[4];
#pragma unroll
  for (int i = 0; i < 16; i++) {
    const int k = 2 * (16 * w + g + 8 * (i & 1)) + 1, n = 2 * (8 * (i >> 1) + 2 * c) + 1;
    float c0, s0, c1, s1;
    sincos_turn(((k * n) << 23) >> 23, 1.f / 512, c0, s0);
    sincos_turn(((k * n + 2 * k) << 23) >> 23, 1.f / 512, c1, s1);
    f1[i >> 2][i & 3] = pack_bf16(c0 * C_ALPHA, c1 * C_ALPHA);
    f1[4 + (i >> 2)][i & 3] = pack_bf16(s0 * -C_ALPHA, s1 * -C_ALPHA);
  }
#pragma unroll
  for (int i = 0; i < 16; i++) {
    const int k = 2 * (16 * w + g + 8 * ((i >> 1) & 1)) + 1, n = 16 - (8 * (i >> 2) + 2 * c + (i & 1));
    float cs;
    sincos_turn(k * n, 1.f / 8192, cs, ts[i]);
    tt[i] = ts[i] * rcp(1.f + cs);
  }
#pragma unroll
  for (int j = 0; j < 4; j++) {
    const int k = 8 * w + g, n = 8 * c + 2 * j;
    float c0, s0, c1, s1;
    sincos_turn((int8_t)(k * n * 8), 1.f / 256, c0, s0);
    sincos_turn((int8_t)((k * n + k) * 8), 1.f / 256, c1, s1);
    cc[j] = pack_bf16(c0, c1);
    ss[j] = pack_bf16(s0, s1);
  }
  named_bar_sync(3, 256);
  fetch(first, 0);
  fetch(first + step, 1);
  const uint32_t va = ca + g * 64 + ((c ^ (g >> 1)) << 4);
  {
    const uint32_t a = va + C_MAT + w * 512, m = 0x80008000u;
    sts128(a, make_uint4(cc[0], cc[1], cc[2], cc[3]));
    sts128(a + 2048, make_uint4(ss[0], ss[1], ss[2], ss[3]));
    sts128(a + 4096, make_uint4(ss[0] ^ m, ss[1] ^ m, ss[2] ^ m, ss[3] ^ m));
    sts128(a + 6144, make_uint4(cc[0], cc[1], cc[2], cc[3]));
  }
  fence_proxy_async();
  named_bar_sync(1 + wg, 128);
  constexpr uint64_t DHI = (2ull << 62) | ((uint64_t)(512 >> 4) << 32);
  const uint32_t d0 = (uint32_t)make_desc(ca, 4096, 0, 0);
  float a5[16];
  uint4* const yb = reinterpret_cast<uint4*>(g_y2T) + (16 * w + g) * 4 + c;
  auto issue5 = [&]() {
#pragma unroll
    for (int ks = 0; ks < 8; ks++) wgmma_m64n32_rs_tb(a5, f1[ks], DHI | (d0 + (C_V >> 4) + ks * 64), ks != 0);
    wgmma_commit();
  };
  auto finish = [&](uint32_t ch, bool on) {
    fence_regs(a5);
    uint4* y = yb + (size_t)ch * 256;
    if (on) {
      y[0] = make_uint4(pack_bf16(a5[0], a5[1]), pack_bf16(a5[4], a5[5]), pack_bf16(a5[8], a5[9]), pack_bf16(a5[12], a5[13]));
      y[32] = make_uint4(pack_bf16(a5[2], a5[3]), pack_bf16(a5[6], a5[7]), pack_bf16(a5[10], a5[11]), pack_bf16(a5[14], a5[15]));
    }
  };
  auto dft32 = [&](float (&d)[32], const float* re, const float* im) {
    uint32_t a[4][4];
#pragma unroll
    for (int i = 0; i < 8; i++) {
      a[i >> 2][i & 3] = pack_bf16(re[2 * i], re[2 * i + 1]);
      a[2 + (i >> 2)][i & 3] = pack_bf16(im[2 * i], im[2 * i + 1]);
    }
    wgmma_fence();
#pragma unroll
    for (int ks = 0; ks < 4; ks++) wgmma_m64n64_rs_tb(d, a[ks], DHI | (d0 + (C_MAT >> 4) + ks * 64), ks != 0);
    wgmma_commit();
  };
  auto rot = [&](float* x, float* y) {
#pragma unroll
    for (int i = 0; i < 16; i++) {
      x[i] = fmaf(-tt[i], y[i], x[i]);
      y[i] = fmaf(ts[i], x[i], y[i]);
      x[i] = fmaf(-tt[i], y[i], x[i]);
    }
  };
  auto load_d = [&](uint32_t ch) {
    return __ldg(reinterpret_cast<const unsigned short*>(maps.ssm_D) + ((ch & (DM - 1)) | (lane & rt_zero)));
  };
  uint32_t dn = load_d(first);
  uint32_t n = 0, ch = first;
#pragma unroll 1
  for (; ch < end; n++, ch += step) {
    CT(0)
    float a1[2][32], a2[2][32], a4[32];
    const float dsk = c ? 0.f : __uint_as_float(dn << 16) * C_ALPHA;
    dn = load_d(ch + step);
    mbar_wait(in_full + (n & 1) * 8, (n >> 1) & 1);
    if (pp) named_bar_sync(4 + wg, 256);
    CT(1)
    wgmma_fence();
#pragma unroll
    for (int ks = 0; ks < 8; ks++)
      wgmma_m64n64_rs_tb(a1[ks >> 2], f1[ks], DHI | (d0 + (n & 1) * 512 + (ks & 3) * 64), (ks & 3) != 0);
    wgmma_commit();
    issue5();
    wgmma_wait<1>();
    fence_regs(a1[0]);
    fence_regs(a1[1]);
    CT(2)
    rot(a1[0], a1[1]);
    dft32(a2[0], a1[0], a1[1]);
    rot(a1[0] + 16, a1[1] + 16);
    a1[0][16] += dsk;
    a1[0][18] += dsk;
    dft32(a2[1], a1[0] + 16, a1[1] + 16);
    CT(3)
    wgmma_wait<2>();
    finish(ch - step, n > 0);
    wgmma_wait<0>();
    fence_regs(a2[0]);
    fence_regs(a2[1]);
    CT(4)
    if (pp) named_bar_arrive(5 - wg, 256);
    float re[16], im[16];
#pragma unroll
    for (int i = 0; i < 16; i++) {
      re[i] = a2[0][i] * a2[1][i] - a2[0][16 + i] * a2[1][16 + i];
      im[i] = a2[0][i] * a2[1][16 + i] + a2[0][16 + i] * a2[1][i];
    }
    dft32(a4, im, re);
    wgmma_wait<0>();
    fence_regs(a4);
    CT(5)
    rot(a4, a4 + 16);
#pragma unroll
    for (int i = 0; i < 4; i++) {
      const float* x = a4 + 16 - 16 * (i >> 1) + 2 * (i & 1);
      sts128(va + C_V + w * 1024 + (i >> 1) * 4096 + (i & 1) * 512,
             make_uint4(pack_bf16(x[0], x[1]), pack_bf16(x[4], x[5]), pack_bf16(x[8], x[9]), pack_bf16(x[12], x[13])));
    }
    CT(6)
    fence_proxy_async();
    named_bar_sync(1 + wg, 128);
    fetch(ch + 2 * step, n);
    if (wtid == 96 && n > 0) note(bar, CNT_Y2 + (((ch - step) & 112) == 112));
    CT(7)
  }
  wgmma_fence();
  issue5();
  wgmma_wait<0>();
  finish(ch - step, true);
  named_bar_sync(1 + wg, 128);
  if (wtid == 96 && wg) { TD(8) }
  if (wtid == 96) cnt_signal_release(CNT_Y2 + (((ch - step) & 112) == 112), 1);
  if (wtid == 64) note(bar, CNT_DONE);
  if (wtid == 96 && wg) { TD(9) }
}

__device__ __forceinline__ void attn_producer(const Maps& maps, uint32_t sbase, bool after_qkv, bool to_out,
                                              bool dry) {
  const uint32_t bar = sbase + BAR_OFF;
  const uint32_t q_full = bar + B_QFULL, q_empty = bar + B_QEMPTY;
  const uint32_t k_full = bar + B_KFULL, k_empty = bar + B_KEMPTY, v_full = bar + B_VFULL, v_empty = bar + B_VEMPTY;
  int ndrained = after_qkv ? 0 : G_STAGES;
  auto wait = [&](uint32_t b, uint32_t par) {
    if (!dry) mbar_wait_sleep(b, par);
  };
  auto drained = [&](int upto) {
#pragma unroll 1
    for (; ndrained <= upto; ndrained++) wait(bar + B_GEMPTY + 8 * ndrained, 1);
  };
  uint32_t st = 0, ph = 1, vs = 0, vp = 1;
  int pend_j = -1, pend_h = 0;
  int round = -1, m = -1, h = 0;
  bool last = false;
#pragma unroll 1
  for (;; round++) {
    uint32_t nitem = 0;
    const int tpost = m >= 3 ? m - 1 : m;
#pragma unroll 1
    for (int t = m < 0 ? -1 : 0; t <= m; t++) {
      const int j = (t < m && (round & 1)) ? m - 1 - t : t;
      if (t >= 0) {
        drained(1 + st);
        wait(k_empty + 8 * st, ph);
        if (!dry) {
          mbar_expect_tx(k_full + 8 * st, A_TILE);
          tma_load_3d(sbase + A_K_OFF + st * A_TILE, &maps.k, k_full + 8 * st, 0, j * 128, h * 2);
        }
        if (++st == 2) { st = 0; ph ^= 1; }
      }
      if (pend_j >= 0) {
        drained(3);
        wait(v_empty + 8 * vs, vp);
        if (!dry) {
          mbar_expect_tx(v_full + 8 * vs, A_TILE);
          tma_load_3d(sbase + A_V_OFF + vs * A_TILE, &maps.v, v_full + 8 * vs, 0, pend_j * 128, pend_h * 2);
        }
        if (++vs == 2) { vs = 0; vp ^= 1; }
      }
      pend_j = j;
      pend_h = h;
      if (t == tpost && !last) {
        nitem = dry ? 1 : item_of(maps, round + 1);
        if (round == (dry ? 0 : 3) || blockIdx.x >= 128) {
          nitem = A_ITEMS;
          if (!to_out) cnt_wait(CNT_PREP, dry ? 0 : 260);
          if (to_out) {
            wait(bar + seen_bar(1), 0);
            asm volatile("cp.async.bulk.prefetch.L2.global [%0], 4096;" ::"l"(maps.ssm_k + (size_t)conv_first(maps) * S_LEN));
            if (!dry)
              asm volatile("cp.async.bulk.prefetch.L2.global [%0], 4096;" ::"l"(g_kvT + (size_t)conv_first(maps) * S_LEN));
          }
        }
        const uint32_t qs = (round + 1) & 1;
        wait(q_empty + 8 * qs, (((round + 1) >> 1) & 1) ^ 1);
        if (round == 1 && after_qkv) wait(bar + B_QDONE, 0);
        if (round == 0 && after_qkv) wait(bar + seen_bar(0), 0);
        if (round < 0 && after_qkv) {
          if (!dry) { TD(2) }
          cnt_wait(CNT_KV, dry ? 0 : 512);
          if (!dry) { TD(3) }
        }
        if (nitem >= A_ITEMS || (round < 0 && after_qkv && !dry)) {
          if (!dry) mbar_arrive(q_full + 8 * qs);
        } else {
          drained(qs);
          if (!dry) {
            mbar_expect_tx(q_full + 8 * qs, A_TILE);
            tma_load_3d_hint(sbase + A_Q_OFF + qs * A_TILE, &maps.q, q_full + 8 * qs, 0, item_m(nitem) * 128,
                             item_h(nitem) * 2, policy_evict_first());
          }
        }
      }
    }
    if (last) break;
    last = nitem >= A_ITEMS;
    m = last ? -1 : item_m(nitem);
    h = item_h(nitem);
  }
}

__device__ __forceinline__ uint32_t attn_consumer(const Maps& maps, uint32_t smem0, uint32_t sn,
                                                  float (&rest)[64], bool after_qkv) {
  PHASE_PROLOGUE
  const uint32_t q_full = bar + B_QFULL, q_empty = bar + B_QEMPTY;
  const uint32_t k_full = bar + B_KFULL, k_empty = bar + B_KEMPTY, v_full = bar + B_VFULL;
  float o[64], s[64];
  uint32_t p[32];
  float e[32];
  uint32_t dep = 0;
  constexpr int MIDJ = 5;
  float l0 = 0.f, l1 = 0.f, b0 = 0.f, b1 = 0.f;
  const int sched_own = 4 + wg, sched_other = 5 - wg;
  if (wg == 1) named_bar_arrive(4, 256);

  const uint32_t qd0 = (uint32_t)make_desc(sbase + A_Q_OFF + wg * 8192, 16, 0, 0);
  const uint32_t kd0 = (uint32_t)make_desc(sbase + A_K_OFF, 16, 0, 0);
  const uint32_t vd0 = (uint32_t)make_desc(sbase + A_V_OFF, 16384, 0, 0);
  constexpr uint64_t DHI = DESC_SW128 | ((uint64_t)(1024 >> 4) << 32);
  constexpr uint32_t DST = A_TILE >> 4;
  auto issue_qk = [&](uint32_t qd, uint32_t kd) {
#pragma unroll
    for (int kk = 0; kk < 8; kk++) {
      const uint32_t off = ((kk >> 2) * 16384 + (kk & 3) * 32) >> 4;
      wgmma_m64n128_ss(s, DHI | (qd + off), DHI | (kd + off), kk != 0);
    }
    wgmma_commit();
  };
  auto issue_pv = [&](uint32_t vd, bool accumulate, int nk) {
#pragma unroll
    for (int kk = 0; kk < 8; kk++) {
      if (kk < nk)
        wgmma_m64n128_rs_tb(o, p[4 * kk], p[4 * kk + 1], p[4 * kk + 2], p[4 * kk + 3], DHI | (vd + kk * 128),
                            accumulate || (kk != 0));
    }
    wgmma_commit();
  };
  auto exp_lo = [&](float& a0, float& a1) {
#pragma unroll
    for (int j = 0; j < 8; j++) {
      e[4 * j] = ex2(s[4 * j]);
      e[4 * j + 1] = ex2(s[4 * j + 1]);
      e[4 * j + 2] = ex2(s[4 * j + 2]);
      e[4 * j + 3] = ex2(s[4 * j + 3]);
      a0 += e[4 * j];
      a0 += e[4 * j + 1];
      a1 += e[4 * j + 2];
      a1 += e[4 * j + 3];
      if (j == MIDJ) dep = (__float_as_uint(a0) | __float_as_uint(a1)) & rt_zero;
    }
  };
  auto pack_lo = [&]() {
#pragma unroll
    for (int j = 0; j < 16; j++) p[j] = pack_bf16(e[2 * j], e[2 * j + 1]);
  };
  auto finish_p = [&](float& a0, float& a1) {
    pack_lo();
#pragma unroll
    for (int j = 8; j < 16; j++) {
      const float e0 = ex2(s[4 * j]), e1 = ex2(s[4 * j + 1]), e2 = ex2(s[4 * j + 2]), e3 = ex2(s[4 * j + 3]);
      a0 += e0;
      a0 += e1;
      a1 += e2;
      a1 += e3;
      p[2 * j] = pack_bf16(e0, e1);
      p[2 * j + 1] = pack_bf16(e2, e3);
      if (j == 8 + MIDJ) dep = __float_as_uint(a0) & rt_zero;
    }
  };
  auto quad_sum = [&](float t) {
    t += __shfl_xor_sync(0xffffffffu, t, 1);
    return t + __shfl_xor_sync(0xffffffffu, t, 2);
  };
  auto write_o = [&](float i0, float i1) {
    st_wait(bar, wg, sn - 1);
    const int st_row = warp * 16 + (lane & 7) + ((lane >> 3) & 1) * 8;
    const uint32_t so = sbase + A_O_OFF + wg * 16384 + st_row * 128;
#pragma unroll
    for (int j = 0; j < 16; j += 2)
      stmatrix_x4(so + (j >> 3) * 8192 + ((((j & 7) + (lane >> 4)) ^ (lane & 7)) << 4),
                  pack_bf16(o[4 * j] * i0, o[4 * j + 1] * i0), pack_bf16(o[4 * j + 2] * i1, o[4 * j + 3] * i1),
                  pack_bf16(o[4 * j + 4] * i0, o[4 * j + 5] * i0), pack_bf16(o[4 * j + 6] * i1, o[4 * j + 7] * i1));
  };
  auto store_o = [&](uint32_t r, int kind) {
    const uint32_t it = item_of(maps, r);
    st_post(bar, wg, wtid, sn, kind, (INPLACE & 1) || kind != ST_BOX2Q ? &maps.o : &maps.c[0], sbase + A_O_OFF + wg * 16384, item_h(it) * 128,
            item_m(it) * 128 + wg * 64, CNT_CTX + (r >> 1));
    sn++;
  };
  auto mask_half = [&](float* sh) {
    const int u = warp * 16 + (lane >> 2) - (lane & 3) * 2;
#pragma unroll
    for (int j = 0; j < 8; j++) {
      if (8 * j > u) sh[4 * j] = -INFINITY;
      if (8 * j + 1 > u) sh[4 * j + 1] = -INFINITY;
      if (8 * j - 8 > u) sh[4 * j + 2] = -INFINITY;
      if (8 * j - 7 > u) sh[4 * j + 3] = -INFINITY;
    }
  };
  ST(0)
  mbar_wait(q_full, 0);
  if (blockIdx.x >= 128) {
    return sn;
  }
  mbar_wait(k_full, 0);
  named_bar_sync(sched_own, 256);
  wgmma_fence();
  issue_qk(qd0, kd0);
  named_bar_arrive(sched_other, 256);
  fence_regs(rest);
#pragma unroll
  for (int i = 0; i < 64; i++) o[i] = rest[i] * Q_SCALE;
  fence_regs(o);
  wgmma_wait<0>();
  fence_regs(s);
  mbar_arrive_if(k_empty, wtid == 32);
  uint32_t g = 0;
  uint32_t rnd = 0;
  int rem = item_m(item_of(maps, 0));
  uint32_t first = 1;
  uint32_t fl = 0;
#define redo (fl & 1)
#define shifted (fl & 2)
  float d0 = 0.f, d1 = 0.f;
  float pi0 = 1.f, pi1 = 1.f;
  ST(1)
  for (;;) {
    if (shifted) {
#pragma unroll
      for (int j = 0; j < 16; j++) {
        s[4 * j] -= d0;
        s[4 * j + 1] -= d0;
        s[4 * j + 2] -= d1;
        s[4 * j + 3] -= d1;
      }
    }
    if (rem == 0 && !redo) {
      mbar_arrive_if(q_empty + 8 * (rnd & 1), wtid == 96);
      rnd++;
      if (wg == 0) mask_half(s);
      else mask_half(s + 32);
    }
    for (;;) {
      const bool kill = rem == 0 && wg == 0;
      const uint32_t kd = kd0 + ((g + 1) & 1) * DST, vd = vd0 + (g & 1) * DST;
      float a0 = 0.f, a1 = 0.f;
      exp_lo(a0, a1);
      fence_regs(e);
      const uint32_t kb = k_full + 8 * ((g + 1) & 1);
      const uint32_t kpar = ((((g + 1) >> 1) & 1) ^ (g == A_STEPS - 1 ? 1u : 0u)) | dep;
      if (!mbar_try(kb, kpar)) mbar_wait(kb, kpar | ((__float_as_uint(a0) | __float_as_uint(a1)) & rt_zero));
      wgmma_wait<0>();
      fence_regs(o);
      if (kill) {
        mbar_arrive_if(kb + (B_VEMPTY - B_KFULL), wtid == 64 && !redo && g > 0);
        fence_regs(e);
        pack_lo();
#pragma unroll
        for (int j = 16; j < 32; j++) asm volatile("mov.u32 %0, 0;" : "=r"(p[j]));
        goto check;
      }
#pragma unroll
      for (int i = 32; i < 64; i++) asm volatile("" : "+f"(s[i])::"memory");
      mbar_arrive_if(kb + (B_VEMPTY - B_KFULL), wtid == 64 && !redo && g > 0);
      finish_p(a0, a1);
      if (__any_sync(0xffffffffu, !(mbar_try(v_full + 8 * (g & 1), ((g >> 1) & 1) | dep) &
                                    mbar_try(q_full + 8 * (rnd & 1), ((rnd >> 1) & 1) | dep)) ||
                                      !(a0 + a1 < 1.0995116e12f) || !(fminf(a0, a1) > (first ? 9.094947e-13f : -1.f)))) {
      check:
        bool bad = !(a0 + a1 < 1.0995116e12f);
        if (first) bad |= !(fminf(quad_sum(a0), quad_sum(a1)) > 9.094947e-13f);
        if (!redo && __any_sync(0xffffffffu, bad)) {
          d0 = d1 = first ? -INFINITY : 0.f;
#pragma unroll
          for (int j = 0; j < 16; j++) {
            if (j < 8 || !kill) {
              d0 = fmaxf(d0, fmaxf(s[4 * j], s[4 * j + 1]));
              d1 = fmaxf(d1, fmaxf(s[4 * j + 2], s[4 * j + 3]));
            }
          }
#pragma unroll
          for (int x = 1; x <= 2; x++) {
            d0 = fmaxf(d0, __shfl_xor_sync(0xffffffffu, d0, x));
            d1 = fmaxf(d1, __shfl_xor_sync(0xffffffffu, d1, x));
          }
          b0 += d0;
          b1 += d1;
          if (!first) {
            const float al0 = ex2(-d0), al1 = ex2(-d1);
            l0 *= al0;
            l1 *= al1;
#pragma unroll
            for (int j = 0; j < 16; j++) {
              o[4 * j] *= al0;
              o[4 * j + 1] *= al0;
              o[4 * j + 2] *= al1;
              o[4 * j + 3] *= al1;
            }
          }
          fl = 3;
          break;
        }
        mbar_wait(v_full + 8 * (g & 1), (g >> 1) & 1);
        mbar_wait(q_full + 8 * (rnd & 1), (rnd >> 1) & 1);
      }
      named_bar_sync(sched_own, 256);
      if (g == A_STEPS - 1) {
        if (first) write_o(pi0, pi1);
        fence_regs(o);
        wgmma_fence();
        issue_pv(vd, !first, 8);
        named_bar_arrive(sched_other, 256);
        if (first) store_o(rnd - 2, ST_BOX2);
        pi0 = rcp(quad_sum(l0 + a0));
        pi1 = rcp(quad_sum(l1 + a1));
        goto done;
      }
      wgmma_fence();
      issue_qk(qd0 + (rnd & 1) * DST, kd);
      if (first) write_o(pi0, pi1);
      fence_regs(o);
      if (kill) {
        wgmma_fence();
        issue_pv(vd, !first, 4);
      } else {
        wgmma_fence();
        issue_pv(vd, !first, 8);
      }
      named_bar_arrive(sched_other, 256);
      fl &= 2;
      l0 += a0;
      l1 += a1;
      if (rem == 0 || first) {
        if (first && (g > 0 || after_qkv)) store_o(g ? rnd - (rem == 0 ? 2 : 1) : 2, g ? ST_BOX2 : ST_BOX2Q);
        first = rem == 0;
        if (first) {
          pi0 = rcp(quad_sum(l0));
          pi1 = rcp(quad_sum(l1));
          l0 = l1 = b0 = b1 = 0.f;
          fl = 0;
          rem = item_m(item_of(maps, rnd)) + 1;
        }
      }
      rem--;
      g++;
      wgmma_wait<1>();
      fence_regs(s);
      mbar_arrive_if(kb + (B_KEMPTY - B_KFULL), wtid == 32);
      ST(g + 1)
      if (rem == 0 || shifted) {
        d0 = b0;
        d1 = b1;
        break;
      }
    }
  }
done:
#undef redo
#undef shifted
  wgmma_wait<0>();
  fence_regs(o);
  write_o(pi0, pi1);
  store_o(3, ST_BOX2L);
  ST(35)
  return sn;
}

constexpr int O_STAGES = 5;
constexpr int O_STAGE_BYTES = 32768;
constexpr int O_Y_OFF = 5 * 32768;
constexpr int O_X_OFF = 6 * 32768;
constexpr int O_NK = HDIM / 64;

__device__ __forceinline__ uint32_t out_stage(uint32_t st) { return ((0x43120u >> (4 * st)) & 7) * O_STAGE_BYTES; }

__device__ __forceinline__ void out_producer(const Maps& maps, uint32_t sbase, bool after_attn, bool dry) {
  const uint32_t bar = sbase + BAR_OFF;
  const uint32_t rank = blockIdx.x & 1;
  const int m_tile = maps.id[blockIdx.x][2] & 15, n_tile = maps.id[blockIdx.x][2] >> 4;
  uint32_t stage = 0, phase = 0, xi = 0;
#pragma unroll 1
  for (int ki = 0; ki < (dry ? 1 : O_NK); ki++) {
    const int kt = (ki & 14) * 4 + ((A_ORDER >> ((ki >> 4) * 4)) & 3) * 2 + (ki & 1);
    const uint32_t fb = bar + B_OFULL + 8 * stage, eb = bar + B_OEMPTY + 8 * stage;
    const uint32_t sa = sbase + out_stage(stage);
    if (ki < O_STAGES) {
      constexpr uint32_t LASTB = B_KEMPTY | ((B_QEMPTY + 8) << 8) | ((B_KEMPTY + 8) << 16) | (B_VEMPTY << 24);
      if (ki > 0 && after_attn) mbar_wait_sleep(bar + ((LASTB >> (8 * ki - 8)) & 255), ki == 2);
      mbar_arrive_cluster_if(eb, 0, !dry);
      mbar_arrive_cluster_if(eb, 1, !dry);
    }
    if (ki == 32) mbar_wait_sleep(bar + seen_bar(2), 0);
    if (!dry) {
      mbar_wait_sleep(eb, phase);
      mbar_expect_tx(fb, O_STAGE_BYTES);
      tma_load_2d_mc(sa + 16384 + rank * 8192, &maps.ob, fb, n_tile * 128 + rank * 64, kt * 64, (uint16_t)3);
      tma_load_2d(sa, &maps.oa, fb, kt * 64, m_tile * 128);
    }
    if (++stage == O_STAGES) { stage = 0; phase ^= 1; }
    if ((ki & XMASK) == XMASK && ki >= XFIRST && xi < 8) {
      if (after_attn && xi < 2) mbar_wait_sleep(bar + B_OFREE + 8 * xi, 0);
      tma_load_3d(sbase + O_X_OFF + (xi & 1) * 16384 + (xi >> 1) * 4096, &maps.xs, bar + B_OY, 0,
                  m_tile * 128 + (xi >> 1) * 32, n_tile * 2 + (xi & 1));
      xi++;
    }
  }
  if (!dry) mbar_wait_sleep(bar + B_OY2, 0);
}

__device__ __forceinline__ void out_side(const Maps& maps, uint32_t smem0, const float (&gv)[4]) {
  PHASE_PROLOGUE
  const int m_tile = maps.id[blockIdx.x][2] & 15, n_tile = maps.id[blockIdx.x][2] >> 4;
  const bool w0 = __shfl_sync(0xffffffffu, warp, 0) == 0;
  if (w0) {
    if (elect_one()) {
      mbar_expect_tx(bar + B_OY, 65536 - 4096);
      TD(10)
      cnt_wait(CNT_Y2, DM - 128);
      TD(7)
#pragma unroll 1
      for (int i = 0; i < 7; i++) {
        tma_load_3d(sbase + O_Y_OFF + i * 4096, &maps.y, bar + B_OY, 0, n_tile * 128 + i * 16, m_tile * 2);
        __nanosleep(PACE);
      }
    }
  }
  mbar_wait_sleep(bar + B_OY, 0);
  if (wtid == 0) { TD(12) }
  const int st_row = warp * 16 + (lane & 7) + ((lane >> 3) & 1) * 8;
  const int mrow = (lane & 7) + ((lane >> 4) & 1) * 8;
  const int mchunk = warp * 2 + ((lane >> 3) & 1);
  const uint32_t xrow = sbase + O_X_OFF + st_row * 128;
  const uint32_t yrow = sbase + O_Y_OFF + mrow * 128 + ((mchunk ^ (lane & 7)) << 4);
  uint32_t y[7][4], x[7][4], om[4];
#pragma unroll
  for (int i = 0; i < 4; i++) om[i] = pack_bf16(1.0f - gv[i], 1.0f - gv[i]);
  auto xa = [&](int h, int i) { return xrow + h * 8192 + (i >> 2) * 16384 + ((((i & 3) * 2 + (lane >> 4)) ^ (lane & 7)) << 4); };
  auto load = [&](int r, int h, int i) {
    ldsm4t(y[r], yrow + h * 2048 + i * 4096);
    asm volatile("ldmatrix.sync.aligned.m8n8.x4.shared.b16 {%0, %1, %2, %3}, [%4];"
                 : "=r"(x[r][0]), "=r"(x[r][1]), "=r"(x[r][2]), "=r"(x[r][3])
                 : "r"(xa(h, i)));
  };
  auto store = [&](int r, int h, int i, uint32_t om0, uint32_t om1) {
    stmatrix_x4(xa(h, i), mul_bf2(om0, mul_bf2(x[r][0], y[r][0])), mul_bf2(om1, mul_bf2(x[r][1], y[r][1])),
                mul_bf2(om0, mul_bf2(x[r][2], y[r][2])), mul_bf2(om1, mul_bf2(x[r][3], y[r][3])));
  };
#pragma unroll 1
  for (int h = 0; h < 2; h++) {
#pragma unroll
    for (int i = 0; i < 7; i++) load(i, h, i);
#pragma unroll
    for (int i = 0; i < 7; i++) store(i, h, i, h ? om[2] : om[0], h ? om[3] : om[1]);
  }
  if (w0) {
    if (elect_one()) {
      mbar_expect_tx(bar + B_OY2, 4096);
      cnt_wait(CNT_Y2 + 1, 128);
      TD(11)
      tma_load_3d(sbase + O_Y_OFF + 7 * 4096, &maps.y, bar + B_OY2, 0, n_tile * 128 + 112, m_tile * 2);
    }
  }
  mbar_wait_sleep(bar + B_OY2, 0);
  load(0, 0, 7);
  load(1, 1, 7);
  store(0, 0, 7, om[0], om[1]);
  store(1, 1, 7, om[2], om[3]);
  __syncwarp();
  mbar_arrive_if(bar + B_OY + 8, lane == 0);
  if (wtid == 0) { TD(13) }
}

__device__ __forceinline__ uint32_t out_gemm(const Maps& maps, uint32_t smem0, uint32_t sn) {
  PHASE_PROLOGUE
  const int m_tile = maps.id[blockIdx.x][2] & 15, n_tile = maps.id[blockIdx.x][2] >> 4;
  float acc[2][64];
  undef_regs(acc[0]);
  undef_regs(acc[1]);
  uint32_t stage = 0, phase = 0, prev_stage = 0;
  GT(gti++)
  const float* gp = g_gate + m_tile * 128 + warp * 16 + (lane >> 2);
  const float gv[4] = {__ldcg(gp), __ldcg(gp + 8), __ldcg(gp + 64), __ldcg(gp + 72)};
  if (wg == 1) {
    out_side(maps, smem0, gv);
    return sn;
  }
#pragma unroll 1
  for (int kt = 0; kt < O_NK; kt++) {
    uint32_t da = (uint32_t)make_desc(sbase + out_stage(stage), 16, 0, 0);
    uint32_t db = (uint32_t)make_desc(sbase + out_stage(stage) + 16384, 8192, 0, 0);
    asm volatile("" : "+r"(da), "+r"(db));
    mbar_wait(bar + B_OFULL + 8 * stage, phase);
    GT(gti++)
    constexpr int OWAIT = 2;
    constexpr uint64_t DHI = DESC_SW128 | ((uint64_t)(1024 >> 4) << 32);
#pragma unroll
    for (int kk = 0; kk < 4; kk++) {
      wgmma_wait<OWAIT>();
      if (kk == OWAIT)
        mbar_arrive_cluster_if(bar + B_OEMPTY + 8 * prev_stage, wtid >> 6,
                               (wtid & 63) == 32 && kt > 0 && kt - 1 + O_STAGES < O_NK);
      wgmma_fence();
      wgmma_m64n128_ss_tb(acc[0], DHI | (da + kk * 2), DHI | (db + kk * 128), (kt | kk) != 0);
      wgmma_m64n128_ss_tb(acc[1], DHI | (da + 512 + kk * 2), DHI | (db + kk * 128), (kt | kk) != 0);
      wgmma_commit();
    }
    prev_stage = stage;
    if (++stage == O_STAGES) { stage = 0; phase ^= 1; }
  }
  if (tid == 0) { TD(14) }
  st_wait(bar, wg, sn - 1);
  const int st_row = warp * 16 + (lane & 7) + ((lane >> 3) & 1) * 8;
  const uint32_t rowa = sbase + O_X_OFF + st_row * 128;
  wgmma_wait<0>();
  fence_regs(acc[0]);
  fence_regs(acc[1]);
  GT(gti++)
  uint32_t gg[4];
#pragma unroll
  for (int i = 0; i < 4; i++) gg[i] = pack_bf16(gv[i], gv[i]);
  mbar_wait(bar + B_OY + 8, 0);
#pragma unroll
  for (int i = 0; i < 16; i++) {
    const int h = i & 1, j = i & 14;
    const uint32_t addr = rowa + h * 8192 + (j >> 3) * 16384 + ((((j & 7) + (lane >> 4)) ^ (st_row & 7)) << 4);
    uint32_t b0, b1, b2, b3;
    asm volatile("ldmatrix.sync.aligned.m8n8.x4.shared.b16 {%0, %1, %2, %3}, [%4];"
                 : "=r"(b0), "=r"(b1), "=r"(b2), "=r"(b3)
                 : "r"(addr));
    const float* a = acc[h] + 4 * j;
    const uint32_t gg0 = gg[2 * h], gg1 = gg[2 * h + 1];
    stmatrix_x4(addr, add_bf2(mul_bf2(gg0, pack_bf16(a[0], a[1])), b0),
                add_bf2(mul_bf2(gg1, pack_bf16(a[2], a[3])), b1), add_bf2(mul_bf2(gg0, pack_bf16(a[4], a[5])), b2),
                add_bf2(mul_bf2(gg1, pack_bf16(a[6], a[7])), b3));
    if (i == 7) st_post(bar, wg, wtid, sn, ST_BOX1, &maps.oc, sbase + O_X_OFF, n_tile * 128, m_tile * 128, -1);
  }
  fence_proxy_async();
  named_bar_sync(1, 128);
  if (__shfl_sync(0xffffffffu, warp, 0) == 0) {
    if (elect_one()) {
      tma_store_2d(&maps.oc, sbase + O_X_OFF + 16384, n_tile * 128 + 64, m_tile * 128);
      tma_store_commit();
    }
  }
  GT(gti++)
  return sn + 1;
}

__device__ __noinline__ void leave_kernel(int mask) {
  if (!(mask & 4)) return;
  if (atomicAdd(g_cnt + CNT_DONE * 32, 1u) == 2 * gridDim.x - 1) {
    for (int i = 0; i < CNT_N; i++) g_cnt[i * 32] = 0;
  }
}

__device__ __noinline__ void side_jobs(const Maps& maps, uint32_t sbase) {
  const int w12 = __shfl_sync(0xffffffffu, threadIdx.x >> 5, 0);
  gate_rows(maps, sbase, (blockIdx.x - 128) * 12 + w12, w12, threadIdx.x & 31);
  fence_proxy_async();
  __syncthreads();
  if (threadIdx.x == 320) cnt_signal_release(CNT_PREP, 1);
}

__global__ void __launch_bounds__(384, 1) fused_kernel(int mask, const __grid_constant__ Maps maps) {
  extern __shared__ __align__(1024) uint8_t smem_raw[];
  {
    const uint32_t sbase = __shfl_sync(0xffffffffu, smem_u32(smem_raw), 0);
    const uint32_t bar = sbase + BAR_OFF;
    const int tid = threadIdx.x;
    const bool do_qkv = (mask & 1) && blockIdx.x < 128;
    TL(0, 0)
    if (__shfl_sync(0xffffffffu, tid >> 5, 0) == 1 && do_qkv) {
      if (elect_one()) {
        for (int i = 0; i < G_STAGES; i++) mbar_init(bar + B_GFULL + 8 * i, 1);
        fence_barrier_init();
        qkv_producer(maps, sbase, true);
      }
    }
    if (tid == 0) {
      for (int i = 0; i < G_STAGES; i++) {
        mbar_init(bar + B_GEMPTY + 8 * i, 2);
        mbar_init(bar + B_SFULL + 8 * i, 4);
        mbar_init(bar + B_SFREE + 8 * i, 1);
      }
      for (int i = 0; i < 2; i++) {
        mbar_init(bar + B_OFREE + 8 * i, 1);
        mbar_init(bar + B_QFULL + 8 * i, 1);
        mbar_init(bar + B_QEMPTY + 8 * i, 2);
        mbar_init(bar + B_KFULL + 8 * i, 1);
        mbar_init(bar + B_KEMPTY + 8 * i, 2);
        mbar_init(bar + B_VFULL + 8 * i, 1);
        mbar_init(bar + B_VEMPTY + 8 * i, 2);
      }
      for (int i = 0; i < O_STAGES; i++) {
        mbar_init(bar + B_OFULL + 8 * i, 1);
        mbar_init(bar + B_OEMPTY + 8 * i, 2);
      }
      mbar_init(bar + B_OY, 1);
      for (int i = 0; i < 3; i++) mbar_init(bar + seen_bar(i), 1);
      mbar_init(bar + B_OY2, 1);
      mbar_init(bar + B_OY + 8, 4);
      mbar_init(bar + B_QDONE, 2);
      for (int i = 0; i < 8; i++) mbar_init(bar + B_CFULL + 8 * i, 1);
      for (int i = 0; i < CNT_N; i++) asm volatile("st.shared.u32 [%0], 0;" ::"r"(bar + B_PEND + 4 * i) : "memory");
      fence_barrier_init();
    }
    __syncthreads();
    asm volatile("barrier.cluster.arrive.relaxed.aligned;" ::: "memory");
    if ((mask & 1) && blockIdx.x >= 128) side_jobs(maps, sbase);
  }
  uint32_t smem0 = smem_u32(smem_raw);
  PHASE_PROLOGUE
  const bool do_qkv = (mask & 1) && blockIdx.x < 128, do_out = (mask & 4) && blockIdx.x < 128;
  TL(0, 1)

  if (wg != 2) {
    reg_alloc<232>();
    uint32_t sn = 0;
    float o[64];
    if (do_qkv) {
      sn = qkv_consumer(maps, smem_u32(smem_raw), mask & 2, o);
    } else {
      undef_regs(o);
    }
    TL(0, 2) TL(1, 0) TL(1, 1)
    asm volatile("barrier.cluster.wait.acquire.aligned;" ::: "memory");
    if (mask & 2) {
      sn = attn_consumer(maps, smem_u32(smem_raw), sn, o, mask & 1);
      TL(2, 0)
      if ((mask & 4) && blockIdx.x < 128 && __shfl_sync(0xffffffffu, threadIdx.x, 0) < 128) {
        named_bar_arrive(3, 256);
      } else {
        const uint32_t b2 = blockIdx.x * 2 + (threadIdx.x >> 7);
        const bool fused = mask & 4, mainc = blockIdx.x < 128;
        const uint32_t first = __shfl_sync(0xffffffffu, !fused ? b2 : mainc ? conv_first(maps) : (b2 - 255) * 128 - C_SIDE, 0);
        conv_consumer(maps, smem_u32(smem_raw), first, !fused ? 264 : mainc ? 16 : 1,
                      !fused ? DM : mainc ? (first | 127) + 1 - C_SIDE : first + C_SIDE, fused && !mainc);
      }
      TL(1, 2) TL(2, 1) TL(2, 2)
    }
    TL(3, 0) TL(3, 1)
    if ((mask & 4) && blockIdx.x < 128) sn = out_gemm(maps, smem_u32(smem_raw), sn);
    {
      uint32_t smem0 = smem_u32(smem_raw);
      PHASE_PROLOGUE
      st_wait(bar, wg, sn - 2);
      st_post(bar, wg, wtid, sn, ST_END, nullptr, 0, 0, 0, -1);
      tma_store_wait_read<0>();
    }
  } else {
    reg_dealloc<40>();
    asm volatile("barrier.cluster.wait.acquire.aligned;" ::: "memory");
    const int w = __shfl_sync(0xffffffffu, tid >> 5, 0) - 8;
    if (w < 2) {
      if (do_qkv) prep_agent(maps, sbase, w, lane);
      if (elect_one()) store_agent(bar, w);
      TL2(3, 2)
    } else {
      if (elect_one()) {
        const bool dry = w == 2;
        if (do_qkv && !dry) qkv_producer(maps, sbase, false);
        if (mask & 2) attn_producer(maps, sbase, do_qkv, do_out, dry);
        if (do_out) out_producer(maps, sbase, mask & 2, dry);
        if (dry) { TD(5) }
      }
      __syncwarp();
      if (w == 2) publisher(bar, tid & 31, !(mask & 2) ? 2 : do_out ? 3 : 4, !do_out ? 3 : do_qkv ? 0 : 2, do_qkv ? 4 : 0);
      if ((tid & 31) == 0) leave_kernel(mask);
    }
  }
}

typedef CUresult (*PFN_tmapEncode)(CUtensorMap*, CUtensorMapDataType, cuuint32_t, void*, const cuuint64_t*,
                                   const cuuint64_t*, const cuuint32_t*, const cuuint32_t*, CUtensorMapInterleave,
                                   CUtensorMapSwizzle, CUtensorMapL2promotion, CUtensorMapFloatOOBfill);
static PFN_tmapEncode s_encode = nullptr;

static void make_map_2d(CUtensorMap* m, const void* ptr, int rows, int cols, int box_rows) {
  cuuint64_t dims[2] = {(cuuint64_t)cols, (cuuint64_t)rows};
  cuuint64_t strides[1] = {(cuuint64_t)cols * 2};
  cuuint32_t box[2] = {cols < 64 ? 32u : 64u, (cuuint32_t)box_rows};
  cuuint32_t es[2] = {1, 1};
  s_encode(m, CU_TENSOR_MAP_DATA_TYPE_BFLOAT16, 2, const_cast<void*>(ptr), dims, strides, box, es,
           CU_TENSOR_MAP_INTERLEAVE_NONE, cols < 64 ? CU_TENSOR_MAP_SWIZZLE_64B : CU_TENSOR_MAP_SWIZZLE_128B, CU_TENSOR_MAP_L2_PROMOTION_L2_256B,
           CU_TENSOR_MAP_FLOAT_OOB_FILL_NONE);
}
static void make_map_3d(CUtensorMap* m, const void* ptr, int rows, int cols, int box_rows, int box_chunks) {
  cuuint64_t dims[3] = {64, (cuuint64_t)rows, (cuuint64_t)(cols / 64)};
  cuuint64_t strides[2] = {(cuuint64_t)cols * 2, 128};
  cuuint32_t box[3] = {64, (cuuint32_t)box_rows, (cuuint32_t)box_chunks};
  cuuint32_t es[3] = {1, 1, 1};
  s_encode(m, CU_TENSOR_MAP_DATA_TYPE_BFLOAT16, 3, const_cast<void*>(ptr), dims, strides, box, es,
           CU_TENSOR_MAP_INTERLEAVE_NONE, CU_TENSOR_MAP_SWIZZLE_128B, CU_TENSOR_MAP_L2_PROMOTION_L2_256B,
           CU_TENSOR_MAP_FLOAT_OOB_FILL_NONE);
}

static cudaLaunchConfig_t fused_cfg(cudaLaunchAttribute* at) {
  cudaLaunchConfig_t cfg = {};
  cfg.gridDim = dim3(132);
  cfg.blockDim = dim3(384);
  cfg.dynamicSmemBytes = SMEM_BYTES;
  cfg.stream = cudaStreamPerThread;
  at[0].id = cudaLaunchAttributeClusterDimension;
  at[0].val.clusterDim.x = 2;
  at[0].val.clusterDim.y = 1;
  at[0].val.clusterDim.z = 1;
  cfg.attrs = at;
  cfg.numAttrs = 1;
  return cfg;
}

extern "C" void kernel_launch(void* const* d_in, const int* in_sizes, int n_in, void* d_out, int out_size) {
  const bf16* x = (const bf16*)d_in[0];
  const bf16* ckv = (const bf16*)d_in[1];
  const bf16* wq = (const bf16*)d_in[2];
  const bf16* wuk = (const bf16*)d_in[3];
  const bf16* wuv = (const bf16*)d_in[4];
  const bf16* wo = (const bf16*)d_in[5];
  const bf16* bk = (const bf16*)d_in[7];
  const bf16* bv = (const bf16*)d_in[8];
  const bf16* shift_k = (const bf16*)d_in[9];
  const bf16* ssm_k = (const bf16*)d_in[10];
  const bf16* ssm_D = (const bf16*)d_in[11];
  const bf16* gate_w = (const bf16*)d_in[12];
  bf16* out = (bf16*)d_out;

  static void *pq = nullptr, *pk = nullptr, *pv = nullptr, *pctx = nullptr, *pb = nullptr, *pu = nullptr;
  static int max_clusters = 0;
  if (!s_encode) {
    void* fn = nullptr;
    cudaDriverEntryPointQueryResult qres;
    cudaGetDriverEntryPoint("cuTensorMapEncodeTiled", &fn, cudaEnableDefault, &qres);
    s_encode = (PFN_tmapEncode)fn;
    cudaGetSymbolAddress(&pq, g_q);
    cudaGetSymbolAddress(&pk, g_k);
    cudaGetSymbolAddress(&pv, g_v);
    cudaGetSymbolAddress(&pctx, g_ctx);
    cudaGetSymbolAddress(&pb, g_y2T);
    cudaGetSymbolAddress(&pu, g_kvT);
    cudaFuncSetAttribute(fused_kernel, cudaFuncAttributeMaxDynamicSharedMemorySize, SMEM_BYTES);
    cudaLaunchAttribute at[1];
    cudaLaunchConfig_t cfg = fused_cfg(at);
    if (cudaOccupancyMaxActiveClusters(&max_clusters, fused_kernel, &cfg) != cudaSuccess) max_clusters = 0;
  }

  Maps all = {};
  make_map_2d(&all.a[0], x, S_LEN, DM, 128);
  make_map_2d(&all.a[1], ckv, S_LEN, DC, 128);
  make_map_3d(&all.b[0], wq, DM, HDIM, 64, 4);
  make_map_3d(&all.b[1], wuk, DC, HDIM, 64, 4);
  make_map_3d(&all.b[2], wuv, DC, HDIM, 64, 4);
  make_map_2d(&all.c[0], pq, S_LEN, HDIM, 64);
  make_map_2d(&all.c[1], pk, S_LEN, HDIM, 64);
  make_map_2d(&all.c[2], pv, S_LEN, HDIM, 64);
  make_map_3d(&all.q, pq, S_LEN, HDIM, 128, 2);
  make_map_3d(&all.k, pk, S_LEN, HDIM, 128, 2);
  make_map_3d(&all.v, pv, S_LEN, HDIM, 128, 2);
  make_map_2d(&all.o, pctx, S_LEN, HDIM, 64);
  all.ssm_k = ssm_k;
  all.ssm_D = ssm_D;
  make_map_2d(&all.oa, pctx, S_LEN, HDIM, 128);
  make_map_2d(&all.ob, wo, HDIM, DM, 64);
  make_map_2d(&all.oc, out, S_LEN, DM, 128);
  make_map_3d(&all.y, pb, DM, S_LEN, 16, 2);
  make_map_3d(&all.xs, x, S_LEN, DM, 32, 1);
  make_map_2d(&all.cu, pu, DM * 64, 32, 64);
  make_map_2d(&all.ch, ssm_k, DM * 64, 32, 64);

  make_map_2d(&all.bk, bk, S_LEN, DM, 35);
  make_map_2d(&all.bv, bv, S_LEN, DM, 32);
  for (int b = 0; b < 128; b++) {
    const int c = b >> 1, r = b & 1;
    const int G = c < 4 ? 0 : c < 36 ? (c - 4) % 8 : 1 + (c - 36) % 7;
    const int i = c < 4 ? 4 + c : c < 36 ? (c - 4) / 8 : 4 + (c - 36) / 7;
    all.id[b][0] = r + 2 * (i & 1) + 4 * (G & 3) + 16 * (i >> 1) + 64 * (G >> 2);
    all.id[b][1] = r + 2 * i + 16 * G;
    all.id[b][2] = r + 2 * G + 16 * i;
  }
  all.shift_k = shift_k;
  all.x = x;
  all.gate_w = gate_w;
  cudaLaunchAttribute at[1];
  cudaLaunchConfig_t cfg = fused_cfg(at);
  if (max_clusters >= 66) {
    cudaLaunchKernelEx(&cfg, fused_kernel, 7, all);
  } else {
    for (int m = 1; m <= 4; m <<= 1) cudaLaunchKernelEx(&cfg, fused_kernel, m, all);
  }
}
```

```cpp
#include <cuda_runtime.h>
#include <cuda_bf16.h>
#include <cuda.h>
#include <stdint.h>

typedef __nv_bfloat16 bf16;
#define INPLACE 3

constexpr int S_LEN = 2048;
constexpr int DM = 1024;
constexpr int NH = 32;
constexpr int HD = 128;
constexpr int DC = 512;
constexpr int HDIM = NH * HD;

__device__ __align__(1024) bf16 g_q[S_LEN * HDIM];
__device__ __align__(1024) bf16 g_k[S_LEN * HDIM];
__device__ __align__(1024) bf16 g_v[S_LEN * HDIM];
#define g_ctx g_q
__device__ __align__(1024) bf16 g_kvT[DM * S_LEN];
#define g_y2T g_kvT
__device__ __align__(1024) float g_gate[S_LEN];
enum { CNT_KV = 0, CNT_PREP = CNT_KV + 2, CNT_CTX, CNT_Y2 = CNT_CTX + 2, CNT_DONE = CNT_Y2 + 2, CNT_N };
__device__ unsigned int g_cnt[CNT_N * 32];

#define TL(k, i)
#define TL2(k, i)
#define TD(i)
#define CT(i)
#define GT(i)
#define GA(i)
#define ST(i)

__device__ __forceinline__ uint32_t smem_u32(const void* p) { return (uint32_t)__cvta_generic_to_shared(p); }

__device__ __forceinline__ void mbar_init(uint32_t bar, uint32_t count) {
  asm volatile("mbarrier.init.shared::cta.b64 [%0], %1;" ::"r"(bar), "r"(count));
}
__device__ __forceinline__ void mbar_expect_tx(uint32_t bar, uint32_t bytes) {
  asm volatile("mbarrier.arrive.expect_tx.shared::cta.b64 _, [%0], %1;" ::"r"(bar), "r"(bytes) : "memory");
}
__device__ __forceinline__ void mbar_arrive(uint32_t bar) {
  asm volatile("mbarrier.arrive.shared::cta.b64 _, [%0];" ::"r"(bar) : "memory");
}
__device__ __forceinline__ void mbar_wait(uint32_t bar, uint32_t parity) {
  uint32_t done;
  uint32_t spins = 0;
  do {
    asm volatile(
        "{\n.reg .pred p;\n"
        "mbarrier.try_wait.parity.shared::cta.b64 p, [%1], %2;\n"
        "selp.u32 %0, 1, 0, p;\n}\n"
        : "=r"(done)
        : "r"(bar), "r"(parity)
        : "memory");
    if (++spins > (1u << 22)) break;
  } while (!done);
}
__device__ __forceinline__ bool mbar_try(uint32_t bar, uint32_t parity) {
  uint32_t done;
  asm volatile(
      "{\n.reg .pred p;\n"
      "mbarrier.try_wait.parity.shared::cta.b64 p, [%1], %2;\n"
      "selp.u32 %0, 1, 0, p;\n}\n"
      : "=r"(done)
      : "r"(bar), "r"(parity)
      : "memory");
  return done != 0;
}
__device__ __forceinline__ bool elect_one() {
  uint32_t pred;
  asm volatile("{\n.reg .pred p;\nelect.sync _|p, 0xffffffff;\nselp.u32 %0, 1, 0, p;\n}\n" : "=r"(pred));
  return pred != 0;
}
__device__ __forceinline__ void mbar_arrive_if(uint32_t bar, bool pred) {
  asm volatile(
      "{\n.reg .pred p;\nsetp.ne.b32 p, %1, 0;\n"
      "@p mbarrier.arrive.shared::cta.b64 _, [%0];\n}\n" ::"r"(bar),
      "r"((uint32_t)pred)
      : "memory");
}
__device__ __forceinline__ void mbar_wait_sleep(uint32_t bar, uint32_t parity) {
  uint32_t done;
  uint32_t spins = 0;
  do {
    asm volatile(
        "{\n.reg .pred p;\n"
        "mbarrier.try_wait.parity.shared::cta.b64 p, [%1], %2, %3;\n"
        "selp.u32 %0, 1, 0, p;\n}\n"
        : "=r"(done)
        : "r"(bar), "r"(parity), "r"(20000u)
        : "memory");
    if (++spins > (1u << 16)) break;
  } while (!done);
}
__device__ __forceinline__ void fence_barrier_init() {
  asm volatile("fence.mbarrier_init.release.cluster;" ::: "memory");
}
__device__ __forceinline__ void fence_proxy_async() {
  asm volatile("fence.proxy.async.shared::cta;" ::: "memory");
}
__device__ __forceinline__ void named_bar_sync(int id, int nthreads) {
  asm volatile("bar.sync %0, %1;" ::"r"(id), "r"(nthreads) : "memory");
}
__device__ __forceinline__ void named_bar_arrive(int id, int nthreads) {
  asm volatile("bar.arrive %0, %1;" ::"r"(id), "r"(nthreads) : "memory");
}
__device__ __forceinline__ void tma_load_2d(uint32_t dst, const CUtensorMap* m, uint32_t bar, int c0, int c1) {
  asm volatile(
      "cp.async.bulk.tensor.2d.shared::cluster.global.mbarrier::complete_tx::bytes [%0], [%1, {%3, %4}], [%2];" ::"r"(dst),
      "l"(reinterpret_cast<uint64_t>(m)), "r"(bar), "r"(c0), "r"(c1)
      : "memory");
}
__device__ __forceinline__ void tma_load_3d(uint32_t dst, const CUtensorMap* m, uint32_t bar, int c0, int c1, int c2) {
  asm volatile(
      "cp.async.bulk.tensor.3d.shared::cluster.global.mbarrier::complete_tx::bytes [%0], [%1, {%3, %4, %5}], [%2];" ::"r"(dst),
      "l"(reinterpret_cast<uint64_t>(m)), "r"(bar), "r"(c0), "r"(c1), "r"(c2)
      : "memory");
}
__device__ __forceinline__ void tma_store_2d(const CUtensorMap* m, uint32_t src, int c0, int c1) {
  asm volatile("cp.async.bulk.tensor.2d.global.shared::cta.bulk_group [%0, {%2, %3}], [%1];" ::"l"(
                   reinterpret_cast<uint64_t>(m)),
               "r"(src), "r"(c0), "r"(c1)
               : "memory");
}
__device__ __forceinline__ void bulk_load(uint32_t dst, const void* src, uint32_t bytes, uint32_t bar) {
  asm volatile("cp.async.bulk.shared::cluster.global.mbarrier::complete_tx::bytes [%0], [%1], %2, [%3];" ::"r"(dst),
               "l"(src), "r"(bytes), "r"(bar)
               : "memory");
}
__device__ __forceinline__ void tma_load_2d_mc(uint32_t dst, const CUtensorMap* m, uint32_t bar, int c0, int c1,
                                               uint16_t mask) {
  asm volatile(
      "cp.async.bulk.tensor.2d.shared::cluster.global.mbarrier::complete_tx::bytes.multicast::cluster [%0], [%1, {%3, "
      "%4}], [%2], %5;" ::"r"(dst),
      "l"(reinterpret_cast<uint64_t>(m)), "r"(bar), "r"(c0), "r"(c1), "h"(mask)
      : "memory");
}
__device__ __forceinline__ void mbar_arrive_cluster_if(uint32_t bar, uint32_t cta, bool pred) {
  asm volatile(
      "{\n.reg .b32 ra;\n.reg .pred p;\nsetp.ne.b32 p, %2, 0;\n"
      "mapa.shared::cluster.u32 ra, %0, %1;\n"
      "@p mbarrier.arrive.shared::cluster.b64 _, [ra];\n}\n" ::"r"(bar),
      "r"(cta), "r"((uint32_t)pred)
      : "memory");
}
__device__ __forceinline__ uint64_t policy_evict_first() {
  uint64_t pol;
  asm volatile("createpolicy.fractional.L2::evict_first.b64 %0, 1.0;" : "=l"(pol));
  return pol;
}
__device__ __forceinline__ void tma_load_2d_hint(uint32_t dst, const CUtensorMap* m, uint32_t bar, int c0, int c1,
                                                 uint64_t pol) {
  asm volatile(
      "cp.async.bulk.tensor.2d.shared::cluster.global.mbarrier::complete_tx::bytes.L2::cache_hint [%0], [%1, {%3, %4}], "
      "[%2], %5;" ::"r"(dst),
      "l"(reinterpret_cast<uint64_t>(m)), "r"(bar), "r"(c0), "r"(c1), "l"(pol)
      : "memory");
}
__device__ __forceinline__ void tma_load_3d_hint(uint32_t dst, const CUtensorMap* m, uint32_t bar, int c0, int c1,
                                                 int c2, uint64_t pol) {
  asm volatile(
      "cp.async.bulk.tensor.3d.shared::cluster.global.mbarrier::complete_tx::bytes.L2::cache_hint [%0], [%1, {%3, %4, "
      "%5}], [%2], %6;" ::"r"(dst),
      "l"(reinterpret_cast<uint64_t>(m)), "r"(bar), "r"(c0), "r"(c1), "r"(c2), "l"(pol)
      : "memory");
}
__device__ __forceinline__ void bulk_load_hint(uint32_t dst, const void* src, uint32_t bytes, uint32_t bar, uint64_t pol) {
  asm volatile(
      "cp.async.bulk.shared::cluster.global.mbarrier::complete_tx::bytes.L2::cache_hint [%0], [%1], %2, [%3], %4;" ::"r"(dst),
      "l"(src), "r"(bytes), "r"(bar), "l"(pol)
      : "memory");
}
__device__ __forceinline__ void cnt_signal_release(int which, uint32_t n) {
  asm volatile("red.release.gpu.global.add.u32 [%0], %1;" ::"l"(g_cnt + which * 32), "r"(n) : "memory");
}
__device__ __forceinline__ void cnt_wait(int which, uint32_t target) {
  uint32_t v, spins = 0;
  while (true) {
    asm volatile("ld.acquire.gpu.global.u32 %0, [%1];" : "=r"(v) : "l"(g_cnt + which * 32) : "memory");
    if (v >= target || ++spins > (1u << 18)) break;
    __nanosleep(64);
  }
  asm volatile("fence.proxy.async.global;" ::: "memory");
}
__device__ __forceinline__ void tma_store_commit() { asm volatile("cp.async.bulk.commit_group;" ::: "memory"); }
template <int N>
__device__ __forceinline__ void tma_store_wait_read() {
  asm volatile("cp.async.bulk.wait_group.read %0;" ::"n"(N) : "memory");
}
template <int N>
__device__ __forceinline__ void tma_store_wait() {
  asm volatile("cp.async.bulk.wait_group %0;" ::"n"(N) : "memory");
}
__device__ __forceinline__ void wgmma_fence() { asm volatile("wgmma.fence.sync.aligned;" ::: "memory"); }
__device__ __forceinline__ void wgmma_commit() { asm volatile("wgmma.commit_group.sync.aligned;" ::: "memory"); }
template <int N>
__device__ __forceinline__ void wgmma_wait() {
  asm volatile("wgmma.wait_group.sync.aligned %0;" ::"n"(N) : "memory");
}
template <int R>
__device__ __forceinline__ void reg_alloc() { asm volatile("setmaxnreg.inc.sync.aligned.u32 %0;" ::"n"(R)); }
template <int R>
__device__ __forceinline__ void reg_dealloc() { asm volatile("setmaxnreg.dec.sync.aligned.u32 %0;" ::"n"(R)); }

__device__ __forceinline__ void stmatrix_x4(uint32_t addr, uint32_t r0, uint32_t r1, uint32_t r2, uint32_t r3) {
  asm volatile("stmatrix.sync.aligned.m8n8.x4.shared.b16 [%0], {%1, %2, %3, %4};" ::"r"(addr), "r"(r0), "r"(r1),
               "r"(r2), "r"(r3)
               : "memory");
}
__device__ __forceinline__ uint32_t pack_bf16(float lo, float hi) {
  uint32_t r;
  asm("cvt.rn.bf16x2.f32 %0, %1, %2;" : "=r"(r) : "f"(hi), "f"(lo));
  return r;
}
__device__ __forceinline__ float bf16_round(float x) { return __bfloat162float(__float2bfloat16_rn(x)); }
__device__ __forceinline__ float bf_lo(uint32_t v) { return __uint_as_float(v << 16); }
__device__ __forceinline__ float bf_hi(uint32_t v) { return __uint_as_float(v & 0xffff0000u); }
__device__ __forceinline__ uint4 lds128(uint32_t a) {
  uint4 v;
  asm volatile("ld.shared.v4.u32 {%0, %1, %2, %3}, [%4];" : "=r"(v.x), "=r"(v.y), "=r"(v.z), "=r"(v.w) : "r"(a));
  return v;
}
__device__ __forceinline__ void sts128(uint32_t a, uint4 v) {
  asm volatile("st.shared.v4.u32 [%0], {%1, %2, %3, %4};" ::"r"(a), "r"(v.x), "r"(v.y), "r"(v.z), "r"(v.w) : "memory");
}
__device__ __forceinline__ uint32_t mul_bf2(uint32_t a, uint32_t b) {
  uint32_t r;
  asm("mul.rn.bf16x2 %0, %1, %2;" : "=r"(r) : "r"(a), "r"(b));
  return r;
}
__device__ __forceinline__ uint32_t add_bf2(uint32_t a, uint32_t b) {
  uint32_t r;
  asm("add.rn.bf16x2 %0, %1, %2;" : "=r"(r) : "r"(a), "r"(b));
  return r;
}
__device__ __forceinline__ float ex2(float x) {
  float y;
  asm("ex2.approx.ftz.f32 %0, %1;" : "=f"(y) : "f"(x));
  return y;
}
__device__ __forceinline__ float rcp(float x) {
  float y;
  asm("rcp.approx.ftz.f32 %0, %1;" : "=f"(y) : "f"(x));
  return y;
}
template <int N>
__device__ __forceinline__ void fence_regs(float (&r)[N]) {
#pragma unroll
  for (int i = 0; i < N; i++) asm volatile("" : "+f"(r[i])::"memory");
}

template <int N>
__device__ __forceinline__ void undef_regs(float (&r)[N]) {
#pragma unroll
  for (int i = 0; i < N; i++) asm volatile("" : "=f"(r[i]));
}
template <int N>
__device__ __forceinline__ void fence_regs_u(uint32_t (&r)[N]) {
#pragma unroll
  for (int i = 0; i < N; i++) asm volatile("" : "+r"(r[i])::"memory");
}

constexpr uint64_t DESC_SW128 = 1ull << 62;
__device__ __forceinline__ uint64_t make_desc(uint32_t addr, uint32_t lbo_bytes, uint32_t sbo_bytes, uint64_t swz) {
  return (uint64_t)((addr & 0x3FFFF) >> 4) | ((uint64_t)((lbo_bytes & 0x3FFFF) >> 4) << 16) |
         ((uint64_t)((sbo_bytes & 0x3FFFF) >> 4) << 32) | swz;
}

__device__ __forceinline__ uint64_t desc_add(uint64_t d, uint32_t off16) {
  return (d & 0xFFFFFFFF00000000ull) | (uint64_t)((uint32_t)d + off16);
}

__device__ __forceinline__ void wgmma_m64n256_ss_tb(float (&d)[128], uint64_t da, uint64_t db, int sd) {
  asm volatile(
    "{\n.reg .pred p;\nsetp.ne.b32 p, %130, 0;\n"
    "wgmma.mma_async.sync.aligned.m64n256k16.f32.bf16.bf16 "
    "{%0, %1, %2, %3, %4, %5, %6, %7, %8, %9, %10, %11, %12, %13, %14, %15, %16, %17, %18, %19, %20, %21, %22, %23, %24, %25, %26, %27, %28, %29, %30, %31, %32, %33, %34, %35, %36, %37, %38, %39, %40, %41, %42, %43, %44, %45, %46, %47, %48, %49, %50, %51, %52, %53, %54, %55, %56, %57, %58, %59, %60, %61, %62, %63, %64, %65, %66, %67, %68, %69, %70, %71, %72, %73, %74, %75, %76, %77, %78, %79, %80, %81, %82, %83, %84, %85, %86, %87, %88, %89, %90, %91, %92, %93, %94, %95, %96, %97, %98, %99, %100, %101, %102, %103, %104, %105, %106, %107, %108, %109, %110, %111, %112, %113, %114, %115, %116, %117, %118, %119, %120, %121, %122, %123, %124, %125, %126, %127}, %128, %129, p, 1, 1, 0, 1;\n}\n"
    : "+f"(d[0]), "+f"(d[1]), "+f"(d[2]), "+f"(d[3]), "+f"(d[4]), "+f"(d[5]), "+f"(d[6]), "+f"(d[7]), "+f"(d[8]), "+f"(d[9]), "+f"(d[10]), "+f"(d[11]), "+f"(d[12]), "+f"(d[13]), "+f"(d[14]), "+f"(d[15]), "+f"(d[16]), "+f"(d[17]), "+f"(d[18]), "+f"(d[19]), "+f"(d[20]), "+f"(d[21]), "+f"(d[22]), "+f"(d[23]), "+f"(d[24]), "+f"(d[25]), "+f"(d[26]), "+f"(d[27]), "+f"(d[28]), "+f"(d[29]), "+f"(d[30]), "+f"(d[31]), "+f"(d[32]), "+f"(d[33]), "+f"(d[34]), "+f"(d[35]), "+f"(d[36]), "+f"(d[37]), "+f"(d[38]), "+f"(d[39]), "+f"(d[40]), "+f"(d[41]), "+f"(d[42]), "+f"(d[43]), "+f"(d[44]), "+f"(d[45]), "+f"(d[46]), "+f"(d[47]), "+f"(d[48]), "+f"(d[49]), "+f"(d[50]), "+f"(d[51]), "+f"(d[52]), "+f"(d[53]), "+f"(d[54]), "+f"(d[55]), "+f"(d[56]), "+f"(d[57]), "+f"(d[58]), "+f"(d[59]), "+f"(d[60]), "+f"(d[61]), "+f"(d[62]), "+f"(d[63]), "+f"(d[64]), "+f"(d[65]), "+f"(d[66]), "+f"(d[67]), "+f"(d[68]), "+f"(d[69]), "+f"(d[70]), "+f"(d[71]), "+f"(d[72]), "+f"(d[73]), "+f"(d[74]), "+f"(d[75]), "+f"(d[76]), "+f"(d[77]), "+f"(d[78]), "+f"(d[79]), "+f"(d[80]), "+f"(d[81]), "+f"(d[82]), "+f"(d[83]), "+f"(d[84]), "+f"(d[85]), "+f"(d[86]), "+f"(d[87]), "+f"(d[88]), "+f"(d[89]), "+f"(d[90]), "+f"(d[91]), "+f"(d[92]), "+f"(d[93]), "+f"(d[94]), "+f"(d[95]), "+f"(d[96]), "+f"(d[97]), "+f"(d[98]), "+f"(d[99]), "+f"(d[100]), "+f"(d[101]), "+f"(d[102]), "+f"(d[103]), "+f"(d[104]), "+f"(d[105]), "+f"(d[106]), "+f"(d[107]), "+f"(d[108]), "+f"(d[109]), "+f"(d[110]), "+f"(d[111]), "+f"(d[112]), "+f"(d[113]), "+f"(d[114]), "+f"(d[115]), "+f"(d[116]), "+f"(d[117]), "+f"(d[118]), "+f"(d[119]), "+f"(d[120]), "+f"(d[121]), "+f"(d[122]), "+f"(d[123]), "+f"(d[124]), "+f"(d[125]), "+f"(d[126]), "+f"(d[127])
    : "l"(da), "l"(db), "r"(sd));
}

__device__ __forceinline__ void wgmma_m64n128_ss(float (&d)[64], uint64_t da, uint64_t db, int sd) {
  asm volatile(
    "{\n.reg .pred p;\nsetp.ne.b32 p, %66, 0;\n"
    "wgmma.mma_async.sync.aligned.m64n128k16.f32.bf16.bf16 "
    "{%0, %1, %2, %3, %4, %5, %6, %7, %8, %9, %10, %11, %12, %13, %14, %15, %16, %17, %18, %19, %20, %21, %22, %23, %24, %25, %26, %27, %28, %29, %30, %31, %32, %33, %34, %35, %36, %37, %38, %39, %40, %41, %42, %43, %44, %45, %46, %47, %48, %49, %50, %51, %52, %53, %54, %55, %56, %57, %58, %59, %60, %61, %62, %63}, %64, %65, p, 1, 1, 0, 0;\n}\n"
    : "+f"(d[0]), "+f"(d[1]), "+f"(d[2]), "+f"(d[3]), "+f"(d[4]), "+f"(d[5]), "+f"(d[6]), "+f"(d[7]), "+f"(d[8]), "+f"(d[9]), "+f"(d[10]), "+f"(d[11]), "+f"(d[12]), "+f"(d[13]), "+f"(d[14]), "+f"(d[15]), "+f"(d[16]), "+f"(d[17]), "+f"(d[18]), "+f"(d[19]), "+f"(d[20]), "+f"(d[21]), "+f"(d[22]), "+f"(d[23]), "+f"(d[24]), "+f"(d[25]), "+f"(d[26]), "+f"(d[27]), "+f"(d[28]), "+f"(d[29]), "+f"(d[30]), "+f"(d[31]), "+f"(d[32]), "+f"(d[33]), "+f"(d[34]), "+f"(d[35]), "+f"(d[36]), "+f"(d[37]), "+f"(d[38]), "+f"(d[39]), "+f"(d[40]), "+f"(d[41]), "+f"(d[42]), "+f"(d[43]), "+f"(d[44]), "+f"(d[45]), "+f"(d[46]), "+f"(d[47]), "+f"(d[48]), "+f"(d[49]), "+f"(d[50]), "+f"(d[51]), "+f"(d[52]), "+f"(d[53]), "+f"(d[54]), "+f"(d[55]), "+f"(d[56]), "+f"(d[57]), "+f"(d[58]), "+f"(d[59]), "+f"(d[60]), "+f"(d[61]), "+f"(d[62]), "+f"(d[63])
    : "l"(da), "l"(db), "r"(sd));
}

__device__ __forceinline__ void wgmma_m64n128_ss_tb(float (&d)[64], uint64_t da, uint64_t db, int sd) {
  asm volatile(
    "{\n.reg .pred p;\nsetp.ne.b32 p, %66, 0;\n"
    "wgmma.mma_async.sync.aligned.m64n128k16.f32.bf16.bf16 "
    "{%0, %1, %2, %3, %4, %5, %6, %7, %8, %9, %10, %11, %12, %13, %14, %15, %16, %17, %18, %19, %20, %21, %22, %23, %24, %25, %26, %27, %28, %29, %30, %31, %32, %33, %34, %35, %36, %37, %38, %39, %40, %41, %42, %43, %44, %45, %46, %47, %48, %49, %50, %51, %52, %53, %54, %55, %56, %57, %58, %59, %60, %61, %62, %63}, %64, %65, p, 1, 1, 0, 1;\n}\n"
    : "+f"(d[0]), "+f"(d[1]), "+f"(d[2]), "+f"(d[3]), "+f"(d[4]), "+f"(d[5]), "+f"(d[6]), "+f"(d[7]), "+f"(d[8]), "+f"(d[9]), "+f"(d[10]), "+f"(d[11]), "+f"(d[12]), "+f"(d[13]), "+f"(d[14]), "+f"(d[15]), "+f"(d[16]), "+f"(d[17]), "+f"(d[18]), "+f"(d[19]), "+f"(d[20]), "+f"(d[21]), "+f"(d[22]), "+f"(d[23]), "+f"(d[24]), "+f"(d[25]), "+f"(d[26]), "+f"(d[27]), "+f"(d[28]), "+f"(d[29]), "+f"(d[30]), "+f"(d[31]), "+f"(d[32]), "+f"(d[33]), "+f"(d[34]), "+f"(d[35]), "+f"(d[36]), "+f"(d[37]), "+f"(d[38]), "+f"(d[39]), "+f"(d[40]), "+f"(d[41]), "+f"(d[42]), "+f"(d[43]), "+f"(d[44]), "+f"(d[45]), "+f"(d[46]), "+f"(d[47]), "+f"(d[48]), "+f"(d[49]), "+f"(d[50]), "+f"(d[51]), "+f"(d[52]), "+f"(d[53]), "+f"(d[54]), "+f"(d[55]), "+f"(d[56]), "+f"(d[57]), "+f"(d[58]), "+f"(d[59]), "+f"(d[60]), "+f"(d[61]), "+f"(d[62]), "+f"(d[63])
    : "l"(da), "l"(db), "r"(sd));
}

__device__ __forceinline__ void wgmma_m64n128_rs_tb(float* d, uint32_t a0, uint32_t a1, uint32_t a2, uint32_t a3, uint64_t db, int sd) {
  asm volatile(
    "{\n.reg .pred p;\nsetp.ne.b32 p, %69, 0;\n"
    "wgmma.mma_async.sync.aligned.m64n128k16.f32.bf16.bf16 "
    "{%0, %1, %2, %3, %4, %5, %6, %7, %8, %9, %10, %11, %12, %13, %14, %15, %16, %17, %18, %19, %20, %21, %22, %23, %24, %25, %26, %27, %28, %29, %30, %31, %32, %33, %34, %35, %36, %37, %38, %39, %40, %41, %42, %43, %44, %45, %46, %47, %48, %49, %50, %51, %52, %53, %54, %55, %56, %57, %58, %59, %60, %61, %62, %63}, {%64, %65, %66, %67}, %68, p, 1, 1, 1;\n}\n"
    : "+f"(d[0]), "+f"(d[1]), "+f"(d[2]), "+f"(d[3]), "+f"(d[4]), "+f"(d[5]), "+f"(d[6]), "+f"(d[7]), "+f"(d[8]), "+f"(d[9]), "+f"(d[10]), "+f"(d[11]), "+f"(d[12]), "+f"(d[13]), "+f"(d[14]), "+f"(d[15]), "+f"(d[16]), "+f"(d[17]), "+f"(d[18]), "+f"(d[19]), "+f"(d[20]), "+f"(d[21]), "+f"(d[22]), "+f"(d[23]), "+f"(d[24]), "+f"(d[25]), "+f"(d[26]), "+f"(d[27]), "+f"(d[28]), "+f"(d[29]), "+f"(d[30]), "+f"(d[31]), "+f"(d[32]), "+f"(d[33]), "+f"(d[34]), "+f"(d[35]), "+f"(d[36]), "+f"(d[37]), "+f"(d[38]), "+f"(d[39]), "+f"(d[40]), "+f"(d[41]), "+f"(d[42]), "+f"(d[43]), "+f"(d[44]), "+f"(d[45]), "+f"(d[46]), "+f"(d[47]), "+f"(d[48]), "+f"(d[49]), "+f"(d[50]), "+f"(d[51]), "+f"(d[52]), "+f"(d[53]), "+f"(d[54]), "+f"(d[55]), "+f"(d[56]), "+f"(d[57]), "+f"(d[58]), "+f"(d[59]), "+f"(d[60]), "+f"(d[61]), "+f"(d[62]), "+f"(d[63])
    : "r"(a0), "r"(a1), "r"(a2), "r"(a3), "l"(db), "r"(sd));
}

__device__ __forceinline__ void wgmma_m64n64_rs_tb(float (&d)[32], const uint32_t (&a)[4], uint64_t db, int sd) {
  asm volatile(
    "{\n.reg .pred p;\nsetp.ne.b32 p, %37, 0;\n"
    "wgmma.mma_async.sync.aligned.m64n64k16.f32.bf16.bf16 "
    "{%0, %1, %2, %3, %4, %5, %6, %7, %8, %9, %10, %11, %12, %13, %14, %15, %16, %17, %18, %19, %20, %21, %22, %23, %24, %25, %26, %27, %28, %29, %30, %31}, {%32, %33, %34, %35}, %36, p, 1, 1, 1;\n}\n"
    : "+f"(d[0]), "+f"(d[1]), "+f"(d[2]), "+f"(d[3]), "+f"(d[4]), "+f"(d[5]), "+f"(d[6]), "+f"(d[7]), "+f"(d[8]), "+f"(d[9]), "+f"(d[10]), "+f"(d[11]), "+f"(d[12]), "+f"(d[13]), "+f"(d[14]), "+f"(d[15]), "+f"(d[16]), "+f"(d[17]), "+f"(d[18]), "+f"(d[19]), "+f"(d[20]), "+f"(d[21]), "+f"(d[22]), "+f"(d[23]), "+f"(d[24]), "+f"(d[25]), "+f"(d[26]), "+f"(d[27]), "+f"(d[28]), "+f"(d[29]), "+f"(d[30]), "+f"(d[31])
    : "r"(a[0]), "r"(a[1]), "r"(a[2]), "r"(a[3]), "l"(db), "r"(sd));
}

__device__ __forceinline__ void wgmma_m64n32_rs_tb(float (&d)[16], const uint32_t (&a)[4], uint64_t db, int sd) {
  asm volatile(
    "{\n.reg .pred p;\nsetp.ne.b32 p, %21, 0;\n"
    "wgmma.mma_async.sync.aligned.m64n32k16.f32.bf16.bf16 "
    "{%0, %1, %2, %3, %4, %5, %6, %7, %8, %9, %10, %11, %12, %13, %14, %15}, {%16, %17, %18, %19}, %20, p, 1, 1, 1;\n}\n"
    : "+f"(d[0]), "+f"(d[1]), "+f"(d[2]), "+f"(d[3]), "+f"(d[4]), "+f"(d[5]), "+f"(d[6]), "+f"(d[7]), "+f"(d[8]), "+f"(d[9]), "+f"(d[10]), "+f"(d[11]), "+f"(d[12]), "+f"(d[13]), "+f"(d[14]), "+f"(d[15])
    : "r"(a[0]), "r"(a[1]), "r"(a[2]), "r"(a[3]), "l"(db), "r"(sd));
}

constexpr int G_STAGES = 4;
constexpr int G_A_BYTES = 128 * 64 * 2;
constexpr int G_B_BYTES = 256 * 64 * 2;
constexpr int G_STAGE_BYTES = G_A_BYTES + G_B_BYTES;
constexpr int G_STG_OFF = G_STAGES * G_STAGE_BYTES;
constexpr int BAR_OFF = G_STG_OFF + 32768 + 2048;
constexpr int SMEM_BYTES = BAR_OFF + 1024;
constexpr int B_GFULL = 0, B_GEMPTY = 32, B_SEEN = 64, B_PFULL = 224;
constexpr int B_KFULL = 80, B_KEMPTY = 96, B_VFULL = 112, B_VEMPTY = 128, B_QFULL = 144, B_QEMPTY = 160,
              B_QDONE = 184;
constexpr int B_CFULL = 192;
constexpr int B_OFREE = 256, B_OFULL = 272, B_OEMPTY = 320, B_OY = 368, B_OY2 = 384;
constexpr int B_SFULL = 392, B_SFREE = 424, B_PEND = 456, B_SCMD = 512;

#define PHASE_PROLOGUE                                                                \
  uint32_t tid, rt_zero;                                                              \
  asm volatile("mov.u32 %0, %%tid.x;" : "=r"(tid));                                   \
  asm volatile("mov.u32 %0, %%nctaid.y;" : "=r"(rt_zero));                            \
  asm volatile("" : "+r"(smem0));                                                     \
  rt_zero = __shfl_sync(0xffffffffu, rt_zero >> 8, 0);   \
  const uint32_t sbase = __shfl_sync(0xffffffffu, smem0, 0);                          \
  const uint32_t bar = sbase + BAR_OFF;                                               \
  const int wg = __shfl_sync(0xffffffffu, tid >> 7, 0);                               \
  const int warp = (tid >> 5) & 3, lane = tid & 31, wtid = tid & 127;                 \
  (void)rt_zero; (void)bar; (void)warp; (void)lane; (void)wtid;

enum { ST_END = 0, ST_BOX1, ST_BOX2, ST_BOX2Q, ST_BOX2L };
__device__ __forceinline__ void st_post(uint32_t bar, int wg, int wtid, uint32_t n, int kind, const void* dst,
                                        uint32_t src, int c0, int c1, int sig) {
  if (wtid == 0) {
    const uint32_t c = bar + B_SCMD + wg * 64 + (n & 1) * 32;
    const uint64_t d = reinterpret_cast<uint64_t>(dst);
    sts128(c, make_uint4(kind, src, c0, c1));
    sts128(c + 16, make_uint4((uint32_t)d, (uint32_t)(d >> 32), sig, 0));
  }
  fence_proxy_async();
  __syncwarp();
  mbar_arrive_if(bar + B_SFULL + wg * 16 + (n & 1) * 8, (wtid & 31) == 0);
}
__device__ __forceinline__ void st_wait(uint32_t bar, int wg, uint32_t n) {
  const uint32_t b = bar + B_SFREE + wg * 16 + (n & 1) * 8;
  if (!mbar_try(b, ~(n >> 1) & 1)) mbar_wait(b, ~(n >> 1) & 1);
}
__device__ __forceinline__ void note(uint32_t bar, uint32_t cnt) {
  asm volatile("red.release.cta.shared.add.u32 [%0], 1;" ::"r"(bar + B_PEND + 4 * cnt) : "memory");
}
__device__ __forceinline__ void store_agent(uint32_t bar, int wg) {
  mbar_arrive(bar + B_SFREE + wg * 16);
  mbar_arrive(bar + B_SFREE + wg * 16 + 8);
  bool more = true;
  for (uint32_t n = 0;; n++) {
    mbar_wait_sleep(bar + B_SFULL + wg * 16 + (n & 1) * 8, (n >> 1) & 1);
    const uint4 c = lds128(bar + B_SCMD + wg * 64 + (n & 1) * 32);
    const uint4 d = lds128(bar + B_SCMD + wg * 64 + (n & 1) * 32 + 16);
    if (c.x == ST_END) break;
    const CUtensorMap* dst = reinterpret_cast<const CUtensorMap*>((uint64_t)d.x | ((uint64_t)d.y << 32));
    tma_store_2d(dst, c.y, c.z, c.w);
    if (c.x >= ST_BOX2) tma_store_2d(dst, c.y + 8192, c.z + 64, c.w);
    tma_store_commit();
    tma_store_wait_read<0>();
    mbar_arrive(bar + B_SFREE + wg * 16 + (n & 1) * 8);
    if (c.x == ST_BOX2L) mbar_arrive(bar + B_OFREE + 8 * wg);
    if ((int)d.z >= 0) {
      tma_store_wait<0>();
      if (d.z == 0) { TD(6) }
      asm volatile("fence.proxy.async.global;" ::: "memory");
      if (c.x == ST_BOX2Q) mbar_arrive(bar + B_QDONE);
      else note(bar, d.z);
      if (c.x == ST_BOX2L) {
        note(bar, CNT_DONE);
        more = false;
      }
    }
  }
  if (more) note(bar, CNT_DONE);
}

struct Maps {
  const bf16 *shift_k, *x, *gate_w, *ssm_k, *ssm_D;
  uint8_t id[128][4];
  CUtensorMap a[2];
  CUtensorMap b[3];
  CUtensorMap c[3];
  CUtensorMap bk, bv;
  CUtensorMap q, k, v, o;
  CUtensorMap oa, ob, oc;
  CUtensorMap y, xs;
  CUtensorMap cu, ch;
};

constexpr int P_SLOT = 67 * 128, P_V = 35 * 128, P_TAPS = 2 * P_SLOT;
__device__ __forceinline__ void ldsm4t(uint32_t (&r)[4], uint32_t a) {
  asm volatile("ldmatrix.sync.aligned.m8n8.x4.trans.shared.b16 {%0, %1, %2, %3}, [%4];"
               : "=r"(r[0]), "=r"(r[1]), "=r"(r[2]), "=r"(r[3])
               : "r"(a));
}
__device__ __forceinline__ uint32_t fma_bf2(uint32_t a, uint32_t b, uint32_t c) {
  uint32_t r;
  asm("fma.rn.bf16x2 %0, %1, %2, %3;" : "=r"(r) : "r"(a), "r"(b), "r"(c));
  return r;
}
__device__ __forceinline__ void prep_agent(const Maps& maps, uint32_t sbase, int w, int lane) {
  const uint32_t bar = sbase + BAR_OFF, pb = bar + B_PFULL + w * 16;
  const int d0 = (blockIdx.x >> 3) * 64, t0 = (blockIdx.x & 7) * 256 + w * 128;
  mbar_wait_sleep(bar + B_GFULL + 8 * (G_STAGES - 1), 0);
#pragma unroll 1
  for (int i = -1; i < 4; i++) {
    GA(82 + 2 * i)
    if (i >= 0) mbar_wait_sleep(pb + (i & 1) * 8, i >> 1);
    GA(83 + 2 * i)
    const uint32_t so = sbase + G_STG_OFF + w * (P_TAPS + 512) + (i & 1) * P_SLOT;
    if (i < 3 && elect_one()) {
      const uint32_t b = pb + (~i & 1) * 8, dst = so + (i & 1 ? -P_SLOT : P_SLOT);
      mbar_expect_tx(b, i < 0 ? P_SLOT + 512 : P_SLOT);
      const uint64_t pol = policy_evict_first();
      tma_load_2d_hint(dst, &maps.bk, b, d0, t0 + 32 * i + 29, pol);
      tma_load_2d_hint(dst + P_V, &maps.bv, b, d0, t0 + 32 * i + 32, pol);
      if (i < 0) bulk_load(sbase + G_STG_OFF + P_TAPS, maps.shift_k + d0 * 4, 512, b);
    }
    if (i < 0) continue;
    uint32_t ak[4];
#pragma unroll
    for (int r = 0; r < 4; r++) {
      const uint32_t a = so / 128 + r + 4 * (lane & 6) + (((lane >> 2) ^ lane) & 6) + (lane & 1);
      ak[r] = a * 128 + (a & 7) * 16;
    }
    bf16* dst = g_kvT + (size_t)(d0 + (lane >> 2)) * S_LEN + t0 + ((lane & 3) + 4 * i) * 8;
#pragma unroll 1
    for (int cg = 0; cg < 128; cg += 16) {
      uint32_t t01, t23, k[4][4], v[4];
      asm volatile("ld.shared.v2.u32 {%0, %1}, [%2];"
                   : "=r"(t01), "=r"(t23)
                   : "r"(sbase + G_STG_OFF + P_TAPS + cg * 4 + (lane >> 2) * 8));
#pragma unroll
      for (int r = 0; r < 4; r++) ldsm4t(k[r], ak[r] ^ cg);
      ldsm4t(v, (ak[3] ^ cg) + 4096);
      const uint32_t w0 = __byte_perm(t01, 0, 0x1010), w1 = __byte_perm(t01, 0, 0x3232);
      const uint32_t w2 = __byte_perm(t23, 0, 0x1010), w3 = __byte_perm(t23, 0, 0x3232);
#pragma unroll
      for (int j = 0; j < 4; j++)
        v[j] = mul_bf2(fma_bf2(k[3][j], w0, fma_bf2(k[2][j], w1, fma_bf2(k[1][j], w2, mul_bf2(k[0][j], w3)))), v[j]);
      const bool s1 = lane & 1, s2 = lane & 2;
      const uint32_t a0 = s1 ? v[1] : v[0], a1 = s1 ? v[0] : v[1], a2 = s1 ? v[3] : v[2], a3 = s1 ? v[2] : v[3];
      *reinterpret_cast<uint4*>(dst) = make_uint4(s2 ? a2 : a0, s2 ? a3 : a1, s2 ? a0 : a2, s2 ? a1 : a3);
      dst += 8 * S_LEN;
    }
    fence_proxy_async();
    __syncwarp();
  }
  GA(90)
  if (lane == 0) note(bar, CNT_PREP);
  __syncwarp();
  GA(91)
}

__device__ __forceinline__ void qkv_tile(const Maps& maps, int it, int& which, int& m_tile, int& n_tile) {
  const bool q = it == 0 || it >= 5;
  const int b = maps.id[blockIdx.x][it >= 5];
  which = q ? 0 : 2 - (it & 1);
  m_tile = b & 15;
  n_tile = (b >> 4) * 2 + ((0x19 >> it) & 1);
}

constexpr int G_NTILES = 6;
__device__ __forceinline__ void qkv_producer(const Maps& maps, uint32_t sbase, bool first) {
  const uint32_t bar = sbase + BAR_OFF;
  uint32_t stage = 0, phase = 0;
#pragma unroll 1
  for (int it = 0; it < (first ? 1 : G_NTILES); it++) {
    int which, m_tile, n_tile;
    qkv_tile(maps, it, which, m_tile, n_tile);
    const CUtensorMap* ma = &maps.a[which == 0 ? 0 : 1];
    const CUtensorMap* mb = &maps.b[which];
    const int nk = first ? G_STAGES : which == 0 ? 16 : 8;
#pragma unroll 1
    for (int kt = (it == 0 && !first) ? G_STAGES : 0; kt < nk; kt++) {
      if (!first) mbar_wait_sleep(bar + B_GEMPTY + 8 * stage, phase);
      const uint32_t fb = bar + B_GFULL + 8 * stage;
      const uint32_t sa = sbase + stage * G_STAGE_BYTES;
      mbar_expect_tx(fb, G_STAGE_BYTES);
      tma_load_2d(sa, ma, fb, kt * 64, m_tile * 128);
      tma_load_3d(sa + G_A_BYTES, mb, fb, 0, kt * 64, n_tile * 4);
      if (++stage == G_STAGES) { stage = 0; phase ^= 1; }
      {
        const int b = maps.id[blockIdx.x][1];
        if (it == 2 && kt == (b & 7)) {
          for (int i = 0; i < 2; i++)
            asm volatile("cp.async.bulk.prefetch.tensor.2d.L2.global.tile [%0, {%1, %2}];" ::"l"(&maps.a[0]),
                         "r"((b >> 4) * 128 + i * 64), "r"((b & 15) * 128)
                         : "memory");
        }
        if (it == 3 && kt == (b & 7))
          asm volatile("cp.async.bulk.prefetch.tensor.3d.L2.global.tile [%0, {%1, %2, %3}];" ::"l"(&maps.b[0]), "r"(0),
                       "r"((b & 15) * 64), "r"((b >> 4) * 8)
                       : "memory");
      }
    }
  }
}

__device__ __forceinline__ uint32_t seen_bar(uint32_t item) { return B_SEEN + ((0x700800u >> (8 * item)) & 255); }
__device__ __noinline__ void publisher(uint32_t bar, int lane, uint32_t nsrc, uint32_t item, uint32_t mine) {
  uint32_t done = 0, tot = 0;
#pragma unroll 1
  for (uint32_t spins = 0; (done < nsrc || item < 3) && spins < (1u << 20); spins++) {
    const uint32_t cnt = item ? CNT_CTX - 1 + item : CNT_KV + 1;
    if (item < 3 && __shfl_sync(0xffffffffu, tot, cnt) >= mine) {
      uint32_t v;
      asm volatile("ld.acquire.gpu.global.u32 %0, [%1];" : "=r"(v) : "l"(g_cnt + (lane ? cnt : CNT_PREP) * 32) : "memory");
      if (__all_sync(0xffffffffu, v >= (lane ? 512 : 260))) {
        asm volatile("fence.proxy.async.global;" ::: "memory");
        mbar_arrive_if(bar + seen_bar(item), lane == 0);
        item++;
      }
    }
    uint32_t v = 0;
    if (lane < CNT_N)
      asm volatile("atom.acquire.cta.shared.exch.b32 %0, [%1], 0;" : "=r"(v) : "r"(bar + B_PEND + 4 * lane) : "memory");
    done += __shfl_sync(0xffffffffu, v, CNT_DONE);
    if (lane == CNT_DONE) v = 0;
    if (done == nsrc && lane < CNT_DONE) {
      uint32_t w;
      asm volatile("atom.acquire.cta.shared.exch.b32 %0, [%1], 0;" : "=r"(w) : "r"(bar + B_PEND + 4 * lane) : "memory");
      v += w;
    }
    if (v && lane == 0) { TD(0) }
    if (v) cnt_signal_release(lane, v);
    tot += v;
    if (v && lane == 0) { TD(1) }
    if (!__any_sync(0xffffffffu, v != 0)) __nanosleep(200);
  }
  __threadfence();
  __syncwarp();
}

__device__ __forceinline__ void gate_rows(const Maps& maps, uint32_t sbase, int w48, int w12, int lane) {
  const uint32_t buf = sbase + w12 * 16384, gb = sbase + BAR_OFF + 768 + w12 * 16;
  if (lane == 0) {
    mbar_init(gb, 1);
    mbar_init(gb + 8, 1);
    fence_barrier_init();
    for (int i = 0; i < 2; i++) {
      mbar_expect_tx(gb + 8 * i, 8192);
      bulk_load(buf + i * 8192, maps.x + (size_t)(w48 + 48 * i) * 4 * DM, 8192, gb + 8 * i);
    }
  }
  __syncwarp();
  uint4 wv[4];
#pragma unroll
  for (int i = 0; i < 4; i++) wv[i] = __ldg(reinterpret_cast<const uint4*>(maps.gate_w + (i * 32 + lane) * 8));
  int it = 0;
#pragma unroll 1
  for (int row = w48 * 4; row < S_LEN; row += 48 * 4, it++) {
    mbar_wait(gb + 8 * (it & 1), (it >> 1) & 1);
    uint4 xv[4][4];
#pragma unroll
    for (int r = 0; r < 4; r++)
#pragma unroll
      for (int i = 0; i < 4; i++) xv[r][i] = lds128(buf + (it & 1) * 8192 + r * 2048 + (i * 32 + lane) * 16);
    float d[2][4];
#pragma unroll
    for (int pr = 0; pr < 2; pr++) {
      d[pr][0] = d[pr][1] = d[pr][2] = d[pr][3] = 0.f;
      auto acc = [&](uint32_t a0, uint32_t a2, uint32_t b0, uint32_t b2, uint32_t w0, uint32_t w2) {
        asm volatile(
            "mma.sync.aligned.m16n8k16.row.col.f32.bf16.bf16.f32 {%0, %1, %2, %3}, {%4, %5, %6, %7}, {%8, %8}, "
            "{%0, %1, %2, %3};"
            : "+f"(d[pr][0]), "+f"(d[pr][1]), "+f"(d[pr][2]), "+f"(d[pr][3])
            : "r"(mul_bf2(a0, w0)), "r"(mul_bf2(b0, w0)), "r"(mul_bf2(a2, w2)), "r"(mul_bf2(b2, w2)), "r"(0x3f803f80u));
      };
#pragma unroll
      for (int i = 0; i < 4; i++) {
        acc(xv[2 * pr][i].x, xv[2 * pr][i].y, xv[2 * pr + 1][i].x, xv[2 * pr + 1][i].y, wv[i].x, wv[i].y);
        acc(xv[2 * pr][i].z, xv[2 * pr][i].w, xv[2 * pr + 1][i].z, xv[2 * pr + 1][i].w, wv[i].z, wv[i].w);
      }
    }
    float sum = (lane & 2) ? ((lane & 1) ? d[1][2] : d[1][0]) : ((lane & 1) ? d[0][2] : d[0][0]);
#pragma unroll
    for (int off = 16; off >= 4; off >>= 1) sum += __shfl_xor_sync(0xffffffffu, sum, off);
    if (lane < 4) g_gate[row + lane] = bf16_round(rcp(1.0f + __expf(-bf16_round(sum))));
    if (lane == 0 && row + 2 * 48 * 4 < S_LEN) {
      mbar_expect_tx(gb + 8 * (it & 1), 8192);
      bulk_load(buf + (it & 1) * 8192, maps.x + (size_t)(row + 2 * 48 * 4) * DM, 8192, gb + 8 * (it & 1));
    }
  }
}

constexpr float Q_SCALE = 0.08838834764831845f * 1.4426950408889634f;
__device__ __forceinline__ uint32_t qkv_consumer(const Maps& maps, uint32_t smem0, bool fused, float (&rest)[64]) {
  PHASE_PROLOGUE
  constexpr int NTILES = G_NTILES;
  float acc[128];
  uint32_t stage = 0, phase = 0;
  const uint32_t stg = sbase + G_STG_OFF + wg * 18432;
  const int st_row = warp * 16 + (lane & 7) + ((lane >> 3) & 1) * 8;
  const int st_cb = lane >> 4;
  uint32_t pend[64];
  const CUtensorMap* pend_map = nullptr;
  int pend_c0 = 0, pend_c1 = 0;
  uint32_t sn = 0;
  auto put_box = [&](uint32_t buf, const uint32_t* v) {
#pragma unroll
    for (int jp = 0; jp < 4; jp++) {
      const int chunk = jp * 2 + st_cb;
      const uint32_t addr = buf + st_row * 128 + ((chunk ^ (st_row & 7)) << 4);
      stmatrix_x4(addr, v[jp * 4], v[jp * 4 + 1], v[jp * 4 + 2], v[jp * 4 + 3]);
    }
  };
  GT(gti++)
#pragma unroll 1
  for (int it = 0; it <= NTILES; it++) {
    int which, m_tile, n_tile;
    qkv_tile(maps, it, which, m_tile, n_tile);
    const int nk = (which == 0 && it < NTILES) ? 16 : 8;
    uint32_t prev_stage = 0;
#pragma unroll 1
    for (int kt = 0; kt < nk; kt++) {
      if (it < NTILES) {
        mbar_wait((bar + B_GFULL) + 8 * stage, phase);
        GT(gti++)
        const uint64_t da0 = make_desc(sbase + stage * G_STAGE_BYTES + wg * 8192, 16, 1024, DESC_SW128);
        const uint64_t db0 = make_desc(sbase + stage * G_STAGE_BYTES + G_A_BYTES, 8192, 1024, DESC_SW128);
        wgmma_fence();
#pragma unroll
        for (int kk = 0; kk < 4; kk++) {
          wgmma_m64n256_ss_tb(acc, desc_add(da0, kk * 2), desc_add(db0, kk * 128), (kt | kk) != 0);
        }
        wgmma_commit();
      }
      const uint32_t when = it == 0 ? 0 : it == 5 ? 0x922 << wg : wg ? 0xAA : 0x55;
      if ((when >> kt) & 1) {
        const int c = __popc(when & ~(~0u << kt));
        st_wait(bar, wg, sn - 2);
        const uint32_t buf = stg + (c & 1) * 8192;
        switch (c) {
          case 0: put_box(buf, pend); break;
          case 1: put_box(buf, pend + 16); break;
          case 2: put_box(buf, pend + 32); break;
          default: put_box(buf, pend + 48); break;
        }
        st_post(bar, wg, wtid, sn, ST_BOX1, pend_map, buf, pend_c0 + c * 64, pend_c1, (c == 3 && it > 1) ? CNT_KV + (it > 3) : -1);
        sn++;
      }
      if (it < NTILES) {
        wgmma_wait<1>();
        mbar_arrive_if((bar + B_GEMPTY) + 8 * prev_stage, wtid == 32 && kt > 0);
        prev_stage = stage;
        if (++stage == G_STAGES) { stage = 0; phase ^= 1; }
      }
    }
    wgmma_wait<0>();
    fence_regs(acc);
    if (it == NTILES) break;
    GT(gti++)
    mbar_arrive_if((bar + B_GEMPTY) + 8 * prev_stage, wtid == 32);
    if (it == NTILES - 1 && fused) break;
    if (which == 0) {
#pragma unroll
      for (int j = 0; j < 128; j++) acc[j] *= Q_SCALE;
    }
#pragma unroll
    for (int j = 0; j < 64; j++) pend[j] = pack_bf16(acc[2 * j], acc[2 * j + 1]);
    pend_map = &maps.c[which];
    pend_c0 = n_tile * 256;
    pend_c1 = m_tile * 128 + wg * 64;
  }
  mbar_wait(bar + B_GEMPTY, 1);
#pragma unroll
  for (int j = 0; j < 32; j++) pend[j] = pack_bf16(acc[2 * j] * Q_SCALE, acc[2 * j + 1] * Q_SCALE);
  put_box(sbase + wg * 8192, pend);
  put_box(sbase + 16384 + wg * 8192, pend + 16);
  fence_proxy_async();
#pragma unroll
  for (int j = 0; j < 64; j++) rest[j] = acc[64 + j];
  GT(gti++)
  return sn;
}

constexpr int A_TILE = 128 * 128 * 2;
constexpr int A_Q_OFF = 0;
constexpr int A_K_OFF = 2 * A_TILE;
constexpr int A_V_OFF = 4 * A_TILE;
constexpr int A_O_OFF = 6 * A_TILE;
constexpr int A_ITEMS = NH * (S_LEN / 128);

constexpr uint32_t A_ORDER = 0x3120, A_STEPS = 34;
__device__ __forceinline__ int item_m(uint32_t it) { return it & 15; }
__device__ __forceinline__ int item_h(uint32_t it) { return it >> 4; }

constexpr int C_V = 16384, C_MAT = 24576;
constexpr float C_ALPHA = 0.07874506561842957f;
__device__ __forceinline__ void sincos_turn(int p, float inv, float& c, float& s) {
  const float a = (float)p * (inv * 6.283185307179586f);
  asm("cos.approx.ftz.f32 %0, %1;" : "=f"(c) : "f"(a));
  asm("sin.approx.ftz.f32 %0, %1;" : "=f"(s) : "f"(a));
}

__device__ __forceinline__ uint32_t item_of(const Maps& maps, uint32_t r) {
  const uint32_t b = maps.id[blockIdx.x & 127][1];
  return (b >> 4) * 64 + ((A_ORDER >> (4 * r)) & 3) * 16 + ((b ^ ((r & 1) * 15)) & 15);
}

#define PACE 250
#define XMASK 3
#define XFIRST 4
#define C_SIDE 64
__device__ __forceinline__ uint32_t conv_first(const Maps& maps) {
  const uint32_t b = maps.id[blockIdx.x & 127][1];
  return (b >> 4) * 128 + ((b + 15) & 15);
}

__device__ __forceinline__ void conv_consumer(const Maps& maps, uint32_t smem0, uint32_t first, uint32_t step,
                                              uint32_t end, bool pp) {
  PHASE_PROLOGUE
  const uint32_t in_full = bar + B_CFULL + wg * 16;
  const uint32_t ca = sbase + (wg ? A_V_OFF + A_TILE : A_Q_OFF);
  const int w = __shfl_sync(0xffffffffu, warp, 0), g = lane >> 2, c = lane & 3;
  auto fetch = [&](uint32_t ch, uint32_t n) {
    if (w == 2 && ch < end) {
      if (elect_one()) {
        const uint32_t b = in_full + (n & 1) * 8, d = ca + (n & 1) * 8192;
        const uint64_t pol = policy_evict_first();
        mbar_expect_tx(b, 8192);
        tma_load_2d_hint(d, &maps.cu, b, 0, ch * 64, pol);
        tma_load_2d_hint(d + 4096, &maps.ch, b, 0, ch * 64, pol);
      }
    }
  };
  if (wtid == 96 && wg) { TD(15) }
  uint32_t f1[8][4];
  float tt[16], ts[16];
  uint32_t cc[4], ss[4];
#pragma unroll
  for (int i = 0; i < 16; i++) {
    const int k = 2 * (16 * w + g + 8 * (i & 1)) + 1, n = 2 * (8 * (i >> 1) + 2 * c) + 1;
    float c0, s0, c1, s1;
    sincos_turn(((k * n) << 23) >> 23, 1.f / 512, c0, s0);
    sincos_turn(((k * n + 2 * k) << 23) >> 23, 1.f / 512, c1, s1);
    f1[i >> 2][i & 3] = pack_bf16(c0 * C_ALPHA, c1 * C_ALPHA);
    f1[4 + (i >> 2)][i & 3] = pack_bf16(s0 * -C_ALPHA, s1 * -C_ALPHA);
  }
#pragma unroll
  for (int i = 0; i < 16; i++) {
    const int k = 2 * (16 * w + g + 8 * ((i >> 1) & 1)) + 1, n = 16 - (8 * (i >> 2) + 2 * c + (i & 1));
    float cs;
    sincos_turn(k * n, 1.f / 8192, cs, ts[i]);
    tt[i] = ts[i] * rcp(1.f + cs);
  }
#pragma unroll
  for (int j = 0; j < 4; j++) {
    const int k = 8 * w + g, n = 8 * c + 2 * j;
    float c0, s0, c1, s1;
    sincos_turn((int8_t)(k * n * 8), 1.f / 256, c0, s0);
    sincos_turn((int8_t)((k * n + k) * 8), 1.f / 256, c1, s1);
    cc[j] = pack_bf16(c0, c1);
    ss[j] = pack_bf16(s0, s1);
  }
  named_bar_sync(3, 256);
  fetch(first, 0);
  fetch(first + step, 1);
  const uint32_t va = ca + g * 64 + ((c ^ (g >> 1)) << 4);
  {
    const uint32_t a = va + C_MAT + w * 512, m = 0x80008000u;
    sts128(a, make_uint4(cc[0], cc[1], cc[2], cc[3]));
    sts128(a + 2048, make_uint4(ss[0], ss[1], ss[2], ss[3]));
    sts128(a + 4096, make_uint4(ss[0] ^ m, ss[1] ^ m, ss[2] ^ m, ss[3] ^ m));
    sts128(a + 6144, make_uint4(cc[0], cc[1], cc[2], cc[3]));
  }
  fence_proxy_async();
  named_bar_sync(1 + wg, 128);
  constexpr uint64_t DHI = (2ull << 62) | ((uint64_t)(512 >> 4) << 32);
  const uint32_t d0 = (uint32_t)make_desc(ca, 4096, 0, 0);
  float a5[16];
  uint4* const yb = reinterpret_cast<uint4*>(g_y2T) + (16 * w + g) * 4 + c;
  auto issue5 = [&]() {
#pragma unroll
    for (int ks = 0; ks < 8; ks++) wgmma_m64n32_rs_tb(a5, f1[ks], DHI | (d0 + (C_V >> 4) + ks * 64), ks != 0);
    wgmma_commit();
  };
  auto finish = [&](uint32_t ch, bool on) {
    fence_regs(a5);
    uint4* y = yb + (size_t)ch * 256;
    if (on) {
      y[0] = make_uint4(pack_bf16(a5[0], a5[1]), pack_bf16(a5[4], a5[5]), pack_bf16(a5[8], a5[9]), pack_bf16(a5[12], a5[13]));
      y[32] = make_uint4(pack_bf16(a5[2], a5[3]), pack_bf16(a5[6], a5[7]), pack_bf16(a5[10], a5[11]), pack_bf16(a5[14], a5[15]));
    }
  };
  auto dft32 = [&](float (&d)[32], const float* re, const float* im) {
    uint32_t a[4][4];
#pragma unroll
    for (int i = 0; i < 8; i++) {
      a[i >> 2][i & 3] = pack_bf16(re[2 * i], re[2 * i + 1]);
      a[2 + (i >> 2)][i & 3] = pack_bf16(im[2 * i], im[2 * i + 1]);
    }
    wgmma_fence();
#pragma unroll
    for (int ks = 0; ks < 4; ks++) wgmma_m64n64_rs_tb(d, a[ks], DHI | (d0 + (C_MAT >> 4) + ks * 64), ks != 0);
    wgmma_commit();
  };
  auto rot = [&](float* x, float* y) {
#pragma unroll
    for (int i = 0; i < 16; i++) {
      x[i] = fmaf(-tt[i], y[i], x[i]);
      y[i] = fmaf(ts[i], x[i], y[i]);
      x[i] = fmaf(-tt[i], y[i], x[i]);
    }
  };
  auto load_d = [&](uint32_t ch) {
    return __ldg(reinterpret_cast<const unsigned short*>(maps.ssm_D) + ((ch & (DM - 1)) | (lane & rt_zero)));
  };
  uint32_t dn = load_d(first);
  uint32_t n = 0, ch = first;
#pragma unroll 1
  for (; ch < end; n++, ch += step) {
    CT(0)
    float a1[2][32], a2[2][32], a4[32];
    const float dsk = c ? 0.f : __uint_as_float(dn << 16) * C_ALPHA;
    dn = load_d(ch + step);
    mbar_wait(in_full + (n & 1) * 8, (n >> 1) & 1);
    if (pp) named_bar_sync(4 + wg, 256);
    CT(1)
    wgmma_fence();
#pragma unroll
    for (int ks = 0; ks < 8; ks++)
      wgmma_m64n64_rs_tb(a1[ks >> 2], f1[ks], DHI | (d0 + (n & 1) * 512 + (ks & 3) * 64), (ks & 3) != 0);
    wgmma_commit();
    issue5();
    wgmma_wait<1>();
    fence_regs(a1[0]);
    fence_regs(a1[1]);
    CT(2)
    rot(a1[0], a1[1]);
    dft32(a2[0], a1[0], a1[1]);
    rot(a1[0] + 16, a1[1] + 16);
    a1[0][16] += dsk;
    a1[0][18] += dsk;
    dft32(a2[1], a1[0] + 16, a1[1] + 16);
    CT(3)
    wgmma_wait<2>();
    finish(ch - step, n > 0);
    wgmma_wait<0>();
    fence_regs(a2[0]);
    fence_regs(a2[1]);
    CT(4)
    if (pp) named_bar_arrive(5 - wg, 256);
    float re[16], im[16];
#pragma unroll
    for (int i = 0; i < 16; i++) {
      re[i] = a2[0][i] * a2[1][i] - a2[0][16 + i] * a2[1][16 + i];
      im[i] = a2[0][i] * a2[1][16 + i] + a2[0][16 + i] * a2[1][i];
    }
    dft32(a4, im, re);
    wgmma_wait<0>();
    fence_regs(a4);
    CT(5)
    rot(a4, a4 + 16);
#pragma unroll
    for (int i = 0; i < 4; i++) {
      const float* x = a4 + 16 - 16 * (i >> 1) + 2 * (i & 1);
      sts128(va + C_V + w * 1024 + (i >> 1) * 4096 + (i & 1) * 512,
             make_uint4(pack_bf16(x[0], x[1]), pack_bf16(x[4], x[5]), pack_bf16(x[8], x[9]), pack_bf16(x[12], x[13])));
    }
    CT(6)
    fence_proxy_async();
    named_bar_sync(1 + wg, 128);
    fetch(ch + 2 * step, n);
    if (wtid == 96 && n > 0) note(bar, CNT_Y2 + (((ch - step) & 112) == 112));
    CT(7)
  }
  wgmma_fence();
  issue5();
  wgmma_wait<0>();
  finish(ch - step, true);
  named_bar_sync(1 + wg, 128);
  if (wtid == 96 && wg) { TD(8) }
  if (wtid == 96) cnt_signal_release(CNT_Y2 + (((ch - step) & 112) == 112), 1);
  if (wtid == 64) note(bar, CNT_DONE);
  if (wtid == 96 && wg) { TD(9) }
}

__device__ __forceinline__ void attn_producer(const Maps& maps, uint32_t sbase, bool after_qkv, bool to_out,
                                              bool dry) {
  const uint32_t bar = sbase + BAR_OFF;
  const uint32_t q_full = bar + B_QFULL, q_empty = bar + B_QEMPTY;
  const uint32_t k_full = bar + B_KFULL, k_empty = bar + B_KEMPTY, v_full = bar + B_VFULL, v_empty = bar + B_VEMPTY;
  int ndrained = after_qkv ? 0 : G_STAGES;
  auto wait = [&](uint32_t b, uint32_t par) {
    if (!dry) mbar_wait_sleep(b, par);
  };
  auto drained = [&](int upto) {
#pragma unroll 1
    for (; ndrained <= upto; ndrained++) wait(bar + B_GEMPTY + 8 * ndrained, 1);
  };
  uint32_t st = 0, ph = 1, vs = 0, vp = 1;
  int pend_j = -1, pend_h = 0;
  int round = -1, m = -1, h = 0;
  bool last = false;
#pragma unroll 1
  for (;; round++) {
    uint32_t nitem = 0;
    const int tpost = m >= 3 ? m - 1 : m;
#pragma unroll 1
    for (int t = m < 0 ? -1 : 0; t <= m; t++) {
      const int j = (t < m && (round & 1)) ? m - 1 - t : t;
      if (t >= 0) {
        drained(1 + st);
        wait(k_empty + 8 * st, ph);
        if (!dry) {
          mbar_expect_tx(k_full + 8 * st, A_TILE);
          tma_load_3d(sbase + A_K_OFF + st * A_TILE, &maps.k, k_full + 8 * st, 0, j * 128, h * 2);
        }
        if (++st == 2) { st = 0; ph ^= 1; }
      }
      if (pend_j >= 0) {
        drained(3);
        wait(v_empty + 8 * vs, vp);
        if (!dry) {
          mbar_expect_tx(v_full + 8 * vs, A_TILE);
          tma_load_3d(sbase + A_V_OFF + vs * A_TILE, &maps.v, v_full + 8 * vs, 0, pend_j * 128, pend_h * 2);
        }
        if (++vs == 2) { vs = 0; vp ^= 1; }
      }
      pend_j = j;
      pend_h = h;
      if (t == tpost && !last) {
        nitem = dry ? 1 : item_of(maps, round + 1);
        if (round == (dry ? 0 : 3) || blockIdx.x >= 128) {
          nitem = A_ITEMS;
          if (!to_out) cnt_wait(CNT_PREP, dry ? 0 : 260);
          if (to_out) {
            wait(bar + seen_bar(1), 0);
            asm volatile("cp.async.bulk.prefetch.L2.global [%0], 4096;" ::"l"(maps.ssm_k + (size_t)conv_first(maps) * S_LEN));
            if (!dry)
              asm volatile("cp.async.bulk.prefetch.L2.global [%0], 4096;" ::"l"(g_kvT + (size_t)conv_first(maps) * S_LEN));
          }
        }
        const uint32_t qs = (round + 1) & 1;
        wait(q_empty + 8 * qs, (((round + 1) >> 1) & 1) ^ 1);
        if (round == 1 && after_qkv) wait(bar + B_QDONE, 0);
        if (round == 0 && after_qkv) wait(bar + seen_bar(0), 0);
        if (round < 0 && after_qkv) {
          if (!dry) { TD(2) }
          cnt_wait(CNT_KV, dry ? 0 : 512);
          if (!dry) { TD(3) }
        }
        if (nitem >= A_ITEMS || (round < 0 && after_qkv && !dry)) {
          if (!dry) mbar_arrive(q_full + 8 * qs);
        } else {
          drained(qs);
          if (!dry) {
            mbar_expect_tx(q_full + 8 * qs, A_TILE);
            tma_load_3d_hint(sbase + A_Q_OFF + qs * A_TILE, &maps.q, q_full + 8 * qs, 0, item_m(nitem) * 128,
                             item_h(nitem) * 2, policy_evict_first());
          }
        }
      }
    }
    if (last) break;
    last = nitem >= A_ITEMS;
    m = last ? -1 : item_m(nitem);
    h = item_h(nitem);
  }
}

__device__ __forceinline__ uint32_t attn_consumer(const Maps& maps, uint32_t smem0, uint32_t sn,
                                                  float (&rest)[64], bool after_qkv) {
  PHASE_PROLOGUE
  const uint32_t q_full = bar + B_QFULL, q_empty = bar + B_QEMPTY;
  const uint32_t k_full = bar + B_KFULL, k_empty = bar + B_KEMPTY, v_full = bar + B_VFULL;
  float o[64], s[64];
  uint32_t p[32];
  float e[32];
  uint32_t dep = 0;
  constexpr int MIDJ = 5;
  float l0 = 0.f, l1 = 0.f, b0 = 0.f, b1 = 0.f;
  const int sched_own = 4 + wg, sched_other = 5 - wg;
  if (wg == 1) named_bar_arrive(4, 256);

  const uint32_t qd0 = (uint32_t)make_desc(sbase + A_Q_OFF + wg * 8192, 16, 0, 0);
  const uint32_t kd0 = (uint32_t)make_desc(sbase + A_K_OFF, 16, 0, 0);
  const uint32_t vd0 = (uint32_t)make_desc(sbase + A_V_OFF, 16384, 0, 0);
  constexpr uint64_t DHI = DESC_SW128 | ((uint64_t)(1024 >> 4) << 32);
  constexpr uint32_t DST = A_TILE >> 4;
  auto issue_qk = [&](uint32_t qd, uint32_t kd) {
#pragma unroll
    for (int kk = 0; kk < 8; kk++) {
      const uint32_t off = ((kk >> 2) * 16384 + (kk & 3) * 32) >> 4;
      wgmma_m64n128_ss(s, DHI | (qd + off), DHI | (kd + off), kk != 0);
    }
    wgmma_commit();
  };
  auto issue_pv = [&](uint32_t vd, bool accumulate, int nk) {
#pragma unroll
    for (int kk = 0; kk < 8; kk++) {
      if (kk < nk)
        wgmma_m64n128_rs_tb(o, p[4 * kk], p[4 * kk + 1], p[4 * kk + 2], p[4 * kk + 3], DHI | (vd + kk * 128),
                            accumulate || (kk != 0));
    }
    wgmma_commit();
  };
  auto exp_lo = [&](float& a0, float& a1) {
#pragma unroll
    for (int j = 0; j < 8; j++) {
      e[4 * j] = ex2(s[4 * j]);
      e[4 * j + 1] = ex2(s[4 * j + 1]);
      e[4 * j + 2] = ex2(s[4 * j + 2]);
      e[4 * j + 3] = ex2(s[4 * j + 3]);
      a0 += e[4 * j];
      a0 += e[4 * j + 1];
      a1 += e[4 * j + 2];
      a1 += e[4 * j + 3];
      if (j == MIDJ) dep = (__float_as_uint(a0) | __float_as_uint(a1)) & rt_zero;
    }
  };
  auto pack_lo = [&]() {
#pragma unroll
    for (int j = 0; j < 16; j++) p[j] = pack_bf16(e[2 * j], e[2 * j + 1]);
  };
  auto finish_p = [&](float& a0, float& a1) {
    pack_lo();
#pragma unroll
    for (int j = 8; j < 16; j++) {
      const float e0 = ex2(s[4 * j]), e1 = ex2(s[4 * j + 1]), e2 = ex2(s[4 * j + 2]), e3 = ex2(s[4 * j + 3]);
      a0 += e0;
      a0 += e1;
      a1 += e2;
      a1 += e3;
      p[2 * j] = pack_bf16(e0, e1);
      p[2 * j + 1] = pack_bf16(e2, e3);
      if (j == 8 + MIDJ) dep = __float_as_uint(a0) & rt_zero;
    }
  };
  auto quad_sum = [&](float t) {
    t += __shfl_xor_sync(0xffffffffu, t, 1);
    return t + __shfl_xor_sync(0xffffffffu, t, 2);
  };
  auto write_o = [&](float i0, float i1) {
    st_wait(bar, wg, sn - 1);
    const int st_row = warp * 16 + (lane & 7) + ((lane >> 3) & 1) * 8;
    const uint32_t so = sbase + A_O_OFF + wg * 16384 + st_row * 128;
#pragma unroll
    for (int j = 0; j < 16; j += 2)
      stmatrix_x4(so + (j >> 3) * 8192 + ((((j & 7) + (lane >> 4)) ^ (lane & 7)) << 4),
                  pack_bf16(o[4 * j] * i0, o[4 * j + 1] * i0), pack_bf16(o[4 * j + 2] * i1, o[4 * j + 3] * i1),
                  pack_bf16(o[4 * j + 4] * i0, o[4 * j + 5] * i0), pack_bf16(o[4 * j + 6] * i1, o[4 * j + 7] * i1));
  };
  auto store_o = [&](uint32_t r, int kind) {
    const uint32_t it = item_of(maps, r);
    st_post(bar, wg, wtid, sn, kind, (INPLACE & 1) || kind != ST_BOX2Q ? &maps.o : &maps.c[0], sbase + A_O_OFF + wg * 16384, item_h(it) * 128,
            item_m(it) * 128 + wg * 64, CNT_CTX + (r >> 1));
    sn++;
  };
  auto mask_half = [&](float* sh) {
    const int u = warp * 16 + (lane >> 2) - (lane & 3) * 2;
#pragma unroll
    for (int j = 0; j < 8; j++) {
      if (8 * j > u) sh[4 * j] = -INFINITY;
      if (8 * j + 1 > u) sh[4 * j + 1] = -INFINITY;
      if (8 * j - 8 > u) sh[4 * j + 2] = -INFINITY;
      if (8 * j - 7 > u) sh[4 * j + 3] = -INFINITY;
    }
  };
  ST(0)
  mbar_wait(q_full, 0);
  if (blockIdx.x >= 128) {
    return sn;
  }
  mbar_wait(k_full, 0);
  named_bar_sync(sched_own, 256);
  wgmma_fence();
  issue_qk(qd0, kd0);
  named_bar_arrive(sched_other, 256);
  fence_regs(rest);
#pragma unroll
  for (int i = 0; i < 64; i++) o[i] = rest[i] * Q_SCALE;
  fence_regs(o);
  wgmma_wait<0>();
  fence_regs(s);
  mbar_arrive_if(k_empty, wtid == 32);
  uint32_t g = 0;
  uint32_t rnd = 0;
  int rem = item_m(item_of(maps, 0));
  uint32_t first = 1;
  uint32_t fl = 0;
#define redo (fl & 1)
#define shifted (fl & 2)
  float d0 = 0.f, d1 = 0.f;
  float pi0 = 1.f, pi1 = 1.f;
  ST(1)
  for (;;) {
    if (shifted) {
#pragma unroll
      for (int j = 0; j < 16; j++) {
        s[4 * j] -= d0;
        s[4 * j + 1] -= d0;
        s[4 * j + 2] -= d1;
        s[4 * j + 3] -= d1;
      }
    }
    if (rem == 0 && !redo) {
      mbar_arrive_if(q_empty + 8 * (rnd & 1), wtid == 96);
      rnd++;
      if (wg == 0) mask_half(s);
      else mask_half(s + 32);
    }
    for (;;) {
      const bool kill = rem == 0 && wg == 0;
      const uint32_t kd = kd0 + ((g + 1) & 1) * DST, vd = vd0 + (g & 1) * DST;
      float a0 = 0.f, a1 = 0.f;
      exp_lo(a0, a1);
      fence_regs(e);
      const uint32_t kb = k_full + 8 * ((g + 1) & 1);
      const uint32_t kpar = ((((g + 1) >> 1) & 1) ^ (g == A_STEPS - 1 ? 1u : 0u)) | dep;
      if (!mbar_try(kb, kpar)) mbar_wait(kb, kpar | ((__float_as_uint(a0) | __float_as_uint(a1)) & rt_zero));
      wgmma_wait<0>();
      fence_regs(o);
      if (kill) {
        mbar_arrive_if(kb + (B_VEMPTY - B_KFULL), wtid == 64 && !redo && g > 0);
        fence_regs(e);
        pack_lo();
#pragma unroll
        for (int j = 16; j < 32; j++) asm volatile("mov.u32 %0, 0;" : "=r"(p[j]));
        goto check;
      }
#pragma unroll
      for (int i = 32; i < 64; i++) asm volatile("" : "+f"(s[i])::"memory");
      mbar_arrive_if(kb + (B_VEMPTY - B_KFULL), wtid == 64 && !redo && g > 0);
      finish_p(a0, a1);
      if (__any_sync(0xffffffffu, !(mbar_try(v_full + 8 * (g & 1), ((g >> 1) & 1) | dep) &
                                    mbar_try(q_full + 8 * (rnd & 1), ((rnd >> 1) & 1) | dep)) ||
                                      !(a0 + a1 < 1.0995116e12f) || !(fminf(a0, a1) > (first ? 9.094947e-13f : -1.f)))) {
      check:
        bool bad = !(a0 + a1 < 1.0995116e12f);
        if (first) bad |= !(fminf(quad_sum(a0), quad_sum(a1)) > 9.094947e-13f);
        if (!redo && __any_sync(0xffffffffu, bad)) {
          d0 = d1 = first ? -INFINITY : 0.f;
#pragma unroll
          for (int j = 0; j < 16; j++) {
            if (j < 8 || !kill) {
              d0 = fmaxf(d0, fmaxf(s[4 * j], s[4 * j + 1]));
              d1 = fmaxf(d1, fmaxf(s[4 * j + 2], s[4 * j + 3]));
            }
          }
#pragma unroll
          for (int x = 1; x <= 2; x++) {
            d0 = fmaxf(d0, __shfl_xor_sync(0xffffffffu, d0, x));
            d1 = fmaxf(d1, __shfl_xor_sync(0xffffffffu, d1, x));
          }
          b0 += d0;
          b1 += d1;
          if (!first) {
            const float al0 = ex2(-d0), al1 = ex2(-d1);
            l0 *= al0;
            l1 *= al1;
#pragma unroll
            for (int j = 0; j < 16; j++) {
              o[4 * j] *= al0;
              o[4 * j + 1] *= al0;
              o[4 * j + 2] *= al1;
              o[4 * j + 3] *= al1;
            }
          }
          fl = 3;
          break;
        }
        mbar_wait(v_full + 8 * (g & 1), (g >> 1) & 1);
        mbar_wait(q_full + 8 * (rnd & 1), (rnd >> 1) & 1);
      }
      named_bar_sync(sched_own, 256);
      if (g == A_STEPS - 1) {
        if (first) write_o(pi0, pi1);
        fence_regs(o);
        wgmma_fence();
        issue_pv(vd, !first, 8);
        named_bar_arrive(sched_other, 256);
        if (first) store_o(rnd - 2, ST_BOX2);
        pi0 = rcp(quad_sum(l0 + a0));
        pi1 = rcp(quad_sum(l1 + a1));
        goto done;
      }
      wgmma_fence();
      issue_qk(qd0 + (rnd & 1) * DST, kd);
      if (first) write_o(pi0, pi1);
      fence_regs(o);
      if (kill) {
        wgmma_fence();
        issue_pv(vd, !first, 4);
      } else {
        wgmma_fence();
        issue_pv(vd, !first, 8);
      }
      named_bar_arrive(sched_other, 256);
      fl &= 2;
      l0 += a0;
      l1 += a1;
      if (rem == 0 || first) {
        if (first && (g > 0 || after_qkv)) store_o(g ? rnd - (rem == 0 ? 2 : 1) : 2, g ? ST_BOX2 : ST_BOX2Q);
        first = rem == 0;
        if (first) {
          pi0 = rcp(quad_sum(l0));
          pi1 = rcp(quad_sum(l1));
          l0 = l1 = b0 = b1 = 0.f;
          fl = 0;
          rem = item_m(item_of(maps, rnd)) + 1;
        }
      }
      rem--;
      g++;
      wgmma_wait<1>();
      fence_regs(s);
      mbar_arrive_if(kb + (B_KEMPTY - B_KFULL), wtid == 32);
      ST(g + 1)
      if (rem == 0 || shifted) {
        d0 = b0;
        d1 = b1;
        break;
      }
    }
  }
done:
#undef redo
#undef shifted
  wgmma_wait<0>();
  fence_regs(o);
  write_o(pi0, pi1);
  store_o(3, ST_BOX2L);
  ST(35)
  return sn;
}

constexpr int O_STAGES = 5;
constexpr int O_STAGE_BYTES = 32768;
constexpr int O_Y_OFF = 5 * 32768;
constexpr int O_X_OFF = 6 * 32768;
constexpr int O_NK = HDIM / 64;

__device__ __forceinline__ uint32_t out_stage(uint32_t st) { return ((0x43120u >> (4 * st)) & 7) * O_STAGE_BYTES; }

__device__ __forceinline__ void out_producer(const Maps& maps, uint32_t sbase, bool after_attn, bool dry) {
  const uint32_t bar = sbase + BAR_OFF;
  const uint32_t rank = blockIdx.x & 1;
  const int m_tile = maps.id[blockIdx.x][2] & 15, n_tile = maps.id[blockIdx.x][2] >> 4;
  uint32_t stage = 0, phase = 0, xi = 0;
#pragma unroll 1
  for (int ki = 0; ki < (dry ? 1 : O_NK); ki++) {
    const int kt = (ki & 14) * 4 + ((A_ORDER >> ((ki >> 4) * 4)) & 3) * 2 + (ki & 1);
    const uint32_t fb = bar + B_OFULL + 8 * stage, eb = bar + B_OEMPTY + 8 * stage;
    const uint32_t sa = sbase + out_stage(stage);
    if (ki < O_STAGES) {
      constexpr uint32_t LASTB = B_KEMPTY | ((B_QEMPTY + 8) << 8) | ((B_KEMPTY + 8) << 16) | (B_VEMPTY << 24);
      if (ki > 0 && after_attn) mbar_wait_sleep(bar + ((LASTB >> (8 * ki - 8)) & 255), ki == 2);
      mbar_arrive_cluster_if(eb, 0, !dry);
      mbar_arrive_cluster_if(eb, 1, !dry);
    }
    if (ki == 32) mbar_wait_sleep(bar + seen_bar(2), 0);
    if (!dry) {
      mbar_wait_sleep(eb, phase);
      mbar_expect_tx(fb, O_STAGE_BYTES);
      tma_load_2d_mc(sa + 16384 + rank * 8192, &maps.ob, fb, n_tile * 128 + rank * 64, kt * 64, (uint16_t)3);
      tma_load_2d(sa, &maps.oa, fb, kt * 64, m_tile * 128);
    }
    if (++stage == O_STAGES) { stage = 0; phase ^= 1; }
    if ((ki & XMASK) == XMASK && ki >= XFIRST && xi < 8) {
      if (after_attn && xi < 2) mbar_wait_sleep(bar + B_OFREE + 8 * xi, 0);
      tma_load_3d(sbase + O_X_OFF + (xi & 1) * 16384 + (xi >> 1) * 4096, &maps.xs, bar + B_OY, 0,
                  m_tile * 128 + (xi >> 1) * 32, n_tile * 2 + (xi & 1));
      xi++;
    }
  }
  if (!dry) mbar_wait_sleep(bar + B_OY2, 0);
}

__device__ __forceinline__ void out_side(const Maps& maps, uint32_t smem0, const float (&gv)[4]) {
  PHASE_PROLOGUE
  const int m_tile = maps.id[blockIdx.x][2] & 15, n_tile = maps.id[blockIdx.x][2] >> 4;
  const bool w0 = __shfl_sync(0xffffffffu, warp, 0) == 0;
  if (w0) {
    if (elect_one()) {
      mbar_expect_tx(bar + B_OY, 65536 - 4096);
      TD(10)
      cnt_wait(CNT_Y2, DM - 128);
      TD(7)
#pragma unroll 1
      for (int i = 0; i < 7; i++) {
        tma_load_3d(sbase + O_Y_OFF + i * 4096, &maps.y, bar + B_OY, 0, n_tile * 128 + i * 16, m_tile * 2);
        __nanosleep(PACE);
      }
    }
  }
  mbar_wait_sleep(bar + B_OY, 0);
  if (wtid == 0) { TD(12) }
  const int st_row = warp * 16 + (lane & 7) + ((lane >> 3) & 1) * 8;
  const int mrow = (lane & 7) + ((lane >> 4) & 1) * 8;
  const int mchunk = warp * 2 + ((lane >> 3) & 1);
  const uint32_t xrow = sbase + O_X_OFF + st_row * 128;
  const uint32_t yrow = sbase + O_Y_OFF + mrow * 128 + ((mchunk ^ (lane & 7)) << 4);
  uint32_t y[7][4], x[7][4], om[4];
#pragma unroll
  for (int i = 0; i < 4; i++) om[i] = pack_bf16(1.0f - gv[i], 1.0f - gv[i]);
  auto xa = [&](int h, int i) { return xrow + h * 8192 + (i >> 2) * 16384 + ((((i & 3) * 2 + (lane >> 4)) ^ (lane & 7)) << 4); };
  auto load = [&](int r, int h, int i) {
    ldsm4t(y[r], yrow + h * 2048 + i * 4096);
    asm volatile("ldmatrix.sync.aligned.m8n8.x4.shared.b16 {%0, %1, %2, %3}, [%4];"
                 : "=r"(x[r][0]), "=r"(x[r][1]), "=r"(x[r][2]), "=r"(x[r][3])
                 : "r"(xa(h, i)));
  };
  auto store = [&](int r, int h, int i, uint32_t om0, uint32_t om1) {
    stmatrix_x4(xa(h, i), mul_bf2(om0, mul_bf2(x[r][0], y[r][0])), mul_bf2(om1, mul_bf2(x[r][1], y[r][1])),
                mul_bf2(om0, mul_bf2(x[r][2], y[r][2])), mul_bf2(om1, mul_bf2(x[r][3], y[r][3])));
  };
#pragma unroll 1
  for (int h = 0; h < 2; h++) {
#pragma unroll
    for (int i = 0; i < 7; i++) load(i, h, i);
#pragma unroll
    for (int i = 0; i < 7; i++) store(i, h, i, h ? om[2] : om[0], h ? om[3] : om[1]);
  }
  if (w0) {
    if (elect_one()) {
      mbar_expect_tx(bar + B_OY2, 4096);
      cnt_wait(CNT_Y2 + 1, 128);
      TD(11)
      tma_load_3d(sbase + O_Y_OFF + 7 * 4096, &maps.y, bar + B_OY2, 0, n_tile * 128 + 112, m_tile * 2);
    }
  }
  mbar_wait_sleep(bar + B_OY2, 0);
  load(0, 0, 7);
  load(1, 1, 7);
  store(0, 0, 7, om[0], om[1]);
  store(1, 1, 7, om[2], om[3]);
  __syncwarp();
  mbar_arrive_if(bar + B_OY + 8, lane == 0);
  if (wtid == 0) { TD(13) }
}

__device__ __forceinline__ uint32_t out_gemm(const Maps& maps, uint32_t smem0, uint32_t sn) {
  PHASE_PROLOGUE
  const int m_tile = maps.id[blockIdx.x][2] & 15, n_tile = maps.id[blockIdx.x][2] >> 4;
  float acc[2][64];
  undef_regs(acc[0]);
  undef_regs(acc[1]);
  uint32_t stage = 0, phase = 0, prev_stage = 0;
  GT(gti++)
  const float* gp = g_gate + m_tile * 128 + warp * 16 + (lane >> 2);
  const float gv[4] = {__ldcg(gp), __ldcg(gp + 8), __ldcg(gp + 64), __ldcg(gp + 72)};
  if (wg == 1) {
    out_side(maps, smem0, gv);
    return sn;
  }
#pragma unroll 1
  for (int kt = 0; kt < O_NK; kt++) {
    uint32_t da = (uint32_t)make_desc(sbase + out_stage(stage), 16, 0, 0);
    uint32_t db = (uint32_t)make_desc(sbase + out_stage(stage) + 16384, 8192, 0, 0);
    asm volatile("" : "+r"(da), "+r"(db));
    mbar_wait(bar + B_OFULL + 8 * stage, phase);
    GT(gti++)
    constexpr int OWAIT = 2;
    constexpr uint64_t DHI = DESC_SW128 | ((uint64_t)(1024 >> 4) << 32);
#pragma unroll
    for (int kk = 0; kk < 4; kk++) {
      wgmma_wait<OWAIT>();
      if (kk == OWAIT)
        mbar_arrive_cluster_if(bar + B_OEMPTY + 8 * prev_stage, wtid >> 6,
                               (wtid & 63) == 32 && kt > 0 && kt - 1 + O_STAGES < O_NK);
      wgmma_fence();
      wgmma_m64n128_ss_tb(acc[0], DHI | (da + kk * 2), DHI | (db + kk * 128), (kt | kk) != 0);
      wgmma_m64n128_ss_tb(acc[1], DHI | (da + 512 + kk * 2), DHI | (db + kk * 128), (kt | kk) != 0);
      wgmma_commit();
    }
    prev_stage = stage;
    if (++stage == O_STAGES) { stage = 0; phase ^= 1; }
  }
  if (tid == 0) { TD(14) }
  st_wait(bar, wg, sn - 1);
  const int st_row = warp * 16 + (lane & 7) + ((lane >> 3) & 1) * 8;
  const uint32_t rowa = sbase + O_X_OFF + st_row * 128;
  auto addr = [&](int i) {
    return rowa + (i & 1) * 8192 + (i >> 3) * 16384 + ((((i & 6) + (lane >> 4)) ^ (st_row & 7)) << 4);
  };
  uint32_t gg[4], b[16][4];
#pragma unroll
  for (int i = 0; i < 4; i++) gg[i] = pack_bf16(gv[i], gv[i]);
  mbar_wait(bar + B_OY + 8, 0);
#pragma unroll
  for (int i = 0; i < 16; i++)
    asm volatile("ldmatrix.sync.aligned.m8n8.x4.shared.b16 {%0, %1, %2, %3}, [%4];"
                 : "=r"(b[i][0]), "=r"(b[i][1]), "=r"(b[i][2]), "=r"(b[i][3])
                 : "r"(addr(i))
                 : "memory");
  wgmma_wait<0>();
  fence_regs(acc[0]);
  fence_regs(acc[1]);
  GT(gti++)
#pragma unroll
  for (int i = 0; i < 16; i++) {
    const float* a = acc[i & 1] + 4 * (i & 14);
    const uint32_t gg0 = gg[2 * (i & 1)], gg1 = gg[2 * (i & 1) + 1];
    stmatrix_x4(addr(i), add_bf2(mul_bf2(gg0, pack_bf16(a[0], a[1])), b[i][0]),
                add_bf2(mul_bf2(gg1, pack_bf16(a[2], a[3])), b[i][1]),
                add_bf2(mul_bf2(gg0, pack_bf16(a[4], a[5])), b[i][2]),
                add_bf2(mul_bf2(gg1, pack_bf16(a[6], a[7])), b[i][3]));
    if (i == 7) st_post(bar, wg, wtid, sn, ST_BOX1, &maps.oc, sbase + O_X_OFF, n_tile * 128, m_tile * 128, -1);
  }
  fence_proxy_async();
  named_bar_sync(1, 128);
  if (__shfl_sync(0xffffffffu, warp, 0) == 0) {
    if (elect_one()) {
      tma_store_2d(&maps.oc, sbase + O_X_OFF + 16384, n_tile * 128 + 64, m_tile * 128);
      tma_store_commit();
    }
  }
  GT(gti++)
  return sn + 1;
}

__device__ __noinline__ void leave_kernel(int mask) {
  if (!(mask & 4)) return;
  if (atomicAdd(g_cnt + CNT_DONE * 32, 1u) == 2 * gridDim.x - 1) {
    for (int i = 0; i < CNT_N; i++) g_cnt[i * 32] = 0;
  }
}

__device__ __noinline__ void side_jobs(const Maps& maps, uint32_t sbase) {
  const int w12 = __shfl_sync(0xffffffffu, threadIdx.x >> 5, 0);
  gate_rows(maps, sbase, (blockIdx.x - 128) * 12 + w12, w12, threadIdx.x & 31);
  fence_proxy_async();
  __syncthreads();
  if (threadIdx.x == 320) cnt_signal_release(CNT_PREP, 1);
}

__global__ void __launch_bounds__(384, 1) fused_kernel(int mask, const __grid_constant__ Maps maps) {
  extern __shared__ __align__(1024) uint8_t smem_raw[];
  {
    const uint32_t sbase = __shfl_sync(0xffffffffu, smem_u32(smem_raw), 0);
    const uint32_t bar = sbase + BAR_OFF;
    const int tid = threadIdx.x;
    const bool do_qkv = (mask & 1) && blockIdx.x < 128;
    TL(0, 0)
    if (__shfl_sync(0xffffffffu, tid >> 5, 0) == 1 && do_qkv) {
      if (elect_one()) {
        for (int i = 0; i < G_STAGES; i++) mbar_init(bar + B_GFULL + 8 * i, 1);
        fence_barrier_init();
        qkv_producer(maps, sbase, true);
      }
    }
    if (tid == 0) {
      for (int i = 0; i < G_STAGES; i++) {
        mbar_init(bar + B_GEMPTY + 8 * i, 2);
        mbar_init(bar + B_SFULL + 8 * i, 4);
        mbar_init(bar + B_SFREE + 8 * i, 1);
      }
      for (int i = 0; i < 2; i++) {
        mbar_init(bar + B_OFREE + 8 * i, 1);
        mbar_init(bar + B_QFULL + 8 * i, 1);
        mbar_init(bar + B_QEMPTY + 8 * i, 2);
        mbar_init(bar + B_KFULL + 8 * i, 1);
        mbar_init(bar + B_KEMPTY + 8 * i, 2);
        mbar_init(bar + B_VFULL + 8 * i, 1);
        mbar_init(bar + B_VEMPTY + 8 * i, 2);
      }
      for (int i = 0; i < O_STAGES; i++) {
        mbar_init(bar + B_OFULL + 8 * i, 1);
        mbar_init(bar + B_OEMPTY + 8 * i, 2);
      }
      mbar_init(bar + B_OY, 1);
      for (int i = 0; i < 3; i++) mbar_init(bar + seen_bar(i), 1);
      mbar_init(bar + B_OY2, 1);
      mbar_init(bar + B_OY + 8, 4);
      mbar_init(bar + B_QDONE, 2);
      for (int i = 0; i < 8; i++) mbar_init(bar + B_CFULL + 8 * i, 1);
      for (int i = 0; i < CNT_N; i++) asm volatile("st.shared.u32 [%0], 0;" ::"r"(bar + B_PEND + 4 * i) : "memory");
      fence_barrier_init();
    }
    __syncthreads();
    asm volatile("barrier.cluster.arrive.relaxed.aligned;" ::: "memory");
    if ((mask & 1) && blockIdx.x >= 128) side_jobs(maps, sbase);
  }
  uint32_t smem0 = smem_u32(smem_raw);
  PHASE_PROLOGUE
  const bool do_qkv = (mask & 1) && blockIdx.x < 128, do_out = (mask & 4) && blockIdx.x < 128;
  TL(0, 1)

  if (wg != 2) {
    reg_alloc<232>();
    uint32_t sn = 0;
    float o[64];
    if (do_qkv) {
      sn = qkv_consumer(maps, smem_u32(smem_raw), mask & 2, o);
    } else {
      undef_regs(o);
    }
    TL(0, 2) TL(1, 0) TL(1, 1)
    asm volatile("barrier.cluster.wait.acquire.aligned;" ::: "memory");
    if (mask & 2) {
      sn = attn_consumer(maps, smem_u32(smem_raw), sn, o, mask & 1);
      TL(2, 0)
      if ((mask & 4) && blockIdx.x < 128 && __shfl_sync(0xffffffffu, threadIdx.x, 0) < 128) {
        named_bar_arrive(3, 256);
      } else {
        const uint32_t b2 = blockIdx.x * 2 + (threadIdx.x >> 7);
        const bool fused = mask & 4, mainc = blockIdx.x < 128;
        const uint32_t first = __shfl_sync(0xffffffffu, !fused ? b2 : mainc ? conv_first(maps) : (b2 - 255) * 128 - C_SIDE, 0);
        conv_consumer(maps, smem_u32(smem_raw), first, !fused ? 264 : mainc ? 16 : 1,
                      !fused ? DM : mainc ? (first | 127) + 1 - C_SIDE : first + C_SIDE, fused && !mainc);
      }
      TL(1, 2) TL(2, 1) TL(2, 2)
    }
    TL(3, 0) TL(3, 1)
    if ((mask & 4) && blockIdx.x < 128) sn = out_gemm(maps, smem_u32(smem_raw), sn);
    {
      uint32_t smem0 = smem_u32(smem_raw);
      PHASE_PROLOGUE
      st_wait(bar, wg, sn - 2);
      st_post(bar, wg, wtid, sn, ST_END, nullptr, 0, 0, 0, -1);
      tma_store_wait_read<0>();
    }
  } else {
    reg_dealloc<40>();
    asm volatile("barrier.cluster.wait.acquire.aligned;" ::: "memory");
    const int w = __shfl_sync(0xffffffffu, tid >> 5, 0) - 8;
    if (w < 2) {
      if (do_qkv) prep_agent(maps, sbase, w, lane);
      if (elect_one()) store_agent(bar, w);
      TL2(3, 2)
    } else {
      if (elect_one()) {
        const bool dry = w == 2;
        if (do_qkv && !dry) qkv_producer(maps, sbase, false);
        if (mask & 2) attn_producer(maps, sbase, do_qkv, do_out, dry);
        if (do_out) out_producer(maps, sbase, mask & 2, dry);
        if (dry) { TD(5) }
      }
      __syncwarp();
      if (w == 2) publisher(bar, tid & 31, !(mask & 2) ? 2 : do_out ? 3 : 4, !do_out ? 3 : do_qkv ? 0 : 2, do_qkv ? 4 : 0);
      if ((tid & 31) == 0) leave_kernel(mask);
    }
  }
}

typedef CUresult (*PFN_tmapEncode)(CUtensorMap*, CUtensorMapDataType, cuuint32_t, void*, const cuuint64_t*,
                                   const cuuint64_t*, const cuuint32_t*, const cuuint32_t*, CUtensorMapInterleave,
                                   CUtensorMapSwizzle, CUtensorMapL2promotion, CUtensorMapFloatOOBfill);
static PFN_tmapEncode s_encode = nullptr;

static void make_map_2d(CUtensorMap* m, const void* ptr, int rows, int cols, int box_rows) {
  cuuint64_t dims[2] = {(cuuint64_t)cols, (cuuint64_t)rows};
  cuuint64_t strides[1] = {(cuuint64_t)cols * 2};
  cuuint32_t box[2] = {cols < 64 ? 32u : 64u, (cuuint32_t)box_rows};
  cuuint32_t es[2] = {1, 1};
  s_encode(m, CU_TENSOR_MAP_DATA_TYPE_BFLOAT16, 2, const_cast<void*>(ptr), dims, strides, box, es,
           CU_TENSOR_MAP_INTERLEAVE_NONE, cols < 64 ? CU_TENSOR_MAP_SWIZZLE_64B : CU_TENSOR_MAP_SWIZZLE_128B, CU_TENSOR_MAP_L2_PROMOTION_L2_256B,
           CU_TENSOR_MAP_FLOAT_OOB_FILL_NONE);
}
static void make_map_3d(CUtensorMap* m, const void* ptr, int rows, int cols, int box_rows, int box_chunks) {
  cuuint64_t dims[3] = {64, (cuuint64_t)rows, (cuuint64_t)(cols / 64)};
  cuuint64_t strides[2] = {(cuuint64_t)cols * 2, 128};
  cuuint32_t box[3] = {64, (cuuint32_t)box_rows, (cuuint32_t)box_chunks};
  cuuint32_t es[3] = {1, 1, 1};
  s_encode(m, CU_TENSOR_MAP_DATA_TYPE_BFLOAT16, 3, const_cast<void*>(ptr), dims, strides, box, es,
           CU_TENSOR_MAP_INTERLEAVE_NONE, CU_TENSOR_MAP_SWIZZLE_128B, CU_TENSOR_MAP_L2_PROMOTION_L2_256B,
           CU_TENSOR_MAP_FLOAT_OOB_FILL_NONE);
}

static cudaLaunchConfig_t fused_cfg(cudaLaunchAttribute* at) {
  cudaLaunchConfig_t cfg = {};
  cfg.gridDim = dim3(132);
  cfg.blockDim = dim3(384);
  cfg.dynamicSmemBytes = SMEM_BYTES;
  cfg.stream = cudaStreamPerThread;
  at[0].id = cudaLaunchAttributeClusterDimension;
  at[0].val.clusterDim.x = 2;
  at[0].val.clusterDim.y = 1;
  at[0].val.clusterDim.z = 1;
  cfg.attrs = at;
  cfg.numAttrs = 1;
  return cfg;
}

extern "C" void kernel_launch(void* const* d_in, const int* in_sizes, int n_in, void* d_out, int out_size) {
  const bf16* x = (const bf16*)d_in[0];
  const bf16* ckv = (const bf16*)d_in[1];
  const bf16* wq = (const bf16*)d_in[2];
  const bf16* wuk = (const bf16*)d_in[3];
  const bf16* wuv = (const bf16*)d_in[4];
  const bf16* wo = (const bf16*)d_in[5];
  const bf16* bk = (const bf16*)d_in[7];
  const bf16* bv = (const bf16*)d_in[8];
  const bf16* shift_k = (const bf16*)d_in[9];
  const bf16* ssm_k = (const bf16*)d_in[10];
  const bf16* ssm_D = (const bf16*)d_in[11];
  const bf16* gate_w = (const bf16*)d_in[12];
  bf16* out = (bf16*)d_out;

  static void *pq = nullptr, *pk = nullptr, *pv = nullptr, *pctx = nullptr, *pb = nullptr, *pu = nullptr;
  static int max_clusters = 0;
  if (!s_encode) {
    void* fn = nullptr;
    cudaDriverEntryPointQueryResult qres;
    cudaGetDriverEntryPoint("cuTensorMapEncodeTiled", &fn, cudaEnableDefault, &qres);
    s_encode = (PFN_tmapEncode)fn;
    cudaGetSymbolAddress(&pq, g_q);
    cudaGetSymbolAddress(&pk, g_k);
    cudaGetSymbolAddress(&pv, g_v);
    cudaGetSymbolAddress(&pctx, g_ctx);
    cudaGetSymbolAddress(&pb, g_y2T);
    cudaGetSymbolAddress(&pu, g_kvT);
    cudaFuncSetAttribute(fused_kernel, cudaFuncAttributeMaxDynamicSharedMemorySize, SMEM_BYTES);
    cudaLaunchAttribute at[1];
    cudaLaunchConfig_t cfg = fused_cfg(at);
    if (cudaOccupancyMaxActiveClusters(&max_clusters, fused_kernel, &cfg) != cudaSuccess) max_clusters = 0;
  }

  Maps all = {};
  make_map_2d(&all.a[0], x, S_LEN, DM, 128);
  make_map_2d(&all.a[1], ckv, S_LEN, DC, 128);
  make_map_3d(&all.b[0], wq, DM, HDIM, 64, 4);
  make_map_3d(&all.b[1], wuk, DC, HDIM, 64, 4);
  make_map_3d(&all.b[2], wuv, DC, HDIM, 64, 4);
  make_map_2d(&all.c[0], pq, S_LEN, HDIM, 64);
  make_map_2d(&all.c[1], pk, S_LEN, HDIM, 64);
  make_map_2d(&all.c[2], pv, S_LEN, HDIM, 64);
  make_map_3d(&all.q, pq, S_LEN, HDIM, 128, 2);
  make_map_3d(&all.k, pk, S_LEN, HDIM, 128, 2);
  make_map_3d(&all.v, pv, S_LEN, HDIM, 128, 2);
  make_map_2d(&all.o, pctx, S_LEN, HDIM, 64);
  all.ssm_k = ssm_k;
  all.ssm_D = ssm_D;
  make_map_2d(&all.oa, pctx, S_LEN, HDIM, 128);
  make_map_2d(&all.ob, wo, HDIM, DM, 64);
  make_map_2d(&all.oc, out, S_LEN, DM, 128);
  make_map_3d(&all.y, pb, DM, S_LEN, 16, 2);
  make_map_3d(&all.xs, x, S_LEN, DM, 32, 1);
  make_map_2d(&all.cu, pu, DM * 64, 32, 64);
  make_map_2d(&all.ch, ssm_k, DM * 64, 32, 64);

  make_map_2d(&all.bk, bk, S_LEN, DM, 35);
  make_map_2d(&all.bv, bv, S_LEN, DM, 32);
  for (int b = 0; b < 128; b++) {
    const int c = b >> 1, r = b & 1;
    const int G = c < 4 ? 0 : c < 36 ? (c - 4) % 8 : 1 + (c - 36) % 7;
    const int i = c < 4 ? 4 + c : c < 36 ? (c - 4) / 8 : 4 + (c - 36) / 7;
    all.id[b][0] = r + 2 * (i & 1) + 4 * (G & 3) + 16 * (i >> 1) + 64 * (G >> 2);
    all.id[b][1] = r + 2 * i + 16 * G;
    all.id[b][2] = r + 2 * G + 16 * i;
  }
  all.shift_k = shift_k;
  all.x = x;
  all.gate_w = gate_w;
  cudaLaunchAttribute at[1];
  cudaLaunchConfig_t cfg = fused_cfg(at);
  if (max_clusters >= 66) {
    cudaLaunchKernelEx(&cfg, fused_kernel, 7, all);
  } else {
    for (int m = 1; m <= 4; m <<= 1) cudaLaunchKernelEx(&cfg, fused_kernel, m, all);
  }
}
```

```cpp
#include <cuda_runtime.h>
#include <cuda_bf16.h>
#include <cuda.h>
#include <stdint.h>

typedef __nv_bfloat16 bf16;
#define INPLACE 3

constexpr int S_LEN = 2048;
constexpr int DM = 1024;
constexpr int NH = 32;
constexpr int HD = 128;
constexpr int DC = 512;
constexpr int HDIM = NH * HD;

__device__ __align__(1024) bf16 g_q[S_LEN * HDIM];
__device__ __align__(1024) bf16 g_k[S_LEN * HDIM];
__device__ __align__(1024) bf16 g_v[S_LEN * HDIM];
#define g_ctx g_q
__device__ __align__(1024) bf16 g_kvT[DM * S_LEN];
#define g_y2T g_kvT
__device__ __align__(1024) float g_gate[S_LEN];
enum { CNT_KV = 0, CNT_PREP = CNT_KV + 2, CNT_CTX, CNT_Y2 = CNT_CTX + 2, CNT_DONE = CNT_Y2 + 2, CNT_RANK, CNT_N };
__device__ unsigned int g_cnt[CNT_N * 32];
__device__ unsigned long long g_slot[128];

#define TL(k, i)
#define TL2(k, i)
#define TD(i)
#define CT(i)
#define GT(i)
#define GA(i)
#define ST(i)

__device__ __forceinline__ uint32_t smem_u32(const void* p) { return (uint32_t)__cvta_generic_to_shared(p); }

__device__ __forceinline__ void mbar_init(uint32_t bar, uint32_t count) {
  asm volatile("mbarrier.init.shared::cta.b64 [%0], %1;" ::"r"(bar), "r"(count));
}
__device__ __forceinline__ void mbar_expect_tx(uint32_t bar, uint32_t bytes) {
  asm volatile("mbarrier.arrive.expect_tx.shared::cta.b64 _, [%0], %1;" ::"r"(bar), "r"(bytes) : "memory");
}
__device__ __forceinline__ void mbar_arrive(uint32_t bar) {
  asm volatile("mbarrier.arrive.shared::cta.b64 _, [%0];" ::"r"(bar) : "memory");
}
__device__ __forceinline__ void mbar_wait(uint32_t bar, uint32_t parity) {
  uint32_t done;
  uint32_t spins = 0;
  do {
    asm volatile(
        "{\n.reg .pred p;\n"
        "mbarrier.try_wait.parity.shared::cta.b64 p, [%1], %2;\n"
        "selp.u32 %0, 1, 0, p;\n}\n"
        : "=r"(done)
        : "r"(bar), "r"(parity)
        : "memory");
    if (++spins > (1u << 22)) break;
  } while (!done);
}
__device__ __forceinline__ bool mbar_try(uint32_t bar, uint32_t parity) {
  uint32_t done;
  asm volatile(
      "{\n.reg .pred p;\n"
      "mbarrier.try_wait.parity.shared::cta.b64 p, [%1], %2;\n"
      "selp.u32 %0, 1, 0, p;\n}\n"
      : "=r"(done)
      : "r"(bar), "r"(parity)
      : "memory");
  return done != 0;
}
__device__ __forceinline__ bool elect_one() {
  uint32_t pred;
  asm volatile("{\n.reg .pred p;\nelect.sync _|p, 0xffffffff;\nselp.u32 %0, 1, 0, p;\n}\n" : "=r"(pred));
  return pred != 0;
}
__device__ __forceinline__ void mbar_arrive_if(uint32_t bar, bool pred) {
  asm volatile(
      "{\n.reg .pred p;\nsetp.ne.b32 p, %1, 0;\n"
      "@p mbarrier.arrive.shared::cta.b64 _, [%0];\n}\n" ::"r"(bar),
      "r"((uint32_t)pred)
      : "memory");
}
__device__ __forceinline__ void mbar_wait_sleep(uint32_t bar, uint32_t parity) {
  uint32_t done;
  uint32_t spins = 0;
  do {
    asm volatile(
        "{\n.reg .pred p;\n"
        "mbarrier.try_wait.parity.shared::cta.b64 p, [%1], %2, %3;\n"
        "selp.u32 %0, 1, 0, p;\n}\n"
        : "=r"(done)
        : "r"(bar), "r"(parity), "r"(20000u)
        : "memory");
    if (++spins > (1u << 16)) break;
  } while (!done);
}
__device__ __forceinline__ void fence_barrier_init() {
  asm volatile("fence.mbarrier_init.release.cluster;" ::: "memory");
}
__device__ __forceinline__ void fence_proxy_async() {
  asm volatile("fence.proxy.async.shared::cta;" ::: "memory");
}
__device__ __forceinline__ void named_bar_sync(int id, int nthreads) {
  asm volatile("bar.sync %0, %1;" ::"r"(id), "r"(nthreads) : "memory");
}
__device__ __forceinline__ void named_bar_arrive(int id, int nthreads) {
  asm volatile("bar.arrive %0, %1;" ::"r"(id), "r"(nthreads) : "memory");
}
__device__ __forceinline__ void tma_load_2d(uint32_t dst, const CUtensorMap* m, uint32_t bar, int c0, int c1) {
  asm volatile(
      "cp.async.bulk.tensor.2d.shared::cluster.global.mbarrier::complete_tx::bytes [%0], [%1, {%3, %4}], [%2];" ::"r"(dst),
      "l"(reinterpret_cast<uint64_t>(m)), "r"(bar), "r"(c0), "r"(c1)
      : "memory");
}
__device__ __forceinline__ void tma_load_3d(uint32_t dst, const CUtensorMap* m, uint32_t bar, int c0, int c1, int c2) {
  asm volatile(
      "cp.async.bulk.tensor.3d.shared::cluster.global.mbarrier::complete_tx::bytes [%0], [%1, {%3, %4, %5}], [%2];" ::"r"(dst),
      "l"(reinterpret_cast<uint64_t>(m)), "r"(bar), "r"(c0), "r"(c1), "r"(c2)
      : "memory");
}
__device__ __forceinline__ void tma_store_2d(const CUtensorMap* m, uint32_t src, int c0, int c1) {
  asm volatile("cp.async.bulk.tensor.2d.global.shared::cta.bulk_group [%0, {%2, %3}], [%1];" ::"l"(
                   reinterpret_cast<uint64_t>(m)),
               "r"(src), "r"(c0), "r"(c1)
               : "memory");
}
__device__ __forceinline__ void bulk_load(uint32_t dst, const void* src, uint32_t bytes, uint32_t bar) {
  asm volatile("cp.async.bulk.shared::cluster.global.mbarrier::complete_tx::bytes [%0], [%1], %2, [%3];" ::"r"(dst),
               "l"(src), "r"(bytes), "r"(bar)
               : "memory");
}
__device__ __forceinline__ void tma_load_2d_mc(uint32_t dst, const CUtensorMap* m, uint32_t bar, int c0, int c1,
                                               uint16_t mask) {
  asm volatile(
      "cp.async.bulk.tensor.2d.shared::cluster.global.mbarrier::complete_tx::bytes.multicast::cluster [%0], [%1, {%3, "
      "%4}], [%2], %5;" ::"r"(dst),
      "l"(reinterpret_cast<uint64_t>(m)), "r"(bar), "r"(c0), "r"(c1), "h"(mask)
      : "memory");
}
__device__ __forceinline__ void mbar_arrive_cluster_if(uint32_t bar, uint32_t cta, bool pred) {
  asm volatile(
      "{\n.reg .b32 ra;\n.reg .pred p;\nsetp.ne.b32 p, %2, 0;\n"
      "mapa.shared::cluster.u32 ra, %0, %1;\n"
      "@p mbarrier.arrive.shared::cluster.b64 _, [ra];\n}\n" ::"r"(bar),
      "r"(cta), "r"((uint32_t)pred)
      : "memory");
}
__device__ __forceinline__ uint64_t policy_evict_first() {
  uint64_t pol;
  asm volatile("createpolicy.fractional.L2::evict_first.b64 %0, 1.0;" : "=l"(pol));
  return pol;
}
__device__ __forceinline__ void tma_load_2d_hint(uint32_t dst, const CUtensorMap* m, uint32_t bar, int c0, int c1,
                                                 uint64_t pol) {
  asm volatile(
      "cp.async.bulk.tensor.2d.shared::cluster.global.mbarrier::complete_tx::bytes.L2::cache_hint [%0], [%1, {%3, %4}], "
      "[%2], %5;" ::"r"(dst),
      "l"(reinterpret_cast<uint64_t>(m)), "r"(bar), "r"(c0), "r"(c1), "l"(pol)
      : "memory");
}
__device__ __forceinline__ void tma_load_3d_hint(uint32_t dst, const CUtensorMap* m, uint32_t bar, int c0, int c1,
                                                 int c2, uint64_t pol) {
  asm volatile(
      "cp.async.bulk.tensor.3d.shared::cluster.global.mbarrier::complete_tx::bytes.L2::cache_hint [%0], [%1, {%3, %4, "
      "%5}], [%2], %6;" ::"r"(dst),
      "l"(reinterpret_cast<uint64_t>(m)), "r"(bar), "r"(c0), "r"(c1), "r"(c2), "l"(pol)
      : "memory");
}
__device__ __forceinline__ void bulk_load_hint(uint32_t dst, const void* src, uint32_t bytes, uint32_t bar, uint64_t pol) {
  asm volatile(
      "cp.async.bulk.shared::cluster.global.mbarrier::complete_tx::bytes.L2::cache_hint [%0], [%1], %2, [%3], %4;" ::"r"(dst),
      "l"(src), "r"(bytes), "r"(bar), "l"(pol)
      : "memory");
}
__device__ __forceinline__ void cnt_signal_release(int which, uint32_t n) {
  asm volatile("red.release.gpu.global.add.u32 [%0], %1;" ::"l"(g_cnt + which * 32), "r"(n) : "memory");
}
__device__ __forceinline__ bool cnt_wait(int which, uint32_t target, uint32_t spins = 0) {
  uint32_t v;
  while (true) {
    asm volatile("ld.acquire.gpu.global.u32 %0, [%1];" : "=r"(v) : "l"(g_cnt + which * 32) : "memory");
    if (v >= target || ++spins > (1u << 18)) break;
    __nanosleep(64);
  }
  asm volatile("fence.proxy.async.global;" ::: "memory");
  return v >= target;
}
__device__ __forceinline__ void tma_store_commit() { asm volatile("cp.async.bulk.commit_group;" ::: "memory"); }
template <int N>
__device__ __forceinline__ void tma_store_wait_read() {
  asm volatile("cp.async.bulk.wait_group.read %0;" ::"n"(N) : "memory");
}
template <int N>
__device__ __forceinline__ void tma_store_wait() {
  asm volatile("cp.async.bulk.wait_group %0;" ::"n"(N) : "memory");
}
__device__ __forceinline__ void wgmma_fence() { asm volatile("wgmma.fence.sync.aligned;" ::: "memory"); }
__device__ __forceinline__ void wgmma_commit() { asm volatile("wgmma.commit_group.sync.aligned;" ::: "memory"); }
template <int N>
__device__ __forceinline__ void wgmma_wait() {
  asm volatile("wgmma.wait_group.sync.aligned %0;" ::"n"(N) : "memory");
}
template <int R>
__device__ __forceinline__ void reg_alloc() { asm volatile("setmaxnreg.inc.sync.aligned.u32 %0;" ::"n"(R)); }
template <int R>
__device__ __forceinline__ void reg_dealloc() { asm volatile("setmaxnreg.dec.sync.aligned.u32 %0;" ::"n"(R)); }

__device__ __forceinline__ void stmatrix_x4(uint32_t addr, uint32_t r0, uint32_t r1, uint32_t r2, uint32_t r3) {
  asm volatile("stmatrix.sync.aligned.m8n8.x4.shared.b16 [%0], {%1, %2, %3, %4};" ::"r"(addr), "r"(r0), "r"(r1),
               "r"(r2), "r"(r3)
               : "memory");
}
__device__ __forceinline__ uint32_t pack_bf16(float lo, float hi) {
  uint32_t r;
  asm("cvt.rn.bf16x2.f32 %0, %1, %2;" : "=r"(r) : "f"(hi), "f"(lo));
  return r;
}
__device__ __forceinline__ float bf16_round(float x) { return __bfloat162float(__float2bfloat16_rn(x)); }
__device__ __forceinline__ float bf_lo(uint32_t v) { return __uint_as_float(v << 16); }
__device__ __forceinline__ float bf_hi(uint32_t v) { return __uint_as_float(v & 0xffff0000u); }
__device__ __forceinline__ uint4 lds128(uint32_t a) {
  uint4 v;
  asm volatile("ld.shared.v4.u32 {%0, %1, %2, %3}, [%4];" : "=r"(v.x), "=r"(v.y), "=r"(v.z), "=r"(v.w) : "r"(a));
  return v;
}
__device__ __forceinline__ void sts128(uint32_t a, uint4 v) {
  asm volatile("st.shared.v4.u32 [%0], {%1, %2, %3, %4};" ::"r"(a), "r"(v.x), "r"(v.y), "r"(v.z), "r"(v.w) : "memory");
}
__device__ __forceinline__ uint32_t mul_bf2(uint32_t a, uint32_t b) {
  uint32_t r;
  asm("mul.rn.bf16x2 %0, %1, %2;" : "=r"(r) : "r"(a), "r"(b));
  return r;
}
__device__ __forceinline__ uint32_t add_bf2(uint32_t a, uint32_t b) {
  uint32_t r;
  asm("add.rn.bf16x2 %0, %1, %2;" : "=r"(r) : "r"(a), "r"(b));
  return r;
}
__device__ __forceinline__ float ex2(float x) {
  float y;
  asm("ex2.approx.ftz.f32 %0, %1;" : "=f"(y) : "f"(x));
  return y;
}
__device__ __forceinline__ float rcp(float x) {
  float y;
  asm("rcp.approx.ftz.f32 %0, %1;" : "=f"(y) : "f"(x));
  return y;
}
template <int N>
__device__ __forceinline__ void fence_regs(float (&r)[N]) {
#pragma unroll
  for (int i = 0; i < N; i++) asm volatile("" : "+f"(r[i])::"memory");
}

template <int N>
__device__ __forceinline__ void undef_regs(float (&r)[N]) {
#pragma unroll
  for (int i = 0; i < N; i++) asm volatile("" : "=f"(r[i]));
}
template <int N>
__device__ __forceinline__ void fence_regs_u(uint32_t (&r)[N]) {
#pragma unroll
  for (int i = 0; i < N; i++) asm volatile("" : "+r"(r[i])::"memory");
}

constexpr uint64_t DESC_SW128 = 1ull << 62;
__device__ __forceinline__ uint64_t make_desc(uint32_t addr, uint32_t lbo_bytes, uint32_t sbo_bytes, uint64_t swz) {
  return (uint64_t)((addr & 0x3FFFF) >> 4) | ((uint64_t)((lbo_bytes & 0x3FFFF) >> 4) << 16) |
         ((uint64_t)((sbo_bytes & 0x3FFFF) >> 4) << 32) | swz;
}

__device__ __forceinline__ uint64_t desc_add(uint64_t d, uint32_t off16) {
  return (d & 0xFFFFFFFF00000000ull) | (uint64_t)((uint32_t)d + off16);
}

__device__ __forceinline__ void wgmma_m64n256_ss_tb(float (&d)[128], uint64_t da, uint64_t db, int sd) {
  asm volatile(
    "{\n.reg .pred p;\nsetp.ne.b32 p, %130, 0;\n"
    "wgmma.mma_async.sync.aligned.m64n256k16.f32.bf16.bf16 "
    "{%0, %1, %2, %3, %4, %5, %6, %7, %8, %9, %10, %11, %12, %13, %14, %15, %16, %17, %18, %19, %20, %21, %22, %23, %24, %25, %26, %27, %28, %29, %30, %31, %32, %33, %34, %35, %36, %37, %38, %39, %40, %41, %42, %43, %44, %45, %46, %47, %48, %49, %50, %51, %52, %53, %54, %55, %56, %57, %58, %59, %60, %61, %62, %63, %64, %65, %66, %67, %68, %69, %70, %71, %72, %73, %74, %75, %76, %77, %78, %79, %80, %81, %82, %83, %84, %85, %86, %87, %88, %89, %90, %91, %92, %93, %94, %95, %96, %97, %98, %99, %100, %101, %102, %103, %104, %105, %106, %107, %108, %109, %110, %111, %112, %113, %114, %115, %116, %117, %118, %119, %120, %121, %122, %123, %124, %125, %126, %127}, %128, %129, p, 1, 1, 0, 1;\n}\n"
    : "+f"(d[0]), "+f"(d[1]), "+f"(d[2]), "+f"(d[3]), "+f"(d[4]), "+f"(d[5]), "+f"(d[6]), "+f"(d[7]), "+f"(d[8]), "+f"(d[9]), "+f"(d[10]), "+f"(d[11]), "+f"(d[12]), "+f"(d[13]), "+f"(d[14]), "+f"(d[15]), "+f"(d[16]), "+f"(d[17]), "+f"(d[18]), "+f"(d[19]), "+f"(d[20]), "+f"(d[21]), "+f"(d[22]), "+f"(d[23]), "+f"(d[24]), "+f"(d[25]), "+f"(d[26]), "+f"(d[27]), "+f"(d[28]), "+f"(d[29]), "+f"(d[30]), "+f"(d[31]), "+f"(d[32]), "+f"(d[33]), "+f"(d[34]), "+f"(d[35]), "+f"(d[36]), "+f"(d[37]), "+f"(d[38]), "+f"(d[39]), "+f"(d[40]), "+f"(d[41]), "+f"(d[42]), "+f"(d[43]), "+f"(d[44]), "+f"(d[45]), "+f"(d[46]), "+f"(d[47]), "+f"(d[48]), "+f"(d[49]), "+f"(d[50]), "+f"(d[51]), "+f"(d[52]), "+f"(d[53]), "+f"(d[54]), "+f"(d[55]), "+f"(d[56]), "+f"(d[57]), "+f"(d[58]), "+f"(d[59]), "+f"(d[60]), "+f"(d[61]), "+f"(d[62]), "+f"(d[63]), "+f"(d[64]), "+f"(d[65]), "+f"(d[66]), "+f"(d[67]), "+f"(d[68]), "+f"(d[69]), "+f"(d[70]), "+f"(d[71]), "+f"(d[72]), "+f"(d[73]), "+f"(d[74]), "+f"(d[75]), "+f"(d[76]), "+f"(d[77]), "+f"(d[78]), "+f"(d[79]), "+f"(d[80]), "+f"(d[81]), "+f"(d[82]), "+f"(d[83]), "+f"(d[84]), "+f"(d[85]), "+f"(d[86]), "+f"(d[87]), "+f"(d[88]), "+f"(d[89]), "+f"(d[90]), "+f"(d[91]), "+f"(d[92]), "+f"(d[93]), "+f"(d[94]), "+f"(d[95]), "+f"(d[96]), "+f"(d[97]), "+f"(d[98]), "+f"(d[99]), "+f"(d[100]), "+f"(d[101]), "+f"(d[102]), "+f"(d[103]), "+f"(d[104]), "+f"(d[105]), "+f"(d[106]), "+f"(d[107]), "+f"(d[108]), "+f"(d[109]), "+f"(d[110]), "+f"(d[111]), "+f"(d[112]), "+f"(d[113]), "+f"(d[114]), "+f"(d[115]), "+f"(d[116]), "+f"(d[117]), "+f"(d[118]), "+f"(d[119]), "+f"(d[120]), "+f"(d[121]), "+f"(d[122]), "+f"(d[123]), "+f"(d[124]), "+f"(d[125]), "+f"(d[126]), "+f"(d[127])
    : "l"(da), "l"(db), "r"(sd));
}

__device__ __forceinline__ void wgmma_m64n128_ss(float (&d)[64], uint64_t da, uint64_t db, int sd) {
  asm volatile(
    "{\n.reg .pred p;\nsetp.ne.b32 p, %66, 0;\n"
    "wgmma.mma_async.sync.aligned.m64n128k16.f32.bf16.bf16 "
    "{%0, %1, %2, %3, %4, %5, %6, %7, %8, %9, %10, %11, %12, %13, %14, %15, %16, %17, %18, %19, %20, %21, %22, %23, %24, %25, %26, %27, %28, %29, %30, %31, %32, %33, %34, %35, %36, %37, %38, %39, %40, %41, %42, %43, %44, %45, %46, %47, %48, %49, %50, %51, %52, %53, %54, %55, %56, %57, %58, %59, %60, %61, %62, %63}, %64, %65, p, 1, 1, 0, 0;\n}\n"
    : "+f"(d[0]), "+f"(d[1]), "+f"(d[2]), "+f"(d[3]), "+f"(d[4]), "+f"(d[5]), "+f"(d[6]), "+f"(d[7]), "+f"(d[8]), "+f"(d[9]), "+f"(d[10]), "+f"(d[11]), "+f"(d[12]), "+f"(d[13]), "+f"(d[14]), "+f"(d[15]), "+f"(d[16]), "+f"(d[17]), "+f"(d[18]), "+f"(d[19]), "+f"(d[20]), "+f"(d[21]), "+f"(d[22]), "+f"(d[23]), "+f"(d[24]), "+f"(d[25]), "+f"(d[26]), "+f"(d[27]), "+f"(d[28]), "+f"(d[29]), "+f"(d[30]), "+f"(d[31]), "+f"(d[32]), "+f"(d[33]), "+f"(d[34]), "+f"(d[35]), "+f"(d[36]), "+f"(d[37]), "+f"(d[38]), "+f"(d[39]), "+f"(d[40]), "+f"(d[41]), "+f"(d[42]), "+f"(d[43]), "+f"(d[44]), "+f"(d[45]), "+f"(d[46]), "+f"(d[47]), "+f"(d[48]), "+f"(d[49]), "+f"(d[50]), "+f"(d[51]), "+f"(d[52]), "+f"(d[53]), "+f"(d[54]), "+f"(d[55]), "+f"(d[56]), "+f"(d[57]), "+f"(d[58]), "+f"(d[59]), "+f"(d[60]), "+f"(d[61]), "+f"(d[62]), "+f"(d[63])
    : "l"(da), "l"(db), "r"(sd));
}

__device__ __forceinline__ void wgmma_m64n128_ss_tb(float (&d)[64], uint64_t da, uint64_t db, int sd) {
  asm volatile(
    "{\n.reg .pred p;\nsetp.ne.b32 p, %66, 0;\n"
    "wgmma.mma_async.sync.aligned.m64n128k16.f32.bf16.bf16 "
    "{%0, %1, %2, %3, %4, %5, %6, %7, %8, %9, %10, %11, %12, %13, %14, %15, %16, %17, %18, %19, %20, %21, %22, %23, %24, %25, %26, %27, %28, %29, %30, %31, %32, %33, %34, %35, %36, %37, %38, %39, %40, %41, %42, %43, %44, %45, %46, %47, %48, %49, %50, %51, %52, %53, %54, %55, %56, %57, %58, %59, %60, %61, %62, %63}, %64, %65, p, 1, 1, 0, 1;\n}\n"
    : "+f"(d[0]), "+f"(d[1]), "+f"(d[2]), "+f"(d[3]), "+f"(d[4]), "+f"(d[5]), "+f"(d[6]), "+f"(d[7]), "+f"(d[8]), "+f"(d[9]), "+f"(d[10]), "+f"(d[11]), "+f"(d[12]), "+f"(d[13]), "+f"(d[14]), "+f"(d[15]), "+f"(d[16]), "+f"(d[17]), "+f"(d[18]), "+f"(d[19]), "+f"(d[20]), "+f"(d[21]), "+f"(d[22]), "+f"(d[23]), "+f"(d[24]), "+f"(d[25]), "+f"(d[26]), "+f"(d[27]), "+f"(d[28]), "+f"(d[29]), "+f"(d[30]), "+f"(d[31]), "+f"(d[32]), "+f"(d[33]), "+f"(d[34]), "+f"(d[35]), "+f"(d[36]), "+f"(d[37]), "+f"(d[38]), "+f"(d[39]), "+f"(d[40]), "+f"(d[41]), "+f"(d[42]), "+f"(d[43]), "+f"(d[44]), "+f"(d[45]), "+f"(d[46]), "+f"(d[47]), "+f"(d[48]), "+f"(d[49]), "+f"(d[50]), "+f"(d[51]), "+f"(d[52]), "+f"(d[53]), "+f"(d[54]), "+f"(d[55]), "+f"(d[56]), "+f"(d[57]), "+f"(d[58]), "+f"(d[59]), "+f"(d[60]), "+f"(d[61]), "+f"(d[62]), "+f"(d[63])
    : "l"(da), "l"(db), "r"(sd));
}

__device__ __forceinline__ void wgmma_m64n128_rs_tb(float* d, uint32_t a0, uint32_t a1, uint32_t a2, uint32_t a3, uint64_t db, int sd) {
  asm volatile(
    "{\n.reg .pred p;\nsetp.ne.b32 p, %69, 0;\n"
    "wgmma.mma_async.sync.aligned.m64n128k16.f32.bf16.bf16 "
    "{%0, %1, %2, %3, %4, %5, %6, %7, %8, %9, %10, %11, %12, %13, %14, %15, %16, %17, %18, %19, %20, %21, %22, %23, %24, %25, %26, %27, %28, %29, %30, %31, %32, %33, %34, %35, %36, %37, %38, %39, %40, %41, %42, %43, %44, %45, %46, %47, %48, %49, %50, %51, %52, %53, %54, %55, %56, %57, %58, %59, %60, %61, %62, %63}, {%64, %65, %66, %67}, %68, p, 1, 1, 1;\n}\n"
    : "+f"(d[0]), "+f"(d[1]), "+f"(d[2]), "+f"(d[3]), "+f"(d[4]), "+f"(d[5]), "+f"(d[6]), "+f"(d[7]), "+f"(d[8]), "+f"(d[9]), "+f"(d[10]), "+f"(d[11]), "+f"(d[12]), "+f"(d[13]), "+f"(d[14]), "+f"(d[15]), "+f"(d[16]), "+f"(d[17]), "+f"(d[18]), "+f"(d[19]), "+f"(d[20]), "+f"(d[21]), "+f"(d[22]), "+f"(d[23]), "+f"(d[24]), "+f"(d[25]), "+f"(d[26]), "+f"(d[27]), "+f"(d[28]), "+f"(d[29]), "+f"(d[30]), "+f"(d[31]), "+f"(d[32]), "+f"(d[33]), "+f"(d[34]), "+f"(d[35]), "+f"(d[36]), "+f"(d[37]), "+f"(d[38]), "+f"(d[39]), "+f"(d[40]), "+f"(d[41]), "+f"(d[42]), "+f"(d[43]), "+f"(d[44]), "+f"(d[45]), "+f"(d[46]), "+f"(d[47]), "+f"(d[48]), "+f"(d[49]), "+f"(d[50]), "+f"(d[51]), "+f"(d[52]), "+f"(d[53]), "+f"(d[54]), "+f"(d[55]), "+f"(d[56]), "+f"(d[57]), "+f"(d[58]), "+f"(d[59]), "+f"(d[60]), "+f"(d[61]), "+f"(d[62]), "+f"(d[63])
    : "r"(a0), "r"(a1), "r"(a2), "r"(a3), "l"(db), "r"(sd));
}

__device__ __forceinline__ void wgmma_m64n64_rs_tb(float (&d)[32], const uint32_t (&a)[4], uint64_t db, int sd) {
  asm volatile(
    "{\n.reg .pred p;\nsetp.ne.b32 p, %37, 0;\n"
    "wgmma.mma_async.sync.aligned.m64n64k16.f32.bf16.bf16 "
    "{%0, %1, %2, %3, %4, %5, %6, %7, %8, %9, %10, %11, %12, %13, %14, %15, %16, %17, %18, %19, %20, %21, %22, %23, %24, %25, %26, %27, %28, %29, %30, %31}, {%32, %33, %34, %35}, %36, p, 1, 1, 1;\n}\n"
    : "+f"(d[0]), "+f"(d[1]), "+f"(d[2]), "+f"(d[3]), "+f"(d[4]), "+f"(d[5]), "+f"(d[6]), "+f"(d[7]), "+f"(d[8]), "+f"(d[9]), "+f"(d[10]), "+f"(d[11]), "+f"(d[12]), "+f"(d[13]), "+f"(d[14]), "+f"(d[15]), "+f"(d[16]), "+f"(d[17]), "+f"(d[18]), "+f"(d[19]), "+f"(d[20]), "+f"(d[21]), "+f"(d[22]), "+f"(d[23]), "+f"(d[24]), "+f"(d[25]), "+f"(d[26]), "+f"(d[27]), "+f"(d[28]), "+f"(d[29]), "+f"(d[30]), "+f"(d[31])
    : "r"(a[0]), "r"(a[1]), "r"(a[2]), "r"(a[3]), "l"(db), "r"(sd));
}

__device__ __forceinline__ void wgmma_m64n32_rs_tb(float (&d)[16], const uint32_t (&a)[4], uint64_t db, int sd) {
  asm volatile(
    "{\n.reg .pred p;\nsetp.ne.b32 p, %21, 0;\n"
    "wgmma.mma_async.sync.aligned.m64n32k16.f32.bf16.bf16 "
    "{%0, %1, %2, %3, %4, %5, %6, %7, %8, %9, %10, %11, %12, %13, %14, %15}, {%16, %17, %18, %19}, %20, p, 1, 1, 1;\n}\n"
    : "+f"(d[0]), "+f"(d[1]), "+f"(d[2]), "+f"(d[3]), "+f"(d[4]), "+f"(d[5]), "+f"(d[6]), "+f"(d[7]), "+f"(d[8]), "+f"(d[9]), "+f"(d[10]), "+f"(d[11]), "+f"(d[12]), "+f"(d[13]), "+f"(d[14]), "+f"(d[15])
    : "r"(a[0]), "r"(a[1]), "r"(a[2]), "r"(a[3]), "l"(db), "r"(sd));
}

constexpr int G_STAGES = 4;
constexpr int G_A_BYTES = 128 * 64 * 2;
constexpr int G_B_BYTES = 256 * 64 * 2;
constexpr int G_STAGE_BYTES = G_A_BYTES + G_B_BYTES;
constexpr int G_STG_OFF = G_STAGES * G_STAGE_BYTES;
constexpr int BAR_OFF = G_STG_OFF + 32768 + 2048;
constexpr int SMEM_BYTES = BAR_OFF + 1024;
constexpr int B_GFULL = 0, B_GEMPTY = 32, B_SEEN = 64, B_PFULL = 224;
constexpr int B_KFULL = 80, B_KEMPTY = 96, B_VFULL = 112, B_VEMPTY = 128, B_QFULL = 144, B_QEMPTY = 160,
              B_QDONE = 184;
constexpr int B_CFULL = 192;
constexpr int B_OFREE = 256, B_OFULL = 272, B_OEMPTY = 320, B_OY = 368, B_OY2 = 384;
constexpr int B_DEAL = 312, B_DEAL2 = 360, B_LIST = 640, B_PAIR = 504;
constexpr int B_SFULL = 392, B_SFREE = 424, B_PEND = 456, B_SCMD = 512;

#define PHASE_PROLOGUE                                                                \
  uint32_t tid, rt_zero;                                                              \
  asm volatile("mov.u32 %0, %%tid.x;" : "=r"(tid));                                   \
  asm volatile("mov.u32 %0, %%nctaid.y;" : "=r"(rt_zero));                            \
  asm volatile("" : "+r"(smem0));                                                     \
  rt_zero = __shfl_sync(0xffffffffu, rt_zero >> 8, 0);   \
  const uint32_t sbase = __shfl_sync(0xffffffffu, smem0, 0);                          \
  const uint32_t bar = sbase + BAR_OFF;                                               \
  const int wg = __shfl_sync(0xffffffffu, tid >> 7, 0);                               \
  const int warp = (tid >> 5) & 3, lane = tid & 31, wtid = tid & 127;                 \
  (void)rt_zero; (void)bar; (void)warp; (void)lane; (void)wtid;

enum { ST_END = 0, ST_BOX1, ST_BOX2, ST_BOX2Q, ST_BOX2L };
__device__ __forceinline__ void st_post(uint32_t bar, int wg, int wtid, uint32_t n, int kind, const void* dst,
                                        uint32_t src, int c0, int c1, int sig) {
  if (wtid == 0) {
    const uint32_t c = bar + B_SCMD + wg * 64 + (n & 1) * 32;
    const uint64_t d = reinterpret_cast<uint64_t>(dst);
    sts128(c, make_uint4(kind, src, c0, c1));
    sts128(c + 16, make_uint4((uint32_t)d, (uint32_t)(d >> 32), sig, 0));
  }
  fence_proxy_async();
  __syncwarp();
  mbar_arrive_if(bar + B_SFULL + wg * 16 + (n & 1) * 8, (wtid & 31) == 0);
}
__device__ __forceinline__ void st_wait(uint32_t bar, int wg, uint32_t n) {
  const uint32_t b = bar + B_SFREE + wg * 16 + (n & 1) * 8;
  if (!mbar_try(b, ~(n >> 1) & 1)) mbar_wait(b, ~(n >> 1) & 1);
}
__device__ __forceinline__ void note(uint32_t bar, uint32_t cnt) {
  asm volatile("red.release.cta.shared.add.u32 [%0], 1;" ::"r"(bar + B_PEND + 4 * cnt) : "memory");
}
#define DEAL_NS 400
#define DEAL_NS2 1250
constexpr uint32_t C_NONE = 0x10000;
__device__ __forceinline__ void deal(uint32_t bar, uint32_t r, uint32_t t, uint32_t own) {
  uint64_t p;
  uint32_t spins = 0;
  while (true) {
    asm volatile("ld.relaxed.gpu.global.u64 %0, [%1];" : "=l"(p) : "l"(g_slot + 127 - r) : "memory");
    if (p || ++spins > (1u << 18)) break;
    __nanosleep(100);
  }
  const uint32_t pc = (uint32_t)p;
  int dt = (uint32_t)(p >> 32) - t;
  if (r >= 64) {
    sts128(bar + B_LIST, make_uint4(-dt > DEAL_NS2 ? C_NONE : own - 16, -dt > DEAL_NS ? C_NONE : own, C_NONE, C_NONE));
    mbar_arrive(bar + B_DEAL);
    dt = 0;
  }
  sts128(bar + B_LIST + 16, make_uint4(dt > DEAL_NS ? pc : C_NONE, dt > DEAL_NS2 ? pc - 16 : C_NONE, C_NONE, C_NONE));
  mbar_arrive(bar + B_DEAL2);
}
__device__ __forceinline__ void store_agent(uint32_t bar, int wg, uint32_t last_ch) {
  mbar_arrive(bar + B_SFREE + wg * 16);
  mbar_arrive(bar + B_SFREE + wg * 16 + 8);
  bool more = true;
  for (uint32_t n = 0;; n++) {
    mbar_wait_sleep(bar + B_SFULL + wg * 16 + (n & 1) * 8, (n >> 1) & 1);
    const uint4 c = lds128(bar + B_SCMD + wg * 64 + (n & 1) * 32);
    const uint4 d = lds128(bar + B_SCMD + wg * 64 + (n & 1) * 32 + 16);
    if (c.x == ST_END) break;
    uint32_t t;
    asm volatile("mov.u32 %0, %%globaltimer_lo;" : "=r"(t));
    const CUtensorMap* dst = reinterpret_cast<const CUtensorMap*>((uint64_t)d.x | ((uint64_t)d.y << 32));
    tma_store_2d(dst, c.y, c.z, c.w);
    if (c.x >= ST_BOX2) tma_store_2d(dst, c.y + 8192, c.z + 64, c.w);
    tma_store_commit();
    uint32_t r = 0;
    if (c.x == ST_BOX2L && last_ch) {
      mbar_expect_tx(bar + B_PAIR, 4);
      asm volatile(
          "{\n.reg .b32 ra;\nmapa.shared::cluster.u32 ra, %0, %1;\n"
          "st.async.weak.shared::cluster.mbarrier::complete_tx::bytes.u32 [ra + 224], %2, [ra];\n}\n" ::"r"(bar + B_PAIR),
          "r"(~blockIdx.x & 1), "r"(t)
          : "memory");
    }
    tma_store_wait_read<0>();
    mbar_arrive(bar + B_SFREE + wg * 16 + (n & 1) * 8);
    if (c.x == ST_BOX2L) mbar_arrive(bar + B_OFREE + 8 * wg);
    if (c.x == ST_BOX2L && last_ch) {
      uint32_t tp;
      mbar_wait_sleep(bar + B_PAIR, 0);
      r = atomicAdd(g_cnt + CNT_RANK * 32, 1u) & 127;
      asm volatile("ld.shared.u32 %0, [%1];" : "=r"(tp) : "r"(bar + B_PAIR + 224) : "memory");
      if ((int)(tp - t) > 0) t = tp;
      asm volatile("st.relaxed.gpu.global.u64 [%0], %1;" ::"l"(g_slot + r), "l"(((uint64_t)t << 32) | last_ch) : "memory");
      if (r < 64) {
        sts128(bar + B_LIST, make_uint4(last_ch - 16, last_ch, C_NONE, C_NONE));
        mbar_arrive(bar + B_DEAL);
      }
    }
    if ((int)d.z >= 0) {
      tma_store_wait<0>();
      if (d.z == 0) { TD(6) }
      asm volatile("fence.proxy.async.global;" ::: "memory");
      if (c.x == ST_BOX2Q) mbar_arrive(bar + B_QDONE);
      else note(bar, d.z);
      if (c.x == ST_BOX2L) {
        note(bar, CNT_DONE);
        more = false;
        if (last_ch) deal(bar, r, t, last_ch);
      }
    }
  }
  if (more) note(bar, CNT_DONE);
}

struct Maps {
  const bf16 *shift_k, *x, *gate_w, *ssm_k, *ssm_D;
  uint8_t id[128][4];
  CUtensorMap a[2];
  CUtensorMap b[3];
  CUtensorMap c[3];
  CUtensorMap bk, bv;
  CUtensorMap q, k, v, o;
  CUtensorMap oa, ob, oc;
  CUtensorMap y, xs;
  CUtensorMap cu, ch;
};

constexpr int P_SLOT = 67 * 128, P_V = 35 * 128, P_TAPS = 2 * P_SLOT;
__device__ __forceinline__ void ldsm4t(uint32_t (&r)[4], uint32_t a) {
  asm volatile("ldmatrix.sync.aligned.m8n8.x4.trans.shared.b16 {%0, %1, %2, %3}, [%4];"
               : "=r"(r[0]), "=r"(r[1]), "=r"(r[2]), "=r"(r[3])
               : "r"(a));
}
__device__ __forceinline__ uint32_t fma_bf2(uint32_t a, uint32_t b, uint32_t c) {
  uint32_t r;
  asm("fma.rn.bf16x2 %0, %1, %2, %3;" : "=r"(r) : "r"(a), "r"(b), "r"(c));
  return r;
}
__device__ __forceinline__ void prep_agent(const Maps& maps, uint32_t sbase, int w, int lane) {
  const uint32_t bar = sbase + BAR_OFF, pb = bar + B_PFULL + w * 16;
  const int d0 = (blockIdx.x >> 3) * 64, t0 = (blockIdx.x & 7) * 256 + w * 128;
  mbar_wait_sleep(bar + B_GFULL + 8 * (G_STAGES - 1), 0);
#pragma unroll 1
  for (int i = -1; i < 4; i++) {
    GA(82 + 2 * i)
    if (i >= 0) mbar_wait_sleep(pb + (i & 1) * 8, i >> 1);
    GA(83 + 2 * i)
    const uint32_t so = sbase + G_STG_OFF + w * (P_TAPS + 512) + (i & 1) * P_SLOT;
    if (i < 3 && elect_one()) {
      const uint32_t b = pb + (~i & 1) * 8, dst = so + (i & 1 ? -P_SLOT : P_SLOT);
      mbar_expect_tx(b, i < 0 ? P_SLOT + 512 : P_SLOT);
      const uint64_t pol = policy_evict_first();
      tma_load_2d_hint(dst, &maps.bk, b, d0, t0 + 32 * i + 29, pol);
      tma_load_2d_hint(dst + P_V, &maps.bv, b, d0, t0 + 32 * i + 32, pol);
      if (i < 0) bulk_load(sbase + G_STG_OFF + P_TAPS, maps.shift_k + d0 * 4, 512, b);
    }
    if (i < 0) continue;
    uint32_t ak[4];
#pragma unroll
    for (int r = 0; r < 4; r++) {
      const uint32_t a = so / 128 + r + 4 * (lane & 6) + (((lane >> 2) ^ lane) & 6) + (lane & 1);
      ak[r] = a * 128 + (a & 7) * 16;
    }
    bf16* dst = g_kvT + (size_t)(d0 + (lane >> 2)) * S_LEN + t0 + ((lane & 3) + 4 * i) * 8;
#pragma unroll 1
    for (int cg = 0; cg < 128; cg += 16) {
      uint32_t t01, t23, k[4][4], v[4];
      asm volatile("ld.shared.v2.u32 {%0, %1}, [%2];"
                   : "=r"(t01), "=r"(t23)
                   : "r"(sbase + G_STG_OFF + P_TAPS + cg * 4 + (lane >> 2) * 8));
#pragma unroll
      for (int r = 0; r < 4; r++) ldsm4t(k[r], ak[r] ^ cg);
      ldsm4t(v, (ak[3] ^ cg) + 4096);
      const uint32_t w0 = __byte_perm(t01, 0, 0x1010), w1 = __byte_perm(t01, 0, 0x3232);
      const uint32_t w2 = __byte_perm(t23, 0, 0x1010), w3 = __byte_perm(t23, 0, 0x3232);
#pragma unroll
      for (int j = 0; j < 4; j++)
        v[j] = mul_bf2(fma_bf2(k[3][j], w0, fma_bf2(k[2][j], w1, fma_bf2(k[1][j], w2, mul_bf2(k[0][j], w3)))), v[j]);
      const bool s1 = lane & 1, s2 = lane & 2;
      const uint32_t a0 = s1 ? v[1] : v[0], a1 = s1 ? v[0] : v[1], a2 = s1 ? v[3] : v[2], a3 = s1 ? v[2] : v[3];
      *reinterpret_cast<uint4*>(dst) = make_uint4(s2 ? a2 : a0, s2 ? a3 : a1, s2 ? a0 : a2, s2 ? a1 : a3);
      dst += 8 * S_LEN;
    }
    fence_proxy_async();
    __syncwarp();
  }
  GA(90)
  if (lane == 0) note(bar, CNT_PREP);
  __syncwarp();
  GA(91)
}

__device__ __forceinline__ void qkv_tile(const Maps& maps, int it, int& which, int& m_tile, int& n_tile) {
  const bool q = it == 0 || it >= 5;
  const int b = maps.id[blockIdx.x][it >= 5];
  which = q ? 0 : 2 - (it & 1);
  m_tile = b & 15;
  n_tile = (b >> 4) * 2 + ((0x19 >> it) & 1);
}

constexpr int G_NTILES = 6;
__device__ __forceinline__ void qkv_producer(const Maps& maps, uint32_t sbase, bool first) {
  const uint32_t bar = sbase + BAR_OFF;
  uint32_t stage = 0, phase = 0;
#pragma unroll 1
  for (int it = 0; it < (first ? 1 : G_NTILES); it++) {
    int which, m_tile, n_tile;
    qkv_tile(maps, it, which, m_tile, n_tile);
    const CUtensorMap* ma = &maps.a[which == 0 ? 0 : 1];
    const CUtensorMap* mb = &maps.b[which];
    const int nk = first ? G_STAGES : which == 0 ? 16 : 8;
#pragma unroll 1
    for (int kt = (it == 0 && !first) ? G_STAGES : 0; kt < nk; kt++) {
      if (!first) mbar_wait_sleep(bar + B_GEMPTY + 8 * stage, phase);
      const uint32_t fb = bar + B_GFULL + 8 * stage;
      const uint32_t sa = sbase + stage * G_STAGE_BYTES;
      mbar_expect_tx(fb, G_STAGE_BYTES);
      tma_load_2d(sa, ma, fb, kt * 64, m_tile * 128);
      tma_load_3d(sa + G_A_BYTES, mb, fb, 0, kt * 64, n_tile * 4);
      if (++stage == G_STAGES) { stage = 0; phase ^= 1; }
      {
        const int b = maps.id[blockIdx.x][1];
        if (it == 2 && kt == (b & 7)) {
          for (int i = 0; i < 2; i++)
            asm volatile("cp.async.bulk.prefetch.tensor.2d.L2.global.tile [%0, {%1, %2}];" ::"l"(&maps.a[0]),
                         "r"((b >> 4) * 128 + i * 64), "r"((b & 15) * 128)
                         : "memory");
        }
        if (it == 3 && kt == (b & 7))
          asm volatile("cp.async.bulk.prefetch.tensor.3d.L2.global.tile [%0, {%1, %2, %3}];" ::"l"(&maps.b[0]), "r"(0),
                       "r"((b & 15) * 64), "r"((b >> 4) * 8)
                       : "memory");
      }
    }
  }
}

__device__ __forceinline__ uint32_t seen_bar(uint32_t item) { return B_SEEN + ((0x700800u >> (8 * item)) & 255); }
__device__ __noinline__ void publisher(uint32_t bar, int lane, uint32_t nsrc, uint32_t item, uint32_t mine) {
  uint32_t done = 0, tot = 0;
#pragma unroll 1
  for (uint32_t spins = 0; (done < nsrc || item < 3) && spins < (1u << 20); spins++) {
    const uint32_t cnt = item ? CNT_CTX - 1 + item : CNT_KV + 1;
    if (item < 3 && __shfl_sync(0xffffffffu, tot, cnt) >= mine) {
      uint32_t v;
      asm volatile("ld.acquire.gpu.global.u32 %0, [%1];" : "=r"(v) : "l"(g_cnt + (lane ? cnt : CNT_PREP) * 32) : "memory");
      if (__all_sync(0xffffffffu, v >= (lane ? 512 : 260))) {
        asm volatile("fence.proxy.async.global;" ::: "memory");
        mbar_arrive_if(bar + seen_bar(item), lane == 0);
        item++;
      }
    }
    uint32_t v = 0;
    if (lane < CNT_N)
      asm volatile("atom.acquire.cta.shared.exch.b32 %0, [%1], 0;" : "=r"(v) : "r"(bar + B_PEND + 4 * lane) : "memory");
    done += __shfl_sync(0xffffffffu, v, CNT_DONE);
    if (lane == CNT_DONE) v = 0;
    if (done == nsrc && lane < CNT_DONE) {
      uint32_t w;
      asm volatile("atom.acquire.cta.shared.exch.b32 %0, [%1], 0;" : "=r"(w) : "r"(bar + B_PEND + 4 * lane) : "memory");
      v += w;
    }
    if (v && lane == 0) { TD(0) }
    if (v) cnt_signal_release(lane, v);
    tot += v;
    if (v && lane == 0) { TD(1) }
    if (!__any_sync(0xffffffffu, v != 0)) __nanosleep(200);
  }
  __threadfence();
  __syncwarp();
}

__device__ __forceinline__ void gate_rows(const Maps& maps, uint32_t sbase, int w48, int w12, int lane) {
  const uint32_t buf = sbase + w12 * 16384, gb = sbase + BAR_OFF + 768 + w12 * 16;
  if (lane == 0) {
    mbar_init(gb, 1);
    mbar_init(gb + 8, 1);
    fence_barrier_init();
    for (int i = 0; i < 2; i++) {
      mbar_expect_tx(gb + 8 * i, 8192);
      bulk_load(buf + i * 8192, maps.x + (size_t)(w48 + 48 * i) * 4 * DM, 8192, gb + 8 * i);
    }
  }
  __syncwarp();
  uint4 wv[4];
#pragma unroll
  for (int i = 0; i < 4; i++) wv[i] = __ldg(reinterpret_cast<const uint4*>(maps.gate_w + (i * 32 + lane) * 8));
  int it = 0;
#pragma unroll 1
  for (int row = w48 * 4; row < S_LEN; row += 48 * 4, it++) {
    mbar_wait(gb + 8 * (it & 1), (it >> 1) & 1);
    uint4 xv[4][4];
#pragma unroll
    for (int r = 0; r < 4; r++)
#pragma unroll
      for (int i = 0; i < 4; i++) xv[r][i] = lds128(buf + (it & 1) * 8192 + r * 2048 + (i * 32 + lane) * 16);
    float d[2][4];
#pragma unroll
    for (int pr = 0; pr < 2; pr++) {
      d[pr][0] = d[pr][1] = d[pr][2] = d[pr][3] = 0.f;
      auto acc = [&](uint32_t a0, uint32_t a2, uint32_t b0, uint32_t b2, uint32_t w0, uint32_t w2) {
        asm volatile(
            "mma.sync.aligned.m16n8k16.row.col.f32.bf16.bf16.f32 {%0, %1, %2, %3}, {%4, %5, %6, %7}, {%8, %8}, "
            "{%0, %1, %2, %3};"
            : "+f"(d[pr][0]), "+f"(d[pr][1]), "+f"(d[pr][2]), "+f"(d[pr][3])
            : "r"(mul_bf2(a0, w0)), "r"(mul_bf2(b0, w0)), "r"(mul_bf2(a2, w2)), "r"(mul_bf2(b2, w2)), "r"(0x3f803f80u));
      };
#pragma unroll
      for (int i = 0; i < 4; i++) {
        acc(xv[2 * pr][i].x, xv[2 * pr][i].y, xv[2 * pr + 1][i].x, xv[2 * pr + 1][i].y, wv[i].x, wv[i].y);
        acc(xv[2 * pr][i].z, xv[2 * pr][i].w, xv[2 * pr + 1][i].z, xv[2 * pr + 1][i].w, wv[i].z, wv[i].w);
      }
    }
    float sum = (lane & 2) ? ((lane & 1) ? d[1][2] : d[1][0]) : ((lane & 1) ? d[0][2] : d[0][0]);
#pragma unroll
    for (int off = 16; off >= 4; off >>= 1) sum += __shfl_xor_sync(0xffffffffu, sum, off);
    if (lane < 4) g_gate[row + lane] = bf16_round(rcp(1.0f + __expf(-bf16_round(sum))));
    if (lane == 0 && row + 2 * 48 * 4 < S_LEN) {
      mbar_expect_tx(gb + 8 * (it & 1), 8192);
      bulk_load(buf + (it & 1) * 8192, maps.x + (size_t)(row + 2 * 48 * 4) * DM, 8192, gb + 8 * (it & 1));
    }
  }
}

constexpr float Q_SCALE = 0.08838834764831845f * 1.4426950408889634f;
__device__ __forceinline__ uint32_t qkv_consumer(const Maps& maps, uint32_t smem0, bool fused, float (&rest)[64]) {
  PHASE_PROLOGUE
  constexpr int NTILES = G_NTILES;
  float acc[128];
  uint32_t stage = 0, phase = 0;
  const uint32_t stg = sbase + G_STG_OFF + wg * 18432;
  const int st_row = warp * 16 + (lane & 7) + ((lane >> 3) & 1) * 8;
  const int st_cb = lane >> 4;
  uint32_t pend[64];
  const CUtensorMap* pend_map = nullptr;
  int pend_c0 = 0, pend_c1 = 0;
  uint32_t sn = 0;
  auto put_box = [&](uint32_t buf, const uint32_t* v) {
#pragma unroll
    for (int jp = 0; jp < 4; jp++) {
      const int chunk = jp * 2 + st_cb;
      const uint32_t addr = buf + st_row * 128 + ((chunk ^ (st_row & 7)) << 4);
      stmatrix_x4(addr, v[jp * 4], v[jp * 4 + 1], v[jp * 4 + 2], v[jp * 4 + 3]);
    }
  };
  GT(gti++)
#pragma unroll 1
  for (int it = 0; it <= NTILES; it++) {
    int which, m_tile, n_tile;
    qkv_tile(maps, it, which, m_tile, n_tile);
    const int nk = (which == 0 && it < NTILES) ? 16 : 8;
    uint32_t prev_stage = 0;
#pragma unroll 1
    for (int kt = 0; kt < nk; kt++) {
      if (it < NTILES) {
        mbar_wait((bar + B_GFULL) + 8 * stage, phase);
        GT(gti++)
        const uint64_t da0 = make_desc(sbase + stage * G_STAGE_BYTES + wg * 8192, 16, 1024, DESC_SW128);
        const uint64_t db0 = make_desc(sbase + stage * G_STAGE_BYTES + G_A_BYTES, 8192, 1024, DESC_SW128);
        wgmma_fence();
#pragma unroll
        for (int kk = 0; kk < 4; kk++) {
          wgmma_m64n256_ss_tb(acc, desc_add(da0, kk * 2), desc_add(db0, kk * 128), (kt | kk) != 0);
        }
        wgmma_commit();
      }
      const uint32_t when = it == 0 ? 0 : it == 5 ? 0x922 << wg : wg ? 0xAA : 0x55;
      if ((when >> kt) & 1) {
        const int c = __popc(when & ~(~0u << kt));
        st_wait(bar, wg, sn - 2);
        const uint32_t buf = stg + (c & 1) * 8192;
        switch (c) {
          case 0: put_box(buf, pend); break;
          case 1: put_box(buf, pend + 16); break;
          case 2: put_box(buf, pend + 32); break;
          default: put_box(buf, pend + 48); break;
        }
        st_post(bar, wg, wtid, sn, ST_BOX1, pend_map, buf, pend_c0 + c * 64, pend_c1, (c == 3 && it > 1) ? CNT_KV + (it > 3) : -1);
        sn++;
      }
      if (it < NTILES) {
        wgmma_wait<1>();
        mbar_arrive_if((bar + B_GEMPTY) + 8 * prev_stage, wtid == 32 && kt > 0);
        prev_stage = stage;
        if (++stage == G_STAGES) { stage = 0; phase ^= 1; }
      }
    }
    wgmma_wait<0>();
    fence_regs(acc);
    if (it == NTILES) break;
    GT(gti++)
    mbar_arrive_if((bar + B_GEMPTY) + 8 * prev_stage, wtid == 32);
    if (it == NTILES - 1 && fused) break;
    if (which == 0) {
#pragma unroll
      for (int j = 0; j < 128; j++) acc[j] *= Q_SCALE;
    }
#pragma unroll
    for (int j = 0; j < 64; j++) pend[j] = pack_bf16(acc[2 * j], acc[2 * j + 1]);
    pend_map = &maps.c[which];
    pend_c0 = n_tile * 256;
    pend_c1 = m_tile * 128 + wg * 64;
  }
  mbar_wait(bar + B_GEMPTY, 1);
#pragma unroll
  for (int j = 0; j < 32; j++) pend[j] = pack_bf16(acc[2 * j] * Q_SCALE, acc[2 * j + 1] * Q_SCALE);
  put_box(sbase + wg * 8192, pend);
  put_box(sbase + 16384 + wg * 8192, pend + 16);
  fence_proxy_async();
#pragma unroll
  for (int j = 0; j < 64; j++) rest[j] = acc[64 + j];
  GT(gti++)
  return sn;
}

constexpr int A_TILE = 128 * 128 * 2;
constexpr int A_Q_OFF = 0;
constexpr int A_K_OFF = 2 * A_TILE;
constexpr int A_V_OFF = 4 * A_TILE;
constexpr int A_O_OFF = 6 * A_TILE;
constexpr int A_ITEMS = NH * (S_LEN / 128);

constexpr uint32_t A_ORDER = 0x3120, A_STEPS = 34;
__device__ __forceinline__ int item_m(uint32_t it) { return it & 15; }
__device__ __forceinline__ int item_h(uint32_t it) { return it >> 4; }

constexpr int C_V = 16384, C_MAT = 24576;
constexpr float C_ALPHA = 0.07874506561842957f;
__device__ __forceinline__ void sincos_turn(int p, float inv, float& c, float& s) {
  const float a = (float)p * (inv * 6.283185307179586f);
  asm("cos.approx.ftz.f32 %0, %1;" : "=f"(c) : "f"(a));
  asm("sin.approx.ftz.f32 %0, %1;" : "=f"(s) : "f"(a));
}

__device__ __forceinline__ uint32_t item_of(const Maps& maps, uint32_t r) {
  const uint32_t b = maps.id[blockIdx.x & 127][1];
  return (b >> 4) * 64 + ((A_ORDER >> (4 * r)) & 3) * 16 + ((b ^ ((r & 1) * 15)) & 15);
}

#define PACE 250
#define SPACE 0
#define LCHK 1
#define XMASK 3
#define XFIRST 4
#define C_SIDE 64
__device__ __forceinline__ uint32_t conv_first(const Maps& maps) {
  const uint32_t b = maps.id[blockIdx.x & 127][1];
  return (b >> 4) * 128 + ((b + 15) & 15);
}

__device__ __forceinline__ void conv_consumer(const Maps& maps, uint32_t smem0, uint32_t first, uint32_t step,
                                              uint32_t end, bool pp, bool dealt) {
  PHASE_PROLOGUE
  const uint32_t in_full = bar + B_CFULL + wg * 16;
  const uint32_t ca = sbase + (wg ? A_V_OFF + A_TILE : A_Q_OFF);
  const int w = __shfl_sync(0xffffffffu, warp, 0), g = lane >> 2, c = lane & 3;
  auto fetch = [&](uint32_t ch, uint32_t n) {
    if (w == 2 && ch < C_NONE) {
      if (elect_one()) {
        const uint32_t b = in_full + (n & 1) * 8, d = ca + (n & 1) * 8192;
        const uint64_t pol = policy_evict_first();
        mbar_expect_tx(b, 8192);
        tma_load_2d_hint(d, &maps.cu, b, 0, ch * 64, pol);
        tma_load_2d_hint(d + 4096, &maps.ch, b, 0, ch * 64, pol);
      }
    }
  };
  if (wtid == 96 && wg) { TD(15) }
  uint32_t f1[8][4];
  float tt[16], ts[16];
  uint32_t cc[4], ss[4];
#pragma unroll
  for (int i = 0; i < 16; i++) {
    const int k = 2 * (16 * w + g + 8 * (i & 1)) + 1, n = 2 * (8 * (i >> 1) + 2 * c) + 1;
    float c0, s0, c1, s1;
    sincos_turn(((k * n) << 23) >> 23, 1.f / 512, c0, s0);
    sincos_turn(((k * n + 2 * k) << 23) >> 23, 1.f / 512, c1, s1);
    f1[i >> 2][i & 3] = pack_bf16(c0 * C_ALPHA, c1 * C_ALPHA);
    f1[4 + (i >> 2)][i & 3] = pack_bf16(s0 * -C_ALPHA, s1 * -C_ALPHA);
  }
#pragma unroll
  for (int i = 0; i < 16; i++) {
    const int k = 2 * (16 * w + g + 8 * ((i >> 1) & 1)) + 1, n = 16 - (8 * (i >> 2) + 2 * c + (i & 1));
    float cs;
    sincos_turn(k * n, 1.f / 8192, cs, ts[i]);
    tt[i] = ts[i] * rcp(1.f + cs);
  }
#pragma unroll
  for (int j = 0; j < 4; j++) {
    const int k = 8 * w + g, n = 8 * c + 2 * j;
    float c0, s0, c1, s1;
    sincos_turn((int8_t)(k * n * 8), 1.f / 256, c0, s0);
    sincos_turn((int8_t)((k * n + k) * 8), 1.f / 256, c1, s1);
    cc[j] = pack_bf16(c0, c1);
    ss[j] = pack_bf16(s0, s1);
  }
  named_bar_sync(3, 256);
  fetch(first, 0);
  fetch(first + step, 1);
  const uint32_t va = ca + g * 64 + ((c ^ (g >> 1)) << 4);
  {
    const uint32_t a = va + C_MAT + w * 512, m = 0x80008000u;
    sts128(a, make_uint4(cc[0], cc[1], cc[2], cc[3]));
    sts128(a + 2048, make_uint4(ss[0], ss[1], ss[2], ss[3]));
    sts128(a + 4096, make_uint4(ss[0] ^ m, ss[1] ^ m, ss[2] ^ m, ss[3] ^ m));
    sts128(a + 6144, make_uint4(cc[0], cc[1], cc[2], cc[3]));
  }
  fence_proxy_async();
  named_bar_sync(1 + wg, 128);
  constexpr uint64_t DHI = (2ull << 62) | ((uint64_t)(512 >> 4) << 32);
  const uint32_t d0 = (uint32_t)make_desc(ca, 4096, 0, 0);
  float a5[16];
  uint4* const yb = reinterpret_cast<uint4*>(g_y2T) + (16 * w + g) * 4 + c;
  auto issue5 = [&]() {
#pragma unroll
    for (int ks = 0; ks < 8; ks++) wgmma_m64n32_rs_tb(a5, f1[ks], DHI | (d0 + (C_V >> 4) + ks * 64), ks != 0);
    wgmma_commit();
  };
  auto finish = [&](uint32_t ch, bool on) {
    fence_regs(a5);
    uint4* y = yb + (size_t)ch * 256;
    if (on) {
      y[0] = make_uint4(pack_bf16(a5[0], a5[1]), pack_bf16(a5[4], a5[5]), pack_bf16(a5[8], a5[9]), pack_bf16(a5[12], a5[13]));
      y[32] = make_uint4(pack_bf16(a5[2], a5[3]), pack_bf16(a5[6], a5[7]), pack_bf16(a5[10], a5[11]), pack_bf16(a5[14], a5[15]));
    }
  };
  auto dft32 = [&](float (&d)[32], const float* re, const float* im) {
    uint32_t a[4][4];
#pragma unroll
    for (int i = 0; i < 8; i++) {
      a[i >> 2][i & 3] = pack_bf16(re[2 * i], re[2 * i + 1]);
      a[2 + (i >> 2)][i & 3] = pack_bf16(im[2 * i], im[2 * i + 1]);
    }
    wgmma_fence();
#pragma unroll
    for (int ks = 0; ks < 4; ks++) wgmma_m64n64_rs_tb(d, a[ks], DHI | (d0 + (C_MAT >> 4) + ks * 64), ks != 0);
    wgmma_commit();
  };
  auto rot = [&](float* x, float* y) {
#pragma unroll
    for (int i = 0; i < 16; i++) {
      x[i] = fmaf(-tt[i], y[i], x[i]);
      y[i] = fmaf(ts[i], x[i], y[i]);
      x[i] = fmaf(-tt[i], y[i], x[i]);
    }
  };
  auto load_d = [&](uint32_t ch) {
    return __ldg(reinterpret_cast<const unsigned short*>(maps.ssm_D) + ((ch & (DM - 1)) | (lane & rt_zero)));
  };
  uint32_t dn = load_d(first);
  uint32_t n = 0, prev = 0, ch = first, next = first + step;
#pragma unroll 1
  for (; ch < C_NONE; n++) {
    CT(0)
    float a1[2][32], a2[2][32], a4[32];
    const float dsk = c ? 0.f : __uint_as_float(dn << 16) * C_ALPHA;
    dn = load_d(next);
    uint32_t next2 = next + step < end ? next + step : C_NONE;
    mbar_wait(in_full + (n & 1) * 8, (n >> 1) & 1);
    if (pp) named_bar_sync(4 + wg, 256);
    CT(1)
    wgmma_fence();
#pragma unroll
    for (int ks = 0; ks < 8; ks++)
      wgmma_m64n64_rs_tb(a1[ks >> 2], f1[ks], DHI | (d0 + (n & 1) * 512 + (ks & 3) * 64), (ks & 3) != 0);
    wgmma_commit();
    issue5();
    wgmma_wait<1>();
    fence_regs(a1[0]);
    fence_regs(a1[1]);
    CT(2)
    rot(a1[0], a1[1]);
    dft32(a2[0], a1[0], a1[1]);
    rot(a1[0] + 16, a1[1] + 16);
    a1[0][16] += dsk;
    a1[0][18] += dsk;
    dft32(a2[1], a1[0] + 16, a1[1] + 16);
    CT(3)
    wgmma_wait<2>();
    finish(prev, n > 0);
    wgmma_wait<0>();
    fence_regs(a2[0]);
    fence_regs(a2[1]);
    CT(4)
    if (pp) named_bar_arrive(5 - wg, 256);
    float re[16], im[16];
#pragma unroll
    for (int i = 0; i < 16; i++) {
      re[i] = a2[0][i] * a2[1][i] - a2[0][16 + i] * a2[1][16 + i];
      im[i] = a2[0][i] * a2[1][16 + i] + a2[0][16 + i] * a2[1][i];
    }
    dft32(a4, im, re);
    if (dealt) {
      mbar_wait(bar + (n < 2 ? B_DEAL : B_DEAL2), 0);
      asm volatile("ld.shared.u32 %0, [%1];" : "=r"(next2) : "r"(bar + B_LIST + 4 * n + (n < 2 ? 0 : 8)));
    }
    wgmma_wait<0>();
    fence_regs(a4);
    CT(5)
    rot(a4, a4 + 16);
#pragma unroll
    for (int i = 0; i < 4; i++) {
      const float* x = a4 + 16 - 16 * (i >> 1) + 2 * (i & 1);
      sts128(va + C_V + w * 1024 + (i >> 1) * 4096 + (i & 1) * 512,
             make_uint4(pack_bf16(x[0], x[1]), pack_bf16(x[4], x[5]), pack_bf16(x[8], x[9]), pack_bf16(x[12], x[13])));
    }
    CT(6)
    fence_proxy_async();
    named_bar_sync(1 + wg, 128);
    fetch(next2, n);
    if (wtid == 96 && n > 0) note(bar, CNT_Y2 + ((prev & 112) == 112));
    prev = ch;
    ch = next;
    next = next2;
    CT(7)
  }
  wgmma_fence();
  issue5();
  wgmma_wait<0>();
  finish(prev, (dn | ~rt_zero) != 0);
  named_bar_sync(1 + wg, 128);
  if (wtid == 96 && wg) { TD(8) }
  if (wtid == 96) cnt_signal_release(CNT_Y2 + ((prev & 112) == 112), 1);
  if (wtid == 64) note(bar, CNT_DONE);
  if (wtid == 96 && wg) { TD(9) }
}

__device__ __forceinline__ void attn_producer(const Maps& maps, uint32_t sbase, bool after_qkv, bool to_out,
                                              bool dry) {
  const uint32_t bar = sbase + BAR_OFF;
  const uint32_t q_full = bar + B_QFULL, q_empty = bar + B_QEMPTY;
  const uint32_t k_full = bar + B_KFULL, k_empty = bar + B_KEMPTY, v_full = bar + B_VFULL, v_empty = bar + B_VEMPTY;
  int ndrained = after_qkv ? 0 : G_STAGES;
  auto wait = [&](uint32_t b, uint32_t par) {
    if (!dry) mbar_wait_sleep(b, par);
  };
  auto drained = [&](int upto) {
#pragma unroll 1
    for (; ndrained <= upto; ndrained++) wait(bar + B_GEMPTY + 8 * ndrained, 1);
  };
  uint32_t st = 0, ph = 1, vs = 0, vp = 1;
  int pend_j = -1, pend_h = 0;
  int round = -1, m = -1, h = 0;
  bool last = false;
#pragma unroll 1
  for (;; round++) {
    uint32_t nitem = 0;
    const int tpost = m >= 3 ? m - 1 : m;
#pragma unroll 1
    for (int t = m < 0 ? -1 : 0; t <= m; t++) {
      const int j = (t < m && (round & 1)) ? m - 1 - t : t;
      if (t >= 0) {
        drained(1 + st);
        wait(k_empty + 8 * st, ph);
        if (!dry) {
          mbar_expect_tx(k_full + 8 * st, A_TILE);
          tma_load_3d(sbase + A_K_OFF + st * A_TILE, &maps.k, k_full + 8 * st, 0, j * 128, h * 2);
        }
        if (++st == 2) { st = 0; ph ^= 1; }
      }
      if (pend_j >= 0) {
        drained(3);
        wait(v_empty + 8 * vs, vp);
        if (!dry) {
          mbar_expect_tx(v_full + 8 * vs, A_TILE);
          tma_load_3d(sbase + A_V_OFF + vs * A_TILE, &maps.v, v_full + 8 * vs, 0, pend_j * 128, pend_h * 2);
        }
        if (++vs == 2) { vs = 0; vp ^= 1; }
      }
      pend_j = j;
      pend_h = h;
      if (t == tpost && !last) {
        nitem = dry ? 1 : item_of(maps, round + 1);
        if (round == (dry ? 0 : 3) || blockIdx.x >= 128) {
          nitem = A_ITEMS;
          if (!to_out) cnt_wait(CNT_PREP, dry ? 0 : 260);
          if (to_out) {
            wait(bar + seen_bar(1), 0);
            asm volatile("cp.async.bulk.prefetch.L2.global [%0], 4096;" ::"l"(maps.ssm_k + (size_t)conv_first(maps) * S_LEN));
            if (!dry)
              asm volatile("cp.async.bulk.prefetch.L2.global [%0], 4096;" ::"l"(g_kvT + (size_t)conv_first(maps) * S_LEN));
          }
        }
        const uint32_t qs = (round + 1) & 1;
        wait(q_empty + 8 * qs, (((round + 1) >> 1) & 1) ^ 1);
        if (round == 1 && after_qkv) wait(bar + B_QDONE, 0);
        if (round == 0 && after_qkv) wait(bar + seen_bar(0), 0);
        if (round < 0 && after_qkv) {
          if (!dry) { TD(2) }
          cnt_wait(CNT_KV, dry ? 0 : 512);
          if (!dry) { TD(3) }
        }
        if (nitem >= A_ITEMS || (round < 0 && after_qkv && !dry)) {
          if (!dry) mbar_arrive(q_full + 8 * qs);
        } else {
          drained(qs);
          if (!dry) {
            mbar_expect_tx(q_full + 8 * qs, A_TILE);
            tma_load_3d_hint(sbase + A_Q_OFF + qs * A_TILE, &maps.q, q_full + 8 * qs, 0, item_m(nitem) * 128,
                             item_h(nitem) * 2, policy_evict_first());
          }
        }
      }
    }
    if (last) break;
    last = nitem >= A_ITEMS;
    m = last ? -1 : item_m(nitem);
    h = item_h(nitem);
  }
}

__device__ __forceinline__ uint32_t attn_consumer(const Maps& maps, uint32_t smem0, uint32_t sn,
                                                  float (&rest)[64], bool after_qkv) {
  PHASE_PROLOGUE
  const uint32_t q_full = bar + B_QFULL, q_empty = bar + B_QEMPTY;
  const uint32_t k_full = bar + B_KFULL, k_empty = bar + B_KEMPTY, v_full = bar + B_VFULL;
  float o[64], s[64];
  uint32_t p[32];
  float e[32];
  uint32_t dep = 0;
  constexpr int MIDJ = 5;
  float l0 = 0.f, l1 = 0.f, b0 = 0.f, b1 = 0.f;
  const int sched_own = 4 + wg, sched_other = 5 - wg;
  if (wg == 1) named_bar_arrive(4, 256);

  const uint32_t qd0 = (uint32_t)make_desc(sbase + A_Q_OFF + wg * 8192, 16, 0, 0);
  const uint32_t kd0 = (uint32_t)make_desc(sbase + A_K_OFF, 16, 0, 0);
  const uint32_t vd0 = (uint32_t)make_desc(sbase + A_V_OFF, 16384, 0, 0);
  constexpr uint64_t DHI = DESC_SW128 | ((uint64_t)(1024 >> 4) << 32);
  constexpr uint32_t DST = A_TILE >> 4;
  auto issue_qk = [&](uint32_t qd, uint32_t kd) {
#pragma unroll
    for (int kk = 0; kk < 8; kk++) {
      const uint32_t off = ((kk >> 2) * 16384 + (kk & 3) * 32) >> 4;
      wgmma_m64n128_ss(s, DHI | (qd + off), DHI | (kd + off), kk != 0);
    }
    wgmma_commit();
  };
  auto issue_pv = [&](uint32_t vd, bool accumulate, int nk) {
#pragma unroll
    for (int kk = 0; kk < 8; kk++) {
      if (kk < nk)
        wgmma_m64n128_rs_tb(o, p[4 * kk], p[4 * kk + 1], p[4 * kk + 2], p[4 * kk + 3], DHI | (vd + kk * 128),
                            accumulate || (kk != 0));
    }
    wgmma_commit();
  };
  auto exp_lo = [&](float& a0, float& a1) {
#pragma unroll
    for (int j = 0; j < 8; j++) {
      e[4 * j] = ex2(s[4 * j]);
      e[4 * j + 1] = ex2(s[4 * j + 1]);
      e[4 * j + 2] = ex2(s[4 * j + 2]);
      e[4 * j + 3] = ex2(s[4 * j + 3]);
      a0 += e[4 * j];
      a0 += e[4 * j + 1];
      a1 += e[4 * j + 2];
      a1 += e[4 * j + 3];
      if (j == MIDJ) dep = (__float_as_uint(a0) | __float_as_uint(a1)) & rt_zero;
    }
  };
  auto pack_lo = [&]() {
#pragma unroll
    for (int j = 0; j < 16; j++) p[j] = pack_bf16(e[2 * j], e[2 * j + 1]);
  };
  auto finish_p = [&](float& a0, float& a1) {
    pack_lo();
#pragma unroll
    for (int j = 8; j < 16; j++) {
      const float e0 = ex2(s[4 * j]), e1 = ex2(s[4 * j + 1]), e2 = ex2(s[4 * j + 2]), e3 = ex2(s[4 * j + 3]);
      a0 += e0;
      a0 += e1;
      a1 += e2;
      a1 += e3;
      p[2 * j] = pack_bf16(e0, e1);
      p[2 * j + 1] = pack_bf16(e2, e3);
      if (j == 8 + MIDJ) dep = __float_as_uint(a0) & rt_zero;
    }
  };
  auto quad_sum = [&](float t) {
    t += __shfl_xor_sync(0xffffffffu, t, 1);
    return t + __shfl_xor_sync(0xffffffffu, t, 2);
  };
  auto write_o = [&](float i0, float i1) {
    st_wait(bar, wg, sn - 1);
    const int st_row = warp * 16 + (lane & 7) + ((lane >> 3) & 1) * 8;
    const uint32_t so = sbase + A_O_OFF + wg * 16384 + st_row * 128;
#pragma unroll
    for (int j = 0; j < 16; j += 2)
      stmatrix_x4(so + (j >> 3) * 8192 + ((((j & 7) + (lane >> 4)) ^ (lane & 7)) << 4),
                  pack_bf16(o[4 * j] * i0, o[4 * j + 1] * i0), pack_bf16(o[4 * j + 2] * i1, o[4 * j + 3] * i1),
                  pack_bf16(o[4 * j + 4] * i0, o[4 * j + 5] * i0), pack_bf16(o[4 * j + 6] * i1, o[4 * j + 7] * i1));
  };
  auto store_o = [&](uint32_t r, int kind) {
    const uint32_t it = item_of(maps, r);
    st_post(bar, wg, wtid, sn, kind, (INPLACE & 1) || kind != ST_BOX2Q ? &maps.o : &maps.c[0], sbase + A_O_OFF + wg * 16384, item_h(it) * 128,
            item_m(it) * 128 + wg * 64, CNT_CTX + (r >> 1));
    sn++;
  };
  auto mask_half = [&](float* sh) {
    const int u = warp * 16 + (lane >> 2) - (lane & 3) * 2;
#pragma unroll
    for (int j = 0; j < 8; j++) {
      if (8 * j > u) sh[4 * j] = -INFINITY;
      if (8 * j + 1 > u) sh[4 * j + 1] = -INFINITY;
      if (8 * j - 8 > u) sh[4 * j + 2] = -INFINITY;
      if (8 * j - 7 > u) sh[4 * j + 3] = -INFINITY;
    }
  };
  ST(0)
  mbar_wait(q_full, 0);
  if (blockIdx.x >= 128) {
    return sn;
  }
  mbar_wait(k_full, 0);
  named_bar_sync(sched_own, 256);
  wgmma_fence();
  issue_qk(qd0, kd0);
  named_bar_arrive(sched_other, 256);
  fence_regs(rest);
#pragma unroll
  for (int i = 0; i < 64; i++) o[i] = rest[i] * Q_SCALE;
  fence_regs(o);
  wgmma_wait<0>();
  fence_regs(s);
  mbar_arrive_if(k_empty, wtid == 32);
  uint32_t g = 0;
  uint32_t rnd = 0;
  int rem = item_m(item_of(maps, 0));
  uint32_t first = 1;
  uint32_t fl = 0;
#define redo (fl & 1)
#define shifted (fl & 2)
  float d0 = 0.f, d1 = 0.f;
  float pi0 = 1.f, pi1 = 1.f;
  ST(1)
  for (;;) {
    if (shifted) {
#pragma unroll
      for (int j = 0; j < 16; j++) {
        s[4 * j] -= d0;
        s[4 * j + 1] -= d0;
        s[4 * j + 2] -= d1;
        s[4 * j + 3] -= d1;
      }
    }
    if (rem == 0 && !redo) {
      mbar_arrive_if(q_empty + 8 * (rnd & 1), wtid == 96);
      rnd++;
      if (wg == 0) mask_half(s);
      else mask_half(s + 32);
    }
    for (;;) {
      const bool kill = rem == 0 && wg == 0;
      const uint32_t kd = kd0 + ((g + 1) & 1) * DST, vd = vd0 + (g & 1) * DST;
      float a0 = 0.f, a1 = 0.f;
      exp_lo(a0, a1);
      fence_regs(e);
      const uint32_t kb = k_full + 8 * ((g + 1) & 1);
      const uint32_t kpar = ((((g + 1) >> 1) & 1) ^ (g == A_STEPS - 1 ? 1u : 0u)) | dep;
      if (!mbar_try(kb, kpar)) mbar_wait(kb, kpar | ((__float_as_uint(a0) | __float_as_uint(a1)) & rt_zero));
      wgmma_wait<0>();
      fence_regs(o);
      if (kill) {
        mbar_arrive_if(kb + (B_VEMPTY - B_KFULL), wtid == 64 && !redo && g > 0);
        fence_regs(e);
        pack_lo();
#pragma unroll
        for (int j = 16; j < 32; j++) asm volatile("mov.u32 %0, 0;" : "=r"(p[j]));
        goto check;
      }
#pragma unroll
      for (int i = 32; i < 64; i++) asm volatile("" : "+f"(s[i])::"memory");
      mbar_arrive_if(kb + (B_VEMPTY - B_KFULL), wtid == 64 && !redo && g > 0);
      finish_p(a0, a1);
      if (__any_sync(0xffffffffu, !(mbar_try(v_full + 8 * (g & 1), ((g >> 1) & 1) | dep) &
                                    mbar_try(q_full + 8 * (rnd & 1), ((rnd >> 1) & 1) | dep)) ||
                                      !(a0 + a1 < 1.0995116e12f) || !(fminf(a0, a1) > (first ? 9.094947e-13f : -1.f)))) {
      check:
        bool bad = !(a0 + a1 < 1.0995116e12f);
        if (first) bad |= !(fminf(quad_sum(a0), quad_sum(a1)) > 9.094947e-13f);
        if (!redo && __any_sync(0xffffffffu, bad)) {
          d0 = d1 = first ? -INFINITY : 0.f;
#pragma unroll
          for (int j = 0; j < 16; j++) {
            if (j < 8 || !kill) {
              d0 = fmaxf(d0, fmaxf(s[4 * j], s[4 * j + 1]));
              d1 = fmaxf(d1, fmaxf(s[4 * j + 2], s[4 * j + 3]));
            }
          }
#pragma unroll
          for (int x = 1; x <= 2; x++) {
            d0 = fmaxf(d0, __shfl_xor_sync(0xffffffffu, d0, x));
            d1 = fmaxf(d1, __shfl_xor_sync(0xffffffffu, d1, x));
          }
          b0 += d0;
          b1 += d1;
          if (!first) {
            const float al0 = ex2(-d0), al1 = ex2(-d1);
            l0 *= al0;
            l1 *= al1;
#pragma unroll
            for (int j = 0; j < 16; j++) {
              o[4 * j] *= al0;
              o[4 * j + 1] *= al0;
              o[4 * j + 2] *= al1;
              o[4 * j + 3] *= al1;
            }
          }
          fl = 3;
          break;
        }
        mbar_wait(v_full + 8 * (g & 1), (g >> 1) & 1);
        mbar_wait(q_full + 8 * (rnd & 1), (rnd >> 1) & 1);
      }
      named_bar_sync(sched_own, 256);
      if (g == A_STEPS - 1) {
        if (first) write_o(pi0, pi1);
        fence_regs(o);
        wgmma_fence();
        issue_pv(vd, !first, 8);
        named_bar_arrive(sched_other, 256);
        if (first) store_o(rnd - 2, ST_BOX2);
        pi0 = rcp(quad_sum(l0 + a0));
        pi1 = rcp(quad_sum(l1 + a1));
        goto done;
      }
      wgmma_fence();
      issue_qk(qd0 + (rnd & 1) * DST, kd);
      if (first) write_o(pi0, pi1);
      fence_regs(o);
      if (kill) {
        wgmma_fence();
        issue_pv(vd, !first, 4);
      } else {
        wgmma_fence();
        issue_pv(vd, !first, 8);
      }
      named_bar_arrive(sched_other, 256);
      fl &= 2;
      l0 += a0;
      l1 += a1;
      if (rem == 0 || first) {
        if (first && (g > 0 || after_qkv)) store_o(g ? rnd - (rem == 0 ? 2 : 1) : 2, g ? ST_BOX2 : ST_BOX2Q);
        first = rem == 0;
        if (first) {
          pi0 = rcp(quad_sum(l0));
          pi1 = rcp(quad_sum(l1));
          l0 = l1 = b0 = b1 = 0.f;
          fl = 0;
          rem = item_m(item_of(maps, rnd)) + 1;
        }
      }
      rem--;
      g++;
      wgmma_wait<1>();
      fence_regs(s);
      mbar_arrive_if(kb + (B_KEMPTY - B_KFULL), wtid == 32);
      ST(g + 1)
      if (rem == 0 || shifted) {
        d0 = b0;
        d1 = b1;
        break;
      }
    }
  }
done:
#undef redo
#undef shifted
  wgmma_wait<0>();
  fence_regs(o);
  write_o(pi0, pi1);
  store_o(3, ST_BOX2L);
  ST(35)
  return sn;
}

constexpr int O_STAGES = 5;
constexpr int O_STAGE_BYTES = 32768;
constexpr int O_Y_OFF = 5 * 32768;
constexpr int O_X_OFF = 6 * 32768;
constexpr int O_NK = HDIM / 64;

__device__ __forceinline__ uint32_t out_stage(uint32_t st) { return ((0x43120u >> (4 * st)) & 7) * O_STAGE_BYTES; }

__device__ __forceinline__ void out_producer(const Maps& maps, uint32_t sbase, bool after_attn, bool dry) {
  const uint32_t bar = sbase + BAR_OFF;
  const uint32_t rank = blockIdx.x & 1;
  const int m_tile = maps.id[blockIdx.x][2] & 15, n_tile = maps.id[blockIdx.x][2] >> 4;
  uint32_t stage = 0, phase = 0, xi = 0;
#pragma unroll 1
  for (int ki = 0; ki < (dry ? 1 : O_NK); ki++) {
    const int kt = (ki & 14) * 4 + ((A_ORDER >> ((ki >> 4) * 4)) & 3) * 2 + (ki & 1);
    const uint32_t fb = bar + B_OFULL + 8 * stage, eb = bar + B_OEMPTY + 8 * stage;
    const uint32_t sa = sbase + out_stage(stage);
    if (ki < O_STAGES) {
      constexpr uint32_t LASTB = B_KEMPTY | ((B_QEMPTY + 8) << 8) | ((B_KEMPTY + 8) << 16) | (B_VEMPTY << 24);
      if (ki > 0 && after_attn) mbar_wait_sleep(bar + ((LASTB >> (8 * ki - 8)) & 255), ki == 2);
      mbar_arrive_cluster_if(eb, 0, !dry);
      mbar_arrive_cluster_if(eb, 1, !dry);
    }
    if (ki == 32) mbar_wait_sleep(bar + seen_bar(2), 0);
    if (!dry) {
      mbar_wait_sleep(eb, phase);
      mbar_expect_tx(fb, O_STAGE_BYTES);
      tma_load_2d_mc(sa + 16384 + rank * 8192, &maps.ob, fb, n_tile * 128 + rank * 64, kt * 64, (uint16_t)3);
      tma_load_2d(sa, &maps.oa, fb, kt * 64, m_tile * 128);
    }
    if (++stage == O_STAGES) { stage = 0; phase ^= 1; }
    if ((ki & XMASK) == XMASK && ki >= XFIRST && xi < 8) {
      if (after_attn && xi < 2) mbar_wait_sleep(bar + B_OFREE + 8 * xi, 0);
      tma_load_3d(sbase + O_X_OFF + (xi & 1) * 16384 + (xi >> 1) * 4096, &maps.xs, bar + B_OY, 0,
                  m_tile * 128 + (xi >> 1) * 32, n_tile * 2 + (xi & 1));
      xi++;
    }
  }
  if (!dry) mbar_wait_sleep(bar + B_OY2, 0);
}

__device__ __forceinline__ void out_side(const Maps& maps, uint32_t smem0, const float (&gv)[4]) {
  PHASE_PROLOGUE
  const int m_tile = maps.id[blockIdx.x][2] & 15, n_tile = maps.id[blockIdx.x][2] >> 4;
  const bool w0 = __shfl_sync(0xffffffffu, warp, 0) == 0;
  bool have = false;
  auto late = [&](uint32_t spins) {
    have = cnt_wait(CNT_Y2 + 1, 128, spins) || !spins;
    TD(11)
    if (have) {
      mbar_expect_tx(bar + B_OY2, 4096);
      tma_load_3d(sbase + O_Y_OFF + 7 * 4096, &maps.y, bar + B_OY2, 0, n_tile * 128 + 112, m_tile * 2);
    }
  };
  if (w0) {
    if (elect_one()) {
      mbar_expect_tx(bar + B_OY, 65536 - 4096);
      TD(10)
      cnt_wait(CNT_Y2, DM - 128);
      TD(7)
#pragma unroll 1
      for (int i = 0; i < 7; i++) {
        tma_load_3d(sbase + O_Y_OFF + i * 4096, &maps.y, bar + B_OY, 0, n_tile * 128 + i * 16, m_tile * 2);
        __nanosleep(PACE);
      }
      late(1u << 18);
    }
  }
  mbar_wait_sleep(bar + B_OY, 0);
  if (wtid == 0) { TD(12) }
  const int st_row = warp * 16 + (lane & 7) + ((lane >> 3) & 1) * 8;
  const int mrow = (lane & 7) + ((lane >> 4) & 1) * 8;
  const int mchunk = warp * 2 + ((lane >> 3) & 1);
  const uint32_t xrow = sbase + O_X_OFF + st_row * 128;
  const uint32_t yrow = sbase + O_Y_OFF + mrow * 128 + ((mchunk ^ (lane & 7)) << 4);
  uint32_t y[7][4], x[7][4], om[4];
#pragma unroll
  for (int i = 0; i < 4; i++) om[i] = pack_bf16(1.0f - gv[i], 1.0f - gv[i]);
  auto xa = [&](int h, int i) { return xrow + h * 8192 + (i >> 2) * 16384 + ((((i & 3) * 2 + (lane >> 4)) ^ (lane & 7)) << 4); };
  auto load = [&](int r, int h, int i) {
    ldsm4t(y[r], yrow + h * 2048 + i * 4096);
    asm volatile("ldmatrix.sync.aligned.m8n8.x4.shared.b16 {%0, %1, %2, %3}, [%4];"
                 : "=r"(x[r][0]), "=r"(x[r][1]), "=r"(x[r][2]), "=r"(x[r][3])
                 : "r"(xa(h, i)));
  };
  auto store = [&](int r, int h, int i, uint32_t om0, uint32_t om1) {
    stmatrix_x4(xa(h, i), mul_bf2(om0, mul_bf2(x[r][0], y[r][0])), mul_bf2(om1, mul_bf2(x[r][1], y[r][1])),
                mul_bf2(om0, mul_bf2(x[r][2], y[r][2])), mul_bf2(om1, mul_bf2(x[r][3], y[r][3])));
  };
#pragma unroll 1
  for (int h = 0; h < 2; h++) {
#pragma unroll
    for (int i = 0; i < 7; i++) load(i, h, i);
#pragma unroll
    for (int i = 0; i < 7; i++) store(i, h, i, h ? om[2] : om[0], h ? om[3] : om[1]);
  }
  if (w0 && !__any_sync(0xffffffffu, have)) {
    if (elect_one()) late(0);
  }
  mbar_wait_sleep(bar + B_OY2, 0);
  load(0, 0, 7);
  load(1, 1, 7);
  store(0, 0, 7, om[0], om[1]);
  store(1, 1, 7, om[2], om[3]);
  __syncwarp();
  mbar_arrive_if(bar + B_OY + 8, lane == 0);
  if (wtid == 0) { TD(13) }
}

__device__ __forceinline__ uint32_t out_gemm(const Maps& maps, uint32_t smem0, uint32_t sn) {
  PHASE_PROLOGUE
  const int m_tile = maps.id[blockIdx.x][2] & 15, n_tile = maps.id[blockIdx.x][2] >> 4;
  float acc[2][64];
  undef_regs(acc[0]);
  undef_regs(acc[1]);
  uint32_t stage = 0, phase = 0, prev_stage = 0;
  GT(gti++)
  const float* gp = g_gate + m_tile * 128 + warp * 16 + (lane >> 2);
  const float gv[4] = {__ldcg(gp), __ldcg(gp + 8), __ldcg(gp + 64), __ldcg(gp + 72)};
  if (wg == 1) {
    out_side(maps, smem0, gv);
    return sn;
  }
#pragma unroll 1
  for (int kt = 0; kt < O_NK; kt++) {
    uint32_t da = (uint32_t)make_desc(sbase + out_stage(stage), 16, 0, 0);
    uint32_t db = (uint32_t)make_desc(sbase + out_stage(stage) + 16384, 8192, 0, 0);
    asm volatile("" : "+r"(da), "+r"(db));
    mbar_wait(bar + B_OFULL + 8 * stage, phase);
    GT(gti++)
#define OWAIT_ 2
    constexpr int OWAIT = OWAIT_;
    constexpr uint64_t DHI = DESC_SW128 | ((uint64_t)(1024 >> 4) << 32);
#pragma unroll
    for (int kk = 0; kk < 4; kk++) {
      wgmma_wait<OWAIT>();
      if (kk == OWAIT)
        mbar_arrive_cluster_if(bar + B_OEMPTY + 8 * prev_stage, wtid >> 6,
                               (wtid & 63) == 32 && kt > 0 && kt - 1 + O_STAGES < O_NK);
      wgmma_fence();
      wgmma_m64n128_ss_tb(acc[0], DHI | (da + kk * 2), DHI | (db + kk * 128), (kt | kk) != 0);
      wgmma_m64n128_ss_tb(acc[1], DHI | (da + 512 + kk * 2), DHI | (db + kk * 128), (kt | kk) != 0);
      wgmma_commit();
    }
    prev_stage = stage;
    if (++stage == O_STAGES) { stage = 0; phase ^= 1; }
  }
  if (tid == 0) { TD(14) }
  st_wait(bar, wg, sn - 1);
  const int st_row = warp * 16 + (lane & 7) + ((lane >> 3) & 1) * 8;
  const uint32_t rowa = sbase + O_X_OFF + st_row * 128;
  auto addr = [&](int i) {
    return rowa + (i & 1) * 8192 + (i >> 3) * 16384 + ((((i & 6) + (lane >> 4)) ^ (st_row & 7)) << 4);
  };
  uint32_t gg[4], b[16][4];
#pragma unroll
  for (int i = 0; i < 4; i++) gg[i] = pack_bf16(gv[i], gv[i]);
  mbar_wait(bar + B_OY + 8, 0);
#pragma unroll
  for (int i = 0; i < 16; i++)
    asm volatile("ldmatrix.sync.aligned.m8n8.x4.shared.b16 {%0, %1, %2, %3}, [%4];"
                 : "=r"(b[i][0]), "=r"(b[i][1]), "=r"(b[i][2]), "=r"(b[i][3])
                 : "r"(addr(i))
                 : "memory");
  wgmma_wait<0>();
  fence_regs(acc[0]);
  fence_regs(acc[1]);
  GT(gti++)
#pragma unroll
  for (int i = 0; i < 16; i++) {
    const float* a = acc[i & 1] + 4 * (i & 14);
    const uint32_t gg0 = gg[2 * (i & 1)], gg1 = gg[2 * (i & 1) + 1];
    stmatrix_x4(addr(i), add_bf2(mul_bf2(gg0, pack_bf16(a[0], a[1])), b[i][0]),
                add_bf2(mul_bf2(gg1, pack_bf16(a[2], a[3])), b[i][1]),
                add_bf2(mul_bf2(gg0, pack_bf16(a[4], a[5])), b[i][2]),
                add_bf2(mul_bf2(gg1, pack_bf16(a[6], a[7])), b[i][3]));
    if (i == 7) st_post(bar, wg, wtid, sn, ST_BOX1, &maps.oc, sbase + O_X_OFF, n_tile * 128, m_tile * 128, -1);
  }
  fence_proxy_async();
  named_bar_sync(1, 128);
  if (__shfl_sync(0xffffffffu, warp, 0) == 0) {
    if (elect_one()) {
      tma_store_2d(&maps.oc, sbase + O_X_OFF + 16384, n_tile * 128 + 64, m_tile * 128);
      tma_store_commit();
    }
  }
  GT(gti++)
  return sn + 1;
}

__device__ __noinline__ void leave_kernel(int mask) {
  if (!(mask & 4)) return;
  if (atomicAdd(g_cnt + CNT_DONE * 32, 1u) == 2 * gridDim.x - 1) {
    for (int i = 0; i < CNT_N; i++) g_cnt[i * 32] = 0;
#pragma unroll 4
    for (int i = 0; i < 128; i++) g_slot[i] = 0;
  }
}

__device__ __noinline__ void side_jobs(const Maps& maps, uint32_t sbase) {
  const int w12 = __shfl_sync(0xffffffffu, threadIdx.x >> 5, 0);
  gate_rows(maps, sbase, (blockIdx.x - 128) * 12 + w12, w12, threadIdx.x & 31);
  fence_proxy_async();
  __syncthreads();
  if (threadIdx.x == 320) cnt_signal_release(CNT_PREP, 1);
}

__global__ void __launch_bounds__(384, 1) fused_kernel(int mask, const __grid_constant__ Maps maps) {
  extern __shared__ __align__(1024) uint8_t smem_raw[];
  {
    const uint32_t sbase = __shfl_sync(0xffffffffu, smem_u32(smem_raw), 0);
    const uint32_t bar = sbase + BAR_OFF;
    const int tid = threadIdx.x;
    const bool do_qkv = (mask & 1) && blockIdx.x < 128;
    TL(0, 0)
    if (__shfl_sync(0xffffffffu, tid >> 5, 0) == 1 && do_qkv) {
      if (elect_one()) {
        for (int i = 0; i < G_STAGES; i++) mbar_init(bar + B_GFULL + 8 * i, 1);
        fence_barrier_init();
        qkv_producer(maps, sbase, true);
      }
    }
    if (tid == 0) {
      for (int i = 0; i < G_STAGES; i++) {
        mbar_init(bar + B_GEMPTY + 8 * i, 2);
        mbar_init(bar + B_SFULL + 8 * i, 4);
        mbar_init(bar + B_SFREE + 8 * i, 1);
      }
      for (int i = 0; i < 2; i++) {
        mbar_init(bar + B_OFREE + 8 * i, 1);
        mbar_init(bar + B_QFULL + 8 * i, 1);
        mbar_init(bar + B_QEMPTY + 8 * i, 2);
        mbar_init(bar + B_KFULL + 8 * i, 1);
        mbar_init(bar + B_KEMPTY + 8 * i, 2);
        mbar_init(bar + B_VFULL + 8 * i, 1);
        mbar_init(bar + B_VEMPTY + 8 * i, 2);
      }
      for (int i = 0; i < O_STAGES; i++) {
        mbar_init(bar + B_OFULL + 8 * i, 1);
        mbar_init(bar + B_OEMPTY + 8 * i, 2);
      }
      mbar_init(bar + B_OY, 1);
      for (int i = 0; i < 3; i++) mbar_init(bar + seen_bar(i), 1);
      mbar_init(bar + B_OY2, 1);
      mbar_init(bar + B_DEAL, 1);
      mbar_init(bar + B_DEAL2, 1);
      mbar_init(bar + B_PAIR, 1);
      mbar_init(bar + B_OY + 8, 4);
      mbar_init(bar + B_QDONE, 2);
      for (int i = 0; i < 8; i++) mbar_init(bar + B_CFULL + 8 * i, 1);
      for (int i = 0; i < CNT_N; i++) asm volatile("st.shared.u32 [%0], 0;" ::"r"(bar + B_PEND + 4 * i) : "memory");
      fence_barrier_init();
    }
    __syncthreads();
    asm volatile("barrier.cluster.arrive.relaxed.aligned;" ::: "memory");
    if ((mask & 1) && blockIdx.x >= 128) side_jobs(maps, sbase);
  }
  uint32_t smem0 = smem_u32(smem_raw);
  PHASE_PROLOGUE
  const bool do_qkv = (mask & 1) && blockIdx.x < 128, do_out = (mask & 4) && blockIdx.x < 128;
  TL(0, 1)

  if (wg != 2) {
    reg_alloc<232>();
    uint32_t sn = 0;
    float o[64];
    if (do_qkv) {
      sn = qkv_consumer(maps, smem_u32(smem_raw), mask & 2, o);
    } else {
      undef_regs(o);
    }
    TL(0, 2) TL(1, 0) TL(1, 1)
    asm volatile("barrier.cluster.wait.acquire.aligned;" ::: "memory");
    if (mask & 2) {
      sn = attn_consumer(maps, smem_u32(smem_raw), sn, o, mask & 1);
      TL(2, 0)
      if ((mask & 4) && blockIdx.x < 128 && __shfl_sync(0xffffffffu, threadIdx.x, 0) < 128) {
        named_bar_arrive(3, 256);
      } else {
        const uint32_t b2 = blockIdx.x * 2 + (threadIdx.x >> 7);
        const bool fused = mask & 4, mainc = blockIdx.x < 128;
        const uint32_t first = __shfl_sync(0xffffffffu, !fused ? b2 : mainc ? conv_first(maps) : (b2 - 255) * 128 - C_SIDE, 0);
        conv_consumer(maps, smem_u32(smem_raw), first, !fused ? 264 : mainc ? 16 : 1,
                      !fused ? DM : mainc ? (first | 127) + 1 - C_SIDE : first + C_SIDE, fused && !mainc,
                      fused && mainc);
      }
      TL(1, 2) TL(2, 1) TL(2, 2)
    }
    TL(3, 0) TL(3, 1)
    if ((mask & 4) && blockIdx.x < 128) sn = out_gemm(maps, smem_u32(smem_raw), sn);
    {
      uint32_t smem0 = smem_u32(smem_raw);
      PHASE_PROLOGUE
      st_wait(bar, wg, sn - 2);
      st_post(bar, wg, wtid, sn, ST_END, nullptr, 0, 0, 0, -1);
      tma_store_wait_read<0>();
    }
  } else {
    reg_dealloc<40>();
    asm volatile("barrier.cluster.wait.acquire.aligned;" ::: "memory");
    const int w = __shfl_sync(0xffffffffu, tid >> 5, 0) - 8;
    if (w < 2) {
      if (do_qkv) prep_agent(maps, sbase, w, lane);
      if (elect_one()) store_agent(bar, w, w && do_out ? conv_first(maps) + 48 : 0);
      TL2(3, 2)
    } else {
      if (elect_one()) {
        const bool dry = w == 2;
        if (do_qkv && !dry) qkv_producer(maps, sbase, false);
        if (mask & 2) attn_producer(maps, sbase, do_qkv, do_out, dry);
        if (do_out) out_producer(maps, sbase, mask & 2, dry);
        if (dry) { TD(5) }
      }
      __syncwarp();
      if (w == 2) publisher(bar, tid & 31, !(mask & 2) ? 2 : do_out ? 3 : 4, !do_out ? 3 : do_qkv ? 0 : 2, do_qkv ? 4 : 0);
      if ((tid & 31) == 0) leave_kernel(mask);
    }
  }
}

typedef CUresult (*PFN_tmapEncode)(CUtensorMap*, CUtensorMapDataType, cuuint32_t, void*, const cuuint64_t*,
                                   const cuuint64_t*, const cuuint32_t*, const cuuint32_t*, CUtensorMapInterleave,
                                   CUtensorMapSwizzle, CUtensorMapL2promotion, CUtensorMapFloatOOBfill);
static PFN_tmapEncode s_encode = nullptr;

static void make_map_2d(CUtensorMap* m, const void* ptr, int rows, int cols, int box_rows) {
  cuuint64_t dims[2] = {(cuuint64_t)cols, (cuuint64_t)rows};
  cuuint64_t strides[1] = {(cuuint64_t)cols * 2};
  cuuint32_t box[2] = {cols < 64 ? 32u : 64u, (cuuint32_t)box_rows};
  cuuint32_t es[2] = {1, 1};
  s_encode(m, CU_TENSOR_MAP_DATA_TYPE_BFLOAT16, 2, const_cast<void*>(ptr), dims, strides, box, es,
           CU_TENSOR_MAP_INTERLEAVE_NONE, cols < 64 ? CU_TENSOR_MAP_SWIZZLE_64B : CU_TENSOR_MAP_SWIZZLE_128B, CU_TENSOR_MAP_L2_PROMOTION_L2_256B,
           CU_TENSOR_MAP_FLOAT_OOB_FILL_NONE);
}
static void make_map_3d(CUtensorMap* m, const void* ptr, int rows, int cols, int box_rows, int box_chunks) {
  cuuint64_t dims[3] = {64, (cuuint64_t)rows, (cuuint64_t)(cols / 64)};
  cuuint64_t strides[2] = {(cuuint64_t)cols * 2, 128};
  cuuint32_t box[3] = {64, (cuuint32_t)box_rows, (cuuint32_t)box_chunks};
  cuuint32_t es[3] = {1, 1, 1};
  s_encode(m, CU_TENSOR_MAP_DATA_TYPE_BFLOAT16, 3, const_cast<void*>(ptr), dims, strides, box, es,
           CU_TENSOR_MAP_INTERLEAVE_NONE, CU_TENSOR_MAP_SWIZZLE_128B, CU_TENSOR_MAP_L2_PROMOTION_L2_256B,
           CU_TENSOR_MAP_FLOAT_OOB_FILL_NONE);
}

static cudaLaunchConfig_t fused_cfg(cudaLaunchAttribute* at) {
  cudaLaunchConfig_t cfg = {};
  cfg.gridDim = dim3(132);
  cfg.blockDim = dim3(384);
  cfg.dynamicSmemBytes = SMEM_BYTES;
  cfg.stream = cudaStreamPerThread;
  at[0].id = cudaLaunchAttributeClusterDimension;
  at[0].val.clusterDim.x = 2;
  at[0].val.clusterDim.y = 1;
  at[0].val.clusterDim.z = 1;
  cfg.attrs = at;
  cfg.numAttrs = 1;
  return cfg;
}

extern "C" void kernel_launch(void* const* d_in, const int* in_sizes, int n_in, void* d_out, int out_size) {
  const bf16* x = (const bf16*)d_in[0];
  const bf16* ckv = (const bf16*)d_in[1];
  const bf16* wq = (const bf16*)d_in[2];
  const bf16* wuk = (const bf16*)d_in[3];
  const bf16* wuv = (const bf16*)d_in[4];
  const bf16* wo = (const bf16*)d_in[5];
  const bf16* bk = (const bf16*)d_in[7];
  const bf16* bv = (const bf16*)d_in[8];
  const bf16* shift_k = (const bf16*)d_in[9];
  const bf16* ssm_k = (const bf16*)d_in[10];
  const bf16* ssm_D = (const bf16*)d_in[11];
  const bf16* gate_w = (const bf16*)d_in[12];
  bf16* out = (bf16*)d_out;

  static void *pq = nullptr, *pk = nullptr, *pv = nullptr, *pctx = nullptr, *pb = nullptr, *pu = nullptr;
  static int max_clusters = 0;
  if (!s_encode) {
    void* fn = nullptr;
    cudaDriverEntryPointQueryResult qres;
    cudaGetDriverEntryPoint("cuTensorMapEncodeTiled", &fn, cudaEnableDefault, &qres);
    s_encode = (PFN_tmapEncode)fn;
    cudaGetSymbolAddress(&pq, g_q);
    cudaGetSymbolAddress(&pk, g_k);
    cudaGetSymbolAddress(&pv, g_v);
    cudaGetSymbolAddress(&pctx, g_ctx);
    cudaGetSymbolAddress(&pb, g_y2T);
    cudaGetSymbolAddress(&pu, g_kvT);
    cudaFuncSetAttribute(fused_kernel, cudaFuncAttributeMaxDynamicSharedMemorySize, SMEM_BYTES);
    cudaLaunchAttribute at[1];
    cudaLaunchConfig_t cfg = fused_cfg(at);
    if (cudaOccupancyMaxActiveClusters(&max_clusters, fused_kernel, &cfg) != cudaSuccess) max_clusters = 0;
  }

  Maps all = {};
  make_map_2d(&all.a[0], x, S_LEN, DM, 128);
  make_map_2d(&all.a[1], ckv, S_LEN, DC, 128);
  make_map_3d(&all.b[0], wq, DM, HDIM, 64, 4);
  make_map_3d(&all.b[1], wuk, DC, HDIM, 64, 4);
  make_map_3d(&all.b[2], wuv, DC, HDIM, 64, 4);
  make_map_2d(&all.c[0], pq, S_LEN, HDIM, 64);
  make_map_2d(&all.c[1], pk, S_LEN, HDIM, 64);
  make_map_2d(&all.c[2], pv, S_LEN, HDIM, 64);
  make_map_3d(&all.q, pq, S_LEN, HDIM, 128, 2);
  make_map_3d(&all.k, pk, S_LEN, HDIM, 128, 2);
  make_map_3d(&all.v, pv, S_LEN, HDIM, 128, 2);
  make_map_2d(&all.o, pctx, S_LEN, HDIM, 64);
  all.ssm_k = ssm_k;
  all.ssm_D = ssm_D;
  make_map_2d(&all.oa, pctx, S_LEN, HDIM, 128);
  make_map_2d(&all.ob, wo, HDIM, DM, 64);
  make_map_2d(&all.oc, out, S_LEN, DM, 128);
  make_map_3d(&all.y, pb, DM, S_LEN, 16, 2);
  make_map_3d(&all.xs, x, S_LEN, DM, 32, 1);
  make_map_2d(&all.cu, pu, DM * 64, 32, 64);
  make_map_2d(&all.ch, ssm_k, DM * 64, 32, 64);

  make_map_2d(&all.bk, bk, S_LEN, DM, 35);
  make_map_2d(&all.bv, bv, S_LEN, DM, 32);
  for (int b = 0; b < 128; b++) {
    const int c = b >> 1, r = b & 1;
    const int G = c < 4 ? 0 : c < 36 ? (c - 4) % 8 : 1 + (c - 36) % 7;
    const int i = c < 4 ? 4 + c : c < 36 ? (c - 4) / 8 : 4 + (c - 36) / 7;
    all.id[b][0] = r + 2 * (i & 1) + 4 * (G & 3) + 16 * (i >> 1) + 64 * (G >> 2);
    all.id[b][1] = r + 2 * i + 16 * G;
    all.id[b][2] = r + 2 * G + 16 * i;
  }
  all.shift_k = shift_k;
  all.x = x;
  all.gate_w = gate_w;
  cudaLaunchAttribute at[1];
  cudaLaunchConfig_t cfg = fused_cfg(at);
  if (max_clusters >= 66) {
    cudaLaunchKernelEx(&cfg, fused_kernel, 7, all);
  } else {
    for (int m = 1; m <= 4; m <<= 1) cudaLaunchKernelEx(&cfg, fused_kernel, m, all);
  }
}
```

```cpp
#include <cuda_runtime.h>
#include <cuda_bf16.h>
#include <cuda.h>
#include <stdint.h>

typedef __nv_bfloat16 bf16;
#define INPLACE 3

constexpr int S_LEN = 2048;
constexpr int DM = 1024;
constexpr int NH = 32;
constexpr int HD = 128;
constexpr int DC = 512;
constexpr int HDIM = NH * HD;

__device__ __align__(1024) bf16 g_q[S_LEN * HDIM];
__device__ __align__(1024) bf16 g_k[S_LEN * HDIM];
__device__ __align__(1024) bf16 g_v[S_LEN * HDIM];
#define g_ctx g_q
__device__ __align__(1024) bf16 g_kvT[DM * S_LEN];
#define g_y2T g_kvT
__device__ __align__(1024) float g_gate[S_LEN];
enum { CNT_KV = 0, CNT_PREP = CNT_KV + 2, CNT_CTX, CNT_Y2 = CNT_CTX + 2, CNT_DONE = CNT_Y2 + 2, CNT_RANK, CNT_N };
__device__ unsigned int g_cnt[CNT_N * 32];
__device__ unsigned long long g_slot[128];

#define TL(k, i)
#define TL2(k, i)
#define TD(i)
#define CT(i)
#define GT(i)
#define GA(i)
#define ST(i)

__device__ __forceinline__ uint32_t smem_u32(const void* p) { return (uint32_t)__cvta_generic_to_shared(p); }

__device__ __forceinline__ void mbar_init(uint32_t bar, uint32_t count) {
  asm volatile("mbarrier.init.shared::cta.b64 [%0], %1;" ::"r"(bar), "r"(count));
}
__device__ __forceinline__ void mbar_expect_tx(uint32_t bar, uint32_t bytes) {
  asm volatile("mbarrier.arrive.expect_tx.shared::cta.b64 _, [%0], %1;" ::"r"(bar), "r"(bytes) : "memory");
}
__device__ __forceinline__ void mbar_arrive(uint32_t bar) {
  asm volatile("mbarrier.arrive.shared::cta.b64 _, [%0];" ::"r"(bar) : "memory");
}
__device__ __forceinline__ void mbar_wait(uint32_t bar, uint32_t parity) {
  uint32_t done;
  uint32_t spins = 0;
  do {
    asm volatile(
        "{\n.reg .pred p;\n"
        "mbarrier.try_wait.parity.shared::cta.b64 p, [%1], %2;\n"
        "selp.u32 %0, 1, 0, p;\n}\n"
        : "=r"(done)
        : "r"(bar), "r"(parity)
        : "memory");
    if (++spins > (1u << 22)) break;
  } while (!done);
}
__device__ __forceinline__ bool mbar_try(uint32_t bar, uint32_t parity) {
  uint32_t done;
  asm volatile(
      "{\n.reg .pred p;\n"
      "mbarrier.try_wait.parity.shared::cta.b64 p, [%1], %2;\n"
      "selp.u32 %0, 1, 0, p;\n}\n"
      : "=r"(done)
      : "r"(bar), "r"(parity)
      : "memory");
  return done != 0;
}
__device__ __forceinline__ bool elect_one() {
  uint32_t pred;
  asm volatile("{\n.reg .pred p;\nelect.sync _|p, 0xffffffff;\nselp.u32 %0, 1, 0, p;\n}\n" : "=r"(pred));
  return pred != 0;
}
__device__ __forceinline__ void mbar_arrive_if(uint32_t bar, bool pred) {
  asm volatile(
      "{\n.reg .pred p;\nsetp.ne.b32 p, %1, 0;\n"
      "@p mbarrier.arrive.shared::cta.b64 _, [%0];\n}\n" ::"r"(bar),
      "r"((uint32_t)pred)
      : "memory");
}
__device__ __forceinline__ void mbar_wait_sleep(uint32_t bar, uint32_t parity) {
  uint32_t done;
  uint32_t spins = 0;
  do {
    asm volatile(
        "{\n.reg .pred p;\n"
        "mbarrier.try_wait.parity.shared::cta.b64 p, [%1], %2, %3;\n"
        "selp.u32 %0, 1, 0, p;\n}\n"
        : "=r"(done)
        : "r"(bar), "r"(parity), "r"(20000u)
        : "memory");
    if (++spins > (1u << 16)) break;
  } while (!done);
}
__device__ __forceinline__ void fence_barrier_init() {
  asm volatile("fence.mbarrier_init.release.cluster;" ::: "memory");
}
__device__ __forceinline__ void fence_proxy_async() {
  asm volatile("fence.proxy.async.shared::cta;" ::: "memory");
}
__device__ __forceinline__ void named_bar_sync(int id, int nthreads) {
  asm volatile("bar.sync %0, %1;" ::"r"(id), "r"(nthreads) : "memory");
}
__device__ __forceinline__ void named_bar_arrive(int id, int nthreads) {
  asm volatile("bar.arrive %0, %1;" ::"r"(id), "r"(nthreads) : "memory");
}
__device__ __forceinline__ void tma_load_2d(uint32_t dst, const CUtensorMap* m, uint32_t bar, int c0, int c1) {
  asm volatile(
      "cp.async.bulk.tensor.2d.shared::cluster.global.mbarrier::complete_tx::bytes [%0], [%1, {%3, %4}], [%2];" ::"r"(dst),
      "l"(reinterpret_cast<uint64_t>(m)), "r"(bar), "r"(c0), "r"(c1)
      : "memory");
}
__device__ __forceinline__ void tma_load_3d(uint32_t dst, const CUtensorMap* m, uint32_t bar, int c0, int c1, int c2) {
  asm volatile(
      "cp.async.bulk.tensor.3d.shared::cluster.global.mbarrier::complete_tx::bytes [%0], [%1, {%3, %4, %5}], [%2];" ::"r"(dst),
      "l"(reinterpret_cast<uint64_t>(m)), "r"(bar), "r"(c0), "r"(c1), "r"(c2)
      : "memory");
}
__device__ __forceinline__ void tma_store_2d(const CUtensorMap* m, uint32_t src, int c0, int c1) {
  asm volatile("cp.async.bulk.tensor.2d.global.shared::cta.bulk_group [%0, {%2, %3}], [%1];" ::"l"(
                   reinterpret_cast<uint64_t>(m)),
               "r"(src), "r"(c0), "r"(c1)
               : "memory");
}
__device__ __forceinline__ void bulk_load(uint32_t dst, const void* src, uint32_t bytes, uint32_t bar) {
  asm volatile("cp.async.bulk.shared::cluster.global.mbarrier::complete_tx::bytes [%0], [%1], %2, [%3];" ::"r"(dst),
               "l"(src), "r"(bytes), "r"(bar)
               : "memory");
}
__device__ __forceinline__ void tma_load_2d_mc(uint32_t dst, const CUtensorMap* m, uint32_t bar, int c0, int c1,
                                               uint16_t mask) {
  asm volatile(
      "cp.async.bulk.tensor.2d.shared::cluster.global.mbarrier::complete_tx::bytes.multicast::cluster [%0], [%1, {%3, "
      "%4}], [%2], %5;" ::"r"(dst),
      "l"(reinterpret_cast<uint64_t>(m)), "r"(bar), "r"(c0), "r"(c1), "h"(mask)
      : "memory");
}
__device__ __forceinline__ void mbar_arrive_cluster_if(uint32_t bar, uint32_t cta, bool pred) {
  asm volatile(
      "{\n.reg .b32 ra;\n.reg .pred p;\nsetp.ne.b32 p, %2, 0;\n"
      "mapa.shared::cluster.u32 ra, %0, %1;\n"
      "@p mbarrier.arrive.shared::cluster.b64 _, [ra];\n}\n" ::"r"(bar),
      "r"(cta), "r"((uint32_t)pred)
      : "memory");
}
__device__ __forceinline__ uint64_t policy_evict_first() {
  uint64_t pol;
  asm volatile("createpolicy.fractional.L2::evict_first.b64 %0, 1.0;" : "=l"(pol));
  return pol;
}
__device__ __forceinline__ void tma_load_2d_hint(uint32_t dst, const CUtensorMap* m, uint32_t bar, int c0, int c1,
                                                 uint64_t pol) {
  asm volatile(
      "cp.async.bulk.tensor.2d.shared::cluster.global.mbarrier::complete_tx::bytes.L2::cache_hint [%0], [%1, {%3, %4}], "
      "[%2], %5;" ::"r"(dst),
      "l"(reinterpret_cast<uint64_t>(m)), "r"(bar), "r"(c0), "r"(c1), "l"(pol)
      : "memory");
}
__device__ __forceinline__ void tma_load_3d_hint(uint32_t dst, const CUtensorMap* m, uint32_t bar, int c0, int c1,
                                                 int c2, uint64_t pol) {
  asm volatile(
      "cp.async.bulk.tensor.3d.shared::cluster.global.mbarrier::complete_tx::bytes.L2::cache_hint [%0], [%1, {%3, %4, "
      "%5}], [%2], %6;" ::"r"(dst),
      "l"(reinterpret_cast<uint64_t>(m)), "r"(bar), "r"(c0), "r"(c1), "r"(c2), "l"(pol)
      : "memory");
}
__device__ __forceinline__ void bulk_load_hint(uint32_t dst, const void* src, uint32_t bytes, uint32_t bar, uint64_t pol) {
  asm volatile(
      "cp.async.bulk.shared::cluster.global.mbarrier::complete_tx::bytes.L2::cache_hint [%0], [%1], %2, [%3], %4;" ::"r"(dst),
      "l"(src), "r"(bytes), "r"(bar), "l"(pol)
      : "memory");
}
__device__ __forceinline__ void cnt_signal_release(int which, uint32_t n) {
  asm volatile("red.release.gpu.global.add.u32 [%0], %1;" ::"l"(g_cnt + which * 32), "r"(n) : "memory");
}
__device__ __forceinline__ bool cnt_wait(int which, uint32_t target, uint32_t spins = 0) {
  uint32_t v;
  while (true) {
    asm volatile("ld.acquire.gpu.global.u32 %0, [%1];" : "=r"(v) : "l"(g_cnt + which * 32) : "memory");
    if (v >= target || ++spins > (1u << 18)) break;
    __nanosleep(64);
  }
  asm volatile("fence.proxy.async.global;" ::: "memory");
  return v >= target;
}
__device__ __forceinline__ void tma_store_commit() { asm volatile("cp.async.bulk.commit_group;" ::: "memory"); }
template <int N>
__device__ __forceinline__ void tma_store_wait_read() {
  asm volatile("cp.async.bulk.wait_group.read %0;" ::"n"(N) : "memory");
}
template <int N>
__device__ __forceinline__ void tma_store_wait() {
  asm volatile("cp.async.bulk.wait_group %0;" ::"n"(N) : "memory");
}
__device__ __forceinline__ void wgmma_fence() { asm volatile("wgmma.fence.sync.aligned;" ::: "memory"); }
__device__ __forceinline__ void wgmma_commit() { asm volatile("wgmma.commit_group.sync.aligned;" ::: "memory"); }
template <int N>
__device__ __forceinline__ void wgmma_wait() {
  asm volatile("wgmma.wait_group.sync.aligned %0;" ::"n"(N) : "memory");
}
template <int R>
__device__ __forceinline__ void reg_alloc() { asm volatile("setmaxnreg.inc.sync.aligned.u32 %0;" ::"n"(R)); }
template <int R>
__device__ __forceinline__ void reg_dealloc() { asm volatile("setmaxnreg.dec.sync.aligned.u32 %0;" ::"n"(R)); }

__device__ __forceinline__ void stmatrix_x4(uint32_t addr, uint32_t r0, uint32_t r1, uint32_t r2, uint32_t r3) {
  asm volatile("stmatrix.sync.aligned.m8n8.x4.shared.b16 [%0], {%1, %2, %3, %4};" ::"r"(addr), "r"(r0), "r"(r1),
               "r"(r2), "r"(r3)
               : "memory");
}
__device__ __forceinline__ uint32_t pack_bf16(float lo, float hi) {
  uint32_t r;
  asm("cvt.rn.bf16x2.f32 %0, %1, %2;" : "=r"(r) : "f"(hi), "f"(lo));
  return r;
}
__device__ __forceinline__ float bf16_round(float x) { return __bfloat162float(__float2bfloat16_rn(x)); }
__device__ __forceinline__ float bf_lo(uint32_t v) { return __uint_as_float(v << 16); }
__device__ __forceinline__ float bf_hi(uint32_t v) { return __uint_as_float(v & 0xffff0000u); }
__device__ __forceinline__ uint4 lds128(uint32_t a) {
  uint4 v;
  asm volatile("ld.shared.v4.u32 {%0, %1, %2, %3}, [%4];" : "=r"(v.x), "=r"(v.y), "=r"(v.z), "=r"(v.w) : "r"(a));
  return v;
}
__device__ __forceinline__ void sts128(uint32_t a, uint4 v) {
  asm volatile("st.shared.v4.u32 [%0], {%1, %2, %3, %4};" ::"r"(a), "r"(v.x), "r"(v.y), "r"(v.z), "r"(v.w) : "memory");
}
__device__ __forceinline__ uint32_t mul_bf2(uint32_t a, uint32_t b) {
  uint32_t r;
  asm("mul.rn.bf16x2 %0, %1, %2;" : "=r"(r) : "r"(a), "r"(b));
  return r;
}
__device__ __forceinline__ uint32_t add_bf2(uint32_t a, uint32_t b) {
  uint32_t r;
  asm("add.rn.bf16x2 %0, %1, %2;" : "=r"(r) : "r"(a), "r"(b));
  return r;
}
__device__ __forceinline__ float ex2(float x) {
  float y;
  asm("ex2.approx.ftz.f32 %0, %1;" : "=f"(y) : "f"(x));
  return y;
}
__device__ __forceinline__ float rcp(float x) {
  float y;
  asm("rcp.approx.ftz.f32 %0, %1;" : "=f"(y) : "f"(x));
  return y;
}
template <int N>
__device__ __forceinline__ void fence_regs(float (&r)[N]) {
#pragma unroll
  for (int i = 0; i < N; i++) asm volatile("" : "+f"(r[i])::"memory");
}

template <int N>
__device__ __forceinline__ void undef_regs(float (&r)[N]) {
#pragma unroll
  for (int i = 0; i < N; i++) asm volatile("" : "=f"(r[i]));
}
template <int N>
__device__ __forceinline__ void fence_regs_u(uint32_t (&r)[N]) {
#pragma unroll
  for (int i = 0; i < N; i++) asm volatile("" : "+r"(r[i])::"memory");
}

constexpr uint64_t DESC_SW128 = 1ull << 62;
__device__ __forceinline__ uint64_t make_desc(uint32_t addr, uint32_t lbo_bytes, uint32_t sbo_bytes, uint64_t swz) {
  return (uint64_t)((addr & 0x3FFFF) >> 4) | ((uint64_t)((lbo_bytes & 0x3FFFF) >> 4) << 16) |
         ((uint64_t)((sbo_bytes & 0x3FFFF) >> 4) << 32) | swz;
}

__device__ __forceinline__ uint64_t desc_add(uint64_t d, uint32_t off16) {
  return (d & 0xFFFFFFFF00000000ull) | (uint64_t)((uint32_t)d + off16);
}

__device__ __forceinline__ void wgmma_m64n256_ss_tb(float (&d)[128], uint64_t da, uint64_t db, int sd) {
  asm volatile(
    "{\n.reg .pred p;\nsetp.ne.b32 p, %130, 0;\n"
    "wgmma.mma_async.sync.aligned.m64n256k16.f32.bf16.bf16 "
    "{%0, %1, %2, %3, %4, %5, %6, %7, %8, %9, %10, %11, %12, %13, %14, %15, %16, %17, %18, %19, %20, %21, %22, %23, %24, %25, %26, %27, %28, %29, %30, %31, %32, %33, %34, %35, %36, %37, %38, %39, %40, %41, %42, %43, %44, %45, %46, %47, %48, %49, %50, %51, %52, %53, %54, %55, %56, %57, %58, %59, %60, %61, %62, %63, %64, %65, %66, %67, %68, %69, %70, %71, %72, %73, %74, %75, %76, %77, %78, %79, %80, %81, %82, %83, %84, %85, %86, %87, %88, %89, %90, %91, %92, %93, %94, %95, %96, %97, %98, %99, %100, %101, %102, %103, %104, %105, %106, %107, %108, %109, %110, %111, %112, %113, %114, %115, %116, %117, %118, %119, %120, %121, %122, %123, %124, %125, %126, %127}, %128, %129, p, 1, 1, 0, 1;\n}\n"
    : "+f"(d[0]), "+f"(d[1]), "+f"(d[2]), "+f"(d[3]), "+f"(d[4]), "+f"(d[5]), "+f"(d[6]), "+f"(d[7]), "+f"(d[8]), "+f"(d[9]), "+f"(d[10]), "+f"(d[11]), "+f"(d[12]), "+f"(d[13]), "+f"(d[14]), "+f"(d[15]), "+f"(d[16]), "+f"(d[17]), "+f"(d[18]), "+f"(d[19]), "+f"(d[20]), "+f"(d[21]), "+f"(d[22]), "+f"(d[23]), "+f"(d[24]), "+f"(d[25]), "+f"(d[26]), "+f"(d[27]), "+f"(d[28]), "+f"(d[29]), "+f"(d[30]), "+f"(d[31]), "+f"(d[32]), "+f"(d[33]), "+f"(d[34]), "+f"(d[35]), "+f"(d[36]), "+f"(d[37]), "+f"(d[38]), "+f"(d[39]), "+f"(d[40]), "+f"(d[41]), "+f"(d[42]), "+f"(d[43]), "+f"(d[44]), "+f"(d[45]), "+f"(d[46]), "+f"(d[47]), "+f"(d[48]), "+f"(d[49]), "+f"(d[50]), "+f"(d[51]), "+f"(d[52]), "+f"(d[53]), "+f"(d[54]), "+f"(d[55]), "+f"(d[56]), "+f"(d[57]), "+f"(d[58]), "+f"(d[59]), "+f"(d[60]), "+f"(d[61]), "+f"(d[62]), "+f"(d[63]), "+f"(d[64]), "+f"(d[65]), "+f"(d[66]), "+f"(d[67]), "+f"(d[68]), "+f"(d[69]), "+f"(d[70]), "+f"(d[71]), "+f"(d[72]), "+f"(d[73]), "+f"(d[74]), "+f"(d[75]), "+f"(d[76]), "+f"(d[77]), "+f"(d[78]), "+f"(d[79]), "+f"(d[80]), "+f"(d[81]), "+f"(d[82]), "+f"(d[83]), "+f"(d[84]), "+f"(d[85]), "+f"(d[86]), "+f"(d[87]), "+f"(d[88]), "+f"(d[89]), "+f"(d[90]), "+f"(d[91]), "+f"(d[92]), "+f"(d[93]), "+f"(d[94]), "+f"(d[95]), "+f"(d[96]), "+f"(d[97]), "+f"(d[98]), "+f"(d[99]), "+f"(d[100]), "+f"(d[101]), "+f"(d[102]), "+f"(d[103]), "+f"(d[104]), "+f"(d[105]), "+f"(d[106]), "+f"(d[107]), "+f"(d[108]), "+f"(d[109]), "+f"(d[110]), "+f"(d[111]), "+f"(d[112]), "+f"(d[113]), "+f"(d[114]), "+f"(d[115]), "+f"(d[116]), "+f"(d[117]), "+f"(d[118]), "+f"(d[119]), "+f"(d[120]), "+f"(d[121]), "+f"(d[122]), "+f"(d[123]), "+f"(d[124]), "+f"(d[125]), "+f"(d[126]), "+f"(d[127])
    : "l"(da), "l"(db), "r"(sd));
}

__device__ __forceinline__ void wgmma_m64n128_ss(float (&d)[64], uint64_t da, uint64_t db, int sd) {
  asm volatile(
    "{\n.reg .pred p;\nsetp.ne.b32 p, %66, 0;\n"
    "wgmma.mma_async.sync.aligned.m64n128k16.f32.bf16.bf16 "
    "{%0, %1, %2, %3, %4, %5, %6, %7, %8, %9, %10, %11, %12, %13, %14, %15, %16, %17, %18, %19, %20, %21, %22, %23, %24, %25, %26, %27, %28, %29, %30, %31, %32, %33, %34, %35, %36, %37, %38, %39, %40, %41, %42, %43, %44, %45, %46, %47, %48, %49, %50, %51, %52, %53, %54, %55, %56, %57, %58, %59, %60, %61, %62, %63}, %64, %65, p, 1, 1, 0, 0;\n}\n"
    : "+f"(d[0]), "+f"(d[1]), "+f"(d[2]), "+f"(d[3]), "+f"(d[4]), "+f"(d[5]), "+f"(d[6]), "+f"(d[7]), "+f"(d[8]), "+f"(d[9]), "+f"(d[10]), "+f"(d[11]), "+f"(d[12]), "+f"(d[13]), "+f"(d[14]), "+f"(d[15]), "+f"(d[16]), "+f"(d[17]), "+f"(d[18]), "+f"(d[19]), "+f"(d[20]), "+f"(d[21]), "+f"(d[22]), "+f"(d[23]), "+f"(d[24]), "+f"(d[25]), "+f"(d[26]), "+f"(d[27]), "+f"(d[28]), "+f"(d[29]), "+f"(d[30]), "+f"(d[31]), "+f"(d[32]), "+f"(d[33]), "+f"(d[34]), "+f"(d[35]), "+f"(d[36]), "+f"(d[37]), "+f"(d[38]), "+f"(d[39]), "+f"(d[40]), "+f"(d[41]), "+f"(d[42]), "+f"(d[43]), "+f"(d[44]), "+f"(d[45]), "+f"(d[46]), "+f"(d[47]), "+f"(d[48]), "+f"(d[49]), "+f"(d[50]), "+f"(d[51]), "+f"(d[52]), "+f"(d[53]), "+f"(d[54]), "+f"(d[55]), "+f"(d[56]), "+f"(d[57]), "+f"(d[58]), "+f"(d[59]), "+f"(d[60]), "+f"(d[61]), "+f"(d[62]), "+f"(d[63])
    : "l"(da), "l"(db), "r"(sd));
}

__device__ __forceinline__ void wgmma_m64n128_ss_tb(float (&d)[64], uint64_t da, uint64_t db, int sd) {
  asm volatile(
    "{\n.reg .pred p;\nsetp.ne.b32 p, %66, 0;\n"
    "wgmma.mma_async.sync.aligned.m64n128k16.f32.bf16.bf16 "
    "{%0, %1, %2, %3, %4, %5, %6, %7, %8, %9, %10, %11, %12, %13, %14, %15, %16, %17, %18, %19, %20, %21, %22, %23, %24, %25, %26, %27, %28, %29, %30, %31, %32, %33, %34, %35, %36, %37, %38, %39, %40, %41, %42, %43, %44, %45, %46, %47, %48, %49, %50, %51, %52, %53, %54, %55, %56, %57, %58, %59, %60, %61, %62, %63}, %64, %65, p, 1, 1, 0, 1;\n}\n"
    : "+f"(d[0]), "+f"(d[1]), "+f"(d[2]), "+f"(d[3]), "+f"(d[4]), "+f"(d[5]), "+f"(d[6]), "+f"(d[7]), "+f"(d[8]), "+f"(d[9]), "+f"(d[10]), "+f"(d[11]), "+f"(d[12]), "+f"(d[13]), "+f"(d[14]), "+f"(d[15]), "+f"(d[16]), "+f"(d[17]), "+f"(d[18]), "+f"(d[19]), "+f"(d[20]), "+f"(d[21]), "+f"(d[22]), "+f"(d[23]), "+f"(d[24]), "+f"(d[25]), "+f"(d[26]), "+f"(d[27]), "+f"(d[28]), "+f"(d[29]), "+f"(d[30]), "+f"(d[31]), "+f"(d[32]), "+f"(d[33]), "+f"(d[34]), "+f"(d[35]), "+f"(d[36]), "+f"(d[37]), "+f"(d[38]), "+f"(d[39]), "+f"(d[40]), "+f"(d[41]), "+f"(d[42]), "+f"(d[43]), "+f"(d[44]), "+f"(d[45]), "+f"(d[46]), "+f"(d[47]), "+f"(d[48]), "+f"(d[49]), "+f"(d[50]), "+f"(d[51]), "+f"(d[52]), "+f"(d[53]), "+f"(d[54]), "+f"(d[55]), "+f"(d[56]), "+f"(d[57]), "+f"(d[58]), "+f"(d[59]), "+f"(d[60]), "+f"(d[61]), "+f"(d[62]), "+f"(d[63])
    : "l"(da), "l"(db), "r"(sd));
}

__device__ __forceinline__ void wgmma_m64n128_rs_tb(float* d, uint32_t a0, uint32_t a1, uint32_t a2, uint32_t a3, uint64_t db, int sd) {
  asm volatile(
    "{\n.reg .pred p;\nsetp.ne.b32 p, %69, 0;\n"
    "wgmma.mma_async.sync.aligned.m64n128k16.f32.bf16.bf16 "
    "{%0, %1, %2, %3, %4, %5, %6, %7, %8, %9, %10, %11, %12, %13, %14, %15, %16, %17, %18, %19, %20, %21, %22, %23, %24, %25, %26, %27, %28, %29, %30, %31, %32, %33, %34, %35, %36, %37, %38, %39, %40, %41, %42, %43, %44, %45, %46, %47, %48, %49, %50, %51, %52, %53, %54, %55, %56, %57, %58, %59, %60, %61, %62, %63}, {%64, %65, %66, %67}, %68, p, 1, 1, 1;\n}\n"
    : "+f"(d[0]), "+f"(d[1]), "+f"(d[2]), "+f"(d[3]), "+f"(d[4]), "+f"(d[5]), "+f"(d[6]), "+f"(d[7]), "+f"(d[8]), "+f"(d[9]), "+f"(d[10]), "+f"(d[11]), "+f"(d[12]), "+f"(d[13]), "+f"(d[14]), "+f"(d[15]), "+f"(d[16]), "+f"(d[17]), "+f"(d[18]), "+f"(d[19]), "+f"(d[20]), "+f"(d[21]), "+f"(d[22]), "+f"(d[23]), "+f"(d[24]), "+f"(d[25]), "+f"(d[26]), "+f"(d[27]), "+f"(d[28]), "+f"(d[29]), "+f"(d[30]), "+f"(d[31]), "+f"(d[32]), "+f"(d[33]), "+f"(d[34]), "+f"(d[35]), "+f"(d[36]), "+f"(d[37]), "+f"(d[38]), "+f"(d[39]), "+f"(d[40]), "+f"(d[41]), "+f"(d[42]), "+f"(d[43]), "+f"(d[44]), "+f"(d[45]), "+f"(d[46]), "+f"(d[47]), "+f"(d[48]), "+f"(d[49]), "+f"(d[50]), "+f"(d[51]), "+f"(d[52]), "+f"(d[53]), "+f"(d[54]), "+f"(d[55]), "+f"(d[56]), "+f"(d[57]), "+f"(d[58]), "+f"(d[59]), "+f"(d[60]), "+f"(d[61]), "+f"(d[62]), "+f"(d[63])
    : "r"(a0), "r"(a1), "r"(a2), "r"(a3), "l"(db), "r"(sd));
}

__device__ __forceinline__ void wgmma_m64n64_rs_tb(float (&d)[32], const uint32_t (&a)[4], uint64_t db, int sd) {
  asm volatile(
    "{\n.reg .pred p;\nsetp.ne.b32 p, %37, 0;\n"
    "wgmma.mma_async.sync.aligned.m64n64k16.f32.bf16.bf16 "
    "{%0, %1, %2, %3, %4, %5, %6, %7, %8, %9, %10, %11, %12, %13, %14, %15, %16, %17, %18, %19, %20, %21, %22, %23, %24, %25, %26, %27, %28, %29, %30, %31}, {%32, %33, %34, %35}, %36, p, 1, 1, 1;\n}\n"
    : "+f"(d[0]), "+f"(d[1]), "+f"(d[2]), "+f"(d[3]), "+f"(d[4]), "+f"(d[5]), "+f"(d[6]), "+f"(d[7]), "+f"(d[8]), "+f"(d[9]), "+f"(d[10]), "+f"(d[11]), "+f"(d[12]), "+f"(d[13]), "+f"(d[14]), "+f"(d[15]), "+f"(d[16]), "+f"(d[17]), "+f"(d[18]), "+f"(d[19]), "+f"(d[20]), "+f"(d[21]), "+f"(d[22]), "+f"(d[23]), "+f"(d[24]), "+f"(d[25]), "+f"(d[26]), "+f"(d[27]), "+f"(d[28]), "+f"(d[29]), "+f"(d[30]), "+f"(d[31])
    : "r"(a[0]), "r"(a[1]), "r"(a[2]), "r"(a[3]), "l"(db), "r"(sd));
}

__device__ __forceinline__ void wgmma_m64n32_rs_tb(float (&d)[16], const uint32_t (&a)[4], uint64_t db, int sd) {
  asm volatile(
    "{\n.reg .pred p;\nsetp.ne.b32 p, %21, 0;\n"
    "wgmma.mma_async.sync.aligned.m64n32k16.f32.bf16.bf16 "
    "{%0, %1, %2, %3, %4, %5, %6, %7, %8, %9, %10, %11, %12, %13, %14, %15}, {%16, %17, %18, %19}, %20, p, 1, 1, 1;\n}\n"
    : "+f"(d[0]), "+f"(d[1]), "+f"(d[2]), "+f"(d[3]), "+f"(d[4]), "+f"(d[5]), "+f"(d[6]), "+f"(d[7]), "+f"(d[8]), "+f"(d[9]), "+f"(d[10]), "+f"(d[11]), "+f"(d[12]), "+f"(d[13]), "+f"(d[14]), "+f"(d[15])
    : "r"(a[0]), "r"(a[1]), "r"(a[2]), "r"(a[3]), "l"(db), "r"(sd));
}

constexpr int G_STAGES = 4;
constexpr int G_A_BYTES = 128 * 64 * 2;
constexpr int G_B_BYTES = 256 * 64 * 2;
constexpr int G_STAGE_BYTES = G_A_BYTES + G_B_BYTES;
constexpr int G_STG_OFF = G_STAGES * G_STAGE_BYTES;
constexpr int BAR_OFF = G_STG_OFF + 32768 + 2048;
constexpr int SMEM_BYTES = BAR_OFF + 1024;
constexpr int B_GFULL = 0, B_GEMPTY = 32, B_SEEN = 64, B_PFULL = 224;
constexpr int B_KFULL = 80, B_KEMPTY = 96, B_VFULL = 112, B_VEMPTY = 128, B_QFULL = 144, B_QEMPTY = 160,
              B_QDONE = 184;
constexpr int B_CFULL = 192;
constexpr int B_OFREE = 256, B_OFULL = 272, B_OEMPTY = 320, B_OY = 368, B_OY2 = 384;
constexpr int B_DEAL = 312, B_DEAL2 = 360, B_LIST = 640, B_PAIR = 504;
constexpr int B_SFULL = 392, B_SFREE = 424, B_PEND = 456, B_SCMD = 512;

#define PHASE_PROLOGUE                                                                \
  uint32_t tid, rt_zero;                                                              \
  asm volatile("mov.u32 %0, %%tid.x;" : "=r"(tid));                                   \
  asm volatile("mov.u32 %0, %%nctaid.y;" : "=r"(rt_zero));                            \
  asm volatile("" : "+r"(smem0));                                                     \
  rt_zero = __shfl_sync(0xffffffffu, rt_zero >> 8, 0);   \
  const uint32_t sbase = __shfl_sync(0xffffffffu, smem0, 0);                          \
  const uint32_t bar = sbase + BAR_OFF;                                               \
  const int wg = __shfl_sync(0xffffffffu, tid >> 7, 0);                               \
  const int warp = (tid >> 5) & 3, lane = tid & 31, wtid = tid & 127;                 \
  (void)rt_zero; (void)bar; (void)warp; (void)lane; (void)wtid;

enum { ST_END = 0, ST_BOX1, ST_BOX2, ST_BOX2Q, ST_BOX2L };
__device__ __forceinline__ void st_post(uint32_t bar, int wg, int wtid, uint32_t n, int kind, const void* dst,
                                        uint32_t src, int c0, int c1, int sig, uint32_t lazy = 0) {
  if (wtid == 0) {
    const uint32_t c = bar + B_SCMD + wg * 64 + (n & 1) * 32;
    const uint64_t d = reinterpret_cast<uint64_t>(dst);
    sts128(c, make_uint4(kind, src, c0, c1));
    sts128(c + 16, make_uint4((uint32_t)d, (uint32_t)(d >> 32), sig, lazy));
  }
  fence_proxy_async();
  __syncwarp();
  mbar_arrive_if(bar + B_SFULL + wg * 16 + (n & 1) * 8, (wtid & 31) == 0);
}
__device__ __forceinline__ void st_wait(uint32_t bar, int wg, uint32_t n) {
  const uint32_t b = bar + B_SFREE + wg * 16 + (n & 1) * 8;
  if (!mbar_try(b, ~(n >> 1) & 1)) mbar_wait(b, ~(n >> 1) & 1);
}
__device__ __forceinline__ void note(uint32_t bar, uint32_t cnt) {
  asm volatile("red.release.cta.shared.add.u32 [%0], 1;" ::"r"(bar + B_PEND + 4 * cnt) : "memory");
}
#define LAZY_NS 250
#define DEAL_NS 400
#define DEAL_NS2 1250
constexpr uint32_t C_NONE = 0x10000;
__device__ __forceinline__ void deal(uint32_t bar, uint32_t r, uint32_t t, uint32_t own) {
  uint64_t p;
  uint32_t spins = 0;
  while (true) {
    asm volatile("ld.relaxed.gpu.global.u64 %0, [%1];" : "=l"(p) : "l"(g_slot + 127 - r) : "memory");
    if (p || ++spins > (1u << 18)) break;
    __nanosleep(100);
  }
  const uint32_t pc = (uint32_t)p;
  int dt = (uint32_t)(p >> 32) - t;
  if (r >= 64) {
    sts128(bar + B_LIST, make_uint4(-dt > DEAL_NS2 ? C_NONE : own - 16, -dt > DEAL_NS ? C_NONE : own, C_NONE, C_NONE));
    mbar_arrive(bar + B_DEAL);
    dt = 0;
  }
  sts128(bar + B_LIST + 16, make_uint4(dt > DEAL_NS ? pc : C_NONE, dt > DEAL_NS2 ? pc - 16 : C_NONE, C_NONE, C_NONE));
  mbar_arrive(bar + B_DEAL2);
}
__device__ __forceinline__ void store_agent(uint32_t bar, int wg, uint32_t last_ch) {
  mbar_arrive(bar + B_SFREE + wg * 16);
  mbar_arrive(bar + B_SFREE + wg * 16 + 8);
  bool more = true;
  for (uint32_t n = 0;; n++) {
    mbar_wait_sleep(bar + B_SFULL + wg * 16 + (n & 1) * 8, (n >> 1) & 1);
    const uint4 c = lds128(bar + B_SCMD + wg * 64 + (n & 1) * 32);
    const uint4 d = lds128(bar + B_SCMD + wg * 64 + (n & 1) * 32 + 16);
    if (c.x == ST_END) break;
    uint32_t t;
    asm volatile("mov.u32 %0, %%globaltimer_lo;" : "=r"(t));
    for (uint32_t t1 = t; d.w && t1 - t < (2 * d.w + wg) * LAZY_NS;) {
      __nanosleep(200);
      asm volatile("mov.u32 %0, %%globaltimer_lo;" : "=r"(t1));
    }
    const CUtensorMap* dst = reinterpret_cast<const CUtensorMap*>((uint64_t)d.x | ((uint64_t)d.y << 32));
    tma_store_2d(dst, c.y, c.z, c.w);
    if (c.x >= ST_BOX2) tma_store_2d(dst, c.y + 8192, c.z + 64, c.w);
    tma_store_commit();
    uint32_t r = 0;
    if (c.x == ST_BOX2L && last_ch) {
      mbar_expect_tx(bar + B_PAIR, 4);
      asm volatile(
          "{\n.reg .b32 ra;\nmapa.shared::cluster.u32 ra, %0, %1;\n"
          "st.async.weak.shared::cluster.mbarrier::complete_tx::bytes.u32 [ra + 224], %2, [ra];\n}\n" ::"r"(bar + B_PAIR),
          "r"(~blockIdx.x & 1), "r"(t)
          : "memory");
    }
    tma_store_wait_read<0>();
    mbar_arrive(bar + B_SFREE + wg * 16 + (n & 1) * 8);
    if (c.x == ST_BOX2L) mbar_arrive(bar + B_OFREE + 8 * wg);
    if (c.x == ST_BOX2L && last_ch) {
      uint32_t tp;
      mbar_wait_sleep(bar + B_PAIR, 0);
      r = atomicAdd(g_cnt + CNT_RANK * 32, 1u) & 127;
      asm volatile("ld.shared.u32 %0, [%1];" : "=r"(tp) : "r"(bar + B_PAIR + 224) : "memory");
      if ((int)(tp - t) > 0) t = tp;
      asm volatile("st.relaxed.gpu.global.u64 [%0], %1;" ::"l"(g_slot + r), "l"(((uint64_t)t << 32) | last_ch) : "memory");
      if (r < 64) {
        sts128(bar + B_LIST, make_uint4(last_ch - 16, last_ch, C_NONE, C_NONE));
        mbar_arrive(bar + B_DEAL);
      }
    }
    if ((int)d.z >= 0) {
      tma_store_wait<0>();
      if (d.z == 0) { TD(6) }
      asm volatile("fence.proxy.async.global;" ::: "memory");
      if (c.x == ST_BOX2Q) mbar_arrive(bar + B_QDONE);
      else note(bar, d.z);
      if (c.x == ST_BOX2L) {
        note(bar, CNT_DONE);
        more = false;
        if (last_ch) deal(bar, r, t, last_ch);
      }
    }
  }
  if (more) note(bar, CNT_DONE);
}

struct Maps {
  const bf16 *shift_k, *x, *gate_w, *ssm_k, *ssm_D;
  uint8_t id[128][4];
  CUtensorMap a[2];
  CUtensorMap b[3];
  CUtensorMap c[3];
  CUtensorMap bk, bv;
  CUtensorMap q, k, v, o;
  CUtensorMap oa, ob, oc;
  CUtensorMap y, xs;
  CUtensorMap cu, ch;
};

constexpr int P_SLOT = 67 * 128, P_V = 35 * 128, P_TAPS = 2 * P_SLOT;
__device__ __forceinline__ void ldsm4t(uint32_t (&r)[4], uint32_t a) {
  asm volatile("ldmatrix.sync.aligned.m8n8.x4.trans.shared.b16 {%0, %1, %2, %3}, [%4];"
               : "=r"(r[0]), "=r"(r[1]), "=r"(r[2]), "=r"(r[3])
               : "r"(a));
}
__device__ __forceinline__ uint32_t fma_bf2(uint32_t a, uint32_t b, uint32_t c) {
  uint32_t r;
  asm("fma.rn.bf16x2 %0, %1, %2, %3;" : "=r"(r) : "r"(a), "r"(b), "r"(c));
  return r;
}
__device__ __forceinline__ void prep_agent(const Maps& maps, uint32_t sbase, int w, int lane) {
  const uint32_t bar = sbase + BAR_OFF, pb = bar + B_PFULL + w * 16;
  const int d0 = (blockIdx.x >> 3) * 64, t0 = (blockIdx.x & 7) * 256 + w * 128;
  mbar_wait_sleep(bar + B_GFULL + 8 * (G_STAGES - 1), 0);
#pragma unroll 1
  for (int i = -1; i < 4; i++) {
    GA(82 + 2 * i)
    if (i >= 0) mbar_wait_sleep(pb + (i & 1) * 8, i >> 1);
    GA(83 + 2 * i)
    const uint32_t so = sbase + G_STG_OFF + w * (P_TAPS + 512) + (i & 1) * P_SLOT;
    if (i < 3 && elect_one()) {
      const uint32_t b = pb + (~i & 1) * 8, dst = so + (i & 1 ? -P_SLOT : P_SLOT);
      mbar_expect_tx(b, i < 0 ? P_SLOT + 512 : P_SLOT);
      const uint64_t pol = policy_evict_first();
      tma_load_2d_hint(dst, &maps.bk, b, d0, t0 + 32 * i + 29, pol);
      tma_load_2d_hint(dst + P_V, &maps.bv, b, d0, t0 + 32 * i + 32, pol);
      if (i < 0) bulk_load(sbase + G_STG_OFF + P_TAPS, maps.shift_k + d0 * 4, 512, b);
    }
    if (i < 0) continue;
    uint32_t ak[4];
#pragma unroll
    for (int r = 0; r < 4; r++) {
      const uint32_t a = so / 128 + r + 4 * (lane & 6) + (((lane >> 2) ^ lane) & 6) + (lane & 1);
      ak[r] = a * 128 + (a & 7) * 16;
    }
    bf16* dst = g_kvT + (size_t)(d0 + (lane >> 2)) * S_LEN + t0 + ((lane & 3) + 4 * i) * 8;
#pragma unroll 1
    for (int cg = 0; cg < 128; cg += 16) {
      uint32_t t01, t23, k[4][4], v[4];
      asm volatile("ld.shared.v2.u32 {%0, %1}, [%2];"
                   : "=r"(t01), "=r"(t23)
                   : "r"(sbase + G_STG_OFF + P_TAPS + cg * 4 + (lane >> 2) * 8));
#pragma unroll
      for (int r = 0; r < 4; r++) ldsm4t(k[r], ak[r] ^ cg);
      ldsm4t(v, (ak[3] ^ cg) + 4096);
      const uint32_t w0 = __byte_perm(t01, 0, 0x1010), w1 = __byte_perm(t01, 0, 0x3232);
      const uint32_t w2 = __byte_perm(t23, 0, 0x1010), w3 = __byte_perm(t23, 0, 0x3232);
#pragma unroll
      for (int j = 0; j < 4; j++)
        v[j] = mul_bf2(fma_bf2(k[3][j], w0, fma_bf2(k[2][j], w1, fma_bf2(k[1][j], w2, mul_bf2(k[0][j], w3)))), v[j]);
      const bool s1 = lane & 1, s2 = lane & 2;
      const uint32_t a0 = s1 ? v[1] : v[0], a1 = s1 ? v[0] : v[1], a2 = s1 ? v[3] : v[2], a3 = s1 ? v[2] : v[3];
      *reinterpret_cast<uint4*>(dst) = make_uint4(s2 ? a2 : a0, s2 ? a3 : a1, s2 ? a0 : a2, s2 ? a1 : a3);
      dst += 8 * S_LEN;
    }
    fence_proxy_async();
    __syncwarp();
  }
  GA(90)
  if (lane == 0) note(bar, CNT_PREP);
  __syncwarp();
  GA(91)
}

__device__ __forceinline__ void qkv_tile(const Maps& maps, int it, int& which, int& m_tile, int& n_tile) {
  const bool q = it == 0 || it >= 5;
  const int b = maps.id[blockIdx.x][it >= 5];
  which = q ? 0 : 2 - (it & 1);
  m_tile = b & 15;
  n_tile = (b >> 4) * 2 + ((0x19 >> it) & 1);
}

constexpr int G_NTILES = 6;
__device__ __forceinline__ void qkv_producer(const Maps& maps, uint32_t sbase, bool first) {
  const uint32_t bar = sbase + BAR_OFF;
  uint32_t stage = 0, phase = 0;
#pragma unroll 1
  for (int it = 0; it < (first ? 1 : G_NTILES); it++) {
    int which, m_tile, n_tile;
    qkv_tile(maps, it, which, m_tile, n_tile);
    const CUtensorMap* ma = &maps.a[which == 0 ? 0 : 1];
    const CUtensorMap* mb = &maps.b[which];
    const int nk = first ? G_STAGES : which == 0 ? 16 : 8;
#pragma unroll 1
    for (int kt = (it == 0 && !first) ? G_STAGES : 0; kt < nk; kt++) {
      if (!first) mbar_wait_sleep(bar + B_GEMPTY + 8 * stage, phase);
      const uint32_t fb = bar + B_GFULL + 8 * stage;
      const uint32_t sa = sbase + stage * G_STAGE_BYTES;
      mbar_expect_tx(fb, G_STAGE_BYTES);
      tma_load_2d(sa, ma, fb, kt * 64, m_tile * 128);
      tma_load_3d(sa + G_A_BYTES, mb, fb, 0, kt * 64, n_tile * 4);
      if (++stage == G_STAGES) { stage = 0; phase ^= 1; }
      {
        const int b = maps.id[blockIdx.x][1];
        if (it == 2 && kt == (b & 7)) {
          for (int i = 0; i < 2; i++)
            asm volatile("cp.async.bulk.prefetch.tensor.2d.L2.global.tile [%0, {%1, %2}];" ::"l"(&maps.a[0]),
                         "r"((b >> 4) * 128 + i * 64), "r"((b & 15) * 128)
                         : "memory");
        }
        if (it == 3 && kt == (b & 7))
          asm volatile("cp.async.bulk.prefetch.tensor.3d.L2.global.tile [%0, {%1, %2, %3}];" ::"l"(&maps.b[0]), "r"(0),
                       "r"((b & 15) * 64), "r"((b >> 4) * 8)
                       : "memory");
      }
    }
  }
}

__device__ __forceinline__ uint32_t seen_bar(uint32_t item) { return B_SEEN + ((0x700800u >> (8 * item)) & 255); }
__device__ __noinline__ void publisher(uint32_t bar, int lane, uint32_t nsrc, uint32_t item, uint32_t mine) {
  uint32_t done = 0, tot = 0;
#pragma unroll 1
  for (uint32_t spins = 0; (done < nsrc || item < 3) && spins < (1u << 20); spins++) {
    const uint32_t cnt = item ? CNT_CTX - 1 + item : CNT_KV + 1;
    if (item < 3 && __shfl_sync(0xffffffffu, tot, cnt) >= mine) {
      uint32_t v;
      asm volatile("ld.acquire.gpu.global.u32 %0, [%1];" : "=r"(v) : "l"(g_cnt + (lane ? cnt : CNT_PREP) * 32) : "memory");
      if (__all_sync(0xffffffffu, v >= (lane ? 512 : 260))) {
        asm volatile("fence.proxy.async.global;" ::: "memory");
        mbar_arrive_if(bar + seen_bar(item), lane == 0);
        item++;
      }
    }
    uint32_t v = 0;
    if (lane < CNT_N)
      asm volatile("atom.acquire.cta.shared.exch.b32 %0, [%1], 0;" : "=r"(v) : "r"(bar + B_PEND + 4 * lane) : "memory");
    done += __shfl_sync(0xffffffffu, v, CNT_DONE);
    if (lane == CNT_DONE) v = 0;
    if (done == nsrc && lane < CNT_DONE) {
      uint32_t w;
      asm volatile("atom.acquire.cta.shared.exch.b32 %0, [%1], 0;" : "=r"(w) : "r"(bar + B_PEND + 4 * lane) : "memory");
      v += w;
    }
    if (v && lane == 0) { TD(0) }
    if (v) cnt_signal_release(lane, v);
    tot += v;
    if (v && lane == 0) { TD(1) }
    if (!__any_sync(0xffffffffu, v != 0)) __nanosleep(item == 1 ? 1000 : 200);
  }
  __threadfence();
  __syncwarp();
}

__device__ __forceinline__ void gate_rows(const Maps& maps, uint32_t sbase, int w48, int w12, int lane) {
  const uint32_t buf = sbase + w12 * 16384, gb = sbase + BAR_OFF + 768 + w12 * 16;
  if (lane == 0) {
    mbar_init(gb, 1);
    mbar_init(gb + 8, 1);
    fence_barrier_init();
    for (int i = 0; i < 2; i++) {
      mbar_expect_tx(gb + 8 * i, 8192);
      bulk_load(buf + i * 8192, maps.x + (size_t)(w48 + 48 * i) * 4 * DM, 8192, gb + 8 * i);
    }
  }
  __syncwarp();
  uint4 wv[4];
#pragma unroll
  for (int i = 0; i < 4; i++) wv[i] = __ldg(reinterpret_cast<const uint4*>(maps.gate_w + (i * 32 + lane) * 8));
  int it = 0;
#pragma unroll 1
  for (int row = w48 * 4; row < S_LEN; row += 48 * 4, it++) {
    mbar_wait(gb + 8 * (it & 1), (it >> 1) & 1);
    uint4 xv[4][4];
#pragma unroll
    for (int r = 0; r < 4; r++)
#pragma unroll
      for (int i = 0; i < 4; i++) xv[r][i] = lds128(buf + (it & 1) * 8192 + r * 2048 + (i * 32 + lane) * 16);
    float d[2][4];
#pragma unroll
    for (int pr = 0; pr < 2; pr++) {
      d[pr][0] = d[pr][1] = d[pr][2] = d[pr][3] = 0.f;
      auto acc = [&](uint32_t a0, uint32_t a2, uint32_t b0, uint32_t b2, uint32_t w0, uint32_t w2) {
        asm volatile(
            "mma.sync.aligned.m16n8k16.row.col.f32.bf16.bf16.f32 {%0, %1, %2, %3}, {%4, %5, %6, %7}, {%8, %8}, "
            "{%0, %1, %2, %3};"
            : "+f"(d[pr][0]), "+f"(d[pr][1]), "+f"(d[pr][2]), "+f"(d[pr][3])
            : "r"(mul_bf2(a0, w0)), "r"(mul_bf2(b0, w0)), "r"(mul_bf2(a2, w2)), "r"(mul_bf2(b2, w2)), "r"(0x3f803f80u));
      };
#pragma unroll
      for (int i = 0; i < 4; i++) {
        acc(xv[2 * pr][i].x, xv[2 * pr][i].y, xv[2 * pr + 1][i].x, xv[2 * pr + 1][i].y, wv[i].x, wv[i].y);
        acc(xv[2 * pr][i].z, xv[2 * pr][i].w, xv[2 * pr + 1][i].z, xv[2 * pr + 1][i].w, wv[i].z, wv[i].w);
      }
    }
    float sum = (lane & 2) ? ((lane & 1) ? d[1][2] : d[1][0]) : ((lane & 1) ? d[0][2] : d[0][0]);
#pragma unroll
    for (int off = 16; off >= 4; off >>= 1) sum += __shfl_xor_sync(0xffffffffu, sum, off);
    if (lane < 4) g_gate[row + lane] = bf16_round(rcp(1.0f + __expf(-bf16_round(sum))));
    if (lane == 0 && row + 2 * 48 * 4 < S_LEN) {
      mbar_expect_tx(gb + 8 * (it & 1), 8192);
      bulk_load(buf + (it & 1) * 8192, maps.x + (size_t)(row + 2 * 48 * 4) * DM, 8192, gb + 8 * (it & 1));
    }
  }
}

constexpr float Q_SCALE = 0.08838834764831845f * 1.4426950408889634f;
__device__ __forceinline__ uint32_t qkv_consumer(const Maps& maps, uint32_t smem0, bool fused, float (&rest)[64]) {
  PHASE_PROLOGUE
  constexpr int NTILES = G_NTILES;
  float acc[128];
  uint32_t stage = 0, phase = 0;
  const uint32_t stg = sbase + G_STG_OFF + wg * 18432;
  const int st_row = warp * 16 + (lane & 7) + ((lane >> 3) & 1) * 8;
  const int st_cb = lane >> 4;
  uint32_t pend[64];
  const CUtensorMap* pend_map = nullptr;
  int pend_c0 = 0, pend_c1 = 0;
  uint32_t sn = 0;
  auto put_box = [&](uint32_t buf, const uint32_t* v) {
#pragma unroll
    for (int jp = 0; jp < 4; jp++) {
      const int chunk = jp * 2 + st_cb;
      const uint32_t addr = buf + st_row * 128 + ((chunk ^ (st_row & 7)) << 4);
      stmatrix_x4(addr, v[jp * 4], v[jp * 4 + 1], v[jp * 4 + 2], v[jp * 4 + 3]);
    }
  };
  GT(gti++)
#pragma unroll 1
  for (int it = 0; it <= NTILES; it++) {
    int which, m_tile, n_tile;
    qkv_tile(maps, it, which, m_tile, n_tile);
    const int nk = (which == 0 && it < NTILES) ? 16 : 8;
    uint32_t prev_stage = 0;
#pragma unroll 1
    for (int kt = 0; kt < nk; kt++) {
      if (it < NTILES) {
        mbar_wait((bar + B_GFULL) + 8 * stage, phase);
        GT(gti++)
        const uint64_t da0 = make_desc(sbase + stage * G_STAGE_BYTES + wg * 8192, 16, 1024, DESC_SW128);
        const uint64_t db0 = make_desc(sbase + stage * G_STAGE_BYTES + G_A_BYTES, 8192, 1024, DESC_SW128);
        wgmma_fence();
#pragma unroll
        for (int kk = 0; kk < 4; kk++) {
          wgmma_m64n256_ss_tb(acc, desc_add(da0, kk * 2), desc_add(db0, kk * 128), (kt | kk) != 0);
        }
        wgmma_commit();
      }
      const uint32_t when = it == 0 ? 0 : it == 5 ? 0x922 << wg : wg ? 0xAA : 0x55;
      if ((when >> kt) & 1) {
        const int c = __popc(when & ~(~0u << kt));
        st_wait(bar, wg, sn - 2);
        const uint32_t buf = stg + (c & 1) * 8192;
        switch (c) {
          case 0: put_box(buf, pend); break;
          case 1: put_box(buf, pend + 16); break;
          case 2: put_box(buf, pend + 32); break;
          default: put_box(buf, pend + 48); break;
        }
        st_post(bar, wg, wtid, sn, ST_BOX1, pend_map, buf, pend_c0 + c * 64, pend_c1, (c == 3 && it > 1) ? CNT_KV + (it > 3) : -1);
        sn++;
      }
      if (it < NTILES) {
        wgmma_wait<1>();
        mbar_arrive_if((bar + B_GEMPTY) + 8 * prev_stage, wtid == 32 && kt > 0);
        prev_stage = stage;
        if (++stage == G_STAGES) { stage = 0; phase ^= 1; }
      }
    }
    wgmma_wait<0>();
    fence_regs(acc);
    if (it == NTILES) break;
    GT(gti++)
    mbar_arrive_if((bar + B_GEMPTY) + 8 * prev_stage, wtid == 32);
    if (it == NTILES - 1 && fused) break;
    if (which == 0) {
#pragma unroll
      for (int j = 0; j < 128; j++) acc[j] *= Q_SCALE;
    }
#pragma unroll
    for (int j = 0; j < 64; j++) pend[j] = pack_bf16(acc[2 * j], acc[2 * j + 1]);
    pend_map = &maps.c[which];
    pend_c0 = n_tile * 256;
    pend_c1 = m_tile * 128 + wg * 64;
  }
  mbar_wait(bar + B_GEMPTY, 1);
#pragma unroll
  for (int j = 0; j < 32; j++) pend[j] = pack_bf16(acc[2 * j] * Q_SCALE, acc[2 * j + 1] * Q_SCALE);
  put_box(sbase + wg * 8192, pend);
  put_box(sbase + 16384 + wg * 8192, pend + 16);
  fence_proxy_async();
#pragma unroll
  for (int j = 0; j < 64; j++) rest[j] = acc[64 + j];
  GT(gti++)
  return sn;
}

constexpr int A_TILE = 128 * 128 * 2;
constexpr int A_Q_OFF = 0;
constexpr int A_K_OFF = 2 * A_TILE;
constexpr int A_V_OFF = 4 * A_TILE;
constexpr int A_O_OFF = 6 * A_TILE;
constexpr int A_ITEMS = NH * (S_LEN / 128);

constexpr uint32_t A_ORDER = 0x3120, A_STEPS = 34;
__device__ __forceinline__ int item_m(uint32_t it) { return it & 15; }
__device__ __forceinline__ int item_h(uint32_t it) { return it >> 4; }

constexpr int C_V = 16384, C_MAT = 24576;
constexpr float C_ALPHA = 0.07874506561842957f;
__device__ __forceinline__ void sincos_turn(int p, float inv, float& c, float& s) {
  const float a = (float)p * (inv * 6.283185307179586f);
  asm("cos.approx.ftz.f32 %0, %1;" : "=f"(c) : "f"(a));
  asm("sin.approx.ftz.f32 %0, %1;" : "=f"(s) : "f"(a));
}

__device__ __forceinline__ uint32_t item_of(const Maps& maps, uint32_t r) {
  const uint32_t b = maps.id[blockIdx.x & 127][1];
  return (b >> 4) * 64 + ((A_ORDER >> (4 * r)) & 3) * 16 + ((b ^ ((r & 1) * 15)) & 15);
}

#define PACE 250
#define SPACE 0
#define LCHK 1
#define XMASK 3
#define XFIRST 4
#define C_SIDE 64
__device__ __forceinline__ uint32_t conv_first(const Maps& maps) {
  const uint32_t b = maps.id[blockIdx.x & 127][1];
  return (b >> 4) * 128 + ((b + 15) & 15);
}

__device__ __forceinline__ void conv_consumer(const Maps& maps, uint32_t smem0, uint32_t first, uint32_t step,
                                              uint32_t end, bool pp, bool dealt) {
  PHASE_PROLOGUE
  const uint32_t in_full = bar + B_CFULL + wg * 16;
  const uint32_t ca = sbase + (wg ? A_V_OFF + A_TILE : A_Q_OFF);
  const int w = __shfl_sync(0xffffffffu, warp, 0), g = lane >> 2, c = lane & 3;
  auto fetch = [&](uint32_t ch, uint32_t n) {
    if (w == 2 && ch < C_NONE) {
      if (elect_one()) {
        const uint32_t b = in_full + (n & 1) * 8, d = ca + (n & 1) * 8192;
        const uint64_t pol = policy_evict_first();
        mbar_expect_tx(b, 8192);
        tma_load_2d_hint(d, &maps.cu, b, 0, ch * 64, pol);
        tma_load_2d_hint(d + 4096, &maps.ch, b, 0, ch * 64, pol);
      }
    }
  };
  if (wtid == 96 && wg) { TD(15) }
  uint32_t f1[8][4];
  float tt[16], ts[16];
  uint32_t cc[4], ss[4];
#pragma unroll
  for (int i = 0; i < 16; i++) {
    const int k = 2 * (16 * w + g + 8 * (i & 1)) + 1, n = 2 * (8 * (i >> 1) + 2 * c) + 1;
    float c0, s0, c1, s1;
    sincos_turn(((k * n) << 23) >> 23, 1.f / 512, c0, s0);
    sincos_turn(((k * n + 2 * k) << 23) >> 23, 1.f / 512, c1, s1);
    f1[i >> 2][i & 3] = pack_bf16(c0 * C_ALPHA, c1 * C_ALPHA);
    f1[4 + (i >> 2)][i & 3] = pack_bf16(s0 * -C_ALPHA, s1 * -C_ALPHA);
  }
#pragma unroll
  for (int i = 0; i < 16; i++) {
    const int k = 2 * (16 * w + g + 8 * ((i >> 1) & 1)) + 1, n = 16 - (8 * (i >> 2) + 2 * c + (i & 1));
    float cs;
    sincos_turn(k * n, 1.f / 8192, cs, ts[i]);
    tt[i] = ts[i] * rcp(1.f + cs);
  }
#pragma unroll
  for (int j = 0; j < 4; j++) {
    const int k = 8 * w + g, n = 8 * c + 2 * j;
    float c0, s0, c1, s1;
    sincos_turn((int8_t)(k * n * 8), 1.f / 256, c0, s0);
    sincos_turn((int8_t)((k * n + k) * 8), 1.f / 256, c1, s1);
    cc[j] = pack_bf16(c0, c1);
    ss[j] = pack_bf16(s0, s1);
  }
  named_bar_sync(3, 256);
  fetch(first, 0);
  fetch(first + step, 1);
  const uint32_t va = ca + g * 64 + ((c ^ (g >> 1)) << 4);
  {
    const uint32_t a = va + C_MAT + w * 512, m = 0x80008000u;
    sts128(a, make_uint4(cc[0], cc[1], cc[2], cc[3]));
    sts128(a + 2048, make_uint4(ss[0], ss[1], ss[2], ss[3]));
    sts128(a + 4096, make_uint4(ss[0] ^ m, ss[1] ^ m, ss[2] ^ m, ss[3] ^ m));
    sts128(a + 6144, make_uint4(cc[0], cc[1], cc[2], cc[3]));
  }
  fence_proxy_async();
  named_bar_sync(1 + wg, 128);
  constexpr uint64_t DHI = (2ull << 62) | ((uint64_t)(512 >> 4) << 32);
  const uint32_t d0 = (uint32_t)make_desc(ca, 4096, 0, 0);
  float a5[16];
  uint4* const yb = reinterpret_cast<uint4*>(g_y2T) + (16 * w + g) * 4 + c;
  auto issue5 = [&]() {
#pragma unroll
    for (int ks = 0; ks < 8; ks++) wgmma_m64n32_rs_tb(a5, f1[ks], DHI | (d0 + (C_V >> 4) + ks * 64), ks != 0);
    wgmma_commit();
  };
  auto finish = [&](uint32_t ch, bool on) {
    fence_regs(a5);
    uint4* y = yb + (size_t)ch * 256;
    if (on) {
      y[0] = make_uint4(pack_bf16(a5[0], a5[1]), pack_bf16(a5[4], a5[5]), pack_bf16(a5[8], a5[9]), pack_bf16(a5[12], a5[13]));
      y[32] = make_uint4(pack_bf16(a5[2], a5[3]), pack_bf16(a5[6], a5[7]), pack_bf16(a5[10], a5[11]), pack_bf16(a5[14], a5[15]));
    }
  };
  auto dft32 = [&](float (&d)[32], const float* re, const float* im) {
    uint32_t a[4][4];
#pragma unroll
    for (int i = 0; i < 8; i++) {
      a[i >> 2][i & 3] = pack_bf16(re[2 * i], re[2 * i + 1]);
      a[2 + (i >> 2)][i & 3] = pack_bf16(im[2 * i], im[2 * i + 1]);
    }
    wgmma_fence();
#pragma unroll
    for (int ks = 0; ks < 4; ks++) wgmma_m64n64_rs_tb(d, a[ks], DHI | (d0 + (C_MAT >> 4) + ks * 64), ks != 0);
    wgmma_commit();
  };
  auto rot = [&](float* x, float* y) {
#pragma unroll
    for (int i = 0; i < 16; i++) {
      x[i] = fmaf(-tt[i], y[i], x[i]);
      y[i] = fmaf(ts[i], x[i], y[i]);
      x[i] = fmaf(-tt[i], y[i], x[i]);
    }
  };
  auto load_d = [&](uint32_t ch) {
    return __ldg(reinterpret_cast<const unsigned short*>(maps.ssm_D) + ((ch & (DM - 1)) | (lane & rt_zero)));
  };
  uint32_t dn = load_d(first);
  uint32_t n = 0, prev = 0, ch = first, next = first + step;
#pragma unroll 1
  for (; ch < C_NONE; n++) {
    CT(0)
    float a1[2][32], a2[2][32], a4[32];
    const float dsk = c ? 0.f : __uint_as_float(dn << 16) * C_ALPHA;
    dn = load_d(next);
    uint32_t next2 = next + step < end ? next + step : C_NONE;
    mbar_wait(in_full + (n & 1) * 8, (n >> 1) & 1);
    if (pp) named_bar_sync(4 + wg, 256);
    CT(1)
    wgmma_fence();
#pragma unroll
    for (int ks = 0; ks < 8; ks++)
      wgmma_m64n64_rs_tb(a1[ks >> 2], f1[ks], DHI | (d0 + (n & 1) * 512 + (ks & 3) * 64), (ks & 3) != 0);
    wgmma_commit();
    issue5();
    wgmma_wait<1>();
    fence_regs(a1[0]);
    fence_regs(a1[1]);
    CT(2)
    rot(a1[0], a1[1]);
    dft32(a2[0], a1[0], a1[1]);
    rot(a1[0] + 16, a1[1] + 16);
    a1[0][16] += dsk;
    a1[0][18] += dsk;
    dft32(a2[1], a1[0] + 16, a1[1] + 16);
    CT(3)
    wgmma_wait<2>();
    finish(prev, n > 0);
    wgmma_wait<0>();
    fence_regs(a2[0]);
    fence_regs(a2[1]);
    CT(4)
    if (pp) named_bar_arrive(5 - wg, 256);
    float re[16], im[16];
#pragma unroll
    for (int i = 0; i < 16; i++) {
      re[i] = a2[0][i] * a2[1][i] - a2[0][16 + i] * a2[1][16 + i];
      im[i] = a2[0][i] * a2[1][16 + i] + a2[0][16 + i] * a2[1][i];
    }
    dft32(a4, im, re);
    if (dealt) {
      mbar_wait(bar + (n < 2 ? B_DEAL : B_DEAL2), 0);
      asm volatile("ld.shared.u32 %0, [%1];" : "=r"(next2) : "r"(bar + B_LIST + 4 * n + (n < 2 ? 0 : 8)));
    }
    wgmma_wait<0>();
    fence_regs(a4);
    CT(5)
    rot(a4, a4 + 16);
#pragma unroll
    for (int i = 0; i < 4; i++) {
      const float* x = a4 + 16 - 16 * (i >> 1) + 2 * (i & 1);
      sts128(va + C_V + w * 1024 + (i >> 1) * 4096 + (i & 1) * 512,
             make_uint4(pack_bf16(x[0], x[1]), pack_bf16(x[4], x[5]), pack_bf16(x[8], x[9]), pack_bf16(x[12], x[13])));
    }
    CT(6)
    fence_proxy_async();
    named_bar_sync(1 + wg, 128);
    fetch(next2, n);
    if (wtid == 96 && n > 0) note(bar, CNT_Y2 + ((prev & 112) == 112));
    prev = ch;
    ch = next;
    next = next2;
    CT(7)
  }
  wgmma_fence();
  issue5();
  wgmma_wait<0>();
  finish(prev, (dn | ~rt_zero) != 0);
  named_bar_sync(1 + wg, 128);
  if (wtid == 96 && wg) { TD(8) }
  if (wtid == 96) cnt_signal_release(CNT_Y2 + ((prev & 112) == 112), 1);
  if (wtid == 64) note(bar, CNT_DONE);
  if (wtid == 96 && wg) { TD(9) }
}

__device__ __forceinline__ void attn_producer(const Maps& maps, uint32_t sbase, bool after_qkv, bool to_out,
                                              bool dry) {
  const uint32_t bar = sbase + BAR_OFF;
  const uint32_t q_full = bar + B_QFULL, q_empty = bar + B_QEMPTY;
  const uint32_t k_full = bar + B_KFULL, k_empty = bar + B_KEMPTY, v_full = bar + B_VFULL, v_empty = bar + B_VEMPTY;
  int ndrained = after_qkv ? 0 : G_STAGES;
  auto wait = [&](uint32_t b, uint32_t par) {
    if (!dry) mbar_wait_sleep(b, par);
  };
  auto drained = [&](int upto) {
#pragma unroll 1
    for (; ndrained <= upto; ndrained++) wait(bar + B_GEMPTY + 8 * ndrained, 1);
  };
  uint32_t st = 0, ph = 1, vs = 0, vp = 1;
  int pend_j = -1, pend_h = 0;
  int round = -1, m = -1, h = 0;
  bool last = false;
#pragma unroll 1
  for (;; round++) {
    uint32_t nitem = 0;
    const int tpost = m >= 3 ? m - 1 : m;
#pragma unroll 1
    for (int t = m < 0 ? -1 : 0; t <= m; t++) {
      const int j = (t < m && (round & 1)) ? m - 1 - t : t;
      if (t >= 0) {
        drained(1 + st);
        wait(k_empty + 8 * st, ph);
        if (!dry) {
          mbar_expect_tx(k_full + 8 * st, A_TILE);
          tma_load_3d(sbase + A_K_OFF + st * A_TILE, &maps.k, k_full + 8 * st, 0, j * 128, h * 2);
        }
        if (++st == 2) { st = 0; ph ^= 1; }
      }
      if (pend_j >= 0) {
        drained(3);
        wait(v_empty + 8 * vs, vp);
        if (!dry) {
          mbar_expect_tx(v_full + 8 * vs, A_TILE);
          tma_load_3d(sbase + A_V_OFF + vs * A_TILE, &maps.v, v_full + 8 * vs, 0, pend_j * 128, pend_h * 2);
        }
        if (++vs == 2) { vs = 0; vp ^= 1; }
      }
      pend_j = j;
      pend_h = h;
      if (t == tpost && !last) {
        nitem = dry ? 1 : item_of(maps, round + 1);
        if (round == (dry ? 0 : 3) || blockIdx.x >= 128) {
          nitem = A_ITEMS;
          if (!to_out) cnt_wait(CNT_PREP, dry ? 0 : 260);
          if (to_out) {
            wait(bar + seen_bar(1), 0);
            asm volatile("cp.async.bulk.prefetch.L2.global [%0], 4096;" ::"l"(maps.ssm_k + (size_t)conv_first(maps) * S_LEN));
            if (!dry)
              asm volatile("cp.async.bulk.prefetch.L2.global [%0], 4096;" ::"l"(g_kvT + (size_t)conv_first(maps) * S_LEN));
          }
        }
        const uint32_t qs = (round + 1) & 1;
        wait(q_empty + 8 * qs, (((round + 1) >> 1) & 1) ^ 1);
        if (round == 1 && after_qkv) wait(bar + B_QDONE, 0);
        if (round == 0 && after_qkv) wait(bar + seen_bar(0), 0);
        if (round < 0 && after_qkv) {
          if (!dry) { TD(2) }
          cnt_wait(CNT_KV, dry ? 0 : 512);
          if (!dry) { TD(3) }
        }
        if (nitem >= A_ITEMS || (round < 0 && after_qkv && !dry)) {
          if (!dry) mbar_arrive(q_full + 8 * qs);
        } else {
          drained(qs);
          if (!dry) {
            mbar_expect_tx(q_full + 8 * qs, A_TILE);
            tma_load_3d_hint(sbase + A_Q_OFF + qs * A_TILE, &maps.q, q_full + 8 * qs, 0, item_m(nitem) * 128,
                             item_h(nitem) * 2, policy_evict_first());
          }
        }
      }
    }
    if (last) break;
    last = nitem >= A_ITEMS;
    m = last ? -1 : item_m(nitem);
    h = item_h(nitem);
  }
}

__device__ __forceinline__ uint32_t attn_consumer(const Maps& maps, uint32_t smem0, uint32_t sn,
                                                  float (&rest)[64], bool after_qkv) {
  PHASE_PROLOGUE
  const uint32_t q_full = bar + B_QFULL, q_empty = bar + B_QEMPTY;
  const uint32_t k_full = bar + B_KFULL, k_empty = bar + B_KEMPTY, v_full = bar + B_VFULL;
  float o[64], s[64];
  uint32_t p[32];
  float e[32];
  uint32_t dep = 0;
  constexpr int MIDJ = 5;
  float l0 = 0.f, l1 = 0.f, b0 = 0.f, b1 = 0.f;
  const int sched_own = 4 + wg, sched_other = 5 - wg;
  if (wg == 1) named_bar_arrive(4, 256);

  const uint32_t qd0 = (uint32_t)make_desc(sbase + A_Q_OFF + wg * 8192, 16, 0, 0);
  const uint32_t kd0 = (uint32_t)make_desc(sbase + A_K_OFF, 16, 0, 0);
  const uint32_t vd0 = (uint32_t)make_desc(sbase + A_V_OFF, 16384, 0, 0);
  constexpr uint64_t DHI = DESC_SW128 | ((uint64_t)(1024 >> 4) << 32);
  constexpr uint32_t DST = A_TILE >> 4;
  auto issue_qk = [&](uint32_t qd, uint32_t kd) {
#pragma unroll
    for (int kk = 0; kk < 8; kk++) {
      const uint32_t off = ((kk >> 2) * 16384 + (kk & 3) * 32) >> 4;
      wgmma_m64n128_ss(s, DHI | (qd + off), DHI | (kd + off), kk != 0);
    }
    wgmma_commit();
  };
  auto issue_pv = [&](uint32_t vd, bool accumulate, int nk) {
#pragma unroll
    for (int kk = 0; kk < 8; kk++) {
      if (kk < nk)
        wgmma_m64n128_rs_tb(o, p[4 * kk], p[4 * kk + 1], p[4 * kk + 2], p[4 * kk + 3], DHI | (vd + kk * 128),
                            accumulate || (kk != 0));
    }
    wgmma_commit();
  };
  auto exp_lo = [&](float& a0, float& a1) {
#pragma unroll
    for (int j = 0; j < 8; j++) {
      e[4 * j] = ex2(s[4 * j]);
      e[4 * j + 1] = ex2(s[4 * j + 1]);
      e[4 * j + 2] = ex2(s[4 * j + 2]);
      e[4 * j + 3] = ex2(s[4 * j + 3]);
      a0 += e[4 * j];
      a0 += e[4 * j + 1];
      a1 += e[4 * j + 2];
      a1 += e[4 * j + 3];
      if (j == MIDJ) dep = (__float_as_uint(a0) | __float_as_uint(a1)) & rt_zero;
    }
  };
  auto pack_lo = [&]() {
#pragma unroll
    for (int j = 0; j < 16; j++) p[j] = pack_bf16(e[2 * j], e[2 * j + 1]);
  };
  auto finish_p = [&](float& a0, float& a1) {
    pack_lo();
#pragma unroll
    for (int j = 8; j < 16; j++) {
      const float e0 = ex2(s[4 * j]), e1 = ex2(s[4 * j + 1]), e2 = ex2(s[4 * j + 2]), e3 = ex2(s[4 * j + 3]);
      a0 += e0;
      a0 += e1;
      a1 += e2;
      a1 += e3;
      p[2 * j] = pack_bf16(e0, e1);
      p[2 * j + 1] = pack_bf16(e2, e3);
      if (j == 8 + MIDJ) dep = __float_as_uint(a0) & rt_zero;
    }
  };
  auto quad_sum = [&](float t) {
    t += __shfl_xor_sync(0xffffffffu, t, 1);
    return t + __shfl_xor_sync(0xffffffffu, t, 2);
  };
  auto write_o = [&](float i0, float i1) {
    st_wait(bar, wg, sn - 1);
    const int st_row = warp * 16 + (lane & 7) + ((lane >> 3) & 1) * 8;
    const uint32_t so = sbase + A_O_OFF + wg * 16384 + st_row * 128;
#pragma unroll
    for (int j = 0; j < 16; j += 2)
      stmatrix_x4(so + (j >> 3) * 8192 + ((((j & 7) + (lane >> 4)) ^ (lane & 7)) << 4),
                  pack_bf16(o[4 * j] * i0, o[4 * j + 1] * i0), pack_bf16(o[4 * j + 2] * i1, o[4 * j + 3] * i1),
                  pack_bf16(o[4 * j + 4] * i0, o[4 * j + 5] * i0), pack_bf16(o[4 * j + 6] * i1, o[4 * j + 7] * i1));
  };
  auto store_o = [&](uint32_t r, int kind, uint32_t lazy) {
    const uint32_t it = item_of(maps, r);
    st_post(bar, wg, wtid, sn, kind, (INPLACE & 1) || kind != ST_BOX2Q ? &maps.o : &maps.c[0], sbase + A_O_OFF + wg * 16384, item_h(it) * 128,
            item_m(it) * 128 + wg * 64, CNT_CTX + (r >> 1), lazy);
    sn++;
  };
  auto mask_half = [&](float* sh) {
    const int u = warp * 16 + (lane >> 2) - (lane & 3) * 2;
#pragma unroll
    for (int j = 0; j < 8; j++) {
      if (8 * j > u) sh[4 * j] = -INFINITY;
      if (8 * j + 1 > u) sh[4 * j + 1] = -INFINITY;
      if (8 * j - 8 > u) sh[4 * j + 2] = -INFINITY;
      if (8 * j - 7 > u) sh[4 * j + 3] = -INFINITY;
    }
  };
  ST(0)
  mbar_wait(q_full, 0);
  if (blockIdx.x >= 128) {
    return sn;
  }
  mbar_wait(k_full, 0);
  named_bar_sync(sched_own, 256);
  wgmma_fence();
  issue_qk(qd0, kd0);
  named_bar_arrive(sched_other, 256);
  fence_regs(rest);
#pragma unroll
  for (int i = 0; i < 64; i++) o[i] = rest[i] * Q_SCALE;
  fence_regs(o);
  wgmma_wait<0>();
  fence_regs(s);
  mbar_arrive_if(k_empty, wtid == 32);
  uint32_t g = 0;
  uint32_t rnd = 0;
  int rem = item_m(item_of(maps, 0));
  uint32_t first = 1;
  uint32_t fl = 0;
#define redo (fl & 1)
#define shifted (fl & 2)
  float d0 = 0.f, d1 = 0.f;
  float pi0 = 1.f, pi1 = 1.f;
  ST(1)
  for (;;) {
    if (shifted) {
#pragma unroll
      for (int j = 0; j < 16; j++) {
        s[4 * j] -= d0;
        s[4 * j + 1] -= d0;
        s[4 * j + 2] -= d1;
        s[4 * j + 3] -= d1;
      }
    }
    if (rem == 0 && !redo) {
      mbar_arrive_if(q_empty + 8 * (rnd & 1), wtid == 96);
      rnd++;
      if (wg == 0) mask_half(s);
      else mask_half(s + 32);
    }
    for (;;) {
      const bool kill = rem == 0 && wg == 0;
      const uint32_t kd = kd0 + ((g + 1) & 1) * DST, vd = vd0 + (g & 1) * DST;
      float a0 = 0.f, a1 = 0.f;
      exp_lo(a0, a1);
      fence_regs(e);
      const uint32_t kb = k_full + 8 * ((g + 1) & 1);
      const uint32_t kpar = (((g + 1) >> 1) & 1) ^ (g == A_STEPS - 1 ? 1u : 0u);
      const uint32_t qb = q_full + 8 * (rnd & 1), qpar = ((rnd >> 1) & 1) | dep;
      if (!mbar_try(qb, qpar)) mbar_wait(qb, qpar | ((__float_as_uint(a0) | __float_as_uint(a1)) & rt_zero));
      wgmma_wait<0>();
      fence_regs(o);
      if (kill) {
        mbar_arrive_if(kb + (B_VEMPTY - B_KFULL), wtid == 64 && !redo && g > 0);
        fence_regs(e);
        pack_lo();
#pragma unroll
        for (int j = 16; j < 32; j++) asm volatile("mov.u32 %0, 0;" : "=r"(p[j]));
        goto check;
      }
#pragma unroll
      for (int i = 32; i < 64; i++) asm volatile("" : "+f"(s[i])::"memory");
      mbar_arrive_if(kb + (B_VEMPTY - B_KFULL), wtid == 64 && !redo && g > 0);
      finish_p(a0, a1);
      if (__any_sync(0xffffffffu, !(mbar_try(v_full + 8 * (g & 1), ((g >> 1) & 1) | dep) &
                                    mbar_try(kb, kpar | dep)) ||
                                      !(a0 + a1 < 1.0995116e12f) || !(fminf(a0, a1) > (first ? 9.094947e-13f : -1.f)))) {
      check:
        bool bad = !(a0 + a1 < 1.0995116e12f);
        if (first) bad |= !(fminf(quad_sum(a0), quad_sum(a1)) > 9.094947e-13f);
        if (!redo && __any_sync(0xffffffffu, bad)) {
          d0 = d1 = first ? -INFINITY : 0.f;
#pragma unroll
          for (int j = 0; j < 16; j++) {
            if (j < 8 || !kill) {
              d0 = fmaxf(d0, fmaxf(s[4 * j], s[4 * j + 1]));
              d1 = fmaxf(d1, fmaxf(s[4 * j + 2], s[4 * j + 3]));
            }
          }
#pragma unroll
          for (int x = 1; x <= 2; x++) {
            d0 = fmaxf(d0, __shfl_xor_sync(0xffffffffu, d0, x));
            d1 = fmaxf(d1, __shfl_xor_sync(0xffffffffu, d1, x));
          }
          b0 += d0;
          b1 += d1;
          if (!first) {
            const float al0 = ex2(-d0), al1 = ex2(-d1);
            l0 *= al0;
            l1 *= al1;
#pragma unroll
            for (int j = 0; j < 16; j++) {
              o[4 * j] *= al0;
              o[4 * j + 1] *= al0;
              o[4 * j + 2] *= al1;
              o[4 * j + 3] *= al1;
            }
          }
          fl = 3;
          break;
        }
        mbar_wait(v_full + 8 * (g & 1), (g >> 1) & 1);
        mbar_wait(kb, kpar);
      }
      named_bar_sync(sched_own, 256);
      if (g == A_STEPS - 1) {
        if (first) write_o(pi0, pi1);
        fence_regs(o);
        wgmma_fence();
        issue_pv(vd, !first, 8);
        named_bar_arrive(sched_other, 256);
        if (first) store_o(rnd - 2, ST_BOX2, 0);
        pi0 = rcp(quad_sum(l0 + a0));
        pi1 = rcp(quad_sum(l1 + a1));
        goto done;
      }
      wgmma_fence();
      issue_qk(qd0 + (rnd & 1) * DST, kd);
      if (first) write_o(pi0, pi1);
      fence_regs(o);
      if (kill) {
        wgmma_fence();
        issue_pv(vd, !first, 4);
      } else {
        wgmma_fence();
        issue_pv(vd, !first, 8);
      }
      named_bar_arrive(sched_other, 256);
      fl &= 2;
      l0 += a0;
      l1 += a1;
      if (rem == 0 || first) {
        if (first && (g > 0 || after_qkv)) store_o(g ? rnd - (rem == 0 ? 2 : 1) : 2, g ? ST_BOX2 : ST_BOX2Q, rem);
        first = rem == 0;
        if (first) {
          pi0 = rcp(quad_sum(l0));
          pi1 = rcp(quad_sum(l1));
          l0 = l1 = b0 = b1 = 0.f;
          fl = 0;
          rem = item_m(item_of(maps, rnd)) + 1;
        }
      }
      rem--;
      g++;
      wgmma_wait<1>();
      fence_regs(s);
      mbar_arrive_if(kb + (B_KEMPTY - B_KFULL), wtid == 32);
      ST(g + 1)
      if (rem == 0 || shifted) {
        d0 = b0;
        d1 = b1;
        break;
      }
    }
  }
done:
#undef redo
#undef shifted
  wgmma_wait<0>();
  fence_regs(o);
  write_o(pi0, pi1);
  store_o(3, ST_BOX2L, 0);
  ST(35)
  return sn;
}

constexpr int O_STAGES = 5;
constexpr int O_STAGE_BYTES = 32768;
constexpr int O_Y_OFF = 5 * 32768;
constexpr int O_X_OFF = 6 * 32768;
constexpr int O_NK = HDIM / 64;

__device__ __forceinline__ uint32_t out_stage(uint32_t st) { return ((0x43120u >> (4 * st)) & 7) * O_STAGE_BYTES; }

__device__ __forceinline__ void out_producer(const Maps& maps, uint32_t sbase, bool after_attn, bool dry) {
  const uint32_t bar = sbase + BAR_OFF;
  const uint32_t rank = blockIdx.x & 1;
  const int m_tile = maps.id[blockIdx.x][2] & 15, n_tile = maps.id[blockIdx.x][2] >> 4;
  uint32_t stage = 0, phase = 0, xi = 0;
#pragma unroll 1
  for (int ki = 0; ki < (dry ? 1 : O_NK); ki++) {
    const int kt = (ki & 14) * 4 + ((A_ORDER >> ((ki >> 4) * 4)) & 3) * 2 + (ki & 1);
    const uint32_t fb = bar + B_OFULL + 8 * stage, eb = bar + B_OEMPTY + 8 * stage;
    const uint32_t sa = sbase + out_stage(stage);
    if (ki < O_STAGES) {
      constexpr uint32_t LASTB = B_KEMPTY | ((B_QEMPTY + 8) << 8) | ((B_KEMPTY + 8) << 16) | (B_VEMPTY << 24);
      if (ki > 0 && after_attn) mbar_wait_sleep(bar + ((LASTB >> (8 * ki - 8)) & 255), ki == 2);
      mbar_arrive_cluster_if(eb, 0, !dry);
      mbar_arrive_cluster_if(eb, 1, !dry);
    }
    if (ki == 32) mbar_wait_sleep(bar + seen_bar(2), 0);
    if (!dry) {
      mbar_wait_sleep(eb, phase);
      mbar_expect_tx(fb, O_STAGE_BYTES);
      tma_load_2d_mc(sa + 16384 + rank * 8192, &maps.ob, fb, n_tile * 128 + rank * 64, kt * 64, (uint16_t)3);
      tma_load_2d(sa, &maps.oa, fb, kt * 64, m_tile * 128);
    }
    if (++stage == O_STAGES) { stage = 0; phase ^= 1; }
    if ((ki & XMASK) == XMASK && ki >= XFIRST && xi < 8) {
      if (after_attn && xi < 2) mbar_wait_sleep(bar + B_OFREE + 8 * xi, 0);
      tma_load_3d(sbase + O_X_OFF + (xi & 1) * 16384 + (xi >> 1) * 4096, &maps.xs, bar + B_OY, 0,
                  m_tile * 128 + (xi >> 1) * 32, n_tile * 2 + (xi & 1));
      xi++;
    }
  }
  if (!dry) mbar_wait_sleep(bar + B_OY2, 0);
}

__device__ __forceinline__ void out_side(const Maps& maps, uint32_t smem0, const float (&gv)[4]) {
  PHASE_PROLOGUE
  const int m_tile = maps.id[blockIdx.x][2] & 15, n_tile = maps.id[blockIdx.x][2] >> 4;
  const bool w0 = __shfl_sync(0xffffffffu, warp, 0) == 0;
  bool have = false;
  auto late = [&](uint32_t spins) {
    have = cnt_wait(CNT_Y2 + 1, 128, spins) || !spins;
    TD(11)
    if (have) {
      mbar_expect_tx(bar + B_OY2, 4096);
      tma_load_3d(sbase + O_Y_OFF + 7 * 4096, &maps.y, bar + B_OY2, 0, n_tile * 128 + 112, m_tile * 2);
    }
  };
  if (w0) {
    if (elect_one()) {
      mbar_expect_tx(bar + B_OY, 65536 - 4096);
      TD(10)
      cnt_wait(CNT_Y2, DM - 128);
      TD(7)
#pragma unroll 1
      for (int i = 0; i < 7; i++) {
        tma_load_3d(sbase + O_Y_OFF + i * 4096, &maps.y, bar + B_OY, 0, n_tile * 128 + i * 16, m_tile * 2);
        __nanosleep(PACE);
      }
      late(1u << 18);
    }
  }
  mbar_wait_sleep(bar + B_OY, 0);
  if (wtid == 0) { TD(12) }
  const int st_row = warp * 16 + (lane & 7) + ((lane >> 3) & 1) * 8;
  const int mrow = (lane & 7) + ((lane >> 4) & 1) * 8;
  const int mchunk = warp * 2 + ((lane >> 3) & 1);
  const uint32_t xrow = sbase + O_X_OFF + st_row * 128;
  const uint32_t yrow = sbase + O_Y_OFF + mrow * 128 + ((mchunk ^ (lane & 7)) << 4);
  uint32_t y[7][4], x[7][4], om[4];
#pragma unroll
  for (int i = 0; i < 4; i++) om[i] = pack_bf16(1.0f - gv[i], 1.0f - gv[i]);
  auto xa = [&](int h, int i) { return xrow + h * 8192 + (i >> 2) * 16384 + ((((i & 3) * 2 + (lane >> 4)) ^ (lane & 7)) << 4); };
  auto load = [&](int r, int h, int i) {
    ldsm4t(y[r], yrow + h * 2048 + i * 4096);
    asm volatile("ldmatrix.sync.aligned.m8n8.x4.shared.b16 {%0, %1, %2, %3}, [%4];"
                 : "=r"(x[r][0]), "=r"(x[r][1]), "=r"(x[r][2]), "=r"(x[r][3])
                 : "r"(xa(h, i)));
  };
  auto store = [&](int r, int h, int i, uint32_t om0, uint32_t om1) {
    stmatrix_x4(xa(h, i), mul_bf2(om0, mul_bf2(x[r][0], y[r][0])), mul_bf2(om1, mul_bf2(x[r][1], y[r][1])),
                mul_bf2(om0, mul_bf2(x[r][2], y[r][2])), mul_bf2(om1, mul_bf2(x[r][3], y[r][3])));
  };
#pragma unroll 1
  for (int h = 0; h < 2; h++) {
#pragma unroll
    for (int i = 0; i < 7; i++) load(i, h, i);
#pragma unroll
    for (int i = 0; i < 7; i++) store(i, h, i, h ? om[2] : om[0], h ? om[3] : om[1]);
  }
  if (w0 && !__any_sync(0xffffffffu, have)) {
    if (elect_one()) late(0);
  }
  mbar_wait_sleep(bar + B_OY2, 0);
  load(0, 0, 7);
  load(1, 1, 7);
  store(0, 0, 7, om[0], om[1]);
  store(1, 1, 7, om[2], om[3]);
  __syncwarp();
  mbar_arrive_if(bar + B_OY + 8, lane == 0);
  if (wtid == 0) { TD(13) }
}

__device__ __forceinline__ uint32_t out_gemm(const Maps& maps, uint32_t smem0, uint32_t sn) {
  PHASE_PROLOGUE
  const int m_tile = maps.id[blockIdx.x][2] & 15, n_tile = maps.id[blockIdx.x][2] >> 4;
  float acc[2][64];
  undef_regs(acc[0]);
  undef_regs(acc[1]);
  uint32_t stage = 0, phase = 0, prev_stage = 0;
  GT(gti++)
  const float* gp = g_gate + m_tile * 128 + warp * 16 + (lane >> 2);
  const float gv[4] = {__ldcg(gp), __ldcg(gp + 8), __ldcg(gp + 64), __ldcg(gp + 72)};
  if (wg == 1) {
    out_side(maps, smem0, gv);
    return sn;
  }
#pragma unroll 1
  for (int kt = 0; kt < O_NK; kt++) {
    uint32_t da = (uint32_t)make_desc(sbase + out_stage(stage), 16, 0, 0);
    uint32_t db = (uint32_t)make_desc(sbase + out_stage(stage) + 16384, 8192, 0, 0);
    asm volatile("" : "+r"(da), "+r"(db));
    mbar_wait(bar + B_OFULL + 8 * stage, phase);
    GT(gti++)
#define OWAIT_ 2
    constexpr int OWAIT = OWAIT_;
    constexpr uint64_t DHI = DESC_SW128 | ((uint64_t)(1024 >> 4) << 32);
#pragma unroll
    for (int kk = 0; kk < 4; kk++) {
      wgmma_wait<OWAIT>();
      if (kk == OWAIT)
        mbar_arrive_cluster_if(bar + B_OEMPTY + 8 * prev_stage, wtid >> 6,
                               (wtid & 63) == 32 && kt > 0 && kt - 1 + O_STAGES < O_NK);
      wgmma_fence();
      wgmma_m64n128_ss_tb(acc[0], DHI | (da + kk * 2), DHI | (db + kk * 128), (kt | kk) != 0);
      wgmma_m64n128_ss_tb(acc[1], DHI | (da + 512 + kk * 2), DHI | (db + kk * 128), (kt | kk) != 0);
      wgmma_commit();
    }
    prev_stage = stage;
    if (++stage == O_STAGES) { stage = 0; phase ^= 1; }
  }
  if (tid == 0) { TD(14) }
  st_wait(bar, wg, sn - 1);
  const int st_row = warp * 16 + (lane & 7) + ((lane >> 3) & 1) * 8;
  const uint32_t rowa = sbase + O_X_OFF + st_row * 128;
  auto addr = [&](int i) {
    return rowa + (i & 1) * 8192 + (i >> 3) * 16384 + ((((i & 6) + (lane >> 4)) ^ (st_row & 7)) << 4);
  };
  uint32_t gg[4], b[16][4];
#pragma unroll
  for (int i = 0; i < 4; i++) gg[i] = pack_bf16(gv[i], gv[i]);
  mbar_wait(bar + B_OY + 8, 0);
#pragma unroll
  for (int i = 0; i < 16; i++)
    asm volatile("ldmatrix.sync.aligned.m8n8.x4.shared.b16 {%0, %1, %2, %3}, [%4];"
                 : "=r"(b[i][0]), "=r"(b[i][1]), "=r"(b[i][2]), "=r"(b[i][3])
                 : "r"(addr(i))
                 : "memory");
  wgmma_wait<0>();
  fence_regs(acc[0]);
  fence_regs(acc[1]);
  GT(gti++)
#pragma unroll
  for (int i = 0; i < 16; i++) {
    const float* a = acc[i & 1] + 4 * (i & 14);
    const uint32_t gg0 = gg[2 * (i & 1)], gg1 = gg[2 * (i & 1) + 1];
    stmatrix_x4(addr(i), add_bf2(mul_bf2(gg0, pack_bf16(a[0], a[1])), b[i][0]),
                add_bf2(mul_bf2(gg1, pack_bf16(a[2], a[3])), b[i][1]),
                add_bf2(mul_bf2(gg0, pack_bf16(a[4], a[5])), b[i][2]),
                add_bf2(mul_bf2(gg1, pack_bf16(a[6], a[7])), b[i][3]));
    if (i == 7) st_post(bar, wg, wtid, sn, ST_BOX1, &maps.oc, sbase + O_X_OFF, n_tile * 128, m_tile * 128, -1);
  }
  fence_proxy_async();
  named_bar_sync(1, 128);
  if (__shfl_sync(0xffffffffu, warp, 0) == 0) {
    if (elect_one()) {
      tma_store_2d(&maps.oc, sbase + O_X_OFF + 16384, n_tile * 128 + 64, m_tile * 128);
      tma_store_commit();
    }
  }
  GT(gti++)
  return sn + 1;
}

__device__ __noinline__ void leave_kernel(int mask) {
  if (!(mask & 4)) return;
  if (atomicAdd(g_cnt + CNT_DONE * 32, 1u) == 2 * gridDim.x - 1) {
    for (int i = 0; i < CNT_N; i++) g_cnt[i * 32] = 0;
#pragma unroll 4
    for (int i = 0; i < 128; i++) g_slot[i] = 0;
  }
}

__device__ __noinline__ void side_jobs(const Maps& maps, uint32_t sbase) {
  const int w12 = __shfl_sync(0xffffffffu, threadIdx.x >> 5, 0);
  gate_rows(maps, sbase, (blockIdx.x - 128) * 12 + w12, w12, threadIdx.x & 31);
  fence_proxy_async();
  __syncthreads();
  if (threadIdx.x == 320) cnt_signal_release(CNT_PREP, 1);
}

__global__ void __launch_bounds__(384, 1) fused_kernel(int mask, const __grid_constant__ Maps maps) {
  extern __shared__ __align__(1024) uint8_t smem_raw[];
  {
    const uint32_t sbase = __shfl_sync(0xffffffffu, smem_u32(smem_raw), 0);
    const uint32_t bar = sbase + BAR_OFF;
    const int tid = threadIdx.x;
    const bool do_qkv = (mask & 1) && blockIdx.x < 128;
    TL(0, 0)
    if (__shfl_sync(0xffffffffu, tid >> 5, 0) == 1 && do_qkv) {
      if (elect_one()) {
        for (int i = 0; i < G_STAGES; i++) mbar_init(bar + B_GFULL + 8 * i, 1);
        fence_barrier_init();
        qkv_producer(maps, sbase, true);
      }
    }
    if (tid == 0) {
      for (int i = 0; i < G_STAGES; i++) {
        mbar_init(bar + B_GEMPTY + 8 * i, 2);
        mbar_init(bar + B_SFULL + 8 * i, 4);
        mbar_init(bar + B_SFREE + 8 * i, 1);
      }
      for (int i = 0; i < 2; i++) {
        mbar_init(bar + B_OFREE + 8 * i, 1);
        mbar_init(bar + B_QFULL + 8 * i, 1);
        mbar_init(bar + B_QEMPTY + 8 * i, 2);
        mbar_init(bar + B_KFULL + 8 * i, 1);
        mbar_init(bar + B_KEMPTY + 8 * i, 2);
        mbar_init(bar + B_VFULL + 8 * i, 1);
        mbar_init(bar + B_VEMPTY + 8 * i, 2);
      }
      for (int i = 0; i < O_STAGES; i++) {
        mbar_init(bar + B_OFULL + 8 * i, 1);
        mbar_init(bar + B_OEMPTY + 8 * i, 2);
      }
      mbar_init(bar + B_OY, 1);
      for (int i = 0; i < 3; i++) mbar_init(bar + seen_bar(i), 1);
      mbar_init(bar + B_OY2, 1);
      mbar_init(bar + B_DEAL, 1);
      mbar_init(bar + B_DEAL2, 1);
      mbar_init(bar + B_PAIR, 1);
      mbar_init(bar + B_OY + 8, 4);
      mbar_init(bar + B_QDONE, 2);
      for (int i = 0; i < 8; i++) mbar_init(bar + B_CFULL + 8 * i, 1);
      for (int i = 0; i < CNT_N; i++) asm volatile("st.shared.u32 [%0], 0;" ::"r"(bar + B_PEND + 4 * i) : "memory");
      fence_barrier_init();
    }
    __syncthreads();
    asm volatile("barrier.cluster.arrive.relaxed.aligned;" ::: "memory");
    if ((mask & 1) && blockIdx.x >= 128) side_jobs(maps, sbase);
  }
  uint32_t smem0 = smem_u32(smem_raw);
  PHASE_PROLOGUE
  const bool do_qkv = (mask & 1) && blockIdx.x < 128, do_out = (mask & 4) && blockIdx.x < 128;
  TL(0, 1)

  if (wg != 2) {
    reg_alloc<232>();
    uint32_t sn = 0;
    float o[64];
    if (do_qkv) {
      sn = qkv_consumer(maps, smem_u32(smem_raw), mask & 2, o);
    } else {
      undef_regs(o);
    }
    TL(0, 2) TL(1, 0) TL(1, 1)
    asm volatile("barrier.cluster.wait.acquire.aligned;" ::: "memory");
    if (mask & 2) {
      sn = attn_consumer(maps, smem_u32(smem_raw), sn, o, mask & 1);
      TL(2, 0)
      if ((mask & 4) && blockIdx.x < 128 && __shfl_sync(0xffffffffu, threadIdx.x, 0) < 128) {
        named_bar_arrive(3, 256);
      } else {
        const uint32_t b2 = blockIdx.x * 2 + (threadIdx.x >> 7);
        const bool fused = mask & 4, mainc = blockIdx.x < 128;
        const uint32_t first = __shfl_sync(0xffffffffu, !fused ? b2 : mainc ? conv_first(maps) : (b2 - 255) * 128 - C_SIDE, 0);
        conv_consumer(maps, smem_u32(smem_raw), first, !fused ? 264 : mainc ? 16 : 1,
                      !fused ? DM : mainc ? (first | 127) + 1 - C_SIDE : first + C_SIDE, fused && !mainc,
                      fused && mainc);
      }
      TL(1, 2) TL(2, 1) TL(2, 2)
    }
    TL(3, 0) TL(3, 1)
    if ((mask & 4) && blockIdx.x < 128) sn = out_gemm(maps, smem_u32(smem_raw), sn);
    {
      uint32_t smem0 = smem_u32(smem_raw);
      PHASE_PROLOGUE
      st_wait(bar, wg, sn - 2);
      st_post(bar, wg, wtid, sn, ST_END, nullptr, 0, 0, 0, -1);
      tma_store_wait_read<0>();
    }
  } else {
    reg_dealloc<40>();
    asm volatile("barrier.cluster.wait.acquire.aligned;" ::: "memory");
    const int w = __shfl_sync(0xffffffffu, tid >> 5, 0) - 8;
    if (w < 2) {
      if (do_qkv) prep_agent(maps, sbase, w, lane);
      if (elect_one()) store_agent(bar, w, w && do_out ? conv_first(maps) + 48 : 0);
      TL2(3, 2)
    } else {
      if (elect_one()) {
        const bool dry = w == 2;
        if (do_qkv && !dry) qkv_producer(maps, sbase, false);
        if (mask & 2) attn_producer(maps, sbase, do_qkv, do_out, dry);
        if (do_out) out_producer(maps, sbase, mask & 2, dry);
        if (dry) { TD(5) }
      }
      __syncwarp();
      if (w == 2) publisher(bar, tid & 31, !(mask & 2) ? 2 : do_out ? 3 : 4, !do_out ? 3 : do_qkv ? 0 : 2, do_qkv ? 4 : 0);
      if ((tid & 31) == 0) leave_kernel(mask);
    }
  }
}

typedef CUresult (*PFN_tmapEncode)(CUtensorMap*, CUtensorMapDataType, cuuint32_t, void*, const cuuint64_t*,
                                   const cuuint64_t*, const cuuint32_t*, const cuuint32_t*, CUtensorMapInterleave,
                                   CUtensorMapSwizzle, CUtensorMapL2promotion, CUtensorMapFloatOOBfill);
static PFN_tmapEncode s_encode = nullptr;

static void make_map_2d(CUtensorMap* m, const void* ptr, int rows, int cols, int box_rows) {
  cuuint64_t dims[2] = {(cuuint64_t)cols, (cuuint64_t)rows};
  cuuint64_t strides[1] = {(cuuint64_t)cols * 2};
  cuuint32_t box[2] = {cols < 64 ? 32u : 64u, (cuuint32_t)box_rows};
  cuuint32_t es[2] = {1, 1};
  s_encode(m, CU_TENSOR_MAP_DATA_TYPE_BFLOAT16, 2, const_cast<void*>(ptr), dims, strides, box, es,
           CU_TENSOR_MAP_INTERLEAVE_NONE, cols < 64 ? CU_TENSOR_MAP_SWIZZLE_64B : CU_TENSOR_MAP_SWIZZLE_128B, CU_TENSOR_MAP_L2_PROMOTION_L2_256B,
           CU_TENSOR_MAP_FLOAT_OOB_FILL_NONE);
}
static void make_map_3d(CUtensorMap* m, const void* ptr, int rows, int cols, int box_rows, int box_chunks) {
  cuuint64_t dims[3] = {64, (cuuint64_t)rows, (cuuint64_t)(cols / 64)};
  cuuint64_t strides[2] = {(cuuint64_t)cols * 2, 128};
  cuuint32_t box[3] = {64, (cuuint32_t)box_rows, (cuuint32_t)box_chunks};
  cuuint32_t es[3] = {1, 1, 1};
  s_encode(m, CU_TENSOR_MAP_DATA_TYPE_BFLOAT16, 3, const_cast<void*>(ptr), dims, strides, box, es,
           CU_TENSOR_MAP_INTERLEAVE_NONE, CU_TENSOR_MAP_SWIZZLE_128B, CU_TENSOR_MAP_L2_PROMOTION_L2_256B,
           CU_TENSOR_MAP_FLOAT_OOB_FILL_NONE);
}

static cudaLaunchConfig_t fused_cfg(cudaLaunchAttribute* at) {
  cudaLaunchConfig_t cfg = {};
  cfg.gridDim = dim3(132);
  cfg.blockDim = dim3(384);
  cfg.dynamicSmemBytes = SMEM_BYTES;
  cfg.stream = cudaStreamPerThread;
  at[0].id = cudaLaunchAttributeClusterDimension;
  at[0].val.clusterDim.x = 2;
  at[0].val.clusterDim.y = 1;
  at[0].val.clusterDim.z = 1;
  cfg.attrs = at;
  cfg.numAttrs = 1;
  return cfg;
}

extern "C" void kernel_launch(void* const* d_in, const int* in_sizes, int n_in, void* d_out, int out_size) {
  const bf16* x = (const bf16*)d_in[0];
  const bf16* ckv = (const bf16*)d_in[1];
  const bf16* wq = (const bf16*)d_in[2];
  const bf16* wuk = (const bf16*)d_in[3];
  const bf16* wuv = (const bf16*)d_in[4];
  const bf16* wo = (const bf16*)d_in[5];
  const bf16* bk = (const bf16*)d_in[7];
  const bf16* bv = (const bf16*)d_in[8];
  const bf16* shift_k = (const bf16*)d_in[9];
  const bf16* ssm_k = (const bf16*)d_in[10];
  const bf16* ssm_D = (const bf16*)d_in[11];
  const bf16* gate_w = (const bf16*)d_in[12];
  bf16* out = (bf16*)d_out;

  static void *pq = nullptr, *pk = nullptr, *pv = nullptr, *pctx = nullptr, *pb = nullptr, *pu = nullptr;
  static int max_clusters = 0;
  if (!s_encode) {
    void* fn = nullptr;
    cudaDriverEntryPointQueryResult qres;
    cudaGetDriverEntryPoint("cuTensorMapEncodeTiled", &fn, cudaEnableDefault, &qres);
    s_encode = (PFN_tmapEncode)fn;
    cudaGetSymbolAddress(&pq, g_q);
    cudaGetSymbolAddress(&pk, g_k);
    cudaGetSymbolAddress(&pv, g_v);
    cudaGetSymbolAddress(&pctx, g_ctx);
    cudaGetSymbolAddress(&pb, g_y2T);
    cudaGetSymbolAddress(&pu, g_kvT);
    cudaFuncSetAttribute(fused_kernel, cudaFuncAttributeMaxDynamicSharedMemorySize, SMEM_BYTES);
    cudaLaunchAttribute at[1];
    cudaLaunchConfig_t cfg = fused_cfg(at);
    if (cudaOccupancyMaxActiveClusters(&max_clusters, fused_kernel, &cfg) != cudaSuccess) max_clusters = 0;
  }

  Maps all = {};
  make_map_2d(&all.a[0], x, S_LEN, DM, 128);
  make_map_2d(&all.a[1], ckv, S_LEN, DC, 128);
  make_map_3d(&all.b[0], wq, DM, HDIM, 64, 4);
  make_map_3d(&all.b[1], wuk, DC, HDIM, 64, 4);
  make_map_3d(&all.b[2], wuv, DC, HDIM, 64, 4);
  make_map_2d(&all.c[0], pq, S_LEN, HDIM, 64);
  make_map_2d(&all.c[1], pk, S_LEN, HDIM, 64);
  make_map_2d(&all.c[2], pv, S_LEN, HDIM, 64);
  make_map_3d(&all.q, pq, S_LEN, HDIM, 128, 2);
  make_map_3d(&all.k, pk, S_LEN, HDIM, 128, 2);
  make_map_3d(&all.v, pv, S_LEN, HDIM, 128, 2);
  make_map_2d(&all.o, pctx, S_LEN, HDIM, 64);
  all.ssm_k = ssm_k;
  all.ssm_D = ssm_D;
  make_map_2d(&all.oa, pctx, S_LEN, HDIM, 128);
  make_map_2d(&all.ob, wo, HDIM, DM, 64);
  make_map_2d(&all.oc, out, S_LEN, DM, 128);
  make_map_3d(&all.y, pb, DM, S_LEN, 16, 2);
  make_map_3d(&all.xs, x, S_LEN, DM, 32, 1);
  make_map_2d(&all.cu, pu, DM * 64, 32, 64);
  make_map_2d(&all.ch, ssm_k, DM * 64, 32, 64);

  make_map_2d(&all.bk, bk, S_LEN, DM, 35);
  make_map_2d(&all.bv, bv, S_LEN, DM, 32);
  for (int b = 0; b < 128; b++) {
    const int c = b >> 1, r = b & 1;
    const int G = c < 4 ? 0 : c < 36 ? (c - 4) % 8 : 1 + (c - 36) % 7;
    const int i = c < 4 ? 4 + c : c < 36 ? (c - 4) / 8 : 4 + (c - 36) / 7;
    all.id[b][0] = r + 2 * (i & 1) + 4 * (G & 3) + 16 * (i >> 1) + 64 * (G >> 2);
    all.id[b][1] = r + 2 * i + 16 * G;
    all.id[b][2] = r + 2 * G + 16 * i;
  }
  all.shift_k = shift_k;
  all.x = x;
  all.gate_w = gate_w;
  cudaLaunchAttribute at[1];
  cudaLaunchConfig_t cfg = fused_cfg(at);
  if (max_clusters >= 66) {
    cudaLaunchKernelEx(&cfg, fused_kernel, 7, all);
  } else {
    for (int m = 1; m <= 4; m <<= 1) cudaLaunchKernelEx(&cfg, fused_kernel, m, all);
  }
}
```

```cpp
#include <cuda_runtime.h>
#include <cuda_bf16.h>
#include <cuda.h>
#include <stdint.h>

typedef __nv_bfloat16 bf16;
#define INPLACE 3

constexpr int S_LEN = 2048;
constexpr int DM = 1024;
constexpr int NH = 32;
constexpr int HD = 128;
constexpr int DC = 512;
constexpr int HDIM = NH * HD;

__device__ __align__(1024) bf16 g_q[S_LEN * HDIM];
__device__ __align__(1024) bf16 g_k[S_LEN * HDIM];
__device__ __align__(1024) bf16 g_v[S_LEN * HDIM];
#define g_ctx g_q
__device__ __align__(1024) bf16 g_kvT[DM * S_LEN];
#define g_y2T g_kvT
__device__ __align__(1024) float g_gate[S_LEN];
enum { CNT_KV = 0, CNT_PREP = CNT_KV + 2, CNT_CTX, CNT_Y2 = CNT_CTX + 2, CNT_DONE = CNT_Y2 + 2, CNT_RANK, CNT_N };
__device__ unsigned int g_cnt[CNT_N * 32];
__device__ unsigned long long g_slot[128];

#define TL(k, i)
#define TL2(k, i)
#define TD(i)
#define CT(i)
#define GT(i)
#define GA(i)
#define ST(i)

__device__ __forceinline__ uint32_t smem_u32(const void* p) { return (uint32_t)__cvta_generic_to_shared(p); }

__device__ __forceinline__ void mbar_init(uint32_t bar, uint32_t count) {
  asm volatile("mbarrier.init.shared::cta.b64 [%0], %1;" ::"r"(bar), "r"(count));
}
__device__ __forceinline__ void mbar_expect_tx(uint32_t bar, uint32_t bytes) {
  asm volatile("mbarrier.arrive.expect_tx.shared::cta.b64 _, [%0], %1;" ::"r"(bar), "r"(bytes) : "memory");
}
__device__ __forceinline__ void mbar_arrive(uint32_t bar) {
  asm volatile("mbarrier.arrive.shared::cta.b64 _, [%0];" ::"r"(bar) : "memory");
}
__device__ __forceinline__ void mbar_wait(uint32_t bar, uint32_t parity) {
  uint32_t done;
  uint32_t spins = 0;
  do {
    asm volatile(
        "{\n.reg .pred p;\n"
        "mbarrier.try_wait.parity.shared::cta.b64 p, [%1], %2;\n"
        "selp.u32 %0, 1, 0, p;\n}\n"
        : "=r"(done)
        : "r"(bar), "r"(parity)
        : "memory");
    if (++spins > (1u << 22)) break;
  } while (!done);
}
__device__ __forceinline__ bool mbar_try(uint32_t bar, uint32_t parity) {
  uint32_t done;
  asm volatile(
      "{\n.reg .pred p;\n"
      "mbarrier.try_wait.parity.shared::cta.b64 p, [%1], %2;\n"
      "selp.u32 %0, 1, 0, p;\n}\n"
      : "=r"(done)
      : "r"(bar), "r"(parity)
      : "memory");
  return done != 0;
}
__device__ __forceinline__ bool elect_one() {
  uint32_t pred;
  asm volatile("{\n.reg .pred p;\nelect.sync _|p, 0xffffffff;\nselp.u32 %0, 1, 0, p;\n}\n" : "=r"(pred));
  return pred != 0;
}
__device__ __forceinline__ void mbar_arrive_if(uint32_t bar, bool pred) {
  asm volatile(
      "{\n.reg .pred p;\nsetp.ne.b32 p, %1, 0;\n"
      "@p mbarrier.arrive.shared::cta.b64 _, [%0];\n}\n" ::"r"(bar),
      "r"((uint32_t)pred)
      : "memory");
}
__device__ __forceinline__ void mbar_wait_sleep(uint32_t bar, uint32_t parity) {
  uint32_t done;
  uint32_t spins = 0;
  do {
    asm volatile(
        "{\n.reg .pred p;\n"
        "mbarrier.try_wait.parity.shared::cta.b64 p, [%1], %2, %3;\n"
        "selp.u32 %0, 1, 0, p;\n}\n"
        : "=r"(done)
        : "r"(bar), "r"(parity), "r"(20000u)
        : "memory");
    if (++spins > (1u << 16)) break;
  } while (!done);
}
__device__ __forceinline__ void fence_barrier_init() {
  asm volatile("fence.mbarrier_init.release.cluster;" ::: "memory");
}
__device__ __forceinline__ void fence_proxy_async() {
  asm volatile("fence.proxy.async.shared::cta;" ::: "memory");
}
__device__ __forceinline__ void named_bar_sync(int id, int nthreads) {
  asm volatile("bar.sync %0, %1;" ::"r"(id), "r"(nthreads) : "memory");
}
__device__ __forceinline__ void named_bar_arrive(int id, int nthreads) {
  asm volatile("bar.arrive %0, %1;" ::"r"(id), "r"(nthreads) : "memory");
}
__device__ __forceinline__ void tma_load_2d(uint32_t dst, const CUtensorMap* m, uint32_t bar, int c0, int c1) {
  asm volatile(
      "cp.async.bulk.tensor.2d.shared::cluster.global.mbarrier::complete_tx::bytes [%0], [%1, {%3, %4}], [%2];" ::"r"(dst),
      "l"(reinterpret_cast<uint64_t>(m)), "r"(bar), "r"(c0), "r"(c1)
      : "memory");
}
__device__ __forceinline__ void tma_load_3d(uint32_t dst, const CUtensorMap* m, uint32_t bar, int c0, int c1, int c2) {
  asm volatile(
      "cp.async.bulk.tensor.3d.shared::cluster.global.mbarrier::complete_tx::bytes [%0], [%1, {%3, %4, %5}], [%2];" ::"r"(dst),
      "l"(reinterpret_cast<uint64_t>(m)), "r"(bar), "r"(c0), "r"(c1), "r"(c2)
      : "memory");
}
__device__ __forceinline__ void tma_store_2d(const CUtensorMap* m, uint32_t src, int c0, int c1) {
  asm volatile("cp.async.bulk.tensor.2d.global.shared::cta.bulk_group [%0, {%2, %3}], [%1];" ::"l"(
                   reinterpret_cast<uint64_t>(m)),
               "r"(src), "r"(c0), "r"(c1)
               : "memory");
}
__device__ __forceinline__ void bulk_load(uint32_t dst, const void* src, uint32_t bytes, uint32_t bar) {
  asm volatile("cp.async.bulk.shared::cluster.global.mbarrier::complete_tx::bytes [%0], [%1], %2, [%3];" ::"r"(dst),
               "l"(src), "r"(bytes), "r"(bar)
               : "memory");
}
__device__ __forceinline__ void tma_load_2d_mc(uint32_t dst, const CUtensorMap* m, uint32_t bar, int c0, int c1,
                                               uint16_t mask) {
  asm volatile(
      "cp.async.bulk.tensor.2d.shared::cluster.global.mbarrier::complete_tx::bytes.multicast::cluster [%0], [%1, {%3, "
      "%4}], [%2], %5;" ::"r"(dst),
      "l"(reinterpret_cast<uint64_t>(m)), "r"(bar), "r"(c0), "r"(c1), "h"(mask)
      : "memory");
}
__device__ __forceinline__ void mbar_arrive_cluster_if(uint32_t bar, uint32_t cta, bool pred) {
  asm volatile(
      "{\n.reg .b32 ra;\n.reg .pred p;\nsetp.ne.b32 p, %2, 0;\n"
      "mapa.shared::cluster.u32 ra, %0, %1;\n"
      "@p mbarrier.arrive.shared::cluster.b64 _, [ra];\n}\n" ::"r"(bar),
      "r"(cta), "r"((uint32_t)pred)
      : "memory");
}
__device__ __forceinline__ uint64_t policy_evict_first() {
  uint64_t pol;
  asm volatile("createpolicy.fractional.L2::evict_first.b64 %0, 1.0;" : "=l"(pol));
  return pol;
}
__device__ __forceinline__ void tma_load_2d_hint(uint32_t dst, const CUtensorMap* m, uint32_t bar, int c0, int c1,
                                                 uint64_t pol) {
  asm volatile(
      "cp.async.bulk.tensor.2d.shared::cluster.global.mbarrier::complete_tx::bytes.L2::cache_hint [%0], [%1, {%3, %4}], "
      "[%2], %5;" ::"r"(dst),
      "l"(reinterpret_cast<uint64_t>(m)), "r"(bar), "r"(c0), "r"(c1), "l"(pol)
      : "memory");
}
__device__ __forceinline__ void tma_load_3d_hint(uint32_t dst, const CUtensorMap* m, uint32_t bar, int c0, int c1,
                                                 int c2, uint64_t pol) {
  asm volatile(
      "cp.async.bulk.tensor.3d.shared::cluster.global.mbarrier::complete_tx::bytes.L2::cache_hint [%0], [%1, {%3, %4, "
      "%5}], [%2], %6;" ::"r"(dst),
      "l"(reinterpret_cast<uint64_t>(m)), "r"(bar), "r"(c0), "r"(c1), "r"(c2), "l"(pol)
      : "memory");
}
__device__ __forceinline__ void bulk_load_hint(uint32_t dst, const void* src, uint32_t bytes, uint32_t bar, uint64_t pol) {
  asm volatile(
      "cp.async.bulk.shared::cluster.global.mbarrier::complete_tx::bytes.L2::cache_hint [%0], [%1], %2, [%3], %4;" ::"r"(dst),
      "l"(src), "r"(bytes), "r"(bar), "l"(pol)
      : "memory");
}
__device__ __forceinline__ void cnt_signal_release(int which, uint32_t n) {
  asm volatile("red.release.gpu.global.add.u32 [%0], %1;" ::"l"(g_cnt + which * 32), "r"(n) : "memory");
}
__device__ __forceinline__ bool cnt_wait(int which, uint32_t target, uint32_t spins = 0) {
  uint32_t v;
  while (true) {
    asm volatile("ld.acquire.gpu.global.u32 %0, [%1];" : "=r"(v) : "l"(g_cnt + which * 32) : "memory");
    if (v >= target || ++spins > (1u << 18)) break;
    __nanosleep(64);
  }
  asm volatile("fence.proxy.async.global;" ::: "memory");
  return v >= target;
}
__device__ __forceinline__ void tma_store_3d(const CUtensorMap* m, uint32_t src, int c0, int c1, int c2) {
  asm volatile("cp.async.bulk.tensor.3d.global.shared::cta.bulk_group [%0, {%2, %3, %4}], [%1];" ::"l"(
                   reinterpret_cast<uint64_t>(m)),
               "r"(src), "r"(c0), "r"(c1), "r"(c2)
               : "memory");
}
__device__ __forceinline__ void tma_store_commit() { asm volatile("cp.async.bulk.commit_group;" ::: "memory"); }
template <int N>
__device__ __forceinline__ void tma_store_wait_read() {
  asm volatile("cp.async.bulk.wait_group.read %0;" ::"n"(N) : "memory");
}
template <int N>
__device__ __forceinline__ void tma_store_wait() {
  asm volatile("cp.async.bulk.wait_group %0;" ::"n"(N) : "memory");
}
__device__ __forceinline__ void wgmma_fence() { asm volatile("wgmma.fence.sync.aligned;" ::: "memory"); }
__device__ __forceinline__ void wgmma_commit() { asm volatile("wgmma.commit_group.sync.aligned;" ::: "memory"); }
template <int N>
__device__ __forceinline__ void wgmma_wait() {
  asm volatile("wgmma.wait_group.sync.aligned %0;" ::"n"(N) : "memory");
}
template <int R>
__device__ __forceinline__ void reg_alloc() { asm volatile("setmaxnreg.inc.sync.aligned.u32 %0;" ::"n"(R)); }
template <int R>
__device__ __forceinline__ void reg_dealloc() { asm volatile("setmaxnreg.dec.sync.aligned.u32 %0;" ::"n"(R)); }

__device__ __forceinline__ void stmatrix_x4(uint32_t addr, uint32_t r0, uint32_t r1, uint32_t r2, uint32_t r3) {
  asm volatile("stmatrix.sync.aligned.m8n8.x4.shared.b16 [%0], {%1, %2, %3, %4};" ::"r"(addr), "r"(r0), "r"(r1),
               "r"(r2), "r"(r3)
               : "memory");
}
__device__ __forceinline__ uint32_t pack_bf16(float lo, float hi) {
  uint32_t r;
  asm("cvt.rn.bf16x2.f32 %0, %1, %2;" : "=r"(r) : "f"(hi), "f"(lo));
  return r;
}
__device__ __forceinline__ float bf16_round(float x) { return __bfloat162float(__float2bfloat16_rn(x)); }
__device__ __forceinline__ float bf_lo(uint32_t v) { return __uint_as_float(v << 16); }
__device__ __forceinline__ float bf_hi(uint32_t v) { return __uint_as_float(v & 0xffff0000u); }
__device__ __forceinline__ uint4 lds128(uint32_t a) {
  uint4 v;
  asm volatile("ld.shared.v4.u32 {%0, %1, %2, %3}, [%4];" : "=r"(v.x), "=r"(v.y), "=r"(v.z), "=r"(v.w) : "r"(a));
  return v;
}
__device__ __forceinline__ void sts128(uint32_t a, uint4 v) {
  asm volatile("st.shared.v4.u32 [%0], {%1, %2, %3, %4};" ::"r"(a), "r"(v.x), "r"(v.y), "r"(v.z), "r"(v.w) : "memory");
}
__device__ __forceinline__ uint32_t mul_bf2(uint32_t a, uint32_t b) {
  uint32_t r;
  asm("mul.rn.bf16x2 %0, %1, %2;" : "=r"(r) : "r"(a), "r"(b));
  return r;
}
__device__ __forceinline__ float ex2(float x) {
  float y;
  asm("ex2.approx.ftz.f32 %0, %1;" : "=f"(y) : "f"(x));
  return y;
}
__device__ __forceinline__ float rcp(float x) {
  float y;
  asm("rcp.approx.ftz.f32 %0, %1;" : "=f"(y) : "f"(x));
  return y;
}
template <int N>
__device__ __forceinline__ void fence_regs(float (&r)[N]) {
#pragma unroll
  for (int i = 0; i < N; i++) asm volatile("" : "+f"(r[i])::"memory");
}

template <int N>
__device__ __forceinline__ void undef_regs(float (&r)[N]) {
#pragma unroll
  for (int i = 0; i < N; i++) asm volatile("" : "=f"(r[i]));
}
template <int N>
__device__ __forceinline__ void fence_regs_u(uint32_t (&r)[N]) {
#pragma unroll
  for (int i = 0; i < N; i++) asm volatile("" : "+r"(r[i])::"memory");
}

constexpr uint64_t DESC_SW128 = 1ull << 62;
__device__ __forceinline__ uint64_t make_desc(uint32_t addr, uint32_t lbo_bytes, uint32_t sbo_bytes, uint64_t swz) {
  return (uint64_t)((addr & 0x3FFFF) >> 4) | ((uint64_t)((lbo_bytes & 0x3FFFF) >> 4) << 16) |
         ((uint64_t)((sbo_bytes & 0x3FFFF) >> 4) << 32) | swz;
}

__device__ __forceinline__ uint64_t desc_add(uint64_t d, uint32_t off16) {
  return (d & 0xFFFFFFFF00000000ull) | (uint64_t)((uint32_t)d + off16);
}

__device__ __forceinline__ void wgmma_m64n256_ss_tb(float (&d)[128], uint64_t da, uint64_t db, int sd) {
  asm volatile(
    "{\n.reg .pred p;\nsetp.ne.b32 p, %130, 0;\n"
    "wgmma.mma_async.sync.aligned.m64n256k16.f32.bf16.bf16 "
    "{%0, %1, %2, %3, %4, %5, %6, %7, %8, %9, %10, %11, %12, %13, %14, %15, %16, %17, %18, %19, %20, %21, %22, %23, %24, %25, %26, %27, %28, %29, %30, %31, %32, %33, %34, %35, %36, %37, %38, %39, %40, %41, %42, %43, %44, %45, %46, %47, %48, %49, %50, %51, %52, %53, %54, %55, %56, %57, %58, %59, %60, %61, %62, %63, %64, %65, %66, %67, %68, %69, %70, %71, %72, %73, %74, %75, %76, %77, %78, %79, %80, %81, %82, %83, %84, %85, %86, %87, %88, %89, %90, %91, %92, %93, %94, %95, %96, %97, %98, %99, %100, %101, %102, %103, %104, %105, %106, %107, %108, %109, %110, %111, %112, %113, %114, %115, %116, %117, %118, %119, %120, %121, %122, %123, %124, %125, %126, %127}, %128, %129, p, 1, 1, 0, 1;\n}\n"
    : "+f"(d[0]), "+f"(d[1]), "+f"(d[2]), "+f"(d[3]), "+f"(d[4]), "+f"(d[5]), "+f"(d[6]), "+f"(d[7]), "+f"(d[8]), "+f"(d[9]), "+f"(d[10]), "+f"(d[11]), "+f"(d[12]), "+f"(d[13]), "+f"(d[14]), "+f"(d[15]), "+f"(d[16]), "+f"(d[17]), "+f"(d[18]), "+f"(d[19]), "+f"(d[20]), "+f"(d[21]), "+f"(d[22]), "+f"(d[23]), "+f"(d[24]), "+f"(d[25]), "+f"(d[26]), "+f"(d[27]), "+f"(d[28]), "+f"(d[29]), "+f"(d[30]), "+f"(d[31]), "+f"(d[32]), "+f"(d[33]), "+f"(d[34]), "+f"(d[35]), "+f"(d[36]), "+f"(d[37]), "+f"(d[38]), "+f"(d[39]), "+f"(d[40]), "+f"(d[41]), "+f"(d[42]), "+f"(d[43]), "+f"(d[44]), "+f"(d[45]), "+f"(d[46]), "+f"(d[47]), "+f"(d[48]), "+f"(d[49]), "+f"(d[50]), "+f"(d[51]), "+f"(d[52]), "+f"(d[53]), "+f"(d[54]), "+f"(d[55]), "+f"(d[56]), "+f"(d[57]), "+f"(d[58]), "+f"(d[59]), "+f"(d[60]), "+f"(d[61]), "+f"(d[62]), "+f"(d[63]), "+f"(d[64]), "+f"(d[65]), "+f"(d[66]), "+f"(d[67]), "+f"(d[68]), "+f"(d[69]), "+f"(d[70]), "+f"(d[71]), "+f"(d[72]), "+f"(d[73]), "+f"(d[74]), "+f"(d[75]), "+f"(d[76]), "+f"(d[77]), "+f"(d[78]), "+f"(d[79]), "+f"(d[80]), "+f"(d[81]), "+f"(d[82]), "+f"(d[83]), "+f"(d[84]), "+f"(d[85]), "+f"(d[86]), "+f"(d[87]), "+f"(d[88]), "+f"(d[89]), "+f"(d[90]), "+f"(d[91]), "+f"(d[92]), "+f"(d[93]), "+f"(d[94]), "+f"(d[95]), "+f"(d[96]), "+f"(d[97]), "+f"(d[98]), "+f"(d[99]), "+f"(d[100]), "+f"(d[101]), "+f"(d[102]), "+f"(d[103]), "+f"(d[104]), "+f"(d[105]), "+f"(d[106]), "+f"(d[107]), "+f"(d[108]), "+f"(d[109]), "+f"(d[110]), "+f"(d[111]), "+f"(d[112]), "+f"(d[113]), "+f"(d[114]), "+f"(d[115]), "+f"(d[116]), "+f"(d[117]), "+f"(d[118]), "+f"(d[119]), "+f"(d[120]), "+f"(d[121]), "+f"(d[122]), "+f"(d[123]), "+f"(d[124]), "+f"(d[125]), "+f"(d[126]), "+f"(d[127])
    : "l"(da), "l"(db), "r"(sd));
}

__device__ __forceinline__ void wgmma_m64n128_ss(float (&d)[64], uint64_t da, uint64_t db, int sd) {
  asm volatile(
    "{\n.reg .pred p;\nsetp.ne.b32 p, %66, 0;\n"
    "wgmma.mma_async.sync.aligned.m64n128k16.f32.bf16.bf16 "
    "{%0, %1, %2, %3, %4, %5, %6, %7, %8, %9, %10, %11, %12, %13, %14, %15, %16, %17, %18, %19, %20, %21, %22, %23, %24, %25, %26, %27, %28, %29, %30, %31, %32, %33, %34, %35, %36, %37, %38, %39, %40, %41, %42, %43, %44, %45, %46, %47, %48, %49, %50, %51, %52, %53, %54, %55, %56, %57, %58, %59, %60, %61, %62, %63}, %64, %65, p, 1, 1, 0, 0;\n}\n"
    : "+f"(d[0]), "+f"(d[1]), "+f"(d[2]), "+f"(d[3]), "+f"(d[4]), "+f"(d[5]), "+f"(d[6]), "+f"(d[7]), "+f"(d[8]), "+f"(d[9]), "+f"(d[10]), "+f"(d[11]), "+f"(d[12]), "+f"(d[13]), "+f"(d[14]), "+f"(d[15]), "+f"(d[16]), "+f"(d[17]), "+f"(d[18]), "+f"(d[19]), "+f"(d[20]), "+f"(d[21]), "+f"(d[22]), "+f"(d[23]), "+f"(d[24]), "+f"(d[25]), "+f"(d[26]), "+f"(d[27]), "+f"(d[28]), "+f"(d[29]), "+f"(d[30]), "+f"(d[31]), "+f"(d[32]), "+f"(d[33]), "+f"(d[34]), "+f"(d[35]), "+f"(d[36]), "+f"(d[37]), "+f"(d[38]), "+f"(d[39]), "+f"(d[40]), "+f"(d[41]), "+f"(d[42]), "+f"(d[43]), "+f"(d[44]), "+f"(d[45]), "+f"(d[46]), "+f"(d[47]), "+f"(d[48]), "+f"(d[49]), "+f"(d[50]), "+f"(d[51]), "+f"(d[52]), "+f"(d[53]), "+f"(d[54]), "+f"(d[55]), "+f"(d[56]), "+f"(d[57]), "+f"(d[58]), "+f"(d[59]), "+f"(d[60]), "+f"(d[61]), "+f"(d[62]), "+f"(d[63])
    : "l"(da), "l"(db), "r"(sd));
}

__device__ __forceinline__ void wgmma_m64n128_ss_tb(float (&d)[64], uint64_t da, uint64_t db, int sd) {
  asm volatile(
    "{\n.reg .pred p;\nsetp.ne.b32 p, %66, 0;\n"
    "wgmma.mma_async.sync.aligned.m64n128k16.f32.bf16.bf16 "
    "{%0, %1, %2, %3, %4, %5, %6, %7, %8, %9, %10, %11, %12, %13, %14, %15, %16, %17, %18, %19, %20, %21, %22, %23, %24, %25, %26, %27, %28, %29, %30, %31, %32, %33, %34, %35, %36, %37, %38, %39, %40, %41, %42, %43, %44, %45, %46, %47, %48, %49, %50, %51, %52, %53, %54, %55, %56, %57, %58, %59, %60, %61, %62, %63}, %64, %65, p, 1, 1, 0, 1;\n}\n"
    : "+f"(d[0]), "+f"(d[1]), "+f"(d[2]), "+f"(d[3]), "+f"(d[4]), "+f"(d[5]), "+f"(d[6]), "+f"(d[7]), "+f"(d[8]), "+f"(d[9]), "+f"(d[10]), "+f"(d[11]), "+f"(d[12]), "+f"(d[13]), "+f"(d[14]), "+f"(d[15]), "+f"(d[16]), "+f"(d[17]), "+f"(d[18]), "+f"(d[19]), "+f"(d[20]), "+f"(d[21]), "+f"(d[22]), "+f"(d[23]), "+f"(d[24]), "+f"(d[25]), "+f"(d[26]), "+f"(d[27]), "+f"(d[28]), "+f"(d[29]), "+f"(d[30]), "+f"(d[31]), "+f"(d[32]), "+f"(d[33]), "+f"(d[34]), "+f"(d[35]), "+f"(d[36]), "+f"(d[37]), "+f"(d[38]), "+f"(d[39]), "+f"(d[40]), "+f"(d[41]), "+f"(d[42]), "+f"(d[43]), "+f"(d[44]), "+f"(d[45]), "+f"(d[46]), "+f"(d[47]), "+f"(d[48]), "+f"(d[49]), "+f"(d[50]), "+f"(d[51]), "+f"(d[52]), "+f"(d[53]), "+f"(d[54]), "+f"(d[55]), "+f"(d[56]), "+f"(d[57]), "+f"(d[58]), "+f"(d[59]), "+f"(d[60]), "+f"(d[61]), "+f"(d[62]), "+f"(d[63])
    : "l"(da), "l"(db), "r"(sd));
}

__device__ __forceinline__ void wgmma_m64n128_rs_tb(float* d, uint32_t a0, uint32_t a1, uint32_t a2, uint32_t a3, uint64_t db, int sd) {
  asm volatile(
    "{\n.reg .pred p;\nsetp.ne.b32 p, %69, 0;\n"
    "wgmma.mma_async.sync.aligned.m64n128k16.f32.bf16.bf16 "
    "{%0, %1, %2, %3, %4, %5, %6, %7, %8, %9, %10, %11, %12, %13, %14, %15, %16, %17, %18, %19, %20, %21, %22, %23, %24, %25, %26, %27, %28, %29, %30, %31, %32, %33, %34, %35, %36, %37, %38, %39, %40, %41, %42, %43, %44, %45, %46, %47, %48, %49, %50, %51, %52, %53, %54, %55, %56, %57, %58, %59, %60, %61, %62, %63}, {%64, %65, %66, %67}, %68, p, 1, 1, 1;\n}\n"
    : "+f"(d[0]), "+f"(d[1]), "+f"(d[2]), "+f"(d[3]), "+f"(d[4]), "+f"(d[5]), "+f"(d[6]), "+f"(d[7]), "+f"(d[8]), "+f"(d[9]), "+f"(d[10]), "+f"(d[11]), "+f"(d[12]), "+f"(d[13]), "+f"(d[14]), "+f"(d[15]), "+f"(d[16]), "+f"(d[17]), "+f"(d[18]), "+f"(d[19]), "+f"(d[20]), "+f"(d[21]), "+f"(d[22]), "+f"(d[23]), "+f"(d[24]), "+f"(d[25]), "+f"(d[26]), "+f"(d[27]), "+f"(d[28]), "+f"(d[29]), "+f"(d[30]), "+f"(d[31]), "+f"(d[32]), "+f"(d[33]), "+f"(d[34]), "+f"(d[35]), "+f"(d[36]), "+f"(d[37]), "+f"(d[38]), "+f"(d[39]), "+f"(d[40]), "+f"(d[41]), "+f"(d[42]), "+f"(d[43]), "+f"(d[44]), "+f"(d[45]), "+f"(d[46]), "+f"(d[47]), "+f"(d[48]), "+f"(d[49]), "+f"(d[50]), "+f"(d[51]), "+f"(d[52]), "+f"(d[53]), "+f"(d[54]), "+f"(d[55]), "+f"(d[56]), "+f"(d[57]), "+f"(d[58]), "+f"(d[59]), "+f"(d[60]), "+f"(d[61]), "+f"(d[62]), "+f"(d[63])
    : "r"(a0), "r"(a1), "r"(a2), "r"(a3), "l"(db), "r"(sd));
}

__device__ __forceinline__ void wgmma_m64n64_rs_tb(float (&d)[32], const uint32_t (&a)[4], uint64_t db, int sd) {
  asm volatile(
    "{\n.reg .pred p;\nsetp.ne.b32 p, %37, 0;\n"
    "wgmma.mma_async.sync.aligned.m64n64k16.f32.bf16.bf16 "
    "{%0, %1, %2, %3, %4, %5, %6, %7, %8, %9, %10, %11, %12, %13, %14, %15, %16, %17, %18, %19, %20, %21, %22, %23, %24, %25, %26, %27, %28, %29, %30, %31}, {%32, %33, %34, %35}, %36, p, 1, 1, 1;\n}\n"
    : "+f"(d[0]), "+f"(d[1]), "+f"(d[2]), "+f"(d[3]), "+f"(d[4]), "+f"(d[5]), "+f"(d[6]), "+f"(d[7]), "+f"(d[8]), "+f"(d[9]), "+f"(d[10]), "+f"(d[11]), "+f"(d[12]), "+f"(d[13]), "+f"(d[14]), "+f"(d[15]), "+f"(d[16]), "+f"(d[17]), "+f"(d[18]), "+f"(d[19]), "+f"(d[20]), "+f"(d[21]), "+f"(d[22]), "+f"(d[23]), "+f"(d[24]), "+f"(d[25]), "+f"(d[26]), "+f"(d[27]), "+f"(d[28]), "+f"(d[29]), "+f"(d[30]), "+f"(d[31])
    : "r"(a[0]), "r"(a[1]), "r"(a[2]), "r"(a[3]), "l"(db), "r"(sd));
}

__device__ __forceinline__ void wgmma_m64n32_rs_tb(float (&d)[16], const uint32_t (&a)[4], uint64_t db, int sd) {
  asm volatile(
    "{\n.reg .pred p;\nsetp.ne.b32 p, %21, 0;\n"
    "wgmma.mma_async.sync.aligned.m64n32k16.f32.bf16.bf16 "
    "{%0, %1, %2, %3, %4, %5, %6, %7, %8, %9, %10, %11, %12, %13, %14, %15}, {%16, %17, %18, %19}, %20, p, 1, 1, 1;\n}\n"
    : "+f"(d[0]), "+f"(d[1]), "+f"(d[2]), "+f"(d[3]), "+f"(d[4]), "+f"(d[5]), "+f"(d[6]), "+f"(d[7]), "+f"(d[8]), "+f"(d[9]), "+f"(d[10]), "+f"(d[11]), "+f"(d[12]), "+f"(d[13]), "+f"(d[14]), "+f"(d[15])
    : "r"(a[0]), "r"(a[1]), "r"(a[2]), "r"(a[3]), "l"(db), "r"(sd));
}

constexpr int G_STAGES = 4;
constexpr int G_A_BYTES = 128 * 64 * 2;
constexpr int G_B_BYTES = 256 * 64 * 2;
constexpr int G_STAGE_BYTES = G_A_BYTES + G_B_BYTES;
constexpr int G_STG_OFF = G_STAGES * G_STAGE_BYTES;
constexpr int BAR_OFF = G_STG_OFF + 32768 + 2048;
constexpr int SMEM_BYTES = BAR_OFF + 1024;
constexpr int B_GFULL = 0, B_GEMPTY = 32, B_SEEN = 64, B_PFULL = 224;
constexpr int B_KFULL = 80, B_KEMPTY = 96, B_VFULL = 112, B_VEMPTY = 128, B_QFULL = 144, B_QEMPTY = 160,
              B_QDONE = 184;
constexpr int B_CFULL = 192;
constexpr int B_OFREE = 256, B_OFULL = 272, B_OEMPTY = 320, B_OY = 368, B_OY2 = 384, B_OE = 768;
constexpr int B_DEAL = 312, B_DEAL2 = 360, B_LIST = 640, B_PAIR = 504;
constexpr int B_SFULL = 392, B_SFREE = 424, B_PEND = 456, B_SCMD = 512;

#define PHASE_PROLOGUE                                                                \
  uint32_t tid, rt_zero;                                                              \
  asm volatile("mov.u32 %0, %%tid.x;" : "=r"(tid));                                   \
  asm volatile("mov.u32 %0, %%nctaid.y;" : "=r"(rt_zero));                            \
  asm volatile("" : "+r"(smem0));                                                     \
  rt_zero = __shfl_sync(0xffffffffu, rt_zero >> 8, 0);   \
  const uint32_t sbase = __shfl_sync(0xffffffffu, smem0, 0);                          \
  const uint32_t bar = sbase + BAR_OFF;                                               \
  const int wg = __shfl_sync(0xffffffffu, tid >> 7, 0);                               \
  const int warp = (tid >> 5) & 3, lane = tid & 31, wtid = tid & 127;                 \
  (void)rt_zero; (void)bar; (void)warp; (void)lane; (void)wtid;

enum { ST_END = 0, ST_BOX1, ST_BOX2, ST_BOX2Q, ST_BOX2L };
__device__ __forceinline__ void st_post(uint32_t bar, int wg, int wtid, uint32_t n, int kind, const void* dst,
                                        uint32_t src, int c0, int c1, int sig, uint32_t lazy = 0) {
  if (wtid == 0) {
    const uint32_t c = bar + B_SCMD + wg * 64 + (n & 1) * 32;
    const uint64_t d = reinterpret_cast<uint64_t>(dst);
    sts128(c, make_uint4(kind, src, c0, c1));
    sts128(c + 16, make_uint4((uint32_t)d, (uint32_t)(d >> 32), sig, lazy));
  }
  fence_proxy_async();
  __syncwarp();
  mbar_arrive_if(bar + B_SFULL + wg * 16 + (n & 1) * 8, (wtid & 31) == 0);
}
__device__ __forceinline__ void st_wait(uint32_t bar, int wg, uint32_t n) {
  const uint32_t b = bar + B_SFREE + wg * 16 + (n & 1) * 8;
  if (!mbar_try(b, ~(n >> 1) & 1)) mbar_wait(b, ~(n >> 1) & 1);
}
__device__ __forceinline__ void note(uint32_t bar, uint32_t cnt) {
  asm volatile("red.release.cta.shared.add.u32 [%0], 1;" ::"r"(bar + B_PEND + 4 * cnt) : "memory");
}
#define LAZY_NS 250
#define DEAL_NS 400
#define DEAL_NS2 1250
constexpr uint32_t C_NONE = 0x10000;
__device__ __forceinline__ void deal(uint32_t bar, uint32_t r, uint32_t t, uint32_t own) {
  uint64_t p;
  uint32_t spins = 0;
  while (true) {
    asm volatile("ld.relaxed.gpu.global.u64 %0, [%1];" : "=l"(p) : "l"(g_slot + 127 - r) : "memory");
    if (p || ++spins > (1u << 18)) break;
    __nanosleep(100);
  }
  const uint32_t pc = (uint32_t)p;
  int dt = (uint32_t)(p >> 32) - t;
  if (r >= 64) {
    sts128(bar + B_LIST, make_uint4(-dt > DEAL_NS2 ? C_NONE : own - 16, -dt > DEAL_NS ? C_NONE : own, C_NONE, C_NONE));
    mbar_arrive(bar + B_DEAL);
    dt = 0;
  }
  sts128(bar + B_LIST + 16, make_uint4(dt > DEAL_NS ? pc : C_NONE, dt > DEAL_NS2 ? pc - 16 : C_NONE, C_NONE, C_NONE));
  mbar_arrive(bar + B_DEAL2);
}
__device__ __forceinline__ void store_agent(uint32_t bar, int wg, uint32_t last_ch) {
  mbar_arrive(bar + B_SFREE + wg * 16);
  mbar_arrive(bar + B_SFREE + wg * 16 + 8);
  bool more = true;
  for (uint32_t n = 0;; n++) {
    mbar_wait_sleep(bar + B_SFULL + wg * 16 + (n & 1) * 8, (n >> 1) & 1);
    const uint4 c = lds128(bar + B_SCMD + wg * 64 + (n & 1) * 32);
    const uint4 d = lds128(bar + B_SCMD + wg * 64 + (n & 1) * 32 + 16);
    if (c.x == ST_END) break;
    uint32_t t;
    asm volatile("mov.u32 %0, %%globaltimer_lo;" : "=r"(t));
    for (uint32_t t1 = t; d.w && t1 - t < (2 * d.w + wg) * LAZY_NS;) {
      __nanosleep(200);
      asm volatile("mov.u32 %0, %%globaltimer_lo;" : "=r"(t1));
    }
    const CUtensorMap* dst = reinterpret_cast<const CUtensorMap*>((uint64_t)d.x | ((uint64_t)d.y << 32));
    tma_store_2d(dst, c.y, c.z, c.w);
    if (c.x >= ST_BOX2) tma_store_2d(dst, c.y + 8192, c.z + 64, c.w);
    tma_store_commit();
    uint32_t r = 0;
    if (c.x == ST_BOX2L && last_ch) {
      mbar_expect_tx(bar + B_PAIR, 4);
      asm volatile(
          "{\n.reg .b32 ra;\nmapa.shared::cluster.u32 ra, %0, %1;\n"
          "st.async.weak.shared::cluster.mbarrier::complete_tx::bytes.u32 [ra + 224], %2, [ra];\n}\n" ::"r"(bar + B_PAIR),
          "r"(~blockIdx.x & 1), "r"(t)
          : "memory");
    }
    tma_store_wait_read<0>();
    mbar_arrive(bar + B_SFREE + wg * 16 + (n & 1) * 8);
    if (c.x == ST_BOX2L) mbar_arrive(bar + B_OFREE + 8 * wg);
    if (c.x == ST_BOX2L && last_ch) {
      uint32_t tp;
      mbar_wait_sleep(bar + B_PAIR, 0);
      r = atomicAdd(g_cnt + CNT_RANK * 32, 1u) & 127;
      asm volatile("ld.shared.u32 %0, [%1];" : "=r"(tp) : "r"(bar + B_PAIR + 224) : "memory");
      if ((int)(tp - t) > 0) t = tp;
      asm volatile("st.relaxed.gpu.global.u64 [%0], %1;" ::"l"(g_slot + r), "l"(((uint64_t)t << 32) | last_ch) : "memory");
      if (r < 64) {
        sts128(bar + B_LIST, make_uint4(last_ch - 16, last_ch, C_NONE, C_NONE));
        mbar_arrive(bar + B_DEAL);
      }
    }
    if ((int)d.z >= 0) {
      tma_store_wait<0>();
      if (d.z == 0) { TD(6) }
      asm volatile("fence.proxy.async.global;" ::: "memory");
      if (c.x == ST_BOX2Q) mbar_arrive(bar + B_QDONE);
      else note(bar, d.z);
      if (c.x == ST_BOX2L) {
        note(bar, CNT_DONE);
        more = false;
        if (last_ch) deal(bar, r, t, last_ch);
      }
    }
  }
  if (more) note(bar, CNT_DONE);
}

struct Maps {
  const bf16 *shift_k, *x, *gate_w, *ssm_k, *ssm_D;
  uint8_t id[128][4];
  CUtensorMap a[2];
  CUtensorMap b[3];
  CUtensorMap c[3];
  CUtensorMap bk, bv;
  CUtensorMap q, k, v, o;
  CUtensorMap oa, ob, oc;
  CUtensorMap y, xs;
  CUtensorMap cu, ch;
};

constexpr int P_SLOT = 67 * 128, P_V = 35 * 128, P_TAPS = 2 * P_SLOT;
__device__ __forceinline__ void ldsm4t(uint32_t (&r)[4], uint32_t a) {
  asm volatile("ldmatrix.sync.aligned.m8n8.x4.trans.shared.b16 {%0, %1, %2, %3}, [%4];"
               : "=r"(r[0]), "=r"(r[1]), "=r"(r[2]), "=r"(r[3])
               : "r"(a));
}
__device__ __forceinline__ uint32_t fma_bf2(uint32_t a, uint32_t b, uint32_t c) {
  uint32_t r;
  asm("fma.rn.bf16x2 %0, %1, %2, %3;" : "=r"(r) : "r"(a), "r"(b), "r"(c));
  return r;
}
__device__ __forceinline__ void prep_agent(const Maps& maps, uint32_t sbase, int w, int lane) {
  const uint32_t bar = sbase + BAR_OFF, pb = bar + B_PFULL + w * 16;
  const int d0 = (blockIdx.x >> 3) * 64, t0 = (blockIdx.x & 7) * 256 + w * 128;
  mbar_wait_sleep(bar + B_GFULL + 8 * (G_STAGES - 1), 0);
#pragma unroll 1
  for (int i = -1; i < 4; i++) {
    GA(82 + 2 * i)
    if (i >= 0) mbar_wait_sleep(pb + (i & 1) * 8, i >> 1);
    GA(83 + 2 * i)
    const uint32_t so = sbase + G_STG_OFF + w * (P_TAPS + 512) + (i & 1) * P_SLOT;
    if (i < 3 && elect_one()) {
      const uint32_t b = pb + (~i & 1) * 8, dst = so + (i & 1 ? -P_SLOT : P_SLOT);
      mbar_expect_tx(b, i < 0 ? P_SLOT + 512 : P_SLOT);
      const uint64_t pol = policy_evict_first();
      tma_load_2d_hint(dst, &maps.bk, b, d0, t0 + 32 * i + 29, pol);
      tma_load_2d_hint(dst + P_V, &maps.bv, b, d0, t0 + 32 * i + 32, pol);
      if (i < 0) bulk_load(sbase + G_STG_OFF + P_TAPS, maps.shift_k + d0 * 4, 512, b);
    }
    if (i < 0) continue;
    uint32_t ak[4];
#pragma unroll
    for (int r = 0; r < 4; r++) {
      const uint32_t a = so / 128 + r + 4 * (lane & 6) + (((lane >> 2) ^ lane) & 6) + (lane & 1);
      ak[r] = a * 128 + (a & 7) * 16;
    }
    bf16* dst = g_kvT + (size_t)(d0 + (lane >> 2)) * S_LEN + t0 + ((lane & 3) + 4 * i) * 8;
#pragma unroll 1
    for (int cg = 0; cg < 128; cg += 16) {
      uint32_t t01, t23, k[4][4], v[4];
      asm volatile("ld.shared.v2.u32 {%0, %1}, [%2];"
                   : "=r"(t01), "=r"(t23)
                   : "r"(sbase + G_STG_OFF + P_TAPS + cg * 4 + (lane >> 2) * 8));
#pragma unroll
      for (int r = 0; r < 4; r++) ldsm4t(k[r], ak[r] ^ cg);
      ldsm4t(v, (ak[3] ^ cg) + 4096);
      const uint32_t w0 = __byte_perm(t01, 0, 0x1010), w1 = __byte_perm(t01, 0, 0x3232);
      const uint32_t w2 = __byte_perm(t23, 0, 0x1010), w3 = __byte_perm(t23, 0, 0x3232);
#pragma unroll
      for (int j = 0; j < 4; j++)
        v[j] = mul_bf2(fma_bf2(k[3][j], w0, fma_bf2(k[2][j], w1, fma_bf2(k[1][j], w2, mul_bf2(k[0][j], w3)))), v[j]);
      const bool s1 = lane & 1, s2 = lane & 2;
      const uint32_t a0 = s1 ? v[1] : v[0], a1 = s1 ? v[0] : v[1], a2 = s1 ? v[3] : v[2], a3 = s1 ? v[2] : v[3];
      *reinterpret_cast<uint4*>(dst) = make_uint4(s2 ? a2 : a0, s2 ? a3 : a1, s2 ? a0 : a2, s2 ? a1 : a3);
      dst += 8 * S_LEN;
    }
    fence_proxy_async();
    __syncwarp();
  }
  GA(90)
  if (lane == 0) note(bar, CNT_PREP);
  __syncwarp();
  GA(91)
}

__device__ __forceinline__ void qkv_tile(const Maps& maps, int it, int& which, int& m_tile, int& n_tile) {
  const bool q = it == 0 || it >= 5;
  const int b = maps.id[blockIdx.x][it >= 5];
  which = q ? 0 : 2 - (it & 1);
  m_tile = b & 15;
  n_tile = (b >> 4) * 2 + ((0x19 >> it) & 1);
}

constexpr int G_NTILES = 6;
__device__ __forceinline__ void qkv_producer(const Maps& maps, uint32_t sbase, bool first) {
  const uint32_t bar = sbase + BAR_OFF;
  uint32_t stage = 0, phase = 0;
#pragma unroll 1
  for (int it = 0; it < (first ? 1 : G_NTILES); it++) {
    int which, m_tile, n_tile;
    qkv_tile(maps, it, which, m_tile, n_tile);
    const CUtensorMap* ma = &maps.a[which == 0 ? 0 : 1];
    const CUtensorMap* mb = &maps.b[which];
    const int nk = first ? G_STAGES : which == 0 ? 16 : 8;
#pragma unroll 1
    for (int kt = (it == 0 && !first) ? G_STAGES : 0; kt < nk; kt++) {
      if (!first) mbar_wait_sleep(bar + B_GEMPTY + 8 * stage, phase);
      const uint32_t fb = bar + B_GFULL + 8 * stage;
      const uint32_t sa = sbase + stage * G_STAGE_BYTES;
      mbar_expect_tx(fb, G_STAGE_BYTES);
      tma_load_2d(sa, ma, fb, kt * 64, m_tile * 128);
      tma_load_3d(sa + G_A_BYTES, mb, fb, 0, kt * 64, n_tile * 4);
      if (++stage == G_STAGES) { stage = 0; phase ^= 1; }
      {
        const int b = maps.id[blockIdx.x][1];
        if (it == 2 && kt == (b & 7)) {
          for (int i = 0; i < 2; i++)
            asm volatile("cp.async.bulk.prefetch.tensor.2d.L2.global.tile [%0, {%1, %2}];" ::"l"(&maps.a[0]),
                         "r"((b >> 4) * 128 + i * 64), "r"((b & 15) * 128)
                         : "memory");
          asm volatile("cp.async.bulk.prefetch.tensor.3d.L2.global.tile [%0, {%1, %2, %3}];" ::"l"(&maps.b[1 + ((b >> 3) & 1)]),
                       "r"(0), "r"((b & 7) * 64), "r"((b >> 4) * 8 + 4)
                       : "memory");
        }
        if (it == 3 && kt == (b & 7))
          asm volatile("cp.async.bulk.prefetch.tensor.3d.L2.global.tile [%0, {%1, %2, %3}];" ::"l"(&maps.b[0]), "r"(0),
                       "r"((b & 15) * 64), "r"((b >> 4) * 8)
                       : "memory");
      }
    }
  }
}

__device__ __forceinline__ uint32_t seen_bar(uint32_t item) { return B_SEEN + ((0x700800u >> (8 * item)) & 255); }
__device__ __noinline__ void publisher(uint32_t bar, int lane, uint32_t nsrc, uint32_t item, uint32_t mine) {
  uint32_t done = 0, tot = 0;
#pragma unroll 1
  for (uint32_t spins = 0; (done < nsrc || item < 3) && spins < (1u << 20); spins++) {
    const uint32_t cnt = item ? CNT_CTX - 1 + item : CNT_KV + 1;
    if (item < 3 && __shfl_sync(0xffffffffu, tot, cnt) >= mine) {
      uint32_t v;
      asm volatile("ld.acquire.gpu.global.u32 %0, [%1];" : "=r"(v) : "l"(g_cnt + (lane ? cnt : CNT_PREP) * 32) : "memory");
      if (__all_sync(0xffffffffu, v >= (lane ? 512 : 260))) {
        asm volatile("fence.proxy.async.global;" ::: "memory");
        mbar_arrive_if(bar + seen_bar(item), lane == 0);
        item++;
      }
    }
    uint32_t v = 0;
    if (lane < CNT_N)
      asm volatile("atom.acquire.cta.shared.exch.b32 %0, [%1], 0;" : "=r"(v) : "r"(bar + B_PEND + 4 * lane) : "memory");
    done += __shfl_sync(0xffffffffu, v, CNT_DONE);
    if (lane == CNT_DONE) v = 0;
    if (done == nsrc && lane < CNT_DONE) {
      uint32_t w;
      asm volatile("atom.acquire.cta.shared.exch.b32 %0, [%1], 0;" : "=r"(w) : "r"(bar + B_PEND + 4 * lane) : "memory");
      v += w;
    }
    if (v && lane == 0) { TD(0) }
    if (v) cnt_signal_release(lane, v);
    tot += v;
    if (v && lane == 0) { TD(1) }
    if (!__any_sync(0xffffffffu, v != 0)) __nanosleep(item == 1 ? 1000 : 200);
  }
  __threadfence();
  __syncwarp();
}

__device__ __forceinline__ void gate_rows(const Maps& maps, uint32_t sbase, int w48, int w12, int lane) {
  const uint32_t buf = sbase + w12 * 16384, gb = sbase + BAR_OFF + 768 + w12 * 16;
  if (lane == 0) {
    mbar_init(gb, 1);
    mbar_init(gb + 8, 1);
    fence_barrier_init();
    for (int i = 0; i < 2; i++) {
      mbar_expect_tx(gb + 8 * i, 8192);
      bulk_load(buf + i * 8192, maps.x + (size_t)(w48 + 48 * i) * 4 * DM, 8192, gb + 8 * i);
    }
  }
  __syncwarp();
  uint4 wv[4];
#pragma unroll
  for (int i = 0; i < 4; i++) wv[i] = __ldg(reinterpret_cast<const uint4*>(maps.gate_w + (i * 32 + lane) * 8));
  int it = 0;
#pragma unroll 1
  for (int row = w48 * 4; row < S_LEN; row += 48 * 4, it++) {
    mbar_wait(gb + 8 * (it & 1), (it >> 1) & 1);
    uint4 xv[4][4];
#pragma unroll
    for (int r = 0; r < 4; r++)
#pragma unroll
      for (int i = 0; i < 4; i++) xv[r][i] = lds128(buf + (it & 1) * 8192 + r * 2048 + (i * 32 + lane) * 16);
    float d[2][4];
#pragma unroll
    for (int pr = 0; pr < 2; pr++) {
      d[pr][0] = d[pr][1] = d[pr][2] = d[pr][3] = 0.f;
      auto acc = [&](uint32_t a0, uint32_t a2, uint32_t b0, uint32_t b2, uint32_t w0, uint32_t w2) {
        asm volatile(
            "mma.sync.aligned.m16n8k16.row.col.f32.bf16.bf16.f32 {%0, %1, %2, %3}, {%4, %5, %6, %7}, {%8, %8}, "
            "{%0, %1, %2, %3};"
            : "+f"(d[pr][0]), "+f"(d[pr][1]), "+f"(d[pr][2]), "+f"(d[pr][3])
            : "r"(mul_bf2(a0, w0)), "r"(mul_bf2(b0, w0)), "r"(mul_bf2(a2, w2)), "r"(mul_bf2(b2, w2)), "r"(0x3f803f80u));
      };
#pragma unroll
      for (int i = 0; i < 4; i++) {
        acc(xv[2 * pr][i].x, xv[2 * pr][i].y, xv[2 * pr + 1][i].x, xv[2 * pr + 1][i].y, wv[i].x, wv[i].y);
        acc(xv[2 * pr][i].z, xv[2 * pr][i].w, xv[2 * pr + 1][i].z, xv[2 * pr + 1][i].w, wv[i].z, wv[i].w);
      }
    }
    float sum = (lane & 2) ? ((lane & 1) ? d[1][2] : d[1][0]) : ((lane & 1) ? d[0][2] : d[0][0]);
#pragma unroll
    for (int off = 16; off >= 4; off >>= 1) sum += __shfl_xor_sync(0xffffffffu, sum, off);
    if (lane < 4) g_gate[row + lane] = bf16_round(rcp(1.0f + __expf(-bf16_round(sum))));
    if (lane == 0 && row + 2 * 48 * 4 < S_LEN) {
      mbar_expect_tx(gb + 8 * (it & 1), 8192);
      bulk_load(buf + (it & 1) * 8192, maps.x + (size_t)(row + 2 * 48 * 4) * DM, 8192, gb + 8 * (it & 1));
    }
  }
}

constexpr float Q_SCALE = 0.08838834764831845f * 1.4426950408889634f;
__device__ __forceinline__ uint32_t qkv_consumer(const Maps& maps, uint32_t smem0, bool fused, float (&rest)[64]) {
  PHASE_PROLOGUE
  constexpr int NTILES = G_NTILES;
  float acc[128];
  uint32_t stage = 0, phase = 0;
  const uint32_t stg = sbase + G_STG_OFF + wg * 18432;
  const int st_row = warp * 16 + (lane & 7) + ((lane >> 3) & 1) * 8;
  const int st_cb = lane >> 4;
  uint32_t pend[64];
  const CUtensorMap* pend_map = nullptr;
  int pend_c0 = 0, pend_c1 = 0;
  uint32_t sn = 0;
  auto put_box = [&](uint32_t buf, const uint32_t* v) {
#pragma unroll
    for (int jp = 0; jp < 4; jp++) {
      const int chunk = jp * 2 + st_cb;
      const uint32_t addr = buf + st_row * 128 + ((chunk ^ (st_row & 7)) << 4);
      stmatrix_x4(addr, v[jp * 4], v[jp * 4 + 1], v[jp * 4 + 2], v[jp * 4 + 3]);
    }
  };
  GT(gti++)
#pragma unroll 1
  for (int it = 0; it <= NTILES; it++) {
    int which, m_tile, n_tile;
    qkv_tile(maps, it, which, m_tile, n_tile);
    const int nk = (which == 0 && it < NTILES) ? 16 : 8;
    uint32_t prev_stage = 0;
#pragma unroll 1
    for (int kt = 0; kt < nk; kt++) {
      if (it < NTILES) {
        mbar_wait((bar + B_GFULL) + 8 * stage, phase);
        GT(gti++)
        const uint64_t da0 = make_desc(sbase + stage * G_STAGE_BYTES + wg * 8192, 16, 1024, DESC_SW128);
        const uint64_t db0 = make_desc(sbase + stage * G_STAGE_BYTES + G_A_BYTES, 8192, 1024, DESC_SW128);
        wgmma_fence();
#pragma unroll
        for (int kk = 0; kk < 4; kk++) {
          wgmma_m64n256_ss_tb(acc, desc_add(da0, kk * 2), desc_add(db0, kk * 128), (kt | kk) != 0);
        }
        wgmma_commit();
      }
      const uint32_t when = it == 0 ? 0 : it == 5 ? 0x922 << wg : wg ? 0xAA : 0x55;
      if ((when >> kt) & 1) {
        const int c = __popc(when & ~(~0u << kt));
        st_wait(bar, wg, sn - 2);
        const uint32_t buf = stg + (c & 1) * 8192;
        switch (c) {
          case 0: put_box(buf, pend); break;
          case 1: put_box(buf, pend + 16); break;
          case 2: put_box(buf, pend + 32); break;
          default: put_box(buf, pend + 48); break;
        }
        st_post(bar, wg, wtid, sn, ST_BOX1, pend_map, buf, pend_c0 + c * 64, pend_c1, (c == 3 && it > 1) ? CNT_KV + (it > 3) : -1);
        sn++;
      }
      if (it < NTILES) {
        wgmma_wait<1>();
        mbar_arrive_if((bar + B_GEMPTY) + 8 * prev_stage, wtid == 32 && kt > 0);
        prev_stage = stage;
        if (++stage == G_STAGES) { stage = 0; phase ^= 1; }
      }
    }
    wgmma_wait<0>();
    fence_regs(acc);
    if (it == NTILES) break;
    GT(gti++)
    mbar_arrive_if((bar + B_GEMPTY) + 8 * prev_stage, wtid == 32);
    if (it == NTILES - 1 && fused) break;
    if (which == 0) {
#pragma unroll
      for (int j = 0; j < 128; j++) acc[j] *= Q_SCALE;
    }
#pragma unroll
    for (int j = 0; j < 64; j++) pend[j] = pack_bf16(acc[2 * j], acc[2 * j + 1]);
    pend_map = &maps.c[which];
    pend_c0 = n_tile * 256;
    pend_c1 = m_tile * 128 + wg * 64;
  }
  mbar_wait(bar + B_GEMPTY, 1);
#pragma unroll
  for (int j = 0; j < 32; j++) pend[j] = pack_bf16(acc[2 * j] * Q_SCALE, acc[2 * j + 1] * Q_SCALE);
  put_box(sbase + wg * 8192, pend);
  put_box(sbase + 16384 + wg * 8192, pend + 16);
  fence_proxy_async();
#pragma unroll
  for (int j = 0; j < 64; j++) rest[j] = acc[64 + j];
  GT(gti++)
  return sn;
}

constexpr int A_TILE = 128 * 128 * 2;
constexpr int A_Q_OFF = 0;
constexpr int A_K_OFF = 2 * A_TILE;
constexpr int A_V_OFF = 4 * A_TILE;
constexpr int A_O_OFF = 6 * A_TILE;
constexpr int A_ITEMS = NH * (S_LEN / 128);

constexpr uint32_t A_ORDER = 0x3120, A_STEPS = 34;
__device__ __forceinline__ int item_m(uint32_t it) { return it & 15; }
__device__ __forceinline__ int item_h(uint32_t it) { return it >> 4; }

constexpr int C_V = 16384, C_MAT = 24576;
constexpr float C_ALPHA = 0.07874506561842957f;
__device__ __forceinline__ void sincos_turn(int p, float inv, float& c, float& s) {
  const float a = (float)p * (inv * 6.283185307179586f);
  asm("cos.approx.ftz.f32 %0, %1;" : "=f"(c) : "f"(a));
  asm("sin.approx.ftz.f32 %0, %1;" : "=f"(s) : "f"(a));
}

__device__ __forceinline__ uint32_t item_of(const Maps& maps, uint32_t r) {
  const uint32_t b = maps.id[blockIdx.x & 127][1];
  return (b >> 4) * 64 + ((A_ORDER >> (4 * r)) & 3) * 16 + ((b ^ ((r & 1) * 15)) & 15);
}

#define PACE 250
#define SPACE 0
#define LCHK 1
#define XMASK 3
#define XFIRST 4
#define C_SIDE 64
__device__ __forceinline__ uint32_t conv_first(const Maps& maps) {
  const uint32_t b = maps.id[blockIdx.x & 127][1];
  return (b >> 4) * 128 + ((b + 15) & 15);
}

__device__ __forceinline__ void conv_consumer(const Maps& maps, uint32_t smem0, uint32_t first, uint32_t step,
                                              uint32_t end, bool pp, bool dealt) {
  PHASE_PROLOGUE
  const uint32_t in_full = bar + B_CFULL + wg * 16;
  const uint32_t ca = sbase + (wg ? A_V_OFF + A_TILE : A_Q_OFF);
  const int w = __shfl_sync(0xffffffffu, warp, 0), g = lane >> 2, c = lane & 3;
  auto fetch = [&](uint32_t ch, uint32_t n) {
    if (w == 2 && ch < C_NONE) {
      if (elect_one()) {
        const uint32_t b = in_full + (n & 1) * 8, d = ca + (n & 1) * 8192;
        const uint64_t pol = policy_evict_first();
        mbar_expect_tx(b, 8192);
        tma_load_2d_hint(d, &maps.cu, b, 0, ch * 64, pol);
        tma_load_2d_hint(d + 4096, &maps.ch, b, 0, ch * 64, pol);
      }
    }
  };
  if (wtid == 96 && wg) { TD(15) }
  uint32_t f1[8][4];
  float tt[16], ts[16];
  uint32_t cc[4], ss[4];
#pragma unroll
  for (int i = 0; i < 16; i++) {
    const int k = 2 * (16 * w + g + 8 * (i & 1)) + 1, n = 2 * (8 * (i >> 1) + 2 * c) + 1;
    float c0, s0, c1, s1;
    sincos_turn(((k * n) << 23) >> 23, 1.f / 512, c0, s0);
    sincos_turn(((k * n + 2 * k) << 23) >> 23, 1.f / 512, c1, s1);
    f1[i >> 2][i & 3] = pack_bf16(c0 * C_ALPHA, c1 * C_ALPHA);
    f1[4 + (i >> 2)][i & 3] = pack_bf16(s0 * -C_ALPHA, s1 * -C_ALPHA);
  }
#pragma unroll
  for (int i = 0; i < 16; i++) {
    const int k = 2 * (16 * w + g + 8 * ((i >> 1) & 1)) + 1, n = 16 - (8 * (i >> 2) + 2 * c + (i & 1));
    float cs;
    sincos_turn(k * n, 1.f / 8192, cs, ts[i]);
    tt[i] = ts[i] * rcp(1.f + cs);
  }
#pragma unroll
  for (int j = 0; j < 4; j++) {
    const int k = 8 * w + g, n = 8 * c + 2 * j;
    float c0, s0, c1, s1;
    sincos_turn((int8_t)(k * n * 8), 1.f / 256, c0, s0);
    sincos_turn((int8_t)((k * n + k) * 8), 1.f / 256, c1, s1);
    cc[j] = pack_bf16(c0, c1);
    ss[j] = pack_bf16(s0, s1);
  }
  named_bar_sync(3, 256);
  fetch(first, 0);
  fetch(first + step, 1);
  const uint32_t va = ca + g * 64 + ((c ^ (g >> 1)) << 4);
  {
    const uint32_t a = va + C_MAT + w * 512, m = 0x80008000u;
    sts128(a, make_uint4(cc[0], cc[1], cc[2], cc[3]));
    sts128(a + 2048, make_uint4(ss[0], ss[1], ss[2], ss[3]));
    sts128(a + 4096, make_uint4(ss[0] ^ m, ss[1] ^ m, ss[2] ^ m, ss[3] ^ m));
    sts128(a + 6144, make_uint4(cc[0], cc[1], cc[2], cc[3]));
  }
  fence_proxy_async();
  named_bar_sync(1 + wg, 128);
  constexpr uint64_t DHI = (2ull << 62) | ((uint64_t)(512 >> 4) << 32);
  const uint32_t d0 = (uint32_t)make_desc(ca, 4096, 0, 0);
  float a5[16];
  uint4* const yb = reinterpret_cast<uint4*>(g_y2T) + (16 * w + g) * 4 + c;
  auto issue5 = [&]() {
#pragma unroll
    for (int ks = 0; ks < 8; ks++) wgmma_m64n32_rs_tb(a5, f1[ks], DHI | (d0 + (C_V >> 4) + ks * 64), ks != 0);
    wgmma_commit();
  };
  auto finish = [&](uint32_t ch, bool on) {
    fence_regs(a5);
    uint4* y = yb + (size_t)ch * 256;
    if (on) {
      y[0] = make_uint4(pack_bf16(a5[0], a5[1]), pack_bf16(a5[4], a5[5]), pack_bf16(a5[8], a5[9]), pack_bf16(a5[12], a5[13]));
      y[32] = make_uint4(pack_bf16(a5[2], a5[3]), pack_bf16(a5[6], a5[7]), pack_bf16(a5[10], a5[11]), pack_bf16(a5[14], a5[15]));
    }
  };
  auto dft32 = [&](float (&d)[32], const float* re, const float* im) {
    uint32_t a[4][4];
#pragma unroll
    for (int i = 0; i < 8; i++) {
      a[i >> 2][i & 3] = pack_bf16(re[2 * i], re[2 * i + 1]);
      a[2 + (i >> 2)][i & 3] = pack_bf16(im[2 * i], im[2 * i + 1]);
    }
    wgmma_fence();
#pragma unroll
    for (int ks = 0; ks < 4; ks++) wgmma_m64n64_rs_tb(d, a[ks], DHI | (d0 + (C_MAT >> 4) + ks * 64), ks != 0);
    wgmma_commit();
  };
  auto rot = [&](float* x, float* y) {
#pragma unroll
    for (int i = 0; i < 16; i++) {
      x[i] = fmaf(-tt[i], y[i], x[i]);
      y[i] = fmaf(ts[i], x[i], y[i]);
      x[i] = fmaf(-tt[i], y[i], x[i]);
    }
  };
  auto load_d = [&](uint32_t ch) {
    return __ldg(reinterpret_cast<const unsigned short*>(maps.ssm_D) + ((ch & (DM - 1)) | (lane & rt_zero)));
  };
  uint32_t dn = load_d(first);
  uint32_t n = 0, prev = 0, ch = first, next = first + step;
#pragma unroll 1
  for (; ch < C_NONE; n++) {
    CT(0)
    float a1[2][32], a2[2][32], a4[32];
    const float dsk = c ? 0.f : __uint_as_float(dn << 16) * C_ALPHA;
    dn = load_d(next);
    uint32_t next2 = next + step < end ? next + step : C_NONE;
    mbar_wait(in_full + (n & 1) * 8, (n >> 1) & 1);
    if (pp) named_bar_sync(4 + wg, 256);
    CT(1)
    wgmma_fence();
#pragma unroll
    for (int ks = 0; ks < 8; ks++)
      wgmma_m64n64_rs_tb(a1[ks >> 2], f1[ks], DHI | (d0 + (n & 1) * 512 + (ks & 3) * 64), (ks & 3) != 0);
    wgmma_commit();
    issue5();
    wgmma_wait<1>();
    fence_regs(a1[0]);
    fence_regs(a1[1]);
    CT(2)
    rot(a1[0], a1[1]);
    dft32(a2[0], a1[0], a1[1]);
    rot(a1[0] + 16, a1[1] + 16);
    a1[0][16] += dsk;
    a1[0][18] += dsk;
    dft32(a2[1], a1[0] + 16, a1[1] + 16);
    CT(3)
    wgmma_wait<2>();
    finish(prev, n > 0);
    wgmma_wait<0>();
    fence_regs(a2[0]);
    fence_regs(a2[1]);
    CT(4)
    if (pp) named_bar_arrive(5 - wg, 256);
    float re[16], im[16];
#pragma unroll
    for (int i = 0; i < 16; i++) {
      re[i] = a2[0][i] * a2[1][i] - a2[0][16 + i] * a2[1][16 + i];
      im[i] = a2[0][i] * a2[1][16 + i] + a2[0][16 + i] * a2[1][i];
    }
    dft32(a4, im, re);
    if (dealt) {
      mbar_wait(bar + (n < 2 ? B_DEAL : B_DEAL2), 0);
      asm volatile("ld.shared.u32 %0, [%1];" : "=r"(next2) : "r"(bar + B_LIST + 4 * n + (n < 2 ? 0 : 8)));
    }
    wgmma_wait<0>();
    fence_regs(a4);
    CT(5)
    rot(a4, a4 + 16);
#pragma unroll
    for (int i = 0; i < 4; i++) {
      const float* x = a4 + 16 - 16 * (i >> 1) + 2 * (i & 1);
      sts128(va + C_V + w * 1024 + (i >> 1) * 4096 + (i & 1) * 512,
             make_uint4(pack_bf16(x[0], x[1]), pack_bf16(x[4], x[5]), pack_bf16(x[8], x[9]), pack_bf16(x[12], x[13])));
    }
    CT(6)
    fence_proxy_async();
    named_bar_sync(1 + wg, 128);
    fetch(next2, n);
    if (wtid == 96 && n > 0) note(bar, CNT_Y2 + ((prev & 112) == 112));
    prev = ch;
    ch = next;
    next = next2;
    CT(7)
  }
  wgmma_fence();
  issue5();
  wgmma_wait<0>();
  finish(prev, (dn | ~rt_zero) != 0);
  named_bar_sync(1 + wg, 128);
  if (wtid == 96 && wg) { TD(8) }
  if (wtid == 96) cnt_signal_release(CNT_Y2 + ((prev & 112) == 112), 1);
  if (wtid == 64) note(bar, CNT_DONE);
  if (wtid == 96 && wg) { TD(9) }
}

__device__ __forceinline__ void attn_producer(const Maps& maps, uint32_t sbase, bool after_qkv, bool to_out,
                                              bool dry) {
  const uint32_t bar = sbase + BAR_OFF;
  const uint32_t q_full = bar + B_QFULL, q_empty = bar + B_QEMPTY;
  const uint32_t k_full = bar + B_KFULL, k_empty = bar + B_KEMPTY, v_full = bar + B_VFULL, v_empty = bar + B_VEMPTY;
  int ndrained = after_qkv ? 0 : G_STAGES;
  auto wait = [&](uint32_t b, uint32_t par) {
    if (!dry) mbar_wait_sleep(b, par);
  };
  auto drained = [&](int upto) {
#pragma unroll 1
    for (; ndrained <= upto; ndrained++) wait(bar + B_GEMPTY + 8 * ndrained, 1);
  };
  uint32_t st = 0, ph = 1, vs = 0, vp = 1;
  int pend_j = -1, pend_h = 0;
  int round = -1, m = -1, h = 0;
  bool last = false;
#pragma unroll 1
  for (;; round++) {
    uint32_t nitem = 0;
    const int tpost = m >= 3 ? m - 1 : m;
#pragma unroll 1
    for (int t = m < 0 ? -1 : 0; t <= m; t++) {
      const int j = (t < m && (round & 1)) ? m - 1 - t : t;
      if (t >= 0) {
        drained(1 + st);
        wait(k_empty + 8 * st, ph);
        if (!dry) {
          mbar_expect_tx(k_full + 8 * st, A_TILE);
          tma_load_3d(sbase + A_K_OFF + st * A_TILE, &maps.k, k_full + 8 * st, 0, j * 128, h * 2);
        }
        if (++st == 2) { st = 0; ph ^= 1; }
      }
      if (pend_j >= 0) {
        drained(3);
        wait(v_empty + 8 * vs, vp);
        if (!dry) {
          mbar_expect_tx(v_full + 8 * vs, A_TILE);
          tma_load_3d(sbase + A_V_OFF + vs * A_TILE, &maps.v, v_full + 8 * vs, 0, pend_j * 128, pend_h * 2);
        }
        if (++vs == 2) { vs = 0; vp ^= 1; }
      }
      pend_j = j;
      pend_h = h;
      if (t == tpost && !last) {
        nitem = dry ? 1 : item_of(maps, round + 1);
        if (round == (dry ? 0 : 3) || blockIdx.x >= 128) {
          nitem = A_ITEMS;
          if (!to_out) cnt_wait(CNT_PREP, dry ? 0 : 260);
          if (to_out) {
            wait(bar + seen_bar(1), 0);
            asm volatile("cp.async.bulk.prefetch.L2.global [%0], 4096;" ::"l"(maps.ssm_k + (size_t)conv_first(maps) * S_LEN));
            if (!dry)
              asm volatile("cp.async.bulk.prefetch.L2.global [%0], 4096;" ::"l"(g_kvT + (size_t)conv_first(maps) * S_LEN));
          }
        }
        const uint32_t qs = (round + 1) & 1;
        wait(q_empty + 8 * qs, (((round + 1) >> 1) & 1) ^ 1);
        if (round == 1 && after_qkv) wait(bar + B_QDONE, 0);
        if (round == 0 && after_qkv) wait(bar + seen_bar(0), 0);
        if (round < 0 && after_qkv) {
          if (!dry) { TD(2) }
          cnt_wait(CNT_KV, dry ? 0 : 512);
          if (!dry) { TD(3) }
        }
        if (nitem >= A_ITEMS || (round < 0 && after_qkv && !dry)) {
          if (!dry) mbar_arrive(q_full + 8 * qs);
        } else {
          drained(qs);
          if (!dry) {
            mbar_expect_tx(q_full + 8 * qs, A_TILE);
            tma_load_3d_hint(sbase + A_Q_OFF + qs * A_TILE, &maps.q, q_full + 8 * qs, 0, item_m(nitem) * 128,
                             item_h(nitem) * 2, policy_evict_first());
          }
        }
      }
    }
    if (last) break;
    last = nitem >= A_ITEMS;
    m = last ? -1 : item_m(nitem);
    h = item_h(nitem);
  }
}

__device__ __forceinline__ uint32_t attn_consumer(const Maps& maps, uint32_t smem0, uint32_t sn,
                                                  float (&rest)[64], bool after_qkv) {
  PHASE_PROLOGUE
  const uint32_t q_full = bar + B_QFULL, q_empty = bar + B_QEMPTY;
  const uint32_t k_full = bar + B_KFULL, k_empty = bar + B_KEMPTY, v_full = bar + B_VFULL;
  float o[64], s[64];
  uint32_t p[32];
  float e[32];
  uint32_t dep = 0;
  constexpr int MIDJ = 5;
  float l0 = 0.f, l1 = 0.f, b0 = 0.f, b1 = 0.f;
  const int sched_own = 4 + wg, sched_other = 5 - wg;
  if (wg == 1) named_bar_arrive(4, 256);

  const uint32_t qd0 = (uint32_t)make_desc(sbase + A_Q_OFF + wg * 8192, 16, 0, 0);
  const uint32_t kd0 = (uint32_t)make_desc(sbase + A_K_OFF, 16, 0, 0);
  const uint32_t vd0 = (uint32_t)make_desc(sbase + A_V_OFF, 16384, 0, 0);
  constexpr uint64_t DHI = DESC_SW128 | ((uint64_t)(1024 >> 4) << 32);
  constexpr uint32_t DST = A_TILE >> 4;
  auto issue_qk = [&](uint32_t qd, uint32_t kd) {
#pragma unroll
    for (int kk = 0; kk < 8; kk++) {
      const uint32_t off = ((kk >> 2) * 16384 + (kk & 3) * 32) >> 4;
      wgmma_m64n128_ss(s, DHI | (qd + off), DHI | (kd + off), kk != 0);
    }
    wgmma_commit();
  };
  auto issue_pv = [&](uint32_t vd, bool accumulate, int nk) {
#pragma unroll
    for (int kk = 0; kk < 8; kk++) {
      if (kk < nk)
        wgmma_m64n128_rs_tb(o, p[4 * kk], p[4 * kk + 1], p[4 * kk + 2], p[4 * kk + 3], DHI | (vd + kk * 128),
                            accumulate || (kk != 0));
    }
    wgmma_commit();
  };
  auto exp_lo = [&](float& a0, float& a1) {
#pragma unroll
    for (int j = 0; j < 8; j++) {
      e[4 * j] = ex2(s[4 * j]);
      e[4 * j + 1] = ex2(s[4 * j + 1]);
      e[4 * j + 2] = ex2(s[4 * j + 2]);
      e[4 * j + 3] = ex2(s[4 * j + 3]);
      a0 += e[4 * j];
      a0 += e[4 * j + 1];
      a1 += e[4 * j + 2];
      a1 += e[4 * j + 3];
      if (j == MIDJ) dep = (__float_as_uint(a0) | __float_as_uint(a1)) & rt_zero;
    }
  };
  auto pack_lo = [&]() {
#pragma unroll
    for (int j = 0; j < 16; j++) p[j] = pack_bf16(e[2 * j], e[2 * j + 1]);
  };
  auto finish_p = [&](float& a0, float& a1) {
    pack_lo();
#pragma unroll
    for (int j = 8; j < 16; j++) {
      const float e0 = ex2(s[4 * j]), e1 = ex2(s[4 * j + 1]), e2 = ex2(s[4 * j + 2]), e3 = ex2(s[4 * j + 3]);
      a0 += e0;
      a0 += e1;
      a1 += e2;
      a1 += e3;
      p[2 * j] = pack_bf16(e0, e1);
      p[2 * j + 1] = pack_bf16(e2, e3);
      if (j == 8 + MIDJ) dep = __float_as_uint(a0) & rt_zero;
    }
  };
  auto quad_sum = [&](float t) {
    t += __shfl_xor_sync(0xffffffffu, t, 1);
    return t + __shfl_xor_sync(0xffffffffu, t, 2);
  };
  auto write_o = [&](float i0, float i1) {
    st_wait(bar, wg, sn - 1);
    const int st_row = warp * 16 + (lane & 7) + ((lane >> 3) & 1) * 8;
    const uint32_t so = sbase + A_O_OFF + wg * 16384 + st_row * 128;
#pragma unroll
    for (int j = 0; j < 16; j += 2)
      stmatrix_x4(so + (j >> 3) * 8192 + ((((j & 7) + (lane >> 4)) ^ (lane & 7)) << 4),
                  pack_bf16(o[4 * j] * i0, o[4 * j + 1] * i0), pack_bf16(o[4 * j + 2] * i1, o[4 * j + 3] * i1),
                  pack_bf16(o[4 * j + 4] * i0, o[4 * j + 5] * i0), pack_bf16(o[4 * j + 6] * i1, o[4 * j + 7] * i1));
  };
  auto store_o = [&](uint32_t r, int kind, uint32_t lazy) {
    const uint32_t it = item_of(maps, r);
    st_post(bar, wg, wtid, sn, kind, (INPLACE & 1) || kind != ST_BOX2Q ? &maps.o : &maps.c[0], sbase + A_O_OFF + wg * 16384, item_h(it) * 128,
            item_m(it) * 128 + wg * 64, CNT_CTX + (r >> 1), lazy);
    sn++;
  };
  auto mask_half = [&](float* sh) {
    const int u = warp * 16 + (lane >> 2) - (lane & 3) * 2;
#pragma unroll
    for (int j = 0; j < 8; j++) {
      if (8 * j > u) sh[4 * j] = -INFINITY;
      if (8 * j + 1 > u) sh[4 * j + 1] = -INFINITY;
      if (8 * j - 8 > u) sh[4 * j + 2] = -INFINITY;
      if (8 * j - 7 > u) sh[4 * j + 3] = -INFINITY;
    }
  };
  ST(0)
  mbar_wait(q_full, 0);
  if (blockIdx.x >= 128) {
    return sn;
  }
  mbar_wait(k_full, 0);
  named_bar_sync(sched_own, 256);
  wgmma_fence();
  issue_qk(qd0, kd0);
  named_bar_arrive(sched_other, 256);
  fence_regs(rest);
#pragma unroll
  for (int i = 0; i < 64; i++) o[i] = rest[i] * Q_SCALE;
  fence_regs(o);
  wgmma_wait<0>();
  fence_regs(s);
  mbar_arrive_if(k_empty, wtid == 32);
  uint32_t g = 0;
  uint32_t rnd = 0;
  int rem = item_m(item_of(maps, 0));
  uint32_t first = 1;
  uint32_t fl = 0;
#define redo (fl & 1)
#define shifted (fl & 2)
  float d0 = 0.f, d1 = 0.f;
  float pi0 = 1.f, pi1 = 1.f;
  ST(1)
  for (;;) {
    if (shifted) {
#pragma unroll
      for (int j = 0; j < 16; j++) {
        s[4 * j] -= d0;
        s[4 * j + 1] -= d0;
        s[4 * j + 2] -= d1;
        s[4 * j + 3] -= d1;
      }
    }
    if (rem == 0 && !redo) {
      mbar_arrive_if(q_empty + 8 * (rnd & 1), wtid == 96);
      rnd++;
      if (wg == 0) mask_half(s);
      else mask_half(s + 32);
    }
    for (;;) {
      const bool kill = rem == 0 && wg == 0;
      const uint32_t kd = kd0 + ((g + 1) & 1) * DST, vd = vd0 + (g & 1) * DST;
      float a0 = 0.f, a1 = 0.f;
      exp_lo(a0, a1);
      fence_regs(e);
      const uint32_t kb = k_full + 8 * ((g + 1) & 1);
      const uint32_t kpar = (((g + 1) >> 1) & 1) ^ (g == A_STEPS - 1 ? 1u : 0u);
      const uint32_t qb = q_full + 8 * (rnd & 1), qpar = ((rnd >> 1) & 1) | dep;
      if (!mbar_try(qb, qpar)) mbar_wait(qb, qpar | ((__float_as_uint(a0) | __float_as_uint(a1)) & rt_zero));
      wgmma_wait<0>();
      fence_regs(o);
      if (kill) {
        mbar_arrive_if(kb + (B_VEMPTY - B_KFULL), wtid == 64 && !redo && g > 0);
        fence_regs(e);
        pack_lo();
#pragma unroll
        for (int j = 16; j < 32; j++) asm volatile("mov.u32 %0, 0;" : "=r"(p[j]));
        goto check;
      }
#pragma unroll
      for (int i = 32; i < 64; i++) asm volatile("" : "+f"(s[i])::"memory");
      mbar_arrive_if(kb + (B_VEMPTY - B_KFULL), wtid == 64 && !redo && g > 0);
      finish_p(a0, a1);
      if (__any_sync(0xffffffffu, !(mbar_try(v_full + 8 * (g & 1), ((g >> 1) & 1) | dep) &
                                    mbar_try(kb, kpar | dep)) ||
                                      !(a0 + a1 < 1.0995116e12f) || !(fminf(a0, a1) > (first ? 9.094947e-13f : -1.f)))) {
      check:
        bool bad = !(a0 + a1 < 1.0995116e12f);
        if (first) bad |= !(fminf(quad_sum(a0), quad_sum(a1)) > 9.094947e-13f);
        if (!redo && __any_sync(0xffffffffu, bad)) {
          d0 = d1 = first ? -INFINITY : 0.f;
#pragma unroll
          for (int j = 0; j < 16; j++) {
            if (j < 8 || !kill) {
              d0 = fmaxf(d0, fmaxf(s[4 * j], s[4 * j + 1]));
              d1 = fmaxf(d1, fmaxf(s[4 * j + 2], s[4 * j + 3]));
            }
          }
#pragma unroll
          for (int x = 1; x <= 2; x++) {
            d0 = fmaxf(d0, __shfl_xor_sync(0xffffffffu, d0, x));
            d1 = fmaxf(d1, __shfl_xor_sync(0xffffffffu, d1, x));
          }
          b0 += d0;
          b1 += d1;
          if (!first) {
            const float al0 = ex2(-d0), al1 = ex2(-d1);
            l0 *= al0;
            l1 *= al1;
#pragma unroll
            for (int j = 0; j < 16; j++) {
              o[4 * j] *= al0;
              o[4 * j + 1] *= al0;
              o[4 * j + 2] *= al1;
              o[4 * j + 3] *= al1;
            }
          }
          fl = 3;
          break;
        }
        mbar_wait(v_full + 8 * (g & 1), (g >> 1) & 1);
        mbar_wait(kb, kpar);
      }
      named_bar_sync(sched_own, 256);
      if (g == A_STEPS - 1) {
        if (first) write_o(pi0, pi1);
        fence_regs(o);
        wgmma_fence();
        issue_pv(vd, !first, 8);
        named_bar_arrive(sched_other, 256);
        if (first) store_o(rnd - 2, ST_BOX2, 0);
        pi0 = rcp(quad_sum(l0 + a0));
        pi1 = rcp(quad_sum(l1 + a1));
        goto done;
      }
      wgmma_fence();
      issue_qk(qd0 + (rnd & 1) * DST, kd);
      if (first) write_o(pi0, pi1);
      fence_regs(o);
      if (kill) {
        wgmma_fence();
        issue_pv(vd, !first, 4);
      } else {
        wgmma_fence();
        issue_pv(vd, !first, 8);
      }
      named_bar_arrive(sched_other, 256);
      fl &= 2;
      l0 += a0;
      l1 += a1;
      if (rem == 0 || first) {
        if (first && (g > 0 || after_qkv)) store_o(g ? rnd - (rem == 0 ? 2 : 1) : 2, g ? ST_BOX2 : ST_BOX2Q, rem);
        first = rem == 0;
        if (first) {
          pi0 = rcp(quad_sum(l0));
          pi1 = rcp(quad_sum(l1));
          l0 = l1 = b0 = b1 = 0.f;
          fl = 0;
          rem = item_m(item_of(maps, rnd)) + 1;
        }
      }
      rem--;
      g++;
      wgmma_wait<1>();
      fence_regs(s);
      mbar_arrive_if(kb + (B_KEMPTY - B_KFULL), wtid == 32);
      ST(g + 1)
      if (rem == 0 || shifted) {
        d0 = b0;
        d1 = b1;
        break;
      }
    }
  }
done:
#undef redo
#undef shifted
  wgmma_wait<0>();
  fence_regs(o);
  write_o(pi0, pi1);
  store_o(3, ST_BOX2L, 0);
  ST(35)
  return sn;
}

constexpr int O_STAGES = 5;
constexpr int O_STAGE_BYTES = 32768;
constexpr int O_Y_OFF = 5 * 32768;
constexpr int O_X_OFF = 6 * 32768;
constexpr int O_NK = HDIM / 64;

__device__ __forceinline__ uint32_t out_stage(uint32_t st) { return ((0x43120u >> (4 * st)) & 7) * O_STAGE_BYTES; }

__device__ __forceinline__ void out_producer(const Maps& maps, uint32_t sbase, bool after_attn, bool dry) {
  const uint32_t bar = sbase + BAR_OFF;
  const uint32_t rank = blockIdx.x & 1;
  const int m_tile = maps.id[blockIdx.x][2] & 15, n_tile = maps.id[blockIdx.x][2] >> 4;
  uint32_t stage = 0, phase = 0, xi = 0;
#pragma unroll 1
  for (int ki = 0; ki < (dry ? 1 : O_NK); ki++) {
    const int kt = (ki & 14) * 4 + ((A_ORDER >> ((ki >> 4) * 4)) & 3) * 2 + (ki & 1);
    const uint32_t fb = bar + B_OFULL + 8 * stage, eb = bar + B_OEMPTY + 8 * stage;
    const uint32_t sa = sbase + out_stage(stage);
    if (ki < O_STAGES) {
      constexpr uint32_t LASTB = B_KEMPTY | ((B_QEMPTY + 8) << 8) | ((B_KEMPTY + 8) << 16) | (B_VEMPTY << 24);
      if (ki > 0 && after_attn) mbar_wait_sleep(bar + ((LASTB >> (8 * ki - 8)) & 255), ki == 2);
      mbar_arrive_cluster_if(eb, 0, !dry);
      mbar_arrive_cluster_if(eb, 1, !dry);
    }
    if (ki == 32) mbar_wait_sleep(bar + seen_bar(2), 0);
    if (!dry) {
      mbar_wait_sleep(eb, phase);
      mbar_expect_tx(fb, O_STAGE_BYTES);
      tma_load_2d_mc(sa + 16384 + rank * 8192, &maps.ob, fb, n_tile * 128 + rank * 64, kt * 64, (uint16_t)3);
      tma_load_2d(sa, &maps.oa, fb, kt * 64, m_tile * 128);
    }
    if (++stage == O_STAGES) { stage = 0; phase ^= 1; }
    if ((ki & XMASK) == XMASK && ki >= XFIRST && xi < 8) {
      if (after_attn && xi < 2) mbar_wait_sleep(bar + B_OFREE + 8 * xi, 0);
      tma_load_3d(sbase + O_X_OFF + (xi & 1) * 16384 + (xi >> 1) * 4096, &maps.xs, bar + B_OY, 0,
                  m_tile * 128 + (xi & 1) * 64 + (xi >> 1) * 16, n_tile * 2);
      xi++;
    }
  }
  if (!dry) mbar_wait_sleep(bar + B_OY2, 0);
}

__device__ __forceinline__ void out_side(const Maps& maps, uint32_t smem0, const float (&gv)[4]) {
  PHASE_PROLOGUE
  const int m_tile = maps.id[blockIdx.x][2] & 15, n_tile = maps.id[blockIdx.x][2] >> 4;
  const bool w0 = __shfl_sync(0xffffffffu, warp, 0) == 0;
  bool have = false;
  auto late = [&](uint32_t spins) {
    have = cnt_wait(CNT_Y2 + 1, 128, spins) || !spins;
    TD(11)
    if (have) {
      mbar_expect_tx(bar + B_OY2, 4096);
      tma_load_3d(sbase + O_Y_OFF + 7 * 4096, &maps.y, bar + B_OY2, 0, n_tile * 128 + 112, m_tile * 2);
    }
  };
  if (w0) {
    if (elect_one()) {
      mbar_expect_tx(bar + B_OY, 65536 - 4096);
      TD(10)
      cnt_wait(CNT_Y2, DM - 128);
      TD(7)
#pragma unroll 1
      for (int i = 0; i < 7; i++) {
        tma_load_3d(sbase + O_Y_OFF + i * 4096, &maps.y, bar + B_OY, 0, n_tile * 128 + i * 16, m_tile * 2);
        __nanosleep(PACE);
      }
      late(1u << 18);
    }
  }
  mbar_wait_sleep(bar + B_OY, 0);
  if (wtid == 0) { TD(12) }
  const int mrow = (lane & 7) + ((lane >> 4) & 1) * 8;
  const int mchunk = warp * 2 + ((lane >> 3) & 1);
  const uint32_t xrow = sbase + O_X_OFF + warp * 4096 + (lane & 15) * 128;
  const uint32_t yrow = sbase + O_Y_OFF + mrow * 128 + ((mchunk ^ (lane & 7)) << 4);
  uint32_t y[7][4], x[7][4], om[4];
#pragma unroll
  for (int i = 0; i < 4; i++) om[i] = pack_bf16(1.0f - gv[i], 1.0f - gv[i]);
  auto xa = [&](int h, int i) { return xrow + h * 16384 + (i >> 2) * 2048 + ((((i & 3) * 2 + (lane >> 4)) ^ (lane & 7)) << 4); };
  auto load = [&](int r, int h, int i) {
    ldsm4t(y[r], yrow + h * 2048 + i * 4096);
    asm volatile("ldmatrix.sync.aligned.m8n8.x4.shared.b16 {%0, %1, %2, %3}, [%4];"
                 : "=r"(x[r][0]), "=r"(x[r][1]), "=r"(x[r][2]), "=r"(x[r][3])
                 : "r"(xa(h, i)));
  };
  auto store = [&](int r, int h, int i, uint32_t om0, uint32_t om1) {
    stmatrix_x4(xa(h, i), mul_bf2(om0, mul_bf2(x[r][0], y[r][0])), mul_bf2(om1, mul_bf2(x[r][1], y[r][1])),
                mul_bf2(om0, mul_bf2(x[r][2], y[r][2])), mul_bf2(om1, mul_bf2(x[r][3], y[r][3])));
  };
#pragma unroll 1
  for (int h = 0; h < 2; h++) {
#pragma unroll
    for (int i = 0; i < 7; i++) load(i, h, i);
#pragma unroll
    for (int i = 0; i < 7; i++) store(i, h, i, h ? om[2] : om[0], h ? om[3] : om[1]);
  }
  __syncwarp();
  mbar_arrive_if(bar + B_OE, lane == 0);
  if (w0 && !__any_sync(0xffffffffu, have)) {
    if (elect_one()) late(0);
  }
  mbar_wait_sleep(bar + B_OY2, 0);
  load(0, 0, 7);
  load(1, 1, 7);
  store(0, 0, 7, om[0], om[1]);
  store(1, 1, 7, om[2], om[3]);
  __syncwarp();
  mbar_arrive_if(bar + B_OY + 8, lane == 0);
  if (wtid == 0) { TD(13) }
}

__device__ __forceinline__ void out_gemm(const Maps& maps, uint32_t smem0) {
  PHASE_PROLOGUE
  const int m_tile = maps.id[blockIdx.x][2] & 15, n_tile = maps.id[blockIdx.x][2] >> 4;
  float acc[2][64];
  undef_regs(acc[0]);
  undef_regs(acc[1]);
  uint32_t stage = 0, phase = 0, prev_stage = 0;
  GT(gti++)
  const float* gp = g_gate + m_tile * 128 + warp * 16 + (lane >> 2);
  const float gv[4] = {__ldcg(gp), __ldcg(gp + 8), __ldcg(gp + 64), __ldcg(gp + 72)};
  if (wg == 1) {
    out_side(maps, smem0, gv);
    return;
  }
  const uint32_t xrow = sbase + O_X_OFF + warp * 4096 + (lane & 15) * 128;
  auto addr = [&](int i) {
    return xrow + (i >> 3) * 16384 + ((i >> 2) & 1) * 2048 + ((((i & 3) * 2 + (lane >> 4)) ^ (lane & 7)) << 4);
  };
  uint32_t b[16][4];
#pragma unroll
  for (int i = 0; i < 64; i++) asm volatile("" : "=r"(b[i >> 2][i & 3]));
  auto ld_b = [&](int q0, int q1) {
#pragma unroll
    for (int i = 0; i < 16; i++)
      if ((i & 7) != 7)
        asm volatile(
            "{\n.reg .pred p;\nsetp.ge.s32 p, %5, %6;\nsetp.le.and.s32 p, %5, %7, p;\n"
            "@p ldmatrix.sync.aligned.m8n8.x4.shared.b16 {%0, %1, %2, %3}, [%4];\n}\n"
            : "+r"(b[i][0]), "+r"(b[i][1]), "+r"(b[i][2]), "+r"(b[i][3])
            : "r"(addr(i)), "r"(i / 4), "r"(q0), "r"(q1)
            : "memory");
  };
  int nq = 0;
  constexpr uint64_t DHI = DESC_SW128 | ((uint64_t)(1024 >> 4) << 32);
#pragma unroll 1
  for (int kt = 0; kt < O_NK - 2; kt++) {
    uint32_t da = (uint32_t)make_desc(sbase + out_stage(stage), 16, 0, 0);
    uint32_t db = (uint32_t)make_desc(sbase + out_stage(stage) + 16384, 8192, 0, 0);
    asm volatile("" : "+r"(da), "+r"(db));
    mbar_wait(bar + B_OFULL + 8 * stage, phase);
    GT(gti++)
#pragma unroll
    for (int kk = 0; kk < 4; kk++) {
      wgmma_wait<2>();
      if (kk == 2)
        mbar_arrive_cluster_if(bar + B_OEMPTY + 8 * prev_stage, wtid >> 6,
                               (wtid & 63) == 32 && kt > 0 && kt - 1 + O_STAGES < O_NK);
      wgmma_fence();
      wgmma_m64n128_ss_tb(acc[0], DHI | (da + kk * 2), DHI | (db + kk * 128), (kt | kk) != 0);
      wgmma_m64n128_ss_tb(acc[1], DHI | (da + 512 + kk * 2), DHI | (db + kk * 128), (kt | kk) != 0);
      wgmma_commit();
      if (kk == 0 && kt >= 52) {
        uint32_t ok;
        asm volatile("{\n.reg .pred p;\nmbarrier.test_wait.parity.shared::cta.b64 p, [%1], 0;\nselp.u32 %0, 1, 0, p;\n}\n"
                     : "=r"(ok)
                     : "r"(bar + B_OE)
                     : "memory");
        if (__all_sync(0xffffffffu, ok)) {
          ld_b(nq, nq);
          nq++;
        }
      }
    }
    prev_stage = stage;
    if (++stage == O_STAGES) { stage = 0; phase ^= 1; }
  }
  if (tid == 0) { TD(14) }
  constexpr int S0 = (O_NK - 2) % O_STAGES, P0 = ((O_NK - 2) / O_STAGES) & 1;
  const uint32_t d0 = (uint32_t)make_desc(sbase, 0, 0, 0);
  auto mma = [&](int h, int k0, int k1) {
    wgmma_fence();
#pragma unroll
    for (int k = k0; k < k1; k++) {
      const uint32_t d = d0 + (out_stage(S0 + (k >> 2)) >> 4);
      wgmma_m64n128_ss_tb(acc[h], DHI | (d + 0x10000 + h * 512 + (k & 3) * 2), DHI | (d + 0x2000400 + (k & 3) * 128), 1);
    }
    wgmma_commit();
  };
#pragma unroll
  for (int p = 0; p < 2; p++) {
    mbar_wait(bar + B_OFULL + 8 * (S0 + p), P0);
    mma(0, 4 * p, 4 * p + 4);
  }
  mma(1, 0, 8);
  uint32_t gg[4];
#pragma unroll
  for (int i = 0; i < 4; i++) gg[i] = pack_bf16(gv[i], gv[i]);
  if (nq < 4) {
    mbar_wait(bar + B_OE, 0);
    ld_b(nq, 3);
  }
  const int w4 = __shfl_sync(0xffffffffu, warp, 0);
#pragma unroll
  for (int i = 0; i < 16; i++) {
    const int h = i >> 3;
    if (i == 0) wgmma_wait<1>();
    if (i == 8) wgmma_wait<0>();
    if ((i & 7) == 0) fence_regs(acc[h]);
    if (i == 8) {   }
    if (i == 7) {
      mbar_wait(bar + B_OY + 8, 0);
#pragma unroll
      for (int j = 7; j < 16; j += 8)
        asm volatile("ldmatrix.sync.aligned.m8n8.x4.shared.b16 {%0, %1, %2, %3}, [%4];"
                     : "=r"(b[j][0]), "=r"(b[j][1]), "=r"(b[j][2]), "=r"(b[j][3])
                     : "r"(addr(j))
                     : "memory");
    }
    const float* a = acc[h] + 8 * (i & 7);
    stmatrix_x4(addr(i), fma_bf2(gg[2 * h], pack_bf16(a[0], a[1]), b[i][0]), fma_bf2(gg[2 * h + 1], pack_bf16(a[2], a[3]), b[i][1]),
                fma_bf2(gg[2 * h], pack_bf16(a[4], a[5]), b[i][2]), fma_bf2(gg[2 * h + 1], pack_bf16(a[6], a[7]), b[i][3]));
    if ((i & 7) == 7) {
      fence_proxy_async();
      __syncwarp();
      if (elect_one()) {
        tma_store_3d(&maps.oc, sbase + O_X_OFF + (h * 4 + w4) * 4096, 0, m_tile * 128 + h * 64 + w4 * 16, n_tile * 2);
        if (h == 1) {
          tma_store_commit();
        }
      }
    }
  }
  GT(gti++)
}

__device__ __noinline__ void leave_kernel(int mask) {
  if (!(mask & 4)) return;
  if (atomicAdd(g_cnt + CNT_DONE * 32, 1u) == 2 * gridDim.x - 1) {
    for (int i = 0; i < CNT_N; i++) g_cnt[i * 32] = 0;
#pragma unroll 4
    for (int i = 0; i < 128; i++) g_slot[i] = 0;
  }
}

__device__ __noinline__ void side_jobs(const Maps& maps, uint32_t sbase) {
  const int w12 = __shfl_sync(0xffffffffu, threadIdx.x >> 5, 0);
  gate_rows(maps, sbase, (blockIdx.x - 128) * 12 + w12, w12, threadIdx.x & 31);
  fence_proxy_async();
  __syncthreads();
  if (threadIdx.x == 320) cnt_signal_release(CNT_PREP, 1);
}

__global__ void __launch_bounds__(384, 1) fused_kernel(int mask, const __grid_constant__ Maps maps) {
  extern __shared__ __align__(1024) uint8_t smem_raw[];
  {
    const uint32_t sbase = __shfl_sync(0xffffffffu, smem_u32(smem_raw), 0);
    const uint32_t bar = sbase + BAR_OFF;
    const int tid = threadIdx.x;
    const bool do_qkv = (mask & 1) && blockIdx.x < 128;
    TL(0, 0)
    if (__shfl_sync(0xffffffffu, tid >> 5, 0) == 1 && do_qkv) {
      if (elect_one()) {
        for (int i = 0; i < G_STAGES; i++) mbar_init(bar + B_GFULL + 8 * i, 1);
        fence_barrier_init();
        qkv_producer(maps, sbase, true);
      }
    }
    if (tid == 0) {
      for (int i = 0; i < G_STAGES; i++) {
        mbar_init(bar + B_GEMPTY + 8 * i, 2);
        mbar_init(bar + B_SFULL + 8 * i, 4);
        mbar_init(bar + B_SFREE + 8 * i, 1);
      }
      for (int i = 0; i < 2; i++) {
        mbar_init(bar + B_OFREE + 8 * i, 1);
        mbar_init(bar + B_QFULL + 8 * i, 1);
        mbar_init(bar + B_QEMPTY + 8 * i, 2);
        mbar_init(bar + B_KFULL + 8 * i, 1);
        mbar_init(bar + B_KEMPTY + 8 * i, 2);
        mbar_init(bar + B_VFULL + 8 * i, 1);
        mbar_init(bar + B_VEMPTY + 8 * i, 2);
      }
      for (int i = 0; i < O_STAGES; i++) {
        mbar_init(bar + B_OFULL + 8 * i, 1);
        mbar_init(bar + B_OEMPTY + 8 * i, 2);
      }
      mbar_init(bar + B_OY, 1);
      for (int i = 0; i < 3; i++) mbar_init(bar + seen_bar(i), 1);
      mbar_init(bar + B_OY2, 1);
      mbar_init(bar + B_DEAL, 1);
      mbar_init(bar + B_DEAL2, 1);
      mbar_init(bar + B_PAIR, 1);
      mbar_init(bar + B_OY + 8, 4);
      mbar_init(bar + B_OE, 4);
      mbar_init(bar + B_QDONE, 2);
      for (int i = 0; i < 8; i++) mbar_init(bar + B_CFULL + 8 * i, 1);
      for (int i = 0; i < CNT_N; i++) asm volatile("st.shared.u32 [%0], 0;" ::"r"(bar + B_PEND + 4 * i) : "memory");
      fence_barrier_init();
    }
    __syncthreads();
    asm volatile("barrier.cluster.arrive.relaxed.aligned;" ::: "memory");
    if ((mask & 1) && blockIdx.x >= 128) side_jobs(maps, sbase);
  }
  uint32_t smem0 = smem_u32(smem_raw);
  PHASE_PROLOGUE
  const bool do_qkv = (mask & 1) && blockIdx.x < 128, do_out = (mask & 4) && blockIdx.x < 128;
  TL(0, 1)

  if (wg != 2) {
    reg_alloc<232>();
    uint32_t sn = 0;
    float o[64];
    if (do_qkv) {
      sn = qkv_consumer(maps, smem_u32(smem_raw), mask & 2, o);
    } else {
      undef_regs(o);
    }
    TL(0, 2) TL(1, 0) TL(1, 1)
    asm volatile("barrier.cluster.wait.acquire.aligned;" ::: "memory");
    if (mask & 2) {
      sn = attn_consumer(maps, smem_u32(smem_raw), sn, o, mask & 1);
      TL(2, 0)
      if ((mask & 4) && blockIdx.x < 128 && __shfl_sync(0xffffffffu, threadIdx.x, 0) < 128) {
        named_bar_arrive(3, 256);
      } else {
        const uint32_t b2 = blockIdx.x * 2 + (threadIdx.x >> 7);
        const bool fused = mask & 4, mainc = blockIdx.x < 128;
        const uint32_t first = __shfl_sync(0xffffffffu, !fused ? b2 : mainc ? conv_first(maps) : (b2 - 255) * 128 - C_SIDE, 0);
        conv_consumer(maps, smem_u32(smem_raw), first, !fused ? 264 : mainc ? 16 : 1,
                      !fused ? DM : mainc ? (first | 127) + 1 - C_SIDE : first + C_SIDE, fused && !mainc,
                      fused && mainc);
      }
      TL(1, 2) TL(2, 1) TL(2, 2)
    }
    TL(3, 0) TL(3, 1)
    {
      uint32_t smem0 = smem_u32(smem_raw);
      PHASE_PROLOGUE
      st_wait(bar, wg, sn - 2);
      st_post(bar, wg, wtid, sn, ST_END, nullptr, 0, 0, 0, -1);
    }
    if ((mask & 4) && blockIdx.x < 128) out_gemm(maps, smem_u32(smem_raw));
    tma_store_wait_read<0>();
  } else {
    reg_dealloc<40>();
    asm volatile("barrier.cluster.wait.acquire.aligned;" ::: "memory");
    const int w = __shfl_sync(0xffffffffu, tid >> 5, 0) - 8;
    if (w < 2) {
      if (do_qkv) prep_agent(maps, sbase, w, lane);
      if (elect_one()) store_agent(bar, w, w && do_out ? conv_first(maps) + 48 : 0);
      TL2(3, 2)
    } else {
      if (elect_one()) {
        const bool dry = w == 2;
        if (do_qkv && !dry) qkv_producer(maps, sbase, false);
        if (mask & 2) attn_producer(maps, sbase, do_qkv, do_out, dry);
        if (do_out) out_producer(maps, sbase, mask & 2, dry);
        if (dry) { TD(5) }
      }
      __syncwarp();
      if (w == 2) publisher(bar, tid & 31, !(mask & 2) ? 2 : do_out ? 3 : 4, !do_out ? 3 : do_qkv ? 0 : 2, do_qkv ? 4 : 0);
      if ((tid & 31) == 0) leave_kernel(mask);
    }
  }
}

typedef CUresult (*PFN_tmapEncode)(CUtensorMap*, CUtensorMapDataType, cuuint32_t, void*, const cuuint64_t*,
                                   const cuuint64_t*, const cuuint32_t*, const cuuint32_t*, CUtensorMapInterleave,
                                   CUtensorMapSwizzle, CUtensorMapL2promotion, CUtensorMapFloatOOBfill);
static PFN_tmapEncode s_encode = nullptr;

static void make_map_2d(CUtensorMap* m, const void* ptr, int rows, int cols, int box_rows) {
  cuuint64_t dims[2] = {(cuuint64_t)cols, (cuuint64_t)rows};
  cuuint64_t strides[1] = {(cuuint64_t)cols * 2};
  cuuint32_t box[2] = {cols < 64 ? 32u : 64u, (cuuint32_t)box_rows};
  cuuint32_t es[2] = {1, 1};
  s_encode(m, CU_TENSOR_MAP_DATA_TYPE_BFLOAT16, 2, const_cast<void*>(ptr), dims, strides, box, es,
           CU_TENSOR_MAP_INTERLEAVE_NONE, cols < 64 ? CU_TENSOR_MAP_SWIZZLE_64B : CU_TENSOR_MAP_SWIZZLE_128B, CU_TENSOR_MAP_L2_PROMOTION_L2_256B,
           CU_TENSOR_MAP_FLOAT_OOB_FILL_NONE);
}
static void make_map_3d(CUtensorMap* m, const void* ptr, int rows, int cols, int box_rows, int box_chunks) {
  cuuint64_t dims[3] = {64, (cuuint64_t)rows, (cuuint64_t)(cols / 64)};
  cuuint64_t strides[2] = {(cuuint64_t)cols * 2, 128};
  cuuint32_t box[3] = {64, (cuuint32_t)box_rows, (cuuint32_t)box_chunks};
  cuuint32_t es[3] = {1, 1, 1};
  s_encode(m, CU_TENSOR_MAP_DATA_TYPE_BFLOAT16, 3, const_cast<void*>(ptr), dims, strides, box, es,
           CU_TENSOR_MAP_INTERLEAVE_NONE, CU_TENSOR_MAP_SWIZZLE_128B, CU_TENSOR_MAP_L2_PROMOTION_L2_256B,
           CU_TENSOR_MAP_FLOAT_OOB_FILL_NONE);
}

static cudaLaunchConfig_t fused_cfg(cudaLaunchAttribute* at) {
  cudaLaunchConfig_t cfg = {};
  cfg.gridDim = dim3(132);
  cfg.blockDim = dim3(384);
  cfg.dynamicSmemBytes = SMEM_BYTES;
  cfg.stream = cudaStreamPerThread;
  at[0].id = cudaLaunchAttributeClusterDimension;
  at[0].val.clusterDim.x = 2;
  at[0].val.clusterDim.y = 1;
  at[0].val.clusterDim.z = 1;
  cfg.attrs = at;
  cfg.numAttrs = 1;
  return cfg;
}

extern "C" void kernel_launch(void* const* d_in, const int* in_sizes, int n_in, void* d_out, int out_size) {
  const bf16* x = (const bf16*)d_in[0];
  const bf16* ckv = (const bf16*)d_in[1];
  const bf16* wq = (const bf16*)d_in[2];
  const bf16* wuk = (const bf16*)d_in[3];
  const bf16* wuv = (const bf16*)d_in[4];
  const bf16* wo = (const bf16*)d_in[5];
  const bf16* bk = (const bf16*)d_in[7];
  const bf16* bv = (const bf16*)d_in[8];
  const bf16* shift_k = (const bf16*)d_in[9];
  const bf16* ssm_k = (const bf16*)d_in[10];
  const bf16* ssm_D = (const bf16*)d_in[11];
  const bf16* gate_w = (const bf16*)d_in[12];
  bf16* out = (bf16*)d_out;

  static void *pq = nullptr, *pk = nullptr, *pv = nullptr, *pctx = nullptr, *pb = nullptr, *pu = nullptr;
  static int max_clusters = 0;
  if (!s_encode) {
    void* fn = nullptr;
    cudaDriverEntryPointQueryResult qres;
    cudaGetDriverEntryPoint("cuTensorMapEncodeTiled", &fn, cudaEnableDefault, &qres);
    s_encode = (PFN_tmapEncode)fn;
    cudaGetSymbolAddress(&pq, g_q);
    cudaGetSymbolAddress(&pk, g_k);
    cudaGetSymbolAddress(&pv, g_v);
    cudaGetSymbolAddress(&pctx, g_ctx);
    cudaGetSymbolAddress(&pb, g_y2T);
    cudaGetSymbolAddress(&pu, g_kvT);
    cudaFuncSetAttribute(fused_kernel, cudaFuncAttributeMaxDynamicSharedMemorySize, SMEM_BYTES);
    cudaLaunchAttribute at[1];
    cudaLaunchConfig_t cfg = fused_cfg(at);
    if (cudaOccupancyMaxActiveClusters(&max_clusters, fused_kernel, &cfg) != cudaSuccess) max_clusters = 0;
  }

  Maps all = {};
  make_map_2d(&all.a[0], x, S_LEN, DM, 128);
  make_map_2d(&all.a[1], ckv, S_LEN, DC, 128);
  make_map_3d(&all.b[0], wq, DM, HDIM, 64, 4);
  make_map_3d(&all.b[1], wuk, DC, HDIM, 64, 4);
  make_map_3d(&all.b[2], wuv, DC, HDIM, 64, 4);
  make_map_2d(&all.c[0], pq, S_LEN, HDIM, 64);
  make_map_2d(&all.c[1], pk, S_LEN, HDIM, 64);
  make_map_2d(&all.c[2], pv, S_LEN, HDIM, 64);
  make_map_3d(&all.q, pq, S_LEN, HDIM, 128, 2);
  make_map_3d(&all.k, pk, S_LEN, HDIM, 128, 2);
  make_map_3d(&all.v, pv, S_LEN, HDIM, 128, 2);
  make_map_2d(&all.o, pctx, S_LEN, HDIM, 64);
  all.ssm_k = ssm_k;
  all.ssm_D = ssm_D;
  make_map_2d(&all.oa, pctx, S_LEN, HDIM, 128);
  make_map_2d(&all.ob, wo, HDIM, DM, 64);
  make_map_3d(&all.oc, out, S_LEN, DM, 16, 2);
  make_map_3d(&all.y, pb, DM, S_LEN, 16, 2);
  make_map_3d(&all.xs, x, S_LEN, DM, 16, 2);
  make_map_2d(&all.cu, pu, DM * 64, 32, 64);
  make_map_2d(&all.ch, ssm_k, DM * 64, 32, 64);

  make_map_2d(&all.bk, bk, S_LEN, DM, 35);
  make_map_2d(&all.bv, bv, S_LEN, DM, 32);
  for (int b = 0; b < 128; b++) {
    const int c = b >> 1, r = b & 1;
    const int G = c < 4 ? 0 : c < 36 ? (c - 4) % 8 : 1 + (c - 36) % 7;
    const int i = c < 4 ? 4 + c : c < 36 ? (c - 4) / 8 : 4 + (c - 36) / 7;
    all.id[b][0] = r + 2 * (i & 1) + 4 * (G & 3) + 16 * (i >> 1) + 64 * (G >> 2);
    all.id[b][1] = r + 2 * i + 16 * G;
    all.id[b][2] = r + 2 * G + 16 * i;
  }
  all.shift_k = shift_k;
  all.x = x;
  all.gate_w = gate_w;
  cudaLaunchAttribute at[1];
  cudaLaunchConfig_t cfg = fused_cfg(at);
  if (max_clusters >= 66) {
    cudaLaunchKernelEx(&cfg, fused_kernel, 7, all);
  } else {
    for (int m = 1; m <= 4; m <<= 1) cudaLaunchKernelEx(&cfg, fused_kernel, m, all);
  }
}
```

```cpp
#include <cuda_runtime.h>
#include <cuda_bf16.h>
#include <cuda.h>
#include <stdint.h>

typedef __nv_bfloat16 bf16;
#define INPLACE 3

constexpr int S_LEN = 2048;
constexpr int DM = 1024;
constexpr int NH = 32;
constexpr int HD = 128;
constexpr int DC = 512;
constexpr int HDIM = NH * HD;

__device__ __align__(1024) bf16 g_q[S_LEN * HDIM];
__device__ __align__(1024) bf16 g_k[S_LEN * HDIM];
__device__ __align__(1024) bf16 g_v[S_LEN * HDIM];
#define g_ctx g_q
__device__ __align__(1024) bf16 g_kvT[DM * S_LEN];
#define g_y2T g_kvT
__device__ __align__(1024) float g_gate[S_LEN];
enum { CNT_KV = 0, CNT_PREP = CNT_KV + 2, CNT_CTX, CNT_Y2 = CNT_CTX + 2, CNT_DONE = CNT_Y2 + 2, CNT_RANK, CNT_N };
__device__ unsigned int g_cnt[CNT_N * 32];
__device__ unsigned long long g_slot[128];

#define TL(k, i)
#define TL2(k, i)
#define TD(i)
#define CT(i)
#define GT(i)
#define GA(i)
#define ST(i)

__device__ __forceinline__ uint32_t smem_u32(const void* p) { return (uint32_t)__cvta_generic_to_shared(p); }

__device__ __forceinline__ void mbar_init(uint32_t bar, uint32_t count) {
  asm volatile("mbarrier.init.shared::cta.b64 [%0], %1;" ::"r"(bar), "r"(count));
}
__device__ __forceinline__ void mbar_expect_tx(uint32_t bar, uint32_t bytes) {
  asm volatile("mbarrier.arrive.expect_tx.shared::cta.b64 _, [%0], %1;" ::"r"(bar), "r"(bytes) : "memory");
}
__device__ __forceinline__ void mbar_arrive(uint32_t bar) {
  asm volatile("mbarrier.arrive.shared::cta.b64 _, [%0];" ::"r"(bar) : "memory");
}
__device__ __forceinline__ void mbar_wait(uint32_t bar, uint32_t parity) {
  uint32_t done;
  uint32_t spins = 0;
  do {
    asm volatile(
        "{\n.reg .pred p;\n"
        "mbarrier.try_wait.parity.shared::cta.b64 p, [%1], %2;\n"
        "selp.u32 %0, 1, 0, p;\n}\n"
        : "=r"(done)
        : "r"(bar), "r"(parity)
        : "memory");
    if (++spins > (1u << 22)) break;
  } while (!done);
}
__device__ __forceinline__ bool mbar_try(uint32_t bar, uint32_t parity) {
  uint32_t done;
  asm volatile(
      "{\n.reg .pred p;\n"
      "mbarrier.try_wait.parity.shared::cta.b64 p, [%1], %2;\n"
      "selp.u32 %0, 1, 0, p;\n}\n"
      : "=r"(done)
      : "r"(bar), "r"(parity)
      : "memory");
  return done != 0;
}
__device__ __forceinline__ bool elect_one() {
  uint32_t pred;
  asm volatile("{\n.reg .pred p;\nelect.sync _|p, 0xffffffff;\nselp.u32 %0, 1, 0, p;\n}\n" : "=r"(pred));
  return pred != 0;
}
__device__ __forceinline__ void mbar_arrive_if(uint32_t bar, bool pred) {
  asm volatile(
      "{\n.reg .pred p;\nsetp.ne.b32 p, %1, 0;\n"
      "@p mbarrier.arrive.shared::cta.b64 _, [%0];\n}\n" ::"r"(bar),
      "r"((uint32_t)pred)
      : "memory");
}
__device__ __forceinline__ void mbar_wait_sleep(uint32_t bar, uint32_t parity) {
  uint32_t done;
  uint32_t spins = 0;
  do {
    asm volatile(
        "{\n.reg .pred p;\n"
        "mbarrier.try_wait.parity.shared::cta.b64 p, [%1], %2, %3;\n"
        "selp.u32 %0, 1, 0, p;\n}\n"
        : "=r"(done)
        : "r"(bar), "r"(parity), "r"(20000u)
        : "memory");
    if (++spins > (1u << 16)) break;
  } while (!done);
}
__device__ __forceinline__ void fence_barrier_init() {
  asm volatile("fence.mbarrier_init.release.cluster;" ::: "memory");
}
__device__ __forceinline__ void fence_proxy_async() {
  asm volatile("fence.proxy.async.shared::cta;" ::: "memory");
}
__device__ __forceinline__ void named_bar_sync(int id, int nthreads) {
  asm volatile("bar.sync %0, %1;" ::"r"(id), "r"(nthreads) : "memory");
}
__device__ __forceinline__ void named_bar_arrive(int id, int nthreads) {
  asm volatile("bar.arrive %0, %1;" ::"r"(id), "r"(nthreads) : "memory");
}
__device__ __forceinline__ void tma_load_2d(uint32_t dst, const CUtensorMap* m, uint32_t bar, int c0, int c1) {
  asm volatile(
      "cp.async.bulk.tensor.2d.shared::cluster.global.mbarrier::complete_tx::bytes [%0], [%1, {%3, %4}], [%2];" ::"r"(dst),
      "l"(reinterpret_cast<uint64_t>(m)), "r"(bar), "r"(c0), "r"(c1)
      : "memory");
}
__device__ __forceinline__ void tma_load_3d(uint32_t dst, const CUtensorMap* m, uint32_t bar, int c0, int c1, int c2) {
  asm volatile(
      "cp.async.bulk.tensor.3d.shared::cluster.global.mbarrier::complete_tx::bytes [%0], [%1, {%3, %4, %5}], [%2];" ::"r"(dst),
      "l"(reinterpret_cast<uint64_t>(m)), "r"(bar), "r"(c0), "r"(c1), "r"(c2)
      : "memory");
}
__device__ __forceinline__ void tma_store_2d(const CUtensorMap* m, uint32_t src, int c0, int c1) {
  asm volatile("cp.async.bulk.tensor.2d.global.shared::cta.bulk_group [%0, {%2, %3}], [%1];" ::"l"(
                   reinterpret_cast<uint64_t>(m)),
               "r"(src), "r"(c0), "r"(c1)
               : "memory");
}
__device__ __forceinline__ void bulk_load(uint32_t dst, const void* src, uint32_t bytes, uint32_t bar) {
  asm volatile("cp.async.bulk.shared::cluster.global.mbarrier::complete_tx::bytes [%0], [%1], %2, [%3];" ::"r"(dst),
               "l"(src), "r"(bytes), "r"(bar)
               : "memory");
}
__device__ __forceinline__ void tma_load_2d_mc(uint32_t dst, const CUtensorMap* m, uint32_t bar, int c0, int c1,
                                               uint16_t mask) {
  asm volatile(
      "cp.async.bulk.tensor.2d.shared::cluster.global.mbarrier::complete_tx::bytes.multicast::cluster [%0], [%1, {%3, "
      "%4}], [%2], %5;" ::"r"(dst),
      "l"(reinterpret_cast<uint64_t>(m)), "r"(bar), "r"(c0), "r"(c1), "h"(mask)
      : "memory");
}
__device__ __forceinline__ void mbar_arrive_cluster_if(uint32_t bar, uint32_t cta, bool pred) {
  asm volatile(
      "{\n.reg .b32 ra;\n.reg .pred p;\nsetp.ne.b32 p, %2, 0;\n"
      "mapa.shared::cluster.u32 ra, %0, %1;\n"
      "@p mbarrier.arrive.shared::cluster.b64 _, [ra];\n}\n" ::"r"(bar),
      "r"(cta), "r"((uint32_t)pred)
      : "memory");
}
__device__ __forceinline__ uint64_t policy_evict_first() {
  uint64_t pol;
  asm volatile("createpolicy.fractional.L2::evict_first.b64 %0, 1.0;" : "=l"(pol));
  return pol;
}
__device__ __forceinline__ void tma_load_2d_hint(uint32_t dst, const CUtensorMap* m, uint32_t bar, int c0, int c1,
                                                 uint64_t pol) {
  asm volatile(
      "cp.async.bulk.tensor.2d.shared::cluster.global.mbarrier::complete_tx::bytes.L2::cache_hint [%0], [%1, {%3, %4}], "
      "[%2], %5;" ::"r"(dst),
      "l"(reinterpret_cast<uint64_t>(m)), "r"(bar), "r"(c0), "r"(c1), "l"(pol)
      : "memory");
}
__device__ __forceinline__ void tma_load_3d_hint(uint32_t dst, const CUtensorMap* m, uint32_t bar, int c0, int c1,
                                                 int c2, uint64_t pol) {
  asm volatile(
      "cp.async.bulk.tensor.3d.shared::cluster.global.mbarrier::complete_tx::bytes.L2::cache_hint [%0], [%1, {%3, %4, "
      "%5}], [%2], %6;" ::"r"(dst),
      "l"(reinterpret_cast<uint64_t>(m)), "r"(bar), "r"(c0), "r"(c1), "r"(c2), "l"(pol)
      : "memory");
}
__device__ __forceinline__ void bulk_load_hint(uint32_t dst, const void* src, uint32_t bytes, uint32_t bar, uint64_t pol) {
  asm volatile(
      "cp.async.bulk.shared::cluster.global.mbarrier::complete_tx::bytes.L2::cache_hint [%0], [%1], %2, [%3], %4;" ::"r"(dst),
      "l"(src), "r"(bytes), "r"(bar), "l"(pol)
      : "memory");
}
__device__ __forceinline__ void cnt_signal_release(int which, uint32_t n) {
  asm volatile("red.release.gpu.global.add.u32 [%0], %1;" ::"l"(g_cnt + which * 32), "r"(n) : "memory");
}
__device__ __forceinline__ bool cnt_wait(int which, uint32_t target, uint32_t spins = 0) {
  uint32_t v;
  while (true) {
    asm volatile("ld.acquire.gpu.global.u32 %0, [%1];" : "=r"(v) : "l"(g_cnt + which * 32) : "memory");
    if (v >= target || ++spins > (1u << 18)) break;
    __nanosleep(64);
  }
  asm volatile("fence.proxy.async.global;" ::: "memory");
  return v >= target;
}
__device__ __forceinline__ void tma_store_3d(const CUtensorMap* m, uint32_t src, int c0, int c1, int c2) {
  asm volatile("cp.async.bulk.tensor.3d.global.shared::cta.bulk_group [%0, {%2, %3, %4}], [%1];" ::"l"(
                   reinterpret_cast<uint64_t>(m)),
               "r"(src), "r"(c0), "r"(c1), "r"(c2)
               : "memory");
}
__device__ __forceinline__ void tma_store_commit() { asm volatile("cp.async.bulk.commit_group;" ::: "memory"); }
template <int N>
__device__ __forceinline__ void tma_store_wait_read() {
  asm volatile("cp.async.bulk.wait_group.read %0;" ::"n"(N) : "memory");
}
template <int N>
__device__ __forceinline__ void tma_store_wait() {
  asm volatile("cp.async.bulk.wait_group %0;" ::"n"(N) : "memory");
}
__device__ __forceinline__ void wgmma_fence() { asm volatile("wgmma.fence.sync.aligned;" ::: "memory"); }
__device__ __forceinline__ void wgmma_commit() { asm volatile("wgmma.commit_group.sync.aligned;" ::: "memory"); }
template <int N>
__device__ __forceinline__ void wgmma_wait() {
  asm volatile("wgmma.wait_group.sync.aligned %0;" ::"n"(N) : "memory");
}
template <int R>
__device__ __forceinline__ void reg_alloc() { asm volatile("setmaxnreg.inc.sync.aligned.u32 %0;" ::"n"(R)); }
template <int R>
__device__ __forceinline__ void reg_dealloc() { asm volatile("setmaxnreg.dec.sync.aligned.u32 %0;" ::"n"(R)); }

__device__ __forceinline__ void stmatrix_x4(uint32_t addr, uint32_t r0, uint32_t r1, uint32_t r2, uint32_t r3) {
  asm volatile("stmatrix.sync.aligned.m8n8.x4.shared.b16 [%0], {%1, %2, %3, %4};" ::"r"(addr), "r"(r0), "r"(r1),
               "r"(r2), "r"(r3)
               : "memory");
}
__device__ __forceinline__ uint32_t pack_bf16(float lo, float hi) {
  uint32_t r;
  asm("cvt.rn.bf16x2.f32 %0, %1, %2;" : "=r"(r) : "f"(hi), "f"(lo));
  return r;
}
__device__ __forceinline__ float bf16_round(float x) { return __bfloat162float(__float2bfloat16_rn(x)); }
__device__ __forceinline__ float bf_lo(uint32_t v) { return __uint_as_float(v << 16); }
__device__ __forceinline__ float bf_hi(uint32_t v) { return __uint_as_float(v & 0xffff0000u); }
__device__ __forceinline__ uint4 lds128(uint32_t a) {
  uint4 v;
  asm volatile("ld.shared.v4.u32 {%0, %1, %2, %3}, [%4];" : "=r"(v.x), "=r"(v.y), "=r"(v.z), "=r"(v.w) : "r"(a));
  return v;
}
__device__ __forceinline__ void sts128(uint32_t a, uint4 v) {
  asm volatile("st.shared.v4.u32 [%0], {%1, %2, %3, %4};" ::"r"(a), "r"(v.x), "r"(v.y), "r"(v.z), "r"(v.w) : "memory");
}
__device__ __forceinline__ uint32_t mul_bf2(uint32_t a, uint32_t b) {
  uint32_t r;
  asm("mul.rn.bf16x2 %0, %1, %2;" : "=r"(r) : "r"(a), "r"(b));
  return r;
}
__device__ __forceinline__ float ex2(float x) {
  float y;
  asm("ex2.approx.ftz.f32 %0, %1;" : "=f"(y) : "f"(x));
  return y;
}
__device__ __forceinline__ float rcp(float x) {
  float y;
  asm("rcp.approx.ftz.f32 %0, %1;" : "=f"(y) : "f"(x));
  return y;
}
template <int N>
__device__ __forceinline__ void fence_regs(float (&r)[N]) {
#pragma unroll
  for (int i = 0; i < N; i++) asm volatile("" : "+f"(r[i])::"memory");
}

template <int N>
__device__ __forceinline__ void undef_regs(float (&r)[N]) {
#pragma unroll
  for (int i = 0; i < N; i++) asm volatile("" : "=f"(r[i]));
}
template <int N>
__device__ __forceinline__ void fence_regs_u(uint32_t (&r)[N]) {
#pragma unroll
  for (int i = 0; i < N; i++) asm volatile("" : "+r"(r[i])::"memory");
}

constexpr uint64_t DESC_SW128 = 1ull << 62;
__device__ __forceinline__ uint64_t make_desc(uint32_t addr, uint32_t lbo_bytes, uint32_t sbo_bytes, uint64_t swz) {
  return (uint64_t)((addr & 0x3FFFF) >> 4) | ((uint64_t)((lbo_bytes & 0x3FFFF) >> 4) << 16) |
         ((uint64_t)((sbo_bytes & 0x3FFFF) >> 4) << 32) | swz;
}

__device__ __forceinline__ uint64_t desc_add(uint64_t d, uint32_t off16) {
  return (d & 0xFFFFFFFF00000000ull) | (uint64_t)((uint32_t)d + off16);
}

__device__ __forceinline__ void wgmma_m64n256_ss_tb(float (&d)[128], uint64_t da, uint64_t db, int sd) {
  asm volatile(
    "{\n.reg .pred p;\nsetp.ne.b32 p, %130, 0;\n"
    "wgmma.mma_async.sync.aligned.m64n256k16.f32.bf16.bf16 "
    "{%0, %1, %2, %3, %4, %5, %6, %7, %8, %9, %10, %11, %12, %13, %14, %15, %16, %17, %18, %19, %20, %21, %22, %23, %24, %25, %26, %27, %28, %29, %30, %31, %32, %33, %34, %35, %36, %37, %38, %39, %40, %41, %42, %43, %44, %45, %46, %47, %48, %49, %50, %51, %52, %53, %54, %55, %56, %57, %58, %59, %60, %61, %62, %63, %64, %65, %66, %67, %68, %69, %70, %71, %72, %73, %74, %75, %76, %77, %78, %79, %80, %81, %82, %83, %84, %85, %86, %87, %88, %89, %90, %91, %92, %93, %94, %95, %96, %97, %98, %99, %100, %101, %102, %103, %104, %105, %106, %107, %108, %109, %110, %111, %112, %113, %114, %115, %116, %117, %118, %119, %120, %121, %122, %123, %124, %125, %126, %127}, %128, %129, p, 1, 1, 0, 1;\n}\n"
    : "+f"(d[0]), "+f"(d[1]), "+f"(d[2]), "+f"(d[3]), "+f"(d[4]), "+f"(d[5]), "+f"(d[6]), "+f"(d[7]), "+f"(d[8]), "+f"(d[9]), "+f"(d[10]), "+f"(d[11]), "+f"(d[12]), "+f"(d[13]), "+f"(d[14]), "+f"(d[15]), "+f"(d[16]), "+f"(d[17]), "+f"(d[18]), "+f"(d[19]), "+f"(d[20]), "+f"(d[21]), "+f"(d[22]), "+f"(d[23]), "+f"(d[24]), "+f"(d[25]), "+f"(d[26]), "+f"(d[27]), "+f"(d[28]), "+f"(d[29]), "+f"(d[30]), "+f"(d[31]), "+f"(d[32]), "+f"(d[33]), "+f"(d[34]), "+f"(d[35]), "+f"(d[36]), "+f"(d[37]), "+f"(d[38]), "+f"(d[39]), "+f"(d[40]), "+f"(d[41]), "+f"(d[42]), "+f"(d[43]), "+f"(d[44]), "+f"(d[45]), "+f"(d[46]), "+f"(d[47]), "+f"(d[48]), "+f"(d[49]), "+f"(d[50]), "+f"(d[51]), "+f"(d[52]), "+f"(d[53]), "+f"(d[54]), "+f"(d[55]), "+f"(d[56]), "+f"(d[57]), "+f"(d[58]), "+f"(d[59]), "+f"(d[60]), "+f"(d[61]), "+f"(d[62]), "+f"(d[63]), "+f"(d[64]), "+f"(d[65]), "+f"(d[66]), "+f"(d[67]), "+f"(d[68]), "+f"(d[69]), "+f"(d[70]), "+f"(d[71]), "+f"(d[72]), "+f"(d[73]), "+f"(d[74]), "+f"(d[75]), "+f"(d[76]), "+f"(d[77]), "+f"(d[78]), "+f"(d[79]), "+f"(d[80]), "+f"(d[81]), "+f"(d[82]), "+f"(d[83]), "+f"(d[84]), "+f"(d[85]), "+f"(d[86]), "+f"(d[87]), "+f"(d[88]), "+f"(d[89]), "+f"(d[90]), "+f"(d[91]), "+f"(d[92]), "+f"(d[93]), "+f"(d[94]), "+f"(d[95]), "+f"(d[96]), "+f"(d[97]), "+f"(d[98]), "+f"(d[99]), "+f"(d[100]), "+f"(d[101]), "+f"(d[102]), "+f"(d[103]), "+f"(d[104]), "+f"(d[105]), "+f"(d[106]), "+f"(d[107]), "+f"(d[108]), "+f"(d[109]), "+f"(d[110]), "+f"(d[111]), "+f"(d[112]), "+f"(d[113]), "+f"(d[114]), "+f"(d[115]), "+f"(d[116]), "+f"(d[117]), "+f"(d[118]), "+f"(d[119]), "+f"(d[120]), "+f"(d[121]), "+f"(d[122]), "+f"(d[123]), "+f"(d[124]), "+f"(d[125]), "+f"(d[126]), "+f"(d[127])
    : "l"(da), "l"(db), "r"(sd));
}

__device__ __forceinline__ void wgmma_m64n128_ss(float (&d)[64], uint64_t da, uint64_t db, int sd) {
  asm volatile(
    "{\n.reg .pred p;\nsetp.ne.b32 p, %66, 0;\n"
    "wgmma.mma_async.sync.aligned.m64n128k16.f32.bf16.bf16 "
    "{%0, %1, %2, %3, %4, %5, %6, %7, %8, %9, %10, %11, %12, %13, %14, %15, %16, %17, %18, %19, %20, %21, %22, %23, %24, %25, %26, %27, %28, %29, %30, %31, %32, %33, %34, %35, %36, %37, %38, %39, %40, %41, %42, %43, %44, %45, %46, %47, %48, %49, %50, %51, %52, %53, %54, %55, %56, %57, %58, %59, %60, %61, %62, %63}, %64, %65, p, 1, 1, 0, 0;\n}\n"
    : "+f"(d[0]), "+f"(d[1]), "+f"(d[2]), "+f"(d[3]), "+f"(d[4]), "+f"(d[5]), "+f"(d[6]), "+f"(d[7]), "+f"(d[8]), "+f"(d[9]), "+f"(d[10]), "+f"(d[11]), "+f"(d[12]), "+f"(d[13]), "+f"(d[14]), "+f"(d[15]), "+f"(d[16]), "+f"(d[17]), "+f"(d[18]), "+f"(d[19]), "+f"(d[20]), "+f"(d[21]), "+f"(d[22]), "+f"(d[23]), "+f"(d[24]), "+f"(d[25]), "+f"(d[26]), "+f"(d[27]), "+f"(d[28]), "+f"(d[29]), "+f"(d[30]), "+f"(d[31]), "+f"(d[32]), "+f"(d[33]), "+f"(d[34]), "+f"(d[35]), "+f"(d[36]), "+f"(d[37]), "+f"(d[38]), "+f"(d[39]), "+f"(d[40]), "+f"(d[41]), "+f"(d[42]), "+f"(d[43]), "+f"(d[44]), "+f"(d[45]), "+f"(d[46]), "+f"(d[47]), "+f"(d[48]), "+f"(d[49]), "+f"(d[50]), "+f"(d[51]), "+f"(d[52]), "+f"(d[53]), "+f"(d[54]), "+f"(d[55]), "+f"(d[56]), "+f"(d[57]), "+f"(d[58]), "+f"(d[59]), "+f"(d[60]), "+f"(d[61]), "+f"(d[62]), "+f"(d[63])
    : "l"(da), "l"(db), "r"(sd));
}

__device__ __forceinline__ void wgmma_m64n128_ss_tb(float (&d)[64], uint64_t da, uint64_t db, int sd) {
  asm volatile(
    "{\n.reg .pred p;\nsetp.ne.b32 p, %66, 0;\n"
    "wgmma.mma_async.sync.aligned.m64n128k16.f32.bf16.bf16 "
    "{%0, %1, %2, %3, %4, %5, %6, %7, %8, %9, %10, %11, %12, %13, %14, %15, %16, %17, %18, %19, %20, %21, %22, %23, %24, %25, %26, %27, %28, %29, %30, %31, %32, %33, %34, %35, %36, %37, %38, %39, %40, %41, %42, %43, %44, %45, %46, %47, %48, %49, %50, %51, %52, %53, %54, %55, %56, %57, %58, %59, %60, %61, %62, %63}, %64, %65, p, 1, 1, 0, 1;\n}\n"
    : "+f"(d[0]), "+f"(d[1]), "+f"(d[2]), "+f"(d[3]), "+f"(d[4]), "+f"(d[5]), "+f"(d[6]), "+f"(d[7]), "+f"(d[8]), "+f"(d[9]), "+f"(d[10]), "+f"(d[11]), "+f"(d[12]), "+f"(d[13]), "+f"(d[14]), "+f"(d[15]), "+f"(d[16]), "+f"(d[17]), "+f"(d[18]), "+f"(d[19]), "+f"(d[20]), "+f"(d[21]), "+f"(d[22]), "+f"(d[23]), "+f"(d[24]), "+f"(d[25]), "+f"(d[26]), "+f"(d[27]), "+f"(d[28]), "+f"(d[29]), "+f"(d[30]), "+f"(d[31]), "+f"(d[32]), "+f"(d[33]), "+f"(d[34]), "+f"(d[35]), "+f"(d[36]), "+f"(d[37]), "+f"(d[38]), "+f"(d[39]), "+f"(d[40]), "+f"(d[41]), "+f"(d[42]), "+f"(d[43]), "+f"(d[44]), "+f"(d[45]), "+f"(d[46]), "+f"(d[47]), "+f"(d[48]), "+f"(d[49]), "+f"(d[50]), "+f"(d[51]), "+f"(d[52]), "+f"(d[53]), "+f"(d[54]), "+f"(d[55]), "+f"(d[56]), "+f"(d[57]), "+f"(d[58]), "+f"(d[59]), "+f"(d[60]), "+f"(d[61]), "+f"(d[62]), "+f"(d[63])
    : "l"(da), "l"(db), "r"(sd));
}

__device__ __forceinline__ void wgmma_m64n128_rs_tb(float* d, uint32_t a0, uint32_t a1, uint32_t a2, uint32_t a3, uint64_t db, int sd) {
  asm volatile(
    "{\n.reg .pred p;\nsetp.ne.b32 p, %69, 0;\n"
    "wgmma.mma_async.sync.aligned.m64n128k16.f32.bf16.bf16 "
    "{%0, %1, %2, %3, %4, %5, %6, %7, %8, %9, %10, %11, %12, %13, %14, %15, %16, %17, %18, %19, %20, %21, %22, %23, %24, %25, %26, %27, %28, %29, %30, %31, %32, %33, %34, %35, %36, %37, %38, %39, %40, %41, %42, %43, %44, %45, %46, %47, %48, %49, %50, %51, %52, %53, %54, %55, %56, %57, %58, %59, %60, %61, %62, %63}, {%64, %65, %66, %67}, %68, p, 1, 1, 1;\n}\n"
    : "+f"(d[0]), "+f"(d[1]), "+f"(d[2]), "+f"(d[3]), "+f"(d[4]), "+f"(d[5]), "+f"(d[6]), "+f"(d[7]), "+f"(d[8]), "+f"(d[9]), "+f"(d[10]), "+f"(d[11]), "+f"(d[12]), "+f"(d[13]), "+f"(d[14]), "+f"(d[15]), "+f"(d[16]), "+f"(d[17]), "+f"(d[18]), "+f"(d[19]), "+f"(d[20]), "+f"(d[21]), "+f"(d[22]), "+f"(d[23]), "+f"(d[24]), "+f"(d[25]), "+f"(d[26]), "+f"(d[27]), "+f"(d[28]), "+f"(d[29]), "+f"(d[30]), "+f"(d[31]), "+f"(d[32]), "+f"(d[33]), "+f"(d[34]), "+f"(d[35]), "+f"(d[36]), "+f"(d[37]), "+f"(d[38]), "+f"(d[39]), "+f"(d[40]), "+f"(d[41]), "+f"(d[42]), "+f"(d[43]), "+f"(d[44]), "+f"(d[45]), "+f"(d[46]), "+f"(d[47]), "+f"(d[48]), "+f"(d[49]), "+f"(d[50]), "+f"(d[51]), "+f"(d[52]), "+f"(d[53]), "+f"(d[54]), "+f"(d[55]), "+f"(d[56]), "+f"(d[57]), "+f"(d[58]), "+f"(d[59]), "+f"(d[60]), "+f"(d[61]), "+f"(d[62]), "+f"(d[63])
    : "r"(a0), "r"(a1), "r"(a2), "r"(a3), "l"(db), "r"(sd));
}

__device__ __forceinline__ void wgmma_m64n64_rs_tb(float (&d)[32], const uint32_t (&a)[4], uint64_t db, int sd) {
  asm volatile(
    "{\n.reg .pred p;\nsetp.ne.b32 p, %37, 0;\n"
    "wgmma.mma_async.sync.aligned.m64n64k16.f32.bf16.bf16 "
    "{%0, %1, %2, %3, %4, %5, %6, %7, %8, %9, %10, %11, %12, %13, %14, %15, %16, %17, %18, %19, %20, %21, %22, %23, %24, %25, %26, %27, %28, %29, %30, %31}, {%32, %33, %34, %35}, %36, p, 1, 1, 1;\n}\n"
    : "+f"(d[0]), "+f"(d[1]), "+f"(d[2]), "+f"(d[3]), "+f"(d[4]), "+f"(d[5]), "+f"(d[6]), "+f"(d[7]), "+f"(d[8]), "+f"(d[9]), "+f"(d[10]), "+f"(d[11]), "+f"(d[12]), "+f"(d[13]), "+f"(d[14]), "+f"(d[15]), "+f"(d[16]), "+f"(d[17]), "+f"(d[18]), "+f"(d[19]), "+f"(d[20]), "+f"(d[21]), "+f"(d[22]), "+f"(d[23]), "+f"(d[24]), "+f"(d[25]), "+f"(d[26]), "+f"(d[27]), "+f"(d[28]), "+f"(d[29]), "+f"(d[30]), "+f"(d[31])
    : "r"(a[0]), "r"(a[1]), "r"(a[2]), "r"(a[3]), "l"(db), "r"(sd));
}

__device__ __forceinline__ void wgmma_m64n32_rs_tb(float (&d)[16], const uint32_t (&a)[4], uint64_t db, int sd) {
  asm volatile(
    "{\n.reg .pred p;\nsetp.ne.b32 p, %21, 0;\n"
    "wgmma.mma_async.sync.aligned.m64n32k16.f32.bf16.bf16 "
    "{%0, %1, %2, %3, %4, %5, %6, %7, %8, %9, %10, %11, %12, %13, %14, %15}, {%16, %17, %18, %19}, %20, p, 1, 1, 1;\n}\n"
    : "+f"(d[0]), "+f"(d[1]), "+f"(d[2]), "+f"(d[3]), "+f"(d[4]), "+f"(d[5]), "+f"(d[6]), "+f"(d[7]), "+f"(d[8]), "+f"(d[9]), "+f"(d[10]), "+f"(d[11]), "+f"(d[12]), "+f"(d[13]), "+f"(d[14]), "+f"(d[15])
    : "r"(a[0]), "r"(a[1]), "r"(a[2]), "r"(a[3]), "l"(db), "r"(sd));
}

constexpr int G_STAGES = 4;
constexpr int G_A_BYTES = 128 * 64 * 2;
constexpr int G_B_BYTES = 256 * 64 * 2;
constexpr int G_STAGE_BYTES = G_A_BYTES + G_B_BYTES;
constexpr int G_STG_OFF = G_STAGES * G_STAGE_BYTES;
constexpr int BAR_OFF = G_STG_OFF + 32768 + 2048;
constexpr int SMEM_BYTES = BAR_OFF + 1024;
constexpr int B_GFULL = 0, B_GEMPTY = 32, B_SEEN = 64, B_PFULL = 224;
constexpr int B_KFULL = 80, B_KEMPTY = 96, B_VFULL = 112, B_VEMPTY = 128, B_QFULL = 144, B_QEMPTY = 160,
              B_QDONE = 184;
constexpr int B_CFULL = 192;
constexpr int B_OFREE = 256, B_OFULL = 272, B_OEMPTY = 320, B_OY = 368, B_OY2 = 384, B_OE = 768;
constexpr int B_DEAL = 312, B_DEAL2 = 360, B_LIST = 640, B_PAIR = 504;
constexpr int B_SFULL = 392, B_SFREE = 424, B_PEND = 456, B_SCMD = 512;

#define PHASE_PROLOGUE                                                                \
  uint32_t tid, rt_zero;                                                              \
  asm volatile("mov.u32 %0, %%tid.x;" : "=r"(tid));                                   \
  asm volatile("mov.u32 %0, %%nctaid.y;" : "=r"(rt_zero));                            \
  asm volatile("" : "+r"(smem0));                                                     \
  rt_zero = __shfl_sync(0xffffffffu, rt_zero >> 8, 0);   \
  const uint32_t sbase = __shfl_sync(0xffffffffu, smem0, 0);                          \
  const uint32_t bar = sbase + BAR_OFF;                                               \
  const int wg = __shfl_sync(0xffffffffu, tid >> 7, 0);                               \
  const int warp = (tid >> 5) & 3, lane = tid & 31, wtid = tid & 127;                 \
  (void)rt_zero; (void)bar; (void)warp; (void)lane; (void)wtid;

enum { ST_END = 0, ST_BOX1, ST_BOX2, ST_BOX2Q, ST_BOX2L };
__device__ __forceinline__ void st_post(uint32_t bar, int wg, int wtid, uint32_t n, int kind, const void* dst,
                                        uint32_t src, int c0, int c1, int sig, uint32_t lazy = 0) {
  if (wtid == 0) {
    const uint32_t c = bar + B_SCMD + wg * 64 + (n & 1) * 32;
    const uint64_t d = reinterpret_cast<uint64_t>(dst);
    sts128(c, make_uint4(kind, src, c0, c1));
    sts128(c + 16, make_uint4((uint32_t)d, (uint32_t)(d >> 32), sig, lazy));
  }
  fence_proxy_async();
  __syncwarp();
  mbar_arrive_if(bar + B_SFULL + wg * 16 + (n & 1) * 8, (wtid & 31) == 0);
}
__device__ __forceinline__ void st_wait(uint32_t bar, int wg, uint32_t n) {
  const uint32_t b = bar + B_SFREE + wg * 16 + (n & 1) * 8;
  if (!mbar_try(b, ~(n >> 1) & 1)) mbar_wait(b, ~(n >> 1) & 1);
}
__device__ __forceinline__ void note(uint32_t bar, uint32_t cnt) {
  asm volatile("red.release.cta.shared.add.u32 [%0], 1;" ::"r"(bar + B_PEND + 4 * cnt) : "memory");
}
#define LAZY_NS 250
#define DEAL_NS 400
#define DEAL_NS2 1250
constexpr uint32_t C_NONE = 0x10000;
__device__ __forceinline__ void deal(uint32_t bar, uint32_t r, uint32_t t, uint32_t own) {
  uint64_t p;
  uint32_t spins = 0;
  while (true) {
    asm volatile("ld.relaxed.gpu.global.u64 %0, [%1];" : "=l"(p) : "l"(g_slot + 127 - r) : "memory");
    if (p || ++spins > (1u << 18)) break;
    __nanosleep(100);
  }
  const uint32_t pc = (uint32_t)p;
  int dt = (uint32_t)(p >> 32) - t;
  if (r >= 64) {
    sts128(bar + B_LIST, make_uint4(-dt > DEAL_NS2 ? C_NONE : own - 16, -dt > DEAL_NS ? C_NONE : own, C_NONE, C_NONE));
    mbar_arrive(bar + B_DEAL);
    dt = 0;
  }
  sts128(bar + B_LIST + 16, make_uint4(dt > DEAL_NS ? pc : C_NONE, dt > DEAL_NS2 ? pc - 16 : C_NONE, C_NONE, C_NONE));
  mbar_arrive(bar + B_DEAL2);
}
__device__ __forceinline__ void store_agent(uint32_t bar, int wg, uint32_t last_ch) {
  mbar_arrive(bar + B_SFREE + wg * 16);
  mbar_arrive(bar + B_SFREE + wg * 16 + 8);
  bool more = true;
  for (uint32_t n = 0;; n++) {
    mbar_wait_sleep(bar + B_SFULL + wg * 16 + (n & 1) * 8, (n >> 1) & 1);
    const uint4 c = lds128(bar + B_SCMD + wg * 64 + (n & 1) * 32);
    const uint4 d = lds128(bar + B_SCMD + wg * 64 + (n & 1) * 32 + 16);
    if (c.x == ST_END) break;
    uint32_t t;
    asm volatile("mov.u32 %0, %%globaltimer_lo;" : "=r"(t));
    for (uint32_t t1 = t; d.w && t1 - t < (2 * d.w + wg) * LAZY_NS;) {
      __nanosleep(200);
      asm volatile("mov.u32 %0, %%globaltimer_lo;" : "=r"(t1));
    }
    const CUtensorMap* dst = reinterpret_cast<const CUtensorMap*>((uint64_t)d.x | ((uint64_t)d.y << 32));
    tma_store_2d(dst, c.y, c.z, c.w);
    if (c.x >= ST_BOX2) tma_store_2d(dst, c.y + 8192, c.z + 64, c.w);
    tma_store_commit();
    uint32_t r = 0;
    if (c.x == ST_BOX2L && last_ch) {
      mbar_expect_tx(bar + B_PAIR, 4);
      asm volatile(
          "{\n.reg .b32 ra;\nmapa.shared::cluster.u32 ra, %0, %1;\n"
          "st.async.weak.shared::cluster.mbarrier::complete_tx::bytes.u32 [ra + 224], %2, [ra];\n}\n" ::"r"(bar + B_PAIR),
          "r"(~blockIdx.x & 1), "r"(t)
          : "memory");
    }
    tma_store_wait_read<0>();
    mbar_arrive(bar + B_SFREE + wg * 16 + (n & 1) * 8);
    if (c.x == ST_BOX2L) mbar_arrive(bar + B_OFREE + 8 * wg);
    if (c.x == ST_BOX2L && last_ch) {
      uint32_t tp;
      mbar_wait_sleep(bar + B_PAIR, 0);
      r = atomicAdd(g_cnt + CNT_RANK * 32, 1u) & 127;
      asm volatile("ld.shared.u32 %0, [%1];" : "=r"(tp) : "r"(bar + B_PAIR + 224) : "memory");
      if ((int)(tp - t) > 0) t = tp;
      asm volatile("st.relaxed.gpu.global.u64 [%0], %1;" ::"l"(g_slot + r), "l"(((uint64_t)t << 32) | last_ch) : "memory");
      if (r < 64) {
        sts128(bar + B_LIST, make_uint4(last_ch - 16, last_ch, C_NONE, C_NONE));
        mbar_arrive(bar + B_DEAL);
      }
    }
    if ((int)d.z >= 0) {
      tma_store_wait<0>();
      if (d.z == 0) { TD(6) }
      asm volatile("fence.proxy.async.global;" ::: "memory");
      if (c.x == ST_BOX2Q) mbar_arrive(bar + B_QDONE);
      else note(bar, d.z);
      if (c.x == ST_BOX2L) {
        note(bar, CNT_DONE);
        more = false;
        if (last_ch) deal(bar, r, t, last_ch);
      }
    }
  }
  if (more) note(bar, CNT_DONE);
}

struct Maps {
  const bf16 *shift_k, *x, *gate_w, *ssm_k, *ssm_D;
  uint8_t id[128][4];
  CUtensorMap a[2];
  CUtensorMap b[3];
  CUtensorMap c[3];
  CUtensorMap bk, bv;
  CUtensorMap q, k, v, o;
  CUtensorMap oa, ob, oc;
  CUtensorMap y, xs;
  CUtensorMap cu, ch;
};

constexpr int P_SLOT = 67 * 128, P_V = 35 * 128, P_TAPS = 2 * P_SLOT;
__device__ __forceinline__ void ldsm4t(uint32_t (&r)[4], uint32_t a) {
  asm volatile("ldmatrix.sync.aligned.m8n8.x4.trans.shared.b16 {%0, %1, %2, %3}, [%4];"
               : "=r"(r[0]), "=r"(r[1]), "=r"(r[2]), "=r"(r[3])
               : "r"(a));
}
__device__ __forceinline__ uint32_t fma_bf2(uint32_t a, uint32_t b, uint32_t c) {
  uint32_t r;
  asm("fma.rn.bf16x2 %0, %1, %2, %3;" : "=r"(r) : "r"(a), "r"(b), "r"(c));
  return r;
}
__device__ __forceinline__ void prep_agent(const Maps& maps, uint32_t sbase, int w, int lane) {
  const uint32_t bar = sbase + BAR_OFF, pb = bar + B_PFULL + w * 16;
  const int d0 = (blockIdx.x >> 3) * 64, t0 = (blockIdx.x & 7) * 256 + w * 128;
  mbar_wait_sleep(bar + B_GFULL + 8 * (G_STAGES - 1), 0);
#pragma unroll 1
  for (int i = -1; i < 4; i++) {
    GA(82 + 2 * i)
    if (i >= 0) mbar_wait_sleep(pb + (i & 1) * 8, i >> 1);
    GA(83 + 2 * i)
    const uint32_t so = sbase + G_STG_OFF + w * (P_TAPS + 512) + (i & 1) * P_SLOT;
    if (i < 3 && elect_one()) {
      const uint32_t b = pb + (~i & 1) * 8, dst = so + (i & 1 ? -P_SLOT : P_SLOT);
      mbar_expect_tx(b, i < 0 ? P_SLOT + 512 : P_SLOT);
      const uint64_t pol = policy_evict_first();
      tma_load_2d_hint(dst, &maps.bk, b, d0, t0 + 32 * i + 29, pol);
      tma_load_2d_hint(dst + P_V, &maps.bv, b, d0, t0 + 32 * i + 32, pol);
      if (i < 0) bulk_load(sbase + G_STG_OFF + P_TAPS, maps.shift_k + d0 * 4, 512, b);
    }
    if (i < 0) continue;
    uint32_t ak[4];
#pragma unroll
    for (int r = 0; r < 4; r++) {
      const uint32_t a = so / 128 + r + 4 * (lane & 6) + (((lane >> 2) ^ lane) & 6) + (lane & 1);
      ak[r] = a * 128 + (a & 7) * 16;
    }
    bf16* dst = g_kvT + (size_t)(d0 + (lane >> 2)) * S_LEN + t0 + ((lane & 3) + 4 * i) * 8;
#pragma unroll 1
    for (int cg = 0; cg < 128; cg += 16) {
      uint32_t t01, t23, k[4][4], v[4];
      asm volatile("ld.shared.v2.u32 {%0, %1}, [%2];"
                   : "=r"(t01), "=r"(t23)
                   : "r"(sbase + G_STG_OFF + P_TAPS + cg * 4 + (lane >> 2) * 8));
#pragma unroll
      for (int r = 0; r < 4; r++) ldsm4t(k[r], ak[r] ^ cg);
      ldsm4t(v, (ak[3] ^ cg) + 4096);
      const uint32_t w0 = __byte_perm(t01, 0, 0x1010), w1 = __byte_perm(t01, 0, 0x3232);
      const uint32_t w2 = __byte_perm(t23, 0, 0x1010), w3 = __byte_perm(t23, 0, 0x3232);
#pragma unroll
      for (int j = 0; j < 4; j++)
        v[j] = mul_bf2(fma_bf2(k[3][j], w0, fma_bf2(k[2][j], w1, fma_bf2(k[1][j], w2, mul_bf2(k[0][j], w3)))), v[j]);
      const bool s1 = lane & 1, s2 = lane & 2;
      const uint32_t a0 = s1 ? v[1] : v[0], a1 = s1 ? v[0] : v[1], a2 = s1 ? v[3] : v[2], a3 = s1 ? v[2] : v[3];
      *reinterpret_cast<uint4*>(dst) = make_uint4(s2 ? a2 : a0, s2 ? a3 : a1, s2 ? a0 : a2, s2 ? a1 : a3);
      dst += 8 * S_LEN;
    }
    fence_proxy_async();
    __syncwarp();
  }
  GA(90)
  if (lane == 0) note(bar, CNT_PREP);
  __syncwarp();
  GA(91)
}

__device__ __forceinline__ void qkv_tile(const Maps& maps, int it, int& which, int& m_tile, int& n_tile) {
  const bool q = it == 0 || it >= 5;
  const int b = maps.id[blockIdx.x][it >= 5];
  which = q ? 0 : 2 - (it & 1);
  m_tile = b & 15;
  n_tile = (b >> 4) * 2 + ((0x19 >> it) & 1);
}

constexpr int G_NTILES = 6;
__device__ __forceinline__ void qkv_producer(const Maps& maps, uint32_t sbase, bool first) {
  const uint32_t bar = sbase + BAR_OFF;
  uint32_t stage = 0, phase = 0;
#pragma unroll 1
  for (int it = 0; it < (first ? 1 : G_NTILES); it++) {
    int which, m_tile, n_tile;
    qkv_tile(maps, it, which, m_tile, n_tile);
    const CUtensorMap* ma = &maps.a[which == 0 ? 0 : 1];
    const CUtensorMap* mb = &maps.b[which];
    const int nk = first ? G_STAGES : which == 0 ? 16 : 8;
#pragma unroll 1
    for (int kt = (it == 0 && !first) ? G_STAGES : 0; kt < nk; kt++) {
      if (!first) mbar_wait_sleep(bar + B_GEMPTY + 8 * stage, phase);
      const uint32_t fb = bar + B_GFULL + 8 * stage;
      const uint32_t sa = sbase + stage * G_STAGE_BYTES;
      mbar_expect_tx(fb, G_STAGE_BYTES);
      tma_load_2d(sa, ma, fb, kt * 64, m_tile * 128);
      tma_load_3d(sa + G_A_BYTES, mb, fb, 0, kt * 64, n_tile * 4);
      if (++stage == G_STAGES) { stage = 0; phase ^= 1; }
      {
        const int b = maps.id[blockIdx.x][1];
        if (it == 2 && kt == (b & 7)) {
          for (int i = 0; i < 2; i++)
            asm volatile("cp.async.bulk.prefetch.tensor.2d.L2.global.tile [%0, {%1, %2}];" ::"l"(&maps.a[0]),
                         "r"((b >> 4) * 128 + i * 64), "r"((b & 15) * 128)
                         : "memory");
          asm volatile("cp.async.bulk.prefetch.tensor.3d.L2.global.tile [%0, {%1, %2, %3}];" ::"l"(&maps.b[1 + ((b >> 3) & 1)]),
                       "r"(0), "r"((b & 7) * 64), "r"((b >> 4) * 8 + 4)
                       : "memory");
        }
        if (it == 3 && kt == (b & 7))
          asm volatile("cp.async.bulk.prefetch.tensor.3d.L2.global.tile [%0, {%1, %2, %3}];" ::"l"(&maps.b[0]), "r"(0),
                       "r"((b & 15) * 64), "r"((b >> 4) * 8)
                       : "memory");
      }
    }
  }
}

__device__ __forceinline__ uint32_t seen_bar(uint32_t item) { return B_SEEN + ((0x700800u >> (8 * item)) & 255); }
__device__ __noinline__ void publisher(uint32_t bar, int lane, uint32_t nsrc, uint32_t item, uint32_t mine) {
  uint32_t done = 0, tot = 0;
#pragma unroll 1
  for (uint32_t spins = 0; (done < nsrc || item < 3) && spins < (1u << 20); spins++) {
    const uint32_t cnt = item ? CNT_CTX - 1 + item : CNT_KV + 1;
    if (item < 3 && __shfl_sync(0xffffffffu, tot, cnt) >= mine) {
      uint32_t v;
      asm volatile("ld.acquire.gpu.global.u32 %0, [%1];" : "=r"(v) : "l"(g_cnt + (lane ? cnt : CNT_PREP) * 32) : "memory");
      if (__all_sync(0xffffffffu, v >= (lane ? 512 : 260))) {
        asm volatile("fence.proxy.async.global;" ::: "memory");
        mbar_arrive_if(bar + seen_bar(item), lane == 0);
        item++;
      }
    }
    uint32_t v = 0;
    if (lane < CNT_N)
      asm volatile("atom.acquire.cta.shared.exch.b32 %0, [%1], 0;" : "=r"(v) : "r"(bar + B_PEND + 4 * lane) : "memory");
    done += __shfl_sync(0xffffffffu, v, CNT_DONE);
    if (lane == CNT_DONE) v = 0;
    if (done == nsrc && lane < CNT_DONE) {
      uint32_t w;
      asm volatile("atom.acquire.cta.shared.exch.b32 %0, [%1], 0;" : "=r"(w) : "r"(bar + B_PEND + 4 * lane) : "memory");
      v += w;
    }
    if (v && lane == 0) { TD(0) }
    if (v) cnt_signal_release(lane, v);
    tot += v;
    if (v && lane == 0) { TD(1) }
    if (!__any_sync(0xffffffffu, v != 0)) __nanosleep(item == 1 ? 1000 : 200);
  }
  __threadfence();
  __syncwarp();
}

__device__ __forceinline__ void gate_rows(const Maps& maps, uint32_t sbase, int w48, int w12, int lane) {
  const uint32_t buf = sbase + w12 * 16384, gb = sbase + BAR_OFF + 768 + w12 * 16;
  if (lane == 0) {
    mbar_init(gb, 1);
    mbar_init(gb + 8, 1);
    fence_barrier_init();
    for (int i = 0; i < 2; i++) {
      mbar_expect_tx(gb + 8 * i, 8192);
      bulk_load(buf + i * 8192, maps.x + (size_t)(w48 + 48 * i) * 4 * DM, 8192, gb + 8 * i);
    }
  }
  __syncwarp();
  uint4 wv[4];
#pragma unroll
  for (int i = 0; i < 4; i++) wv[i] = __ldg(reinterpret_cast<const uint4*>(maps.gate_w + (i * 32 + lane) * 8));
  int it = 0;
#pragma unroll 1
  for (int row = w48 * 4; row < S_LEN; row += 48 * 4, it++) {
    mbar_wait(gb + 8 * (it & 1), (it >> 1) & 1);
    uint4 xv[4][4];
#pragma unroll
    for (int r = 0; r < 4; r++)
#pragma unroll
      for (int i = 0; i < 4; i++) xv[r][i] = lds128(buf + (it & 1) * 8192 + r * 2048 + (i * 32 + lane) * 16);
    float d[2][4];
#pragma unroll
    for (int pr = 0; pr < 2; pr++) {
      d[pr][0] = d[pr][1] = d[pr][2] = d[pr][3] = 0.f;
      auto acc = [&](uint32_t a0, uint32_t a2, uint32_t b0, uint32_t b2, uint32_t w0, uint32_t w2) {
        asm volatile(
            "mma.sync.aligned.m16n8k16.row.col.f32.bf16.bf16.f32 {%0, %1, %2, %3}, {%4, %5, %6, %7}, {%8, %8}, "
            "{%0, %1, %2, %3};"
            : "+f"(d[pr][0]), "+f"(d[pr][1]), "+f"(d[pr][2]), "+f"(d[pr][3])
            : "r"(mul_bf2(a0, w0)), "r"(mul_bf2(b0, w0)), "r"(mul_bf2(a2, w2)), "r"(mul_bf2(b2, w2)), "r"(0x3f803f80u));
      };
#pragma unroll
      for (int i = 0; i < 4; i++) {
        acc(xv[2 * pr][i].x, xv[2 * pr][i].y, xv[2 * pr + 1][i].x, xv[2 * pr + 1][i].y, wv[i].x, wv[i].y);
        acc(xv[2 * pr][i].z, xv[2 * pr][i].w, xv[2 * pr + 1][i].z, xv[2 * pr + 1][i].w, wv[i].z, wv[i].w);
      }
    }
    float sum = (lane & 2) ? ((lane & 1) ? d[1][2] : d[1][0]) : ((lane & 1) ? d[0][2] : d[0][0]);
#pragma unroll
    for (int off = 16; off >= 4; off >>= 1) sum += __shfl_xor_sync(0xffffffffu, sum, off);
    if (lane < 4) g_gate[row + lane] = bf16_round(rcp(1.0f + __expf(-bf16_round(sum))));
    if (lane == 0 && row + 2 * 48 * 4 < S_LEN) {
      mbar_expect_tx(gb + 8 * (it & 1), 8192);
      bulk_load(buf + (it & 1) * 8192, maps.x + (size_t)(row + 2 * 48 * 4) * DM, 8192, gb + 8 * (it & 1));
    }
  }
}

constexpr float Q_SCALE = 0.08838834764831845f * 1.4426950408889634f;
__device__ __forceinline__ uint32_t qkv_consumer(const Maps& maps, uint32_t smem0, bool fused, float (&rest)[64]) {
  PHASE_PROLOGUE
  constexpr int NTILES = G_NTILES;
  float acc[128];
  uint32_t stage = 0, phase = 0;
  const uint32_t stg = sbase + G_STG_OFF + wg * 18432;
  const int st_row = warp * 16 + (lane & 7) + ((lane >> 3) & 1) * 8;
  const int st_cb = lane >> 4;
  uint32_t pend[64];
  const CUtensorMap* pend_map = nullptr;
  int pend_c0 = 0, pend_c1 = 0;
  uint32_t sn = 0;
  auto put_box = [&](uint32_t buf, const uint32_t* v) {
#pragma unroll
    for (int jp = 0; jp < 4; jp++) {
      const int chunk = jp * 2 + st_cb;
      const uint32_t addr = buf + st_row * 128 + ((chunk ^ (st_row & 7)) << 4);
      stmatrix_x4(addr, v[jp * 4], v[jp * 4 + 1], v[jp * 4 + 2], v[jp * 4 + 3]);
    }
  };
  GT(gti++)
#pragma unroll 1
  for (int it = 0; it <= NTILES; it++) {
    int which, m_tile, n_tile;
    qkv_tile(maps, it, which, m_tile, n_tile);
    const int nk = (which == 0 && it < NTILES) ? 16 : 8;
    uint32_t prev_stage = 0;
#pragma unroll 1
    for (int kt = 0; kt < nk; kt++) {
      if (it < NTILES) {
        mbar_wait((bar + B_GFULL) + 8 * stage, phase);
        GT(gti++)
        const uint64_t da0 = make_desc(sbase + stage * G_STAGE_BYTES + wg * 8192, 16, 1024, DESC_SW128);
        const uint64_t db0 = make_desc(sbase + stage * G_STAGE_BYTES + G_A_BYTES, 8192, 1024, DESC_SW128);
        wgmma_fence();
#pragma unroll
        for (int kk = 0; kk < 4; kk++) {
          wgmma_m64n256_ss_tb(acc, desc_add(da0, kk * 2), desc_add(db0, kk * 128), (kt | kk) != 0);
        }
        wgmma_commit();
      }
      const uint32_t when = it == 0 ? 0 : it == 5 ? 0x922 << wg : wg ? 0xAA : 0x55;
      if ((when >> kt) & 1) {
        const int c = __popc(when & ~(~0u << kt));
        st_wait(bar, wg, sn - 2);
        const uint32_t buf = stg + (c & 1) * 8192;
        switch (c) {
          case 0: put_box(buf, pend); break;
          case 1: put_box(buf, pend + 16); break;
          case 2: put_box(buf, pend + 32); break;
          default: put_box(buf, pend + 48); break;
        }
        st_post(bar, wg, wtid, sn, ST_BOX1, pend_map, buf, pend_c0 + c * 64, pend_c1, (c == 3 && it > 1) ? CNT_KV + (it > 3) : -1);
        sn++;
      }
      if (it < NTILES) {
        wgmma_wait<1>();
        mbar_arrive_if((bar + B_GEMPTY) + 8 * prev_stage, wtid == 32 && kt > 0);
        prev_stage = stage;
        if (++stage == G_STAGES) { stage = 0; phase ^= 1; }
      }
    }
    wgmma_wait<0>();
    fence_regs(acc);
    if (it == NTILES) break;
    GT(gti++)
    mbar_arrive_if((bar + B_GEMPTY) + 8 * prev_stage, wtid == 32);
    if (it == NTILES - 1 && fused) break;
    if (which == 0) {
#pragma unroll
      for (int j = 0; j < 128; j++) acc[j] *= Q_SCALE;
    }
#pragma unroll
    for (int j = 0; j < 64; j++) pend[j] = pack_bf16(acc[2 * j], acc[2 * j + 1]);
    pend_map = &maps.c[which];
    pend_c0 = n_tile * 256;
    pend_c1 = m_tile * 128 + wg * 64;
  }
  mbar_wait(bar + B_GEMPTY, 1);
#pragma unroll
  for (int j = 0; j < 32; j++) pend[j] = pack_bf16(acc[2 * j] * Q_SCALE, acc[2 * j + 1] * Q_SCALE);
  put_box(sbase + wg * 8192, pend);
  put_box(sbase + 16384 + wg * 8192, pend + 16);
  fence_proxy_async();
#pragma unroll
  for (int j = 0; j < 64; j++) rest[j] = acc[64 + j];
  GT(gti++)
  return sn;
}

constexpr int A_TILE = 128 * 128 * 2;
constexpr int A_Q_OFF = 0;
constexpr int A_K_OFF = 2 * A_TILE;
constexpr int A_V_OFF = 4 * A_TILE;
constexpr int A_O_OFF = 6 * A_TILE;
constexpr int A_ITEMS = NH * (S_LEN / 128);

constexpr uint32_t A_ORDER = 0x3120, A_STEPS = 34;
__device__ __forceinline__ int item_m(uint32_t it) { return it & 15; }
__device__ __forceinline__ int item_h(uint32_t it) { return it >> 4; }

constexpr int C_V = 16384, C_MAT = 24576;
constexpr float C_ALPHA = 0.07874506561842957f;
__device__ __forceinline__ void sincos_turn(int p, float inv, float& c, float& s) {
  const float a = (float)p * (inv * 6.283185307179586f);
  asm("cos.approx.ftz.f32 %0, %1;" : "=f"(c) : "f"(a));
  asm("sin.approx.ftz.f32 %0, %1;" : "=f"(s) : "f"(a));
}

__device__ __forceinline__ uint32_t item_of(const Maps& maps, uint32_t r) {
  const uint32_t b = maps.id[blockIdx.x & 127][1];
  return (b >> 4) * 64 + ((A_ORDER >> (4 * r)) & 3) * 16 + ((b ^ ((r & 1) * 15)) & 15);
}

#define PACE 250
#define SPACE 0
#define LCHK 1
#define XMASK 3
#define XFIRST 4
#define C_SIDE 64
__device__ __forceinline__ uint32_t conv_first(const Maps& maps) {
  const uint32_t b = maps.id[blockIdx.x & 127][1];
  return (b >> 4) * 128 + ((b + 15) & 15);
}

__device__ __forceinline__ void conv_consumer(const Maps& maps, uint32_t smem0, uint32_t first, uint32_t step,
                                              uint32_t end, bool pp, bool dealt) {
  PHASE_PROLOGUE
  const uint32_t in_full = bar + B_CFULL + wg * 16;
  const uint32_t ca = sbase + (wg ? A_V_OFF + A_TILE : A_Q_OFF);
  const int w = __shfl_sync(0xffffffffu, warp, 0), g = lane >> 2, c = lane & 3;
  auto fetch = [&](uint32_t ch, uint32_t n) {
    if (w == 2 && ch < C_NONE) {
      if (elect_one()) {
        const uint32_t b = in_full + (n & 1) * 8, d = ca + (n & 1) * 8192;
        const uint64_t pol = policy_evict_first();
        mbar_expect_tx(b, 8192);
        tma_load_2d_hint(d, &maps.cu, b, 0, ch * 64, pol);
        tma_load_2d_hint(d + 4096, &maps.ch, b, 0, ch * 64, pol);
      }
    }
  };
  if (wtid == 96 && wg) { TD(15) }
  uint32_t f1[8][4];
  float tt[16], ts[16];
  uint32_t cc[4], ss[4];
#pragma unroll
  for (int i = 0; i < 16; i++) {
    const int k = 2 * (16 * w + g + 8 * (i & 1)) + 1, n = 2 * (8 * (i >> 1) + 2 * c) + 1;
    float c0, s0, c1, s1;
    sincos_turn(((k * n) << 23) >> 23, 1.f / 512, c0, s0);
    sincos_turn(((k * n + 2 * k) << 23) >> 23, 1.f / 512, c1, s1);
    f1[i >> 2][i & 3] = pack_bf16(c0 * C_ALPHA, c1 * C_ALPHA);
    f1[4 + (i >> 2)][i & 3] = pack_bf16(s0 * -C_ALPHA, s1 * -C_ALPHA);
  }
#pragma unroll
  for (int i = 0; i < 16; i++) {
    const int k = 2 * (16 * w + g + 8 * ((i >> 1) & 1)) + 1, n = 16 - (8 * (i >> 2) + 2 * c + (i & 1));
    float cs;
    sincos_turn(k * n, 1.f / 8192, cs, ts[i]);
    tt[i] = ts[i] * rcp(1.f + cs);
  }
#pragma unroll
  for (int j = 0; j < 4; j++) {
    const int k = 8 * w + g, n = 8 * c + 2 * j;
    float c0, s0, c1, s1;
    sincos_turn((int8_t)(k * n * 8), 1.f / 256, c0, s0);
    sincos_turn((int8_t)((k * n + k) * 8), 1.f / 256, c1, s1);
    cc[j] = pack_bf16(c0, c1);
    ss[j] = pack_bf16(s0, s1);
  }
  named_bar_sync(3, 256);
  fetch(first, 0);
  fetch(first + step, 1);
  const uint32_t va = ca + g * 64 + ((c ^ (g >> 1)) << 4);
  {
    const uint32_t a = va + C_MAT + w * 512, m = 0x80008000u;
    sts128(a, make_uint4(cc[0], cc[1], cc[2], cc[3]));
    sts128(a + 2048, make_uint4(ss[0], ss[1], ss[2], ss[3]));
    sts128(a + 4096, make_uint4(ss[0] ^ m, ss[1] ^ m, ss[2] ^ m, ss[3] ^ m));
    sts128(a + 6144, make_uint4(cc[0], cc[1], cc[2], cc[3]));
  }
  fence_proxy_async();
  named_bar_sync(1 + wg, 128);
  constexpr uint64_t DHI = (2ull << 62) | ((uint64_t)(512 >> 4) << 32);
  const uint32_t d0 = (uint32_t)make_desc(ca, 4096, 0, 0);
  float a5[16];
  uint4* const yb = reinterpret_cast<uint4*>(g_y2T) + (16 * w + g) * 4 + c;
  auto issue5 = [&]() {
#pragma unroll
    for (int ks = 0; ks < 8; ks++) wgmma_m64n32_rs_tb(a5, f1[ks], DHI | (d0 + (C_V >> 4) + ks * 64), ks != 0);
    wgmma_commit();
  };
  auto finish = [&](uint32_t ch, bool on) {
    fence_regs(a5);
    uint4* y = yb + (size_t)ch * 256;
    if (on) {
      y[0] = make_uint4(pack_bf16(a5[0], a5[1]), pack_bf16(a5[4], a5[5]), pack_bf16(a5[8], a5[9]), pack_bf16(a5[12], a5[13]));
      y[32] = make_uint4(pack_bf16(a5[2], a5[3]), pack_bf16(a5[6], a5[7]), pack_bf16(a5[10], a5[11]), pack_bf16(a5[14], a5[15]));
    }
  };
  auto dft32 = [&](float (&d)[32], const float* re, const float* im) {
    uint32_t a[4][4];
#pragma unroll
    for (int i = 0; i < 8; i++) {
      a[i >> 2][i & 3] = pack_bf16(re[2 * i], re[2 * i + 1]);
      a[2 + (i >> 2)][i & 3] = pack_bf16(im[2 * i], im[2 * i + 1]);
    }
    wgmma_fence();
#pragma unroll
    for (int ks = 0; ks < 4; ks++) wgmma_m64n64_rs_tb(d, a[ks], DHI | (d0 + (C_MAT >> 4) + ks * 64), ks != 0);
    wgmma_commit();
  };
  auto rot = [&](float* x, float* y) {
#pragma unroll
    for (int i = 0; i < 16; i++) {
      x[i] = fmaf(-tt[i], y[i], x[i]);
      y[i] = fmaf(ts[i], x[i], y[i]);
      x[i] = fmaf(-tt[i], y[i], x[i]);
    }
  };
  auto load_d = [&](uint32_t ch) {
    return __ldg(reinterpret_cast<const unsigned short*>(maps.ssm_D) + ((ch & (DM - 1)) | (lane & rt_zero)));
  };
  uint32_t dn = load_d(first);
  uint32_t n = 0, prev = 0, ch = first, next = first + step;
#pragma unroll 1
  for (; ch < C_NONE; n++) {
    CT(0)
    float a1[2][32], a2[2][32], a4[32];
    const float dsk = c ? 0.f : __uint_as_float(dn << 16) * C_ALPHA;
    dn = load_d(next);
    uint32_t next2 = next + step < end ? next + step : C_NONE;
    mbar_wait(in_full + (n & 1) * 8, (n >> 1) & 1);
    if (pp) named_bar_sync(4 + wg, 256);
    CT(1)
    wgmma_fence();
#pragma unroll
    for (int ks = 0; ks < 8; ks++)
      wgmma_m64n64_rs_tb(a1[ks >> 2], f1[ks], DHI | (d0 + (n & 1) * 512 + (ks & 3) * 64), (ks & 3) != 0);
    wgmma_commit();
    issue5();
    wgmma_wait<1>();
    fence_regs(a1[0]);
    fence_regs(a1[1]);
    CT(2)
    rot(a1[0], a1[1]);
    dft32(a2[0], a1[0], a1[1]);
    rot(a1[0] + 16, a1[1] + 16);
    a1[0][16] += dsk;
    a1[0][18] += dsk;
    dft32(a2[1], a1[0] + 16, a1[1] + 16);
    CT(3)
    wgmma_wait<2>();
    finish(prev, n > 0);
    wgmma_wait<0>();
    fence_regs(a2[0]);
    fence_regs(a2[1]);
    CT(4)
    if (pp) named_bar_arrive(5 - wg, 256);
    float re[16], im[16];
#pragma unroll
    for (int i = 0; i < 16; i++) {
      re[i] = a2[0][i] * a2[1][i] - a2[0][16 + i] * a2[1][16 + i];
      im[i] = a2[0][i] * a2[1][16 + i] + a2[0][16 + i] * a2[1][i];
    }
    dft32(a4, im, re);
    if (dealt) {
      mbar_wait(bar + (n < 2 ? B_DEAL : B_DEAL2), 0);
      asm volatile("ld.shared.u32 %0, [%1];" : "=r"(next2) : "r"(bar + B_LIST + 4 * n + (n < 2 ? 0 : 8)));
    }
    wgmma_wait<0>();
    fence_regs(a4);
    CT(5)
    rot(a4, a4 + 16);
#pragma unroll
    for (int i = 0; i < 4; i++) {
      const float* x = a4 + 16 - 16 * (i >> 1) + 2 * (i & 1);
      sts128(va + C_V + w * 1024 + (i >> 1) * 4096 + (i & 1) * 512,
             make_uint4(pack_bf16(x[0], x[1]), pack_bf16(x[4], x[5]), pack_bf16(x[8], x[9]), pack_bf16(x[12], x[13])));
    }
    CT(6)
    fence_proxy_async();
    named_bar_sync(1 + wg, 128);
    fetch(next2, n);
    if (wtid == 96 && n > 0) note(bar, CNT_Y2 + ((prev & 112) == 112));
    prev = ch;
    ch = next;
    next = next2;
    CT(7)
  }
  wgmma_fence();
  issue5();
  wgmma_wait<0>();
  finish(prev, (dn | ~rt_zero) != 0);
  named_bar_sync(1 + wg, 128);
  if (wtid == 96 && wg) { TD(8) }
  if (wtid == 96) cnt_signal_release(CNT_Y2 + ((prev & 112) == 112), 1);
  if (wtid == 64) note(bar, CNT_DONE);
  if (wtid == 96 && wg) { TD(9) }
}

__device__ __forceinline__ void attn_producer(const Maps& maps, uint32_t sbase, bool after_qkv, bool to_out,
                                              bool dry) {
  const uint32_t bar = sbase + BAR_OFF;
  const uint32_t q_full = bar + B_QFULL, q_empty = bar + B_QEMPTY;
  const uint32_t k_full = bar + B_KFULL, k_empty = bar + B_KEMPTY, v_full = bar + B_VFULL, v_empty = bar + B_VEMPTY;
  int ndrained = after_qkv ? 0 : G_STAGES;
  auto wait = [&](uint32_t b, uint32_t par) {
    if (!dry) mbar_wait_sleep(b, par);
  };
  auto drained = [&](int upto) {
#pragma unroll 1
    for (; ndrained <= upto; ndrained++) wait(bar + B_GEMPTY + 8 * ndrained, 1);
  };
  uint32_t st = 0, ph = 1, vs = 0, vp = 1;
  int pend_j = -1, pend_h = 0;
  int round = -1, m = -1, h = 0;
  bool last = false;
#pragma unroll 1
  for (;; round++) {
    uint32_t nitem = 0;
    const int tpost = m >= 3 ? m - 1 : m;
#pragma unroll 1
    for (int t = m < 0 ? -1 : 0; t <= m; t++) {
      const int j = (t < m && (round & 1)) ? m - 1 - t : t;
      if (t >= 0) {
        drained(1 + st);
        wait(k_empty + 8 * st, ph);
        if (!dry) {
          mbar_expect_tx(k_full + 8 * st, A_TILE);
          tma_load_3d(sbase + A_K_OFF + st * A_TILE, &maps.k, k_full + 8 * st, 0, j * 128, h * 2);
        }
        if (++st == 2) { st = 0; ph ^= 1; }
      }
      if (pend_j >= 0) {
        drained(3);
        wait(v_empty + 8 * vs, vp);
        if (!dry) {
          mbar_expect_tx(v_full + 8 * vs, A_TILE);
          tma_load_3d(sbase + A_V_OFF + vs * A_TILE, &maps.v, v_full + 8 * vs, 0, pend_j * 128, pend_h * 2);
        }
        if (++vs == 2) { vs = 0; vp ^= 1; }
      }
      pend_j = j;
      pend_h = h;
      if (t == tpost && !last) {
        nitem = dry ? 1 : item_of(maps, round + 1);
        if (round == (dry ? 0 : 3) || blockIdx.x >= 128) {
          nitem = A_ITEMS;
          if (!to_out) cnt_wait(CNT_PREP, dry ? 0 : 260);
          if (to_out) {
            wait(bar + seen_bar(1), 0);
            asm volatile("cp.async.bulk.prefetch.L2.global [%0], 4096;" ::"l"(maps.ssm_k + (size_t)conv_first(maps) * S_LEN));
            if (!dry)
              asm volatile("cp.async.bulk.prefetch.L2.global [%0], 4096;" ::"l"(g_kvT + (size_t)conv_first(maps) * S_LEN));
          }
        }
        const uint32_t qs = (round + 1) & 1;
        wait(q_empty + 8 * qs, (((round + 1) >> 1) & 1) ^ 1);
        if (round == 1 && after_qkv) wait(bar + B_QDONE, 0);
        if (round == 0 && after_qkv) wait(bar + seen_bar(0), 0);
        if (round < 0 && after_qkv) {
          if (!dry) { TD(2) }
          cnt_wait(CNT_KV, dry ? 0 : 512);
          if (!dry) { TD(3) }
        }
        if (nitem >= A_ITEMS || (round < 0 && after_qkv && !dry)) {
          if (!dry) mbar_arrive(q_full + 8 * qs);
        } else {
          drained(qs);
          if (!dry) {
            mbar_expect_tx(q_full + 8 * qs, A_TILE);
            tma_load_3d_hint(sbase + A_Q_OFF + qs * A_TILE, &maps.q, q_full + 8 * qs, 0, item_m(nitem) * 128,
                             item_h(nitem) * 2, policy_evict_first());
          }
        }
      }
    }
    if (last) break;
    last = nitem >= A_ITEMS;
    m = last ? -1 : item_m(nitem);
    h = item_h(nitem);
  }
}

__device__ __forceinline__ uint32_t attn_consumer(const Maps& maps, uint32_t smem0, uint32_t sn,
                                                  float (&rest)[64], bool after_qkv) {
  PHASE_PROLOGUE
  const uint32_t q_full = bar + B_QFULL, q_empty = bar + B_QEMPTY;
  const uint32_t k_full = bar + B_KFULL, k_empty = bar + B_KEMPTY, v_full = bar + B_VFULL;
  float o[64], s[64];
  uint32_t p[32];
  float e[32];
  uint32_t dep = 0;
  constexpr int MIDJ = 5;
  float l0 = 0.f, l1 = 0.f, b0 = 0.f, b1 = 0.f;
  const int sched_own = 4 + wg, sched_other = 5 - wg;
  if (wg == 1) named_bar_arrive(4, 256);

  const uint32_t qd0 = (uint32_t)make_desc(sbase + A_Q_OFF + wg * 8192, 16, 0, 0);
  const uint32_t kd0 = (uint32_t)make_desc(sbase + A_K_OFF, 16, 0, 0);
  const uint32_t vd0 = (uint32_t)make_desc(sbase + A_V_OFF, 16384, 0, 0);
  constexpr uint64_t DHI = DESC_SW128 | ((uint64_t)(1024 >> 4) << 32);
  constexpr uint32_t DST = A_TILE >> 4;
  auto issue_qk = [&](uint32_t qd, uint32_t kd) {
#pragma unroll
    for (int kk = 0; kk < 8; kk++) {
      const uint32_t off = ((kk >> 2) * 16384 + (kk & 3) * 32) >> 4;
      wgmma_m64n128_ss(s, DHI | (qd + off), DHI | (kd + off), kk != 0);
    }
    wgmma_commit();
  };
  auto issue_pv = [&](uint32_t vd, bool accumulate, int nk) {
#pragma unroll
    for (int kk = 0; kk < 8; kk++) {
      if (kk < nk)
        wgmma_m64n128_rs_tb(o, p[4 * kk], p[4 * kk + 1], p[4 * kk + 2], p[4 * kk + 3], DHI | (vd + kk * 128),
                            accumulate || (kk != 0));
    }
    wgmma_commit();
  };
  auto exp_lo = [&](float& a0, float& a1) {
#pragma unroll
    for (int j = 0; j < 8; j++) {
      e[4 * j] = ex2(s[4 * j]);
      e[4 * j + 1] = ex2(s[4 * j + 1]);
      e[4 * j + 2] = ex2(s[4 * j + 2]);
      e[4 * j + 3] = ex2(s[4 * j + 3]);
      a0 += e[4 * j];
      a0 += e[4 * j + 1];
      a1 += e[4 * j + 2];
      a1 += e[4 * j + 3];
      if (j == MIDJ) dep = (__float_as_uint(a0) | __float_as_uint(a1)) & rt_zero;
    }
  };
  auto pack_lo = [&]() {
#pragma unroll
    for (int j = 0; j < 16; j++) p[j] = pack_bf16(e[2 * j], e[2 * j + 1]);
  };
  auto finish_p = [&](float& a0, float& a1) {
    pack_lo();
#pragma unroll
    for (int j = 8; j < 16; j++) {
      const float e0 = ex2(s[4 * j]), e1 = ex2(s[4 * j + 1]), e2 = ex2(s[4 * j + 2]), e3 = ex2(s[4 * j + 3]);
      a0 += e0;
      a0 += e1;
      a1 += e2;
      a1 += e3;
      p[2 * j] = pack_bf16(e0, e1);
      p[2 * j + 1] = pack_bf16(e2, e3);
      if (j == 8 + MIDJ) dep = __float_as_uint(a0) & rt_zero;
    }
  };
  auto quad_sum = [&](float t) {
    t += __shfl_xor_sync(0xffffffffu, t, 1);
    return t + __shfl_xor_sync(0xffffffffu, t, 2);
  };
  auto write_o = [&](float i0, float i1) {
    st_wait(bar, wg, sn - 1);
    const int st_row = warp * 16 + (lane & 7) + ((lane >> 3) & 1) * 8;
    const uint32_t so = sbase + A_O_OFF + wg * 16384 + st_row * 128;
#pragma unroll
    for (int j = 0; j < 16; j += 2)
      stmatrix_x4(so + (j >> 3) * 8192 + ((((j & 7) + (lane >> 4)) ^ (lane & 7)) << 4),
                  pack_bf16(o[4 * j] * i0, o[4 * j + 1] * i0), pack_bf16(o[4 * j + 2] * i1, o[4 * j + 3] * i1),
                  pack_bf16(o[4 * j + 4] * i0, o[4 * j + 5] * i0), pack_bf16(o[4 * j + 6] * i1, o[4 * j + 7] * i1));
  };
  auto store_o = [&](uint32_t r, int kind, uint32_t lazy) {
    const uint32_t it = item_of(maps, r);
    st_post(bar, wg, wtid, sn, kind, (INPLACE & 1) || kind != ST_BOX2Q ? &maps.o : &maps.c[0], sbase + A_O_OFF + wg * 16384, item_h(it) * 128,
            item_m(it) * 128 + wg * 64, CNT_CTX + (r >> 1), lazy);
    sn++;
  };
  auto mask_half = [&](float* sh) {
    const int u = warp * 16 + (lane >> 2) - (lane & 3) * 2;
#pragma unroll
    for (int j = 0; j < 8; j++) {
      if (8 * j > u) sh[4 * j] = -INFINITY;
      if (8 * j + 1 > u) sh[4 * j + 1] = -INFINITY;
      if (8 * j - 8 > u) sh[4 * j + 2] = -INFINITY;
      if (8 * j - 7 > u) sh[4 * j + 3] = -INFINITY;
    }
  };
  ST(0)
  mbar_wait(q_full, 0);
  if (blockIdx.x >= 128) {
    return sn;
  }
  mbar_wait(k_full, 0);
  named_bar_sync(sched_own, 256);
  wgmma_fence();
  issue_qk(qd0, kd0);
  named_bar_arrive(sched_other, 256);
  fence_regs(rest);
#pragma unroll
  for (int i = 0; i < 64; i++) o[i] = rest[i] * Q_SCALE;
  fence_regs(o);
  wgmma_wait<0>();
  fence_regs(s);
  mbar_arrive_if(k_empty, wtid == 32);
  uint32_t g = 0;
  uint32_t rnd = 0;
  int rem = item_m(item_of(maps, 0));
  uint32_t first = 1;
  uint32_t fl = 0;
#define redo (fl & 1)
#define shifted (fl & 2)
  float d0 = 0.f, d1 = 0.f;
  float pi0 = 1.f, pi1 = 1.f;
  ST(1)
  for (;;) {
    if (shifted) {
#pragma unroll
      for (int j = 0; j < 16; j++) {
        s[4 * j] -= d0;
        s[4 * j + 1] -= d0;
        s[4 * j + 2] -= d1;
        s[4 * j + 3] -= d1;
      }
    }
    if (rem == 0 && !redo) {
      mbar_arrive_if(q_empty + 8 * (rnd & 1), wtid == 96);
      rnd++;
      if (wg == 0) mask_half(s);
      else mask_half(s + 32);
    }
    for (;;) {
      const bool kill = rem == 0 && wg == 0;
      const uint32_t kd = kd0 + ((g + 1) & 1) * DST, vd = vd0 + (g & 1) * DST;
      float a0 = 0.f, a1 = 0.f;
      exp_lo(a0, a1);
      fence_regs(e);
      const uint32_t kb = k_full + 8 * ((g + 1) & 1);
      const uint32_t kpar = (((g + 1) >> 1) & 1) ^ (g == A_STEPS - 1 ? 1u : 0u);
      const uint32_t qb = q_full + 8 * (rnd & 1), qpar = ((rnd >> 1) & 1) | dep;
      if (!mbar_try(qb, qpar)) mbar_wait(qb, qpar | ((__float_as_uint(a0) | __float_as_uint(a1)) & rt_zero));
      wgmma_wait<0>();
      fence_regs(o);
      if (kill) {
        mbar_arrive_if(kb + (B_VEMPTY - B_KFULL), wtid == 64 && !redo && g > 0);
        fence_regs(e);
        pack_lo();
#pragma unroll
        for (int j = 16; j < 32; j++) asm volatile("mov.u32 %0, 0;" : "=r"(p[j]));
        goto check;
      }
#pragma unroll
      for (int i = 32; i < 64; i++) asm volatile("" : "+f"(s[i])::"memory");
      mbar_arrive_if(kb + (B_VEMPTY - B_KFULL), wtid == 64 && !redo && g > 0);
      finish_p(a0, a1);
      if (__any_sync(0xffffffffu, !(mbar_try(v_full + 8 * (g & 1), ((g >> 1) & 1) | dep) &
                                    mbar_try(kb, kpar | dep)) ||
                                      !(a0 + a1 < 1.0995116e12f) || !(fminf(a0, a1) > (first ? 9.094947e-13f : -1.f)))) {
      check:
        bool bad = !(a0 + a1 < 1.0995116e12f);
        if (first) bad |= !(fminf(quad_sum(a0), quad_sum(a1)) > 9.094947e-13f);
        if (!redo && __any_sync(0xffffffffu, bad)) {
          d0 = d1 = first ? -INFINITY : 0.f;
#pragma unroll
          for (int j = 0; j < 16; j++) {
            if (j < 8 || !kill) {
              d0 = fmaxf(d0, fmaxf(s[4 * j], s[4 * j + 1]));
              d1 = fmaxf(d1, fmaxf(s[4 * j + 2], s[4 * j + 3]));
            }
          }
#pragma unroll
          for (int x = 1; x <= 2; x++) {
            d0 = fmaxf(d0, __shfl_xor_sync(0xffffffffu, d0, x));
            d1 = fmaxf(d1, __shfl_xor_sync(0xffffffffu, d1, x));
          }
          b0 += d0;
          b1 += d1;
          if (!first) {
            const float al0 = ex2(-d0), al1 = ex2(-d1);
            l0 *= al0;
            l1 *= al1;
#pragma unroll
            for (int j = 0; j < 16; j++) {
              o[4 * j] *= al0;
              o[4 * j + 1] *= al0;
              o[4 * j + 2] *= al1;
              o[4 * j + 3] *= al1;
            }
          }
          fl = 3;
          break;
        }
        mbar_wait(v_full + 8 * (g & 1), (g >> 1) & 1);
        mbar_wait(kb, kpar);
      }
      named_bar_sync(sched_own, 256);
      if (g == A_STEPS - 1) {
        if (first) write_o(pi0, pi1);
        fence_regs(o);
        wgmma_fence();
        issue_pv(vd, !first, 8);
        named_bar_arrive(sched_other, 256);
        if (first) store_o(rnd - 2, ST_BOX2, 0);
        pi0 = rcp(quad_sum(l0 + a0));
        pi1 = rcp(quad_sum(l1 + a1));
        goto done;
      }
      wgmma_fence();
      issue_qk(qd0 + (rnd & 1) * DST, kd);
      if (first) write_o(pi0, pi1);
      fence_regs(o);
      if (kill) {
        wgmma_fence();
        issue_pv(vd, !first, 4);
      } else {
        wgmma_fence();
        issue_pv(vd, !first, 8);
      }
      named_bar_arrive(sched_other, 256);
      fl &= 2;
      l0 += a0;
      l1 += a1;
      if (rem == 0 || first) {
        if (first && (g > 0 || after_qkv)) store_o(g ? rnd - (rem == 0 ? 2 : 1) : 2, g ? ST_BOX2 : ST_BOX2Q, rem);
        first = rem == 0;
        if (first) {
          pi0 = rcp(quad_sum(l0));
          pi1 = rcp(quad_sum(l1));
          l0 = l1 = b0 = b1 = 0.f;
          fl = 0;
          rem = item_m(item_of(maps, rnd)) + 1;
        }
      }
      rem--;
      g++;
      wgmma_wait<1>();
      fence_regs(s);
      mbar_arrive_if(kb + (B_KEMPTY - B_KFULL), wtid == 32);
      ST(g + 1)
      if (rem == 0 || shifted) {
        d0 = b0;
        d1 = b1;
        break;
      }
    }
  }
done:
#undef redo
#undef shifted
  wgmma_wait<0>();
  fence_regs(o);
  write_o(pi0, pi1);
  store_o(3, ST_BOX2L, 0);
  ST(35)
  return sn;
}

constexpr int O_STAGES = 5;
constexpr int O_STAGE_BYTES = 32768;
constexpr int O_Y_OFF = 5 * 32768;
constexpr int O_X_OFF = 6 * 32768;
constexpr int O_NK = HDIM / 64;

__device__ __forceinline__ uint32_t out_stage(uint32_t st) { return ((0x43120u >> (4 * st)) & 7) * O_STAGE_BYTES; }

__device__ __forceinline__ void out_producer(const Maps& maps, uint32_t sbase, bool after_attn, bool dry) {
  const uint32_t bar = sbase + BAR_OFF;
  const uint32_t rank = blockIdx.x & 1;
  const int m_tile = maps.id[blockIdx.x][2] & 15, n_tile = maps.id[blockIdx.x][2] >> 4;
  uint32_t stage = 0, phase = 0, xi = 0;
#pragma unroll 1
  for (int ki = 0; ki < (dry ? 1 : O_NK); ki++) {
    const int kt = (ki & 14) * 4 + ((A_ORDER >> ((ki >> 4) * 4)) & 3) * 2 + (ki & 1);
    const uint32_t fb = bar + B_OFULL + 8 * stage, eb = bar + B_OEMPTY + 8 * stage;
    const uint32_t sa = sbase + out_stage(stage);
    if (ki < O_STAGES) {
      constexpr uint32_t LASTB = B_KEMPTY | ((B_QEMPTY + 8) << 8) | ((B_KEMPTY + 8) << 16) | (B_VEMPTY << 24);
      if (ki > 0 && after_attn) mbar_wait_sleep(bar + ((LASTB >> (8 * ki - 8)) & 255), ki == 2);
      mbar_arrive_cluster_if(eb, 0, !dry);
      mbar_arrive_cluster_if(eb, 1, !dry);
    }
    if (ki == 32) mbar_wait_sleep(bar + seen_bar(2), 0);
    if (!dry) {
      mbar_wait_sleep(eb, phase);
      mbar_expect_tx(fb, O_STAGE_BYTES);
      tma_load_2d_mc(sa + 16384 + rank * 8192, &maps.ob, fb, n_tile * 128 + rank * 64, kt * 64, (uint16_t)3);
      tma_load_2d(sa, &maps.oa, fb, kt * 64, m_tile * 128);
    }
    if (++stage == O_STAGES) { stage = 0; phase ^= 1; }
    if ((ki & XMASK) == XMASK && ki >= XFIRST && xi < 8) {
      if (after_attn && xi < 2) mbar_wait_sleep(bar + B_OFREE + 8 * xi, 0);
      tma_load_3d(sbase + O_X_OFF + (xi & 1) * 16384 + (xi >> 1) * 4096, &maps.xs, bar + B_OY, 0,
                  m_tile * 128 + (xi & 1) * 64 + (xi >> 1) * 16, n_tile * 2);
      xi++;
    }
  }
  if (!dry) mbar_wait_sleep(bar + B_OY2, 0);
}

__device__ __forceinline__ void out_side(const Maps& maps, uint32_t smem0, const float (&gv)[4]) {
  PHASE_PROLOGUE
  const int m_tile = maps.id[blockIdx.x][2] & 15, n_tile = maps.id[blockIdx.x][2] >> 4;
  const bool w0 = __shfl_sync(0xffffffffu, warp, 0) == 0;
  bool have = false;
  auto late = [&](uint32_t spins) {
    have = cnt_wait(CNT_Y2 + 1, 128, spins) || !spins;
    TD(11)
    if (have) {
      mbar_expect_tx(bar + B_OY2, 4096);
      tma_load_3d(sbase + O_Y_OFF + 7 * 4096, &maps.y, bar + B_OY2, 0, n_tile * 128 + 112, m_tile * 2);
    }
  };
  if (w0) {
    if (elect_one()) {
      mbar_expect_tx(bar + B_OY, 65536 - 4096);
      TD(10)
      cnt_wait(CNT_Y2, DM - 128);
      TD(7)
#pragma unroll 1
      for (int i = 0; i < 7; i++) {
        tma_load_3d(sbase + O_Y_OFF + i * 4096, &maps.y, bar + B_OY, 0, n_tile * 128 + i * 16, m_tile * 2);
        __nanosleep(PACE);
      }
      late(1u << 18);
    }
  }
  mbar_wait_sleep(bar + B_OY, 0);
  if (wtid == 0) { TD(12) }
  const int mrow = (lane & 7) + ((lane >> 4) & 1) * 8;
  const int mchunk = warp * 2 + ((lane >> 3) & 1);
  const uint32_t xrow = sbase + O_X_OFF + warp * 4096 + (lane & 15) * 128;
  const uint32_t yrow = sbase + O_Y_OFF + mrow * 128 + ((mchunk ^ (lane & 7)) << 4);
  uint32_t y[7][4], x[7][4], om[4];
#pragma unroll
  for (int i = 0; i < 4; i++) om[i] = pack_bf16(1.0f - gv[i], 1.0f - gv[i]);
  auto xa = [&](int h, int i) { return xrow + h * 16384 + (i >> 2) * 2048 + ((((i & 3) * 2 + (lane >> 4)) ^ (lane & 7)) << 4); };
  auto load = [&](int r, int h, int i) {
    ldsm4t(y[r], yrow + h * 2048 + i * 4096);
    asm volatile("ldmatrix.sync.aligned.m8n8.x4.shared.b16 {%0, %1, %2, %3}, [%4];"
                 : "=r"(x[r][0]), "=r"(x[r][1]), "=r"(x[r][2]), "=r"(x[r][3])
                 : "r"(xa(h, i)));
  };
  auto store = [&](int r, int h, int i, uint32_t om0, uint32_t om1) {
    stmatrix_x4(xa(h, i), mul_bf2(om0, mul_bf2(x[r][0], y[r][0])), mul_bf2(om1, mul_bf2(x[r][1], y[r][1])),
                mul_bf2(om0, mul_bf2(x[r][2], y[r][2])), mul_bf2(om1, mul_bf2(x[r][3], y[r][3])));
  };
#pragma unroll 1
  for (int h = 0; h < 2; h++) {
#pragma unroll
    for (int i = 0; i < 7; i++) load(i, h, i);
#pragma unroll
    for (int i = 0; i < 7; i++) store(i, h, i, h ? om[2] : om[0], h ? om[3] : om[1]);
  }
  __syncwarp();
  mbar_arrive_if(bar + B_OE, lane == 0);
  if (w0 && !__any_sync(0xffffffffu, have)) {
    if (elect_one()) late(0);
  }
  mbar_wait_sleep(bar + B_OY2, 0);
  load(0, 0, 7);
  load(1, 1, 7);
  store(0, 0, 7, om[0], om[1]);
  store(1, 1, 7, om[2], om[3]);
  __syncwarp();
  mbar_arrive_if(bar + B_OY + 8, lane == 0);
  if (wtid == 0) { TD(13) }
}

__device__ __forceinline__ void out_gemm(const Maps& maps, uint32_t smem0) {
  PHASE_PROLOGUE
  const int m_tile = maps.id[blockIdx.x][2] & 15, n_tile = maps.id[blockIdx.x][2] >> 4;
  float acc[2][64];
  undef_regs(acc[0]);
  undef_regs(acc[1]);
  uint32_t stage = 0, phase = 0, prev_stage = 0;
  GT(gti++)
  const float* gp = g_gate + m_tile * 128 + warp * 16 + (lane >> 2);
  const float gv[4] = {__ldcg(gp), __ldcg(gp + 8), __ldcg(gp + 64), __ldcg(gp + 72)};
  if (wg == 1) {
    out_side(maps, smem0, gv);
    return;
  }
  const uint32_t xrow = sbase + O_X_OFF + warp * 4096 + (lane & 15) * 128;
  auto addr = [&](int i) {
    return xrow + (i >> 3) * 16384 + ((i >> 2) & 1) * 2048 + ((((i & 3) * 2 + (lane >> 4)) ^ (lane & 7)) << 4);
  };
  uint32_t b[16][4];
#pragma unroll
  for (int i = 0; i < 64; i++) asm volatile("" : "=r"(b[i >> 2][i & 3]));
  auto ld_b = [&](int q0, int q1) {
#pragma unroll
    for (int i = 0; i < 16; i++)
      if ((i & 7) != 7)
        asm volatile(
            "{\n.reg .pred p;\nsetp.ge.s32 p, %5, %6;\nsetp.le.and.s32 p, %5, %7, p;\n"
            "@p ldmatrix.sync.aligned.m8n8.x4.shared.b16 {%0, %1, %2, %3}, [%4];\n}\n"
            : "+r"(b[i][0]), "+r"(b[i][1]), "+r"(b[i][2]), "+r"(b[i][3])
            : "r"(addr(i)), "r"(i / 4), "r"(q0), "r"(q1)
            : "memory");
  };
  int nq = 0;
  constexpr uint64_t DHI = DESC_SW128 | ((uint64_t)(1024 >> 4) << 32);
#pragma unroll 1
  for (int kt = 0; kt < O_NK - 2; kt++) {
    uint32_t da = (uint32_t)make_desc(sbase + out_stage(stage), 16, 0, 0);
    uint32_t db = (uint32_t)make_desc(sbase + out_stage(stage) + 16384, 8192, 0, 0);
    asm volatile("" : "+r"(da), "+r"(db));
    mbar_wait(bar + B_OFULL + 8 * stage, phase);
    GT(gti++)
#pragma unroll
    for (int kk = 0; kk < 4; kk++) {
      wgmma_wait<2>();
      if (kk == 2)
        mbar_arrive_cluster_if(bar + B_OEMPTY + 8 * prev_stage, wtid >> 6,
                               (wtid & 63) == 32 && kt > 0 && kt - 1 + O_STAGES < O_NK);
      wgmma_fence();
      wgmma_m64n128_ss_tb(acc[0], DHI | (da + kk * 2), DHI | (db + kk * 128), (kt | kk) != 0);
      wgmma_m64n128_ss_tb(acc[1], DHI | (da + 512 + kk * 2), DHI | (db + kk * 128), (kt | kk) != 0);
      wgmma_commit();
      if (kk == 0 && kt >= 52) {
        uint32_t ok;
        asm volatile("{\n.reg .pred p;\nmbarrier.test_wait.parity.shared::cta.b64 p, [%1], 0;\nselp.u32 %0, 1, 0, p;\n}\n"
                     : "=r"(ok)
                     : "r"(bar + B_OE)
                     : "memory");
        if (__all_sync(0xffffffffu, ok)) {
          ld_b(nq, nq);
          nq++;
        }
      }
    }
    prev_stage = stage;
    if (++stage == O_STAGES) { stage = 0; phase ^= 1; }
  }
  if (tid == 0) { TD(14) }
  constexpr int S0 = (O_NK - 2) % O_STAGES, P0 = ((O_NK - 2) / O_STAGES) & 1;
  const uint32_t d0 = (uint32_t)make_desc(sbase, 0, 0, 0);
  auto mma = [&](int h, int k0, int k1) {
    wgmma_fence();
#pragma unroll
    for (int k = k0; k < k1; k++) {
      const uint32_t d = d0 + (out_stage(S0 + (k >> 2)) >> 4);
      wgmma_m64n128_ss_tb(acc[h], DHI | (d + 0x10000 + h * 512 + (k & 3) * 2), DHI | (d + 0x2000400 + (k & 3) * 128), 1);
    }
    wgmma_commit();
  };
#pragma unroll
  for (int p = 0; p < 2; p++) {
    mbar_wait(bar + B_OFULL + 8 * (S0 + p), P0);
    mma(0, 4 * p, 4 * p + 4);
  }
  mma(1, 0, 8);
  uint32_t gg[4];
#pragma unroll
  for (int i = 0; i < 4; i++) gg[i] = pack_bf16(gv[i], gv[i]);
  if (nq < 4) {
    mbar_wait(bar + B_OE, 0);
    ld_b(nq, 3);
  }
  const int w4 = __shfl_sync(0xffffffffu, warp, 0);
#pragma unroll
  for (int i = 0; i < 16; i++) {
    const int h = i >> 3;
    if (i == 0) wgmma_wait<1>();
    if (i == 8) wgmma_wait<0>();
    if ((i & 7) == 0) fence_regs(acc[h]);
    if (i == 8) {   }
    if (i == 7) {
      mbar_wait(bar + B_OY + 8, 0);
#pragma unroll
      for (int j = 7; j < 16; j += 8)
        asm volatile("ldmatrix.sync.aligned.m8n8.x4.shared.b16 {%0, %1, %2, %3}, [%4];"
                     : "=r"(b[j][0]), "=r"(b[j][1]), "=r"(b[j][2]), "=r"(b[j][3])
                     : "r"(addr(j))
                     : "memory");
    }
    const float* a = acc[h] + 8 * (i & 7);
    stmatrix_x4(addr(i), fma_bf2(gg[2 * h], pack_bf16(a[0], a[1]), b[i][0]), fma_bf2(gg[2 * h + 1], pack_bf16(a[2], a[3]), b[i][1]),
                fma_bf2(gg[2 * h], pack_bf16(a[4], a[5]), b[i][2]), fma_bf2(gg[2 * h + 1], pack_bf16(a[6], a[7]), b[i][3]));
    if ((i & 7) == 7) {
      fence_proxy_async();
      __syncwarp();
      if (elect_one()) {
        tma_store_3d(&maps.oc, sbase + O_X_OFF + (h * 4 + w4) * 4096, 0, m_tile * 128 + h * 64 + w4 * 16, n_tile * 2);
        if (h == 1) {
          tma_store_commit();
        }
      }
    }
  }
  GT(gti++)
}

__device__ __noinline__ void leave_kernel(int mask) {
  if (!(mask & 4)) return;
  if (atomicAdd(g_cnt + CNT_DONE * 32, 1u) == 2 * gridDim.x - 1) {
    for (int i = 0; i < CNT_N; i++) g_cnt[i * 32] = 0;
#pragma unroll 4
    for (int i = 0; i < 128; i++) g_slot[i] = 0;
  }
}

__device__ __noinline__ void side_jobs(const Maps& maps, uint32_t sbase) {
  const int w12 = __shfl_sync(0xffffffffu, threadIdx.x >> 5, 0);
  gate_rows(maps, sbase, (blockIdx.x - 128) * 12 + w12, w12, threadIdx.x & 31);
  fence_proxy_async();
  __syncthreads();
  if (threadIdx.x == 320) cnt_signal_release(CNT_PREP, 1);
}

__global__ void __launch_bounds__(384, 1)
    fused_kernel(int mask, const bf16* px, const bf16* pw, const __grid_constant__ Maps maps) {
  extern __shared__ __align__(1024) uint8_t smem_raw[];
  {
    const uint32_t t = threadIdx.x, l = t & 31, u = (blockIdx.x & 127) * 16 + (l >> 1);
    const uint32_t ow = (u >> 5) * HDIM + ((u >> 2) & 7) * 512 + 256 + (u & 3) * 64, ox = u * DM;
    const bf16* p = ((l & 1) ? pw : px) + ((l & 1) ? ow : ox);
    asm volatile("{\n.reg .pred p;\nsetp.ne.u32 p, %1, 0;\n@p prefetch.global.L2 [%0];\n}\n" ::"l"(p), "r"((uint32_t)(t < 32)));
  }
  {
    const uint32_t sbase = __shfl_sync(0xffffffffu, smem_u32(smem_raw), 0);
    const uint32_t bar = sbase + BAR_OFF;
    const int tid = threadIdx.x;
    const bool do_qkv = (mask & 1) && blockIdx.x < 128;
    TL(0, 0)
    if (__shfl_sync(0xffffffffu, tid >> 5, 0) == 1 && do_qkv) {
      if (elect_one()) {
        for (int i = 0; i < G_STAGES; i++) mbar_init(bar + B_GFULL + 8 * i, 1);
        fence_barrier_init();
        qkv_producer(maps, sbase, true);
      }
    }
    if (tid == 0) {
      for (int i = 0; i < G_STAGES; i++) {
        mbar_init(bar + B_GEMPTY + 8 * i, 2);
        mbar_init(bar + B_SFULL + 8 * i, 4);
        mbar_init(bar + B_SFREE + 8 * i, 1);
      }
      for (int i = 0; i < 2; i++) {
        mbar_init(bar + B_OFREE + 8 * i, 1);
        mbar_init(bar + B_QFULL + 8 * i, 1);
        mbar_init(bar + B_QEMPTY + 8 * i, 2);
        mbar_init(bar + B_KFULL + 8 * i, 1);
        mbar_init(bar + B_KEMPTY + 8 * i, 2);
        mbar_init(bar + B_VFULL + 8 * i, 1);
        mbar_init(bar + B_VEMPTY + 8 * i, 2);
      }
      for (int i = 0; i < O_STAGES; i++) {
        mbar_init(bar + B_OFULL + 8 * i, 1);
        mbar_init(bar + B_OEMPTY + 8 * i, 2);
      }
      mbar_init(bar + B_OY, 1);
      for (int i = 0; i < 3; i++) mbar_init(bar + seen_bar(i), 1);
      mbar_init(bar + B_OY2, 1);
      mbar_init(bar + B_DEAL, 1);
      mbar_init(bar + B_DEAL2, 1);
      mbar_init(bar + B_PAIR, 1);
      mbar_init(bar + B_OY + 8, 4);
      mbar_init(bar + B_OE, 4);
      mbar_init(bar + B_QDONE, 2);
      for (int i = 0; i < 8; i++) mbar_init(bar + B_CFULL + 8 * i, 1);
      for (int i = 0; i < CNT_N; i++) asm volatile("st.shared.u32 [%0], 0;" ::"r"(bar + B_PEND + 4 * i) : "memory");
      fence_barrier_init();
    }
    __syncthreads();
    asm volatile("barrier.cluster.arrive.relaxed.aligned;" ::: "memory");
    if ((mask & 1) && blockIdx.x >= 128) side_jobs(maps, sbase);
  }
  uint32_t smem0 = smem_u32(smem_raw);
  PHASE_PROLOGUE
  const bool do_qkv = (mask & 1) && blockIdx.x < 128, do_out = (mask & 4) && blockIdx.x < 128;
  TL(0, 1)

  if (wg != 2) {
    reg_alloc<232>();
    uint32_t sn = 0;
    float o[64];
    if (do_qkv) {
      sn = qkv_consumer(maps, smem_u32(smem_raw), mask & 2, o);
    } else {
      undef_regs(o);
    }
    TL(0, 2) TL(1, 0) TL(1, 1)
    asm volatile("barrier.cluster.wait.acquire.aligned;" ::: "memory");
    if (mask & 2) {
      sn = attn_consumer(maps, smem_u32(smem_raw), sn, o, mask & 1);
      TL(2, 0)
      if ((mask & 4) && blockIdx.x < 128 && __shfl_sync(0xffffffffu, threadIdx.x, 0) < 128) {
        named_bar_arrive(3, 256);
      } else {
        const uint32_t b2 = blockIdx.x * 2 + (threadIdx.x >> 7);
        const bool fused = mask & 4, mainc = blockIdx.x < 128;
        const uint32_t first = __shfl_sync(0xffffffffu, !fused ? b2 : mainc ? conv_first(maps) : (b2 - 255) * 128 - C_SIDE, 0);
        conv_consumer(maps, smem_u32(smem_raw), first, !fused ? 264 : mainc ? 16 : 1,
                      !fused ? DM : mainc ? (first | 127) + 1 - C_SIDE : first + C_SIDE, fused && !mainc,
                      fused && mainc);
      }
      TL(1, 2) TL(2, 1) TL(2, 2)
    }
    TL(3, 0) TL(3, 1)
    {
      uint32_t smem0 = smem_u32(smem_raw);
      PHASE_PROLOGUE
      st_wait(bar, wg, sn - 2);
      st_post(bar, wg, wtid, sn, ST_END, nullptr, 0, 0, 0, -1);
    }
    if ((mask & 4) && blockIdx.x < 128) out_gemm(maps, smem_u32(smem_raw));
    tma_store_wait_read<0>();
  } else {
    reg_dealloc<40>();
    asm volatile("barrier.cluster.wait.acquire.aligned;" ::: "memory");
    const int w = __shfl_sync(0xffffffffu, tid >> 5, 0) - 8;
    if (w < 2) {
      if (do_qkv) prep_agent(maps, sbase, w, lane);
      if (elect_one()) store_agent(bar, w, w && do_out ? conv_first(maps) + 48 : 0);
      TL2(3, 2)
    } else {
      if (elect_one()) {
        const bool dry = w == 2;
        if (do_qkv && !dry) qkv_producer(maps, sbase, false);
        if (mask & 2) attn_producer(maps, sbase, do_qkv, do_out, dry);
        if (do_out) out_producer(maps, sbase, mask & 2, dry);
        if (dry) { TD(5) }
      }
      __syncwarp();
      if (w == 2) publisher(bar, tid & 31, !(mask & 2) ? 2 : do_out ? 3 : 4, !do_out ? 3 : do_qkv ? 0 : 2, do_qkv ? 4 : 0);
      if ((tid & 31) == 0) leave_kernel(mask);
    }
  }
}

typedef CUresult (*PFN_tmapEncode)(CUtensorMap*, CUtensorMapDataType, cuuint32_t, void*, const cuuint64_t*,
                                   const cuuint64_t*, const cuuint32_t*, const cuuint32_t*, CUtensorMapInterleave,
                                   CUtensorMapSwizzle, CUtensorMapL2promotion, CUtensorMapFloatOOBfill);
static PFN_tmapEncode s_encode = nullptr;

static void make_map_2d(CUtensorMap* m, const void* ptr, int rows, int cols, int box_rows) {
  cuuint64_t dims[2] = {(cuuint64_t)cols, (cuuint64_t)rows};
  cuuint64_t strides[1] = {(cuuint64_t)cols * 2};
  cuuint32_t box[2] = {cols < 64 ? 32u : 64u, (cuuint32_t)box_rows};
  cuuint32_t es[2] = {1, 1};
  s_encode(m, CU_TENSOR_MAP_DATA_TYPE_BFLOAT16, 2, const_cast<void*>(ptr), dims, strides, box, es,
           CU_TENSOR_MAP_INTERLEAVE_NONE, cols < 64 ? CU_TENSOR_MAP_SWIZZLE_64B : CU_TENSOR_MAP_SWIZZLE_128B, CU_TENSOR_MAP_L2_PROMOTION_L2_256B,
           CU_TENSOR_MAP_FLOAT_OOB_FILL_NONE);
}
static void make_map_3d(CUtensorMap* m, const void* ptr, int rows, int cols, int box_rows, int box_chunks) {
  cuuint64_t dims[3] = {64, (cuuint64_t)rows, (cuuint64_t)(cols / 64)};
  cuuint64_t strides[2] = {(cuuint64_t)cols * 2, 128};
  cuuint32_t box[3] = {64, (cuuint32_t)box_rows, (cuuint32_t)box_chunks};
  cuuint32_t es[3] = {1, 1, 1};
  s_encode(m, CU_TENSOR_MAP_DATA_TYPE_BFLOAT16, 3, const_cast<void*>(ptr), dims, strides, box, es,
           CU_TENSOR_MAP_INTERLEAVE_NONE, CU_TENSOR_MAP_SWIZZLE_128B, CU_TENSOR_MAP_L2_PROMOTION_L2_256B,
           CU_TENSOR_MAP_FLOAT_OOB_FILL_NONE);
}

static cudaLaunchConfig_t fused_cfg(cudaLaunchAttribute* at) {
  cudaLaunchConfig_t cfg = {};
  cfg.gridDim = dim3(132);
  cfg.blockDim = dim3(384);
  cfg.dynamicSmemBytes = SMEM_BYTES;
  cfg.stream = cudaStreamPerThread;
  at[0].id = cudaLaunchAttributeClusterDimension;
  at[0].val.clusterDim.x = 2;
  at[0].val.clusterDim.y = 1;
  at[0].val.clusterDim.z = 1;
  cfg.attrs = at;
  cfg.numAttrs = 1;
  return cfg;
}

extern "C" void kernel_launch(void* const* d_in, const int* in_sizes, int n_in, void* d_out, int out_size) {
  const bf16* x = (const bf16*)d_in[0];
  const bf16* ckv = (const bf16*)d_in[1];
  const bf16* wq = (const bf16*)d_in[2];
  const bf16* wuk = (const bf16*)d_in[3];
  const bf16* wuv = (const bf16*)d_in[4];
  const bf16* wo = (const bf16*)d_in[5];
  const bf16* bk = (const bf16*)d_in[7];
  const bf16* bv = (const bf16*)d_in[8];
  const bf16* shift_k = (const bf16*)d_in[9];
  const bf16* ssm_k = (const bf16*)d_in[10];
  const bf16* ssm_D = (const bf16*)d_in[11];
  const bf16* gate_w = (const bf16*)d_in[12];
  bf16* out = (bf16*)d_out;

  static void *pq = nullptr, *pk = nullptr, *pv = nullptr, *pctx = nullptr, *pb = nullptr, *pu = nullptr;
  static int max_clusters = 0;
  if (!s_encode) {
    void* fn = nullptr;
    cudaDriverEntryPointQueryResult qres;
    cudaGetDriverEntryPoint("cuTensorMapEncodeTiled", &fn, cudaEnableDefault, &qres);
    s_encode = (PFN_tmapEncode)fn;
    cudaGetSymbolAddress(&pq, g_q);
    cudaGetSymbolAddress(&pk, g_k);
    cudaGetSymbolAddress(&pv, g_v);
    cudaGetSymbolAddress(&pctx, g_ctx);
    cudaGetSymbolAddress(&pb, g_y2T);
    cudaGetSymbolAddress(&pu, g_kvT);
    cudaFuncSetAttribute(fused_kernel, cudaFuncAttributeMaxDynamicSharedMemorySize, SMEM_BYTES);
    cudaLaunchAttribute at[1];
    cudaLaunchConfig_t cfg = fused_cfg(at);
    if (cudaOccupancyMaxActiveClusters(&max_clusters, fused_kernel, &cfg) != cudaSuccess) max_clusters = 0;
  }

  Maps all = {};
  make_map_2d(&all.a[0], x, S_LEN, DM, 128);
  make_map_2d(&all.a[1], ckv, S_LEN, DC, 128);
  make_map_3d(&all.b[0], wq, DM, HDIM, 64, 4);
  make_map_3d(&all.b[1], wuk, DC, HDIM, 64, 4);
  make_map_3d(&all.b[2], wuv, DC, HDIM, 64, 4);
  make_map_2d(&all.c[0], pq, S_LEN, HDIM, 64);
  make_map_2d(&all.c[1], pk, S_LEN, HDIM, 64);
  make_map_2d(&all.c[2], pv, S_LEN, HDIM, 64);
  make_map_3d(&all.q, pq, S_LEN, HDIM, 128, 2);
  make_map_3d(&all.k, pk, S_LEN, HDIM, 128, 2);
  make_map_3d(&all.v, pv, S_LEN, HDIM, 128, 2);
  make_map_2d(&all.o, pctx, S_LEN, HDIM, 64);
  all.ssm_k = ssm_k;
  all.ssm_D = ssm_D;
  make_map_2d(&all.oa, pctx, S_LEN, HDIM, 128);
  make_map_2d(&all.ob, wo, HDIM, DM, 64);
  make_map_3d(&all.oc, out, S_LEN, DM, 16, 2);
  make_map_3d(&all.y, pb, DM, S_LEN, 16, 2);
  make_map_3d(&all.xs, x, S_LEN, DM, 16, 2);
  make_map_2d(&all.cu, pu, DM * 64, 32, 64);
  make_map_2d(&all.ch, ssm_k, DM * 64, 32, 64);

  make_map_2d(&all.bk, bk, S_LEN, DM, 35);
  make_map_2d(&all.bv, bv, S_LEN, DM, 32);
  for (int b = 0; b < 128; b++) {
    const int c = b >> 1, r = b & 1;
    const int G = c < 4 ? 0 : c < 36 ? (c - 4) % 8 : 1 + (c - 36) % 7;
    const int i = c < 4 ? 4 + c : c < 36 ? (c - 4) / 8 : 4 + (c - 36) / 7;
    all.id[b][0] = r + 2 * (i & 1) + 4 * (G & 3) + 16 * (i >> 1) + 64 * (G >> 2);
    all.id[b][1] = r + 2 * i + 16 * G;
    all.id[b][2] = r + 2 * G + 16 * i;
  }
  all.shift_k = shift_k;
  all.x = x;
  all.gate_w = gate_w;
  cudaLaunchAttribute at[1];
  cudaLaunchConfig_t cfg = fused_cfg(at);
  if (max_clusters >= 66) {
    cudaLaunchKernelEx(&cfg, fused_kernel, 7, x, wq, all);
  } else {
    for (int m = 1; m <= 4; m <<= 1) cudaLaunchKernelEx(&cfg, fused_kernel, m, x, wq, all);
  }
}
```

```cpp
#include <cuda_runtime.h>
#include <cuda_bf16.h>
#include <cuda.h>
#include <stdint.h>

typedef __nv_bfloat16 bf16;
#define INPLACE 3

constexpr int S_LEN = 2048;
constexpr int DM = 1024;
constexpr int NH = 32;
constexpr int HD = 128;
constexpr int DC = 512;
constexpr int HDIM = NH * HD;

__device__ __align__(1024) bf16 g_q[S_LEN * HDIM];
__device__ __align__(1024) bf16 g_k[S_LEN * HDIM];
__device__ __align__(1024) bf16 g_v[S_LEN * HDIM];
#define g_ctx g_q
__device__ __align__(1024) bf16 g_kvT[DM * S_LEN];
#define g_y2T g_kvT
__device__ __align__(1024) float g_gate[S_LEN];
enum { CNT_KV = 0, CNT_PREP = CNT_KV + 2, CNT_CTX, CNT_Y2 = CNT_CTX + 2, CNT_DONE = CNT_Y2 + 2, CNT_RANK, CNT_N };
__device__ unsigned int g_cnt[CNT_N * 32];
__device__ unsigned long long g_slot[128];

#define TL(k, i)
#define TL2(k, i)
#define TD(i)
#define CT(i)
#define GT(i)
#define GA(i)
#define ST(i)

__device__ __forceinline__ uint32_t smem_u32(const void* p) { return (uint32_t)__cvta_generic_to_shared(p); }

__device__ __forceinline__ void mbar_init(uint32_t bar, uint32_t count) {
  asm volatile("mbarrier.init.shared::cta.b64 [%0], %1;" ::"r"(bar), "r"(count));
}
__device__ __forceinline__ void mbar_expect_tx(uint32_t bar, uint32_t bytes) {
  asm volatile("mbarrier.arrive.expect_tx.shared::cta.b64 _, [%0], %1;" ::"r"(bar), "r"(bytes) : "memory");
}
__device__ __forceinline__ void mbar_arrive(uint32_t bar) {
  asm volatile("mbarrier.arrive.shared::cta.b64 _, [%0];" ::"r"(bar) : "memory");
}
__device__ __forceinline__ void mbar_wait(uint32_t bar, uint32_t parity) {
  uint32_t done;
  uint32_t spins = 0;
  do {
    asm volatile(
        "{\n.reg .pred p;\n"
        "mbarrier.try_wait.parity.shared::cta.b64 p, [%1], %2;\n"
        "selp.u32 %0, 1, 0, p;\n}\n"
        : "=r"(done)
        : "r"(bar), "r"(parity)
        : "memory");
    if (++spins > (1u << 22)) break;
  } while (!done);
}
__device__ __forceinline__ bool mbar_try(uint32_t bar, uint32_t parity) {
  uint32_t done;
  asm volatile(
      "{\n.reg .pred p;\n"
      "mbarrier.try_wait.parity.shared::cta.b64 p, [%1], %2;\n"
      "selp.u32 %0, 1, 0, p;\n}\n"
      : "=r"(done)
      : "r"(bar), "r"(parity)
      : "memory");
  return done != 0;
}
__device__ __forceinline__ bool mbar_test(uint32_t bar, uint32_t parity) {
  uint32_t done;
  asm volatile(
      "{\n.reg .pred p;\n"
      "mbarrier.test_wait.parity.shared::cta.b64 p, [%1], %2;\n"
      "selp.u32 %0, 1, 0, p;\n}\n"
      : "=r"(done)
      : "r"(bar), "r"(parity)
      : "memory");
  return done != 0;
}
__device__ __forceinline__ bool elect_one() {
  uint32_t pred;
  asm volatile("{\n.reg .pred p;\nelect.sync _|p, 0xffffffff;\nselp.u32 %0, 1, 0, p;\n}\n" : "=r"(pred));
  return pred != 0;
}
__device__ __forceinline__ void mbar_arrive_if(uint32_t bar, bool pred) {
  asm volatile(
      "{\n.reg .pred p;\nsetp.ne.b32 p, %1, 0;\n"
      "@p mbarrier.arrive.shared::cta.b64 _, [%0];\n}\n" ::"r"(bar),
      "r"((uint32_t)pred)
      : "memory");
}
__device__ __forceinline__ void mbar_wait_sleep(uint32_t bar, uint32_t parity) {
  uint32_t done;
  uint32_t spins = 0;
  do {
    asm volatile(
        "{\n.reg .pred p;\n"
        "mbarrier.try_wait.parity.shared::cta.b64 p, [%1], %2, %3;\n"
        "selp.u32 %0, 1, 0, p;\n}\n"
        : "=r"(done)
        : "r"(bar), "r"(parity), "r"(20000u)
        : "memory");
    if (++spins > (1u << 16)) break;
  } while (!done);
}
__device__ __forceinline__ void fence_barrier_init() {
  asm volatile("fence.mbarrier_init.release.cluster;" ::: "memory");
}
__device__ __forceinline__ void fence_proxy_async() {
  asm volatile("fence.proxy.async.shared::cta;" ::: "memory");
}
__device__ __forceinline__ void named_bar_sync(int id, int nthreads) {
  asm volatile("bar.sync %0, %1;" ::"r"(id), "r"(nthreads) : "memory");
}
__device__ __forceinline__ void named_bar_arrive(int id, int nthreads) {
  asm volatile("bar.arrive %0, %1;" ::"r"(id), "r"(nthreads) : "memory");
}
__device__ __forceinline__ void tma_load_2d(uint32_t dst, const CUtensorMap* m, uint32_t bar, int c0, int c1) {
  asm volatile(
      "cp.async.bulk.tensor.2d.shared::cluster.global.mbarrier::complete_tx::bytes [%0], [%1, {%3, %4}], [%2];" ::"r"(dst),
      "l"(reinterpret_cast<uint64_t>(m)), "r"(bar), "r"(c0), "r"(c1)
      : "memory");
}
__device__ __forceinline__ void tma_load_3d(uint32_t dst, const CUtensorMap* m, uint32_t bar, int c0, int c1, int c2) {
  asm volatile(
      "cp.async.bulk.tensor.3d.shared::cluster.global.mbarrier::complete_tx::bytes [%0], [%1, {%3, %4, %5}], [%2];" ::"r"(dst),
      "l"(reinterpret_cast<uint64_t>(m)), "r"(bar), "r"(c0), "r"(c1), "r"(c2)
      : "memory");
}
__device__ __forceinline__ void tma_store_2d(const CUtensorMap* m, uint32_t src, int c0, int c1) {
  asm volatile("cp.async.bulk.tensor.2d.global.shared::cta.bulk_group [%0, {%2, %3}], [%1];" ::"l"(
                   reinterpret_cast<uint64_t>(m)),
               "r"(src), "r"(c0), "r"(c1)
               : "memory");
}
__device__ __forceinline__ void bulk_load(uint32_t dst, const void* src, uint32_t bytes, uint32_t bar) {
  asm volatile("cp.async.bulk.shared::cluster.global.mbarrier::complete_tx::bytes [%0], [%1], %2, [%3];" ::"r"(dst),
               "l"(src), "r"(bytes), "r"(bar)
               : "memory");
}
__device__ __forceinline__ void tma_load_2d_mc(uint32_t dst, const CUtensorMap* m, uint32_t bar, int c0, int c1,
                                               uint16_t mask) {
  asm volatile(
      "cp.async.bulk.tensor.2d.shared::cluster.global.mbarrier::complete_tx::bytes.multicast::cluster [%0], [%1, {%3, "
      "%4}], [%2], %5;" ::"r"(dst),
      "l"(reinterpret_cast<uint64_t>(m)), "r"(bar), "r"(c0), "r"(c1), "h"(mask)
      : "memory");
}
__device__ __forceinline__ void mbar_arrive_cluster_if(uint32_t bar, uint32_t cta, bool pred) {
  asm volatile(
      "{\n.reg .b32 ra;\n.reg .pred p;\nsetp.ne.b32 p, %2, 0;\n"
      "mapa.shared::cluster.u32 ra, %0, %1;\n"
      "@p mbarrier.arrive.shared::cluster.b64 _, [ra];\n}\n" ::"r"(bar),
      "r"(cta), "r"((uint32_t)pred)
      : "memory");
}
__device__ __forceinline__ uint64_t policy_evict_first() {
  uint64_t pol;
  asm volatile("createpolicy.fractional.L2::evict_first.b64 %0, 1.0;" : "=l"(pol));
  return pol;
}
__device__ __forceinline__ void tma_load_2d_hint(uint32_t dst, const CUtensorMap* m, uint32_t bar, int c0, int c1,
                                                 uint64_t pol) {
  asm volatile(
      "cp.async.bulk.tensor.2d.shared::cluster.global.mbarrier::complete_tx::bytes.L2::cache_hint [%0], [%1, {%3, %4}], "
      "[%2], %5;" ::"r"(dst),
      "l"(reinterpret_cast<uint64_t>(m)), "r"(bar), "r"(c0), "r"(c1), "l"(pol)
      : "memory");
}
__device__ __forceinline__ void tma_load_3d_hint(uint32_t dst, const CUtensorMap* m, uint32_t bar, int c0, int c1,
                                                 int c2, uint64_t pol) {
  asm volatile(
      "cp.async.bulk.tensor.3d.shared::cluster.global.mbarrier::complete_tx::bytes.L2::cache_hint [%0], [%1, {%3, %4, "
      "%5}], [%2], %6;" ::"r"(dst),
      "l"(reinterpret_cast<uint64_t>(m)), "r"(bar), "r"(c0), "r"(c1), "r"(c2), "l"(pol)
      : "memory");
}
__device__ __forceinline__ void bulk_load_hint(uint32_t dst, const void* src, uint32_t bytes, uint32_t bar, uint64_t pol) {
  asm volatile(
      "cp.async.bulk.shared::cluster.global.mbarrier::complete_tx::bytes.L2::cache_hint [%0], [%1], %2, [%3], %4;" ::"r"(dst),
      "l"(src), "r"(bytes), "r"(bar), "l"(pol)
      : "memory");
}
__device__ __forceinline__ void cnt_signal_release(int which, uint32_t n) {
  asm volatile("red.release.gpu.global.add.u32 [%0], %1;" ::"l"(g_cnt + which * 32), "r"(n) : "memory");
}
__device__ __forceinline__ bool cnt_wait(int which, uint32_t target, uint32_t spins = 0) {
  uint32_t v;
  while (true) {
    asm volatile("ld.acquire.gpu.global.u32 %0, [%1];" : "=r"(v) : "l"(g_cnt + which * 32) : "memory");
    if (v >= target || ++spins > (1u << 18)) break;
    __nanosleep(64);
  }
  asm volatile("fence.proxy.async.global;" ::: "memory");
  return v >= target;
}
__device__ __forceinline__ void tma_store_3d(const CUtensorMap* m, uint32_t src, int c0, int c1, int c2) {
  asm volatile("cp.async.bulk.tensor.3d.global.shared::cta.bulk_group [%0, {%2, %3, %4}], [%1];" ::"l"(
                   reinterpret_cast<uint64_t>(m)),
               "r"(src), "r"(c0), "r"(c1), "r"(c2)
               : "memory");
}
__device__ __forceinline__ void tma_store_commit() { asm volatile("cp.async.bulk.commit_group;" ::: "memory"); }
template <int N>
__device__ __forceinline__ void tma_store_wait_read() {
  asm volatile("cp.async.bulk.wait_group.read %0;" ::"n"(N) : "memory");
}
template <int N>
__device__ __forceinline__ void tma_store_wait() {
  asm volatile("cp.async.bulk.wait_group %0;" ::"n"(N) : "memory");
}
__device__ __forceinline__ void wgmma_fence() { asm volatile("wgmma.fence.sync.aligned;" ::: "memory"); }
__device__ __forceinline__ void wgmma_commit() { asm volatile("wgmma.commit_group.sync.aligned;" ::: "memory"); }
template <int N>
__device__ __forceinline__ void wgmma_wait() {
  asm volatile("wgmma.wait_group.sync.aligned %0;" ::"n"(N) : "memory");
}
template <int R>
__device__ __forceinline__ void reg_alloc() { asm volatile("setmaxnreg.inc.sync.aligned.u32 %0;" ::"n"(R)); }
template <int R>
__device__ __forceinline__ void reg_dealloc() { asm volatile("setmaxnreg.dec.sync.aligned.u32 %0;" ::"n"(R)); }

__device__ __forceinline__ void stmatrix_x4(uint32_t addr, uint32_t r0, uint32_t r1, uint32_t r2, uint32_t r3) {
  asm volatile("stmatrix.sync.aligned.m8n8.x4.shared.b16 [%0], {%1, %2, %3, %4};" ::"r"(addr), "r"(r0), "r"(r1),
               "r"(r2), "r"(r3)
               : "memory");
}
__device__ __forceinline__ uint32_t pack_bf16(float lo, float hi) {
  uint32_t r;
  asm("cvt.rn.bf16x2.f32 %0, %1, %2;" : "=r"(r) : "f"(hi), "f"(lo));
  return r;
}
__device__ __forceinline__ float bf16_round(float x) { return __bfloat162float(__float2bfloat16_rn(x)); }
__device__ __forceinline__ float bf_lo(uint32_t v) { return __uint_as_float(v << 16); }
__device__ __forceinline__ float bf_hi(uint32_t v) { return __uint_as_float(v & 0xffff0000u); }
__device__ __forceinline__ uint4 lds128(uint32_t a) {
  uint4 v;
  asm volatile("ld.shared.v4.u32 {%0, %1, %2, %3}, [%4];" : "=r"(v.x), "=r"(v.y), "=r"(v.z), "=r"(v.w) : "r"(a));
  return v;
}
__device__ __forceinline__ void sts128(uint32_t a, uint4 v) {
  asm volatile("st.shared.v4.u32 [%0], {%1, %2, %3, %4};" ::"r"(a), "r"(v.x), "r"(v.y), "r"(v.z), "r"(v.w) : "memory");
}
__device__ __forceinline__ uint32_t mul_bf2(uint32_t a, uint32_t b) {
  uint32_t r;
  asm("mul.rn.bf16x2 %0, %1, %2;" : "=r"(r) : "r"(a), "r"(b));
  return r;
}
__device__ __forceinline__ float ex2(float x) {
  float y;
  asm("ex2.approx.ftz.f32 %0, %1;" : "=f"(y) : "f"(x));
  return y;
}
__device__ __forceinline__ float rcp(float x) {
  float y;
  asm("rcp.approx.ftz.f32 %0, %1;" : "=f"(y) : "f"(x));
  return y;
}
template <int N>
__device__ __forceinline__ void fence_regs(float (&r)[N]) {
#pragma unroll
  for (int i = 0; i < N; i++) asm volatile("" : "+f"(r[i])::"memory");
}

template <int N>
__device__ __forceinline__ void undef_regs(float (&r)[N]) {
#pragma unroll
  for (int i = 0; i < N; i++) asm volatile("" : "=f"(r[i]));
}
template <int N>
__device__ __forceinline__ void fence_regs_u(uint32_t (&r)[N]) {
#pragma unroll
  for (int i = 0; i < N; i++) asm volatile("" : "+r"(r[i])::"memory");
}

constexpr uint64_t DESC_SW128 = 1ull << 62;
__device__ __forceinline__ uint64_t make_desc(uint32_t addr, uint32_t lbo_bytes, uint32_t sbo_bytes, uint64_t swz) {
  return (uint64_t)((addr & 0x3FFFF) >> 4) | ((uint64_t)((lbo_bytes & 0x3FFFF) >> 4) << 16) |
         ((uint64_t)((sbo_bytes & 0x3FFFF) >> 4) << 32) | swz;
}

__device__ __forceinline__ uint64_t desc_add(uint64_t d, uint32_t off16) {
  return (d & 0xFFFFFFFF00000000ull) | (uint64_t)((uint32_t)d + off16);
}

__device__ __forceinline__ void wgmma_m64n256_ss_tb(float (&d)[128], uint64_t da, uint64_t db, int sd) {
  asm volatile(
    "{\n.reg .pred p;\nsetp.ne.b32 p, %130, 0;\n"
    "wgmma.mma_async.sync.aligned.m64n256k16.f32.bf16.bf16 "
    "{%0, %1, %2, %3, %4, %5, %6, %7, %8, %9, %10, %11, %12, %13, %14, %15, %16, %17, %18, %19, %20, %21, %22, %23, %24, %25, %26, %27, %28, %29, %30, %31, %32, %33, %34, %35, %36, %37, %38, %39, %40, %41, %42, %43, %44, %45, %46, %47, %48, %49, %50, %51, %52, %53, %54, %55, %56, %57, %58, %59, %60, %61, %62, %63, %64, %65, %66, %67, %68, %69, %70, %71, %72, %73, %74, %75, %76, %77, %78, %79, %80, %81, %82, %83, %84, %85, %86, %87, %88, %89, %90, %91, %92, %93, %94, %95, %96, %97, %98, %99, %100, %101, %102, %103, %104, %105, %106, %107, %108, %109, %110, %111, %112, %113, %114, %115, %116, %117, %118, %119, %120, %121, %122, %123, %124, %125, %126, %127}, %128, %129, p, 1, 1, 0, 1;\n}\n"
    : "+f"(d[0]), "+f"(d[1]), "+f"(d[2]), "+f"(d[3]), "+f"(d[4]), "+f"(d[5]), "+f"(d[6]), "+f"(d[7]), "+f"(d[8]), "+f"(d[9]), "+f"(d[10]), "+f"(d[11]), "+f"(d[12]), "+f"(d[13]), "+f"(d[14]), "+f"(d[15]), "+f"(d[16]), "+f"(d[17]), "+f"(d[18]), "+f"(d[19]), "+f"(d[20]), "+f"(d[21]), "+f"(d[22]), "+f"(d[23]), "+f"(d[24]), "+f"(d[25]), "+f"(d[26]), "+f"(d[27]), "+f"(d[28]), "+f"(d[29]), "+f"(d[30]), "+f"(d[31]), "+f"(d[32]), "+f"(d[33]), "+f"(d[34]), "+f"(d[35]), "+f"(d[36]), "+f"(d[37]), "+f"(d[38]), "+f"(d[39]), "+f"(d[40]), "+f"(d[41]), "+f"(d[42]), "+f"(d[43]), "+f"(d[44]), "+f"(d[45]), "+f"(d[46]), "+f"(d[47]), "+f"(d[48]), "+f"(d[49]), "+f"(d[50]), "+f"(d[51]), "+f"(d[52]), "+f"(d[53]), "+f"(d[54]), "+f"(d[55]), "+f"(d[56]), "+f"(d[57]), "+f"(d[58]), "+f"(d[59]), "+f"(d[60]), "+f"(d[61]), "+f"(d[62]), "+f"(d[63]), "+f"(d[64]), "+f"(d[65]), "+f"(d[66]), "+f"(d[67]), "+f"(d[68]), "+f"(d[69]), "+f"(d[70]), "+f"(d[71]), "+f"(d[72]), "+f"(d[73]), "+f"(d[74]), "+f"(d[75]), "+f"(d[76]), "+f"(d[77]), "+f"(d[78]), "+f"(d[79]), "+f"(d[80]), "+f"(d[81]), "+f"(d[82]), "+f"(d[83]), "+f"(d[84]), "+f"(d[85]), "+f"(d[86]), "+f"(d[87]), "+f"(d[88]), "+f"(d[89]), "+f"(d[90]), "+f"(d[91]), "+f"(d[92]), "+f"(d[93]), "+f"(d[94]), "+f"(d[95]), "+f"(d[96]), "+f"(d[97]), "+f"(d[98]), "+f"(d[99]), "+f"(d[100]), "+f"(d[101]), "+f"(d[102]), "+f"(d[103]), "+f"(d[104]), "+f"(d[105]), "+f"(d[106]), "+f"(d[107]), "+f"(d[108]), "+f"(d[109]), "+f"(d[110]), "+f"(d[111]), "+f"(d[112]), "+f"(d[113]), "+f"(d[114]), "+f"(d[115]), "+f"(d[116]), "+f"(d[117]), "+f"(d[118]), "+f"(d[119]), "+f"(d[120]), "+f"(d[121]), "+f"(d[122]), "+f"(d[123]), "+f"(d[124]), "+f"(d[125]), "+f"(d[126]), "+f"(d[127])
    : "l"(da), "l"(db), "r"(sd));
}

__device__ __forceinline__ void wgmma_m64n128_ss(float (&d)[64], uint64_t da, uint64_t db, int sd) {
  asm volatile(
    "{\n.reg .pred p;\nsetp.ne.b32 p, %66, 0;\n"
    "wgmma.mma_async.sync.aligned.m64n128k16.f32.bf16.bf16 "
    "{%0, %1, %2, %3, %4, %5, %6, %7, %8, %9, %10, %11, %12, %13, %14, %15, %16, %17, %18, %19, %20, %21, %22, %23, %24, %25, %26, %27, %28, %29, %30, %31, %32, %33, %34, %35, %36, %37, %38, %39, %40, %41, %42, %43, %44, %45, %46, %47, %48, %49, %50, %51, %52, %53, %54, %55, %56, %57, %58, %59, %60, %61, %62, %63}, %64, %65, p, 1, 1, 0, 0;\n}\n"
    : "+f"(d[0]), "+f"(d[1]), "+f"(d[2]), "+f"(d[3]), "+f"(d[4]), "+f"(d[5]), "+f"(d[6]), "+f"(d[7]), "+f"(d[8]), "+f"(d[9]), "+f"(d[10]), "+f"(d[11]), "+f"(d[12]), "+f"(d[13]), "+f"(d[14]), "+f"(d[15]), "+f"(d[16]), "+f"(d[17]), "+f"(d[18]), "+f"(d[19]), "+f"(d[20]), "+f"(d[21]), "+f"(d[22]), "+f"(d[23]), "+f"(d[24]), "+f"(d[25]), "+f"(d[26]), "+f"(d[27]), "+f"(d[28]), "+f"(d[29]), "+f"(d[30]), "+f"(d[31]), "+f"(d[32]), "+f"(d[33]), "+f"(d[34]), "+f"(d[35]), "+f"(d[36]), "+f"(d[37]), "+f"(d[38]), "+f"(d[39]), "+f"(d[40]), "+f"(d[41]), "+f"(d[42]), "+f"(d[43]), "+f"(d[44]), "+f"(d[45]), "+f"(d[46]), "+f"(d[47]), "+f"(d[48]), "+f"(d[49]), "+f"(d[50]), "+f"(d[51]), "+f"(d[52]), "+f"(d[53]), "+f"(d[54]), "+f"(d[55]), "+f"(d[56]), "+f"(d[57]), "+f"(d[58]), "+f"(d[59]), "+f"(d[60]), "+f"(d[61]), "+f"(d[62]), "+f"(d[63])
    : "l"(da), "l"(db), "r"(sd));
}

__device__ __forceinline__ void wgmma_m64n128_ss_tb(float (&d)[64], uint64_t da, uint64_t db, int sd) {
  asm volatile(
    "{\n.reg .pred p;\nsetp.ne.b32 p, %66, 0;\n"
    "wgmma.mma_async.sync.aligned.m64n128k16.f32.bf16.bf16 "
    "{%0, %1, %2, %3, %4, %5, %6, %7, %8, %9, %10, %11, %12, %13, %14, %15, %16, %17, %18, %19, %20, %21, %22, %23, %24, %25, %26, %27, %28, %29, %30, %31, %32, %33, %34, %35, %36, %37, %38, %39, %40, %41, %42, %43, %44, %45, %46, %47, %48, %49, %50, %51, %52, %53, %54, %55, %56, %57, %58, %59, %60, %61, %62, %63}, %64, %65, p, 1, 1, 0, 1;\n}\n"
    : "+f"(d[0]), "+f"(d[1]), "+f"(d[2]), "+f"(d[3]), "+f"(d[4]), "+f"(d[5]), "+f"(d[6]), "+f"(d[7]), "+f"(d[8]), "+f"(d[9]), "+f"(d[10]), "+f"(d[11]), "+f"(d[12]), "+f"(d[13]), "+f"(d[14]), "+f"(d[15]), "+f"(d[16]), "+f"(d[17]), "+f"(d[18]), "+f"(d[19]), "+f"(d[20]), "+f"(d[21]), "+f"(d[22]), "+f"(d[23]), "+f"(d[24]), "+f"(d[25]), "+f"(d[26]), "+f"(d[27]), "+f"(d[28]), "+f"(d[29]), "+f"(d[30]), "+f"(d[31]), "+f"(d[32]), "+f"(d[33]), "+f"(d[34]), "+f"(d[35]), "+f"(d[36]), "+f"(d[37]), "+f"(d[38]), "+f"(d[39]), "+f"(d[40]), "+f"(d[41]), "+f"(d[42]), "+f"(d[43]), "+f"(d[44]), "+f"(d[45]), "+f"(d[46]), "+f"(d[47]), "+f"(d[48]), "+f"(d[49]), "+f"(d[50]), "+f"(d[51]), "+f"(d[52]), "+f"(d[53]), "+f"(d[54]), "+f"(d[55]), "+f"(d[56]), "+f"(d[57]), "+f"(d[58]), "+f"(d[59]), "+f"(d[60]), "+f"(d[61]), "+f"(d[62]), "+f"(d[63])
    : "l"(da), "l"(db), "r"(sd));
}

__device__ __forceinline__ void wgmma_m64n128_rs_tb(float* d, uint32_t a0, uint32_t a1, uint32_t a2, uint32_t a3, uint64_t db, int sd) {
  asm volatile(
    "{\n.reg .pred p;\nsetp.ne.b32 p, %69, 0;\n"
    "wgmma.mma_async.sync.aligned.m64n128k16.f32.bf16.bf16 "
    "{%0, %1, %2, %3, %4, %5, %6, %7, %8, %9, %10, %11, %12, %13, %14, %15, %16, %17, %18, %19, %20, %21, %22, %23, %24, %25, %26, %27, %28, %29, %30, %31, %32, %33, %34, %35, %36, %37, %38, %39, %40, %41, %42, %43, %44, %45, %46, %47, %48, %49, %50, %51, %52, %53, %54, %55, %56, %57, %58, %59, %60, %61, %62, %63}, {%64, %65, %66, %67}, %68, p, 1, 1, 1;\n}\n"
    : "+f"(d[0]), "+f"(d[1]), "+f"(d[2]), "+f"(d[3]), "+f"(d[4]), "+f"(d[5]), "+f"(d[6]), "+f"(d[7]), "+f"(d[8]), "+f"(d[9]), "+f"(d[10]), "+f"(d[11]), "+f"(d[12]), "+f"(d[13]), "+f"(d[14]), "+f"(d[15]), "+f"(d[16]), "+f"(d[17]), "+f"(d[18]), "+f"(d[19]), "+f"(d[20]), "+f"(d[21]), "+f"(d[22]), "+f"(d[23]), "+f"(d[24]), "+f"(d[25]), "+f"(d[26]), "+f"(d[27]), "+f"(d[28]), "+f"(d[29]), "+f"(d[30]), "+f"(d[31]), "+f"(d[32]), "+f"(d[33]), "+f"(d[34]), "+f"(d[35]), "+f"(d[36]), "+f"(d[37]), "+f"(d[38]), "+f"(d[39]), "+f"(d[40]), "+f"(d[41]), "+f"(d[42]), "+f"(d[43]), "+f"(d[44]), "+f"(d[45]), "+f"(d[46]), "+f"(d[47]), "+f"(d[48]), "+f"(d[49]), "+f"(d[50]), "+f"(d[51]), "+f"(d[52]), "+f"(d[53]), "+f"(d[54]), "+f"(d[55]), "+f"(d[56]), "+f"(d[57]), "+f"(d[58]), "+f"(d[59]), "+f"(d[60]), "+f"(d[61]), "+f"(d[62]), "+f"(d[63])
    : "r"(a0), "r"(a1), "r"(a2), "r"(a3), "l"(db), "r"(sd));
}

__device__ __forceinline__ void wgmma_m64n64_rs_tb(float (&d)[32], const uint32_t (&a)[4], uint64_t db, int sd) {
  asm volatile(
    "{\n.reg .pred p;\nsetp.ne.b32 p, %37, 0;\n"
    "wgmma.mma_async.sync.aligned.m64n64k16.f32.bf16.bf16 "
    "{%0, %1, %2, %3, %4, %5, %6, %7, %8, %9, %10, %11, %12, %13, %14, %15, %16, %17, %18, %19, %20, %21, %22, %23, %24, %25, %26, %27, %28, %29, %30, %31}, {%32, %33, %34, %35}, %36, p, 1, 1, 1;\n}\n"
    : "+f"(d[0]), "+f"(d[1]), "+f"(d[2]), "+f"(d[3]), "+f"(d[4]), "+f"(d[5]), "+f"(d[6]), "+f"(d[7]), "+f"(d[8]), "+f"(d[9]), "+f"(d[10]), "+f"(d[11]), "+f"(d[12]), "+f"(d[13]), "+f"(d[14]), "+f"(d[15]), "+f"(d[16]), "+f"(d[17]), "+f"(d[18]), "+f"(d[19]), "+f"(d[20]), "+f"(d[21]), "+f"(d[22]), "+f"(d[23]), "+f"(d[24]), "+f"(d[25]), "+f"(d[26]), "+f"(d[27]), "+f"(d[28]), "+f"(d[29]), "+f"(d[30]), "+f"(d[31])
    : "r"(a[0]), "r"(a[1]), "r"(a[2]), "r"(a[3]), "l"(db), "r"(sd));
}

__device__ __forceinline__ void wgmma_m64n32_rs_tb(float (&d)[16], const uint32_t (&a)[4], uint64_t db, int sd) {
  asm volatile(
    "{\n.reg .pred p;\nsetp.ne.b32 p, %21, 0;\n"
    "wgmma.mma_async.sync.aligned.m64n32k16.f32.bf16.bf16 "
    "{%0, %1, %2, %3, %4, %5, %6, %7, %8, %9, %10, %11, %12, %13, %14, %15}, {%16, %17, %18, %19}, %20, p, 1, 1, 1;\n}\n"
    : "+f"(d[0]), "+f"(d[1]), "+f"(d[2]), "+f"(d[3]), "+f"(d[4]), "+f"(d[5]), "+f"(d[6]), "+f"(d[7]), "+f"(d[8]), "+f"(d[9]), "+f"(d[10]), "+f"(d[11]), "+f"(d[12]), "+f"(d[13]), "+f"(d[14]), "+f"(d[15])
    : "r"(a[0]), "r"(a[1]), "r"(a[2]), "r"(a[3]), "l"(db), "r"(sd));
}

constexpr int G_STAGES = 4;
constexpr int G_A_BYTES = 128 * 64 * 2;
constexpr int G_B_BYTES = 256 * 64 * 2;
constexpr int G_STAGE_BYTES = G_A_BYTES + G_B_BYTES;
constexpr int G_STG_OFF = G_STAGES * G_STAGE_BYTES;
constexpr int BAR_OFF = G_STG_OFF + 32768 + 2048;
constexpr int SMEM_BYTES = BAR_OFF + 1024;
constexpr int B_GFULL = 0, B_GEMPTY = 32, B_SEEN = 64, B_PFULL = 224;
constexpr int B_KFULL = 80, B_KEMPTY = 96, B_VFULL = 112, B_VEMPTY = 128, B_QFULL = 144, B_QEMPTY = 160,
              B_QDONE = 184;
constexpr int B_CFULL = 192;
constexpr int B_OFREE = 256, B_OFULL = 272, B_OEMPTY = 320, B_OY = 368, B_OY2 = 384, B_OE = 768;
constexpr int B_DEAL = 312, B_DEAL2 = 360, B_LIST = 640, B_PAIR = 504;
constexpr int B_SFULL = 392, B_SFREE = 424, B_PEND = 456, B_SCMD = 512;

#define PHASE_PROLOGUE                                                                \
  uint32_t tid, rt_zero;                                                              \
  asm volatile("mov.u32 %0, %%tid.x;" : "=r"(tid));                                   \
  asm volatile("mov.u32 %0, %%nctaid.y;" : "=r"(rt_zero));                            \
  asm volatile("" : "+r"(smem0));                                                     \
  rt_zero = __shfl_sync(0xffffffffu, rt_zero >> 8, 0);   \
  const uint32_t sbase = __shfl_sync(0xffffffffu, smem0, 0);                          \
  const uint32_t bar = sbase + BAR_OFF;                                               \
  const int wg = __shfl_sync(0xffffffffu, tid >> 7, 0);                               \
  const int warp = (tid >> 5) & 3, lane = tid & 31, wtid = tid & 127;                 \
  (void)rt_zero; (void)bar; (void)warp; (void)lane; (void)wtid;

#define PHASE_GIVEN                                                                   \
  uint32_t tid;                                                                       \
  asm volatile("mov.u32 %0, %%tid.x;" : "=r"(tid));                                   \
  const uint32_t bar = sbase + BAR_OFF;                                               \
  const int warp = (tid >> 5) & 3, lane = tid & 31, wtid = tid & 127;

enum { ST_END = 0, ST_BOX1, ST_BOX2, ST_BOX2Q, ST_BOX2L };
__device__ __forceinline__ void st_cmd(uint32_t bar, int wg, int wtid, uint32_t n, int kind, const void* dst,
                                       uint32_t src, int c0, int c1, int sig, uint32_t lazy = 0) {
  if (wtid == 0) {
    const uint32_t c = bar + B_SCMD + wg * 64 + (n & 1) * 32;
    const uint64_t d = reinterpret_cast<uint64_t>(dst);
    sts128(c, make_uint4(kind, src, c0, c1));
    sts128(c + 16, make_uint4((uint32_t)d, (uint32_t)(d >> 32), sig, lazy));
  }
}
__device__ __forceinline__ void st_go(uint32_t bar, int wg, int wtid, uint32_t n) {
  fence_proxy_async();
  __syncwarp();
  mbar_arrive_if(bar + B_SFULL + wg * 16 + (n & 1) * 8, (wtid & 31) == 0);
}
__device__ __forceinline__ void st_post(uint32_t bar, int wg, int wtid, uint32_t n, int kind, const void* dst,
                                        uint32_t src, int c0, int c1, int sig, uint32_t lazy = 0) {
  st_cmd(bar, wg, wtid, n, kind, dst, src, c0, c1, sig, lazy);
  st_go(bar, wg, wtid, n);
}
__device__ __forceinline__ void st_wait(uint32_t bar, int wg, uint32_t n) {
  const uint32_t b = bar + B_SFREE + wg * 16 + (n & 1) * 8;
  if (!mbar_try(b, ~(n >> 1) & 1)) mbar_wait(b, ~(n >> 1) & 1);
}
__device__ __forceinline__ void note(uint32_t bar, uint32_t cnt) {
  asm volatile("red.release.cta.shared.add.u32 [%0], 1;" ::"r"(bar + B_PEND + 4 * cnt) : "memory");
}
#define LAZY_NS 250
#define DEAL_NS 400
#define DEAL_NS2 1250
constexpr uint32_t C_NONE = 0x10000;
__device__ __forceinline__ void deal(uint32_t bar, uint32_t r, uint32_t t, uint32_t own) {
  uint64_t p;
  uint32_t spins = 0;
  while (true) {
    asm volatile("ld.relaxed.gpu.global.u64 %0, [%1];" : "=l"(p) : "l"(g_slot + 127 - r) : "memory");
    if (p || ++spins > (1u << 18)) break;
    __nanosleep(100);
  }
  const uint32_t pc = (uint32_t)p;
  int dt = (uint32_t)(p >> 32) - t;
  if (r >= 64) {
    sts128(bar + B_LIST, make_uint4(-dt > DEAL_NS2 ? C_NONE : own - 16, -dt > DEAL_NS ? C_NONE : own, C_NONE, C_NONE));
    mbar_arrive(bar + B_DEAL);
    dt = 0;
  }
  sts128(bar + B_LIST + 16, make_uint4(dt > DEAL_NS ? pc : C_NONE, dt > DEAL_NS2 ? pc - 16 : C_NONE, C_NONE, C_NONE));
  mbar_arrive(bar + B_DEAL2);
}
__device__ __forceinline__ void store_agent(uint32_t bar, int wg, uint32_t last_ch) {
  mbar_arrive(bar + B_SFREE + wg * 16);
  mbar_arrive(bar + B_SFREE + wg * 16 + 8);
  bool more = true;
  for (uint32_t n = 0;; n++) {
    mbar_wait_sleep(bar + B_SFULL + wg * 16 + (n & 1) * 8, (n >> 1) & 1);
    const uint4 c = lds128(bar + B_SCMD + wg * 64 + (n & 1) * 32);
    const uint4 d = lds128(bar + B_SCMD + wg * 64 + (n & 1) * 32 + 16);
    if (c.x == ST_END) break;
    uint32_t t;
    asm volatile("mov.u32 %0, %%globaltimer_lo;" : "=r"(t));
    for (uint32_t t1 = t; d.w && t1 - t < (2 * d.w + wg) * LAZY_NS;) {
      __nanosleep(200);
      asm volatile("mov.u32 %0, %%globaltimer_lo;" : "=r"(t1));
    }
    const CUtensorMap* dst = reinterpret_cast<const CUtensorMap*>((uint64_t)d.x | ((uint64_t)d.y << 32));
    tma_store_2d(dst, c.y, c.z, c.w);
    if (c.x >= ST_BOX2) tma_store_2d(dst, c.y + 8192, c.z + 64, c.w);
    tma_store_commit();
    uint32_t r = 0;
    if (c.x == ST_BOX2L && last_ch) {
      mbar_expect_tx(bar + B_PAIR, 4);
      asm volatile(
          "{\n.reg .b32 ra;\nmapa.shared::cluster.u32 ra, %0, %1;\n"
          "st.async.weak.shared::cluster.mbarrier::complete_tx::bytes.u32 [ra + 224], %2, [ra];\n}\n" ::"r"(bar + B_PAIR),
          "r"(~blockIdx.x & 1), "r"(t)
          : "memory");
    }
    tma_store_wait_read<0>();
    mbar_arrive(bar + B_SFREE + wg * 16 + (n & 1) * 8);
    if (c.x == ST_BOX2L) mbar_arrive(bar + B_OFREE + 8 * wg);
    if (c.x == ST_BOX2L && last_ch) {
      uint32_t tp;
      mbar_wait_sleep(bar + B_PAIR, 0);
      r = atomicAdd(g_cnt + CNT_RANK * 32, 1u) & 127;
      asm volatile("ld.shared.u32 %0, [%1];" : "=r"(tp) : "r"(bar + B_PAIR + 224) : "memory");
      if ((int)(tp - t) > 0) t = tp;
      asm volatile("st.relaxed.gpu.global.u64 [%0], %1;" ::"l"(g_slot + r), "l"(((uint64_t)t << 32) | last_ch) : "memory");
      if (r < 64) {
        sts128(bar + B_LIST, make_uint4(last_ch - 16, last_ch, C_NONE, C_NONE));
        mbar_arrive(bar + B_DEAL);
      }
    }
    if ((int)d.z >= 0) {
      tma_store_wait<0>();
      if (d.z == 0) { TD(6) }
      asm volatile("fence.proxy.async.global;" ::: "memory");
      if (c.x == ST_BOX2Q) mbar_arrive(bar + B_QDONE);
      else note(bar, d.z);
      if (c.x == ST_BOX2L) {
        note(bar, CNT_DONE);
        more = false;
        if (last_ch) deal(bar, r, t, last_ch);
      }
    }
  }
  if (more) note(bar, CNT_DONE);
}

struct Maps {
  const bf16 *shift_k, *x, *gate_w, *ssm_k, *ssm_D;
  uint8_t id[128][4];
  CUtensorMap a[2];
  CUtensorMap b[3];
  CUtensorMap c[3];
  CUtensorMap bk, bv;
  CUtensorMap q, k, v, o;
  CUtensorMap oa, ob, oc;
  CUtensorMap y, xs;
  CUtensorMap cu, ch;
};

constexpr int P_SLOT = 67 * 128, P_V = 35 * 128, P_TAPS = 2 * P_SLOT;
__device__ __forceinline__ void ldsm4t(uint32_t (&r)[4], uint32_t a) {
  asm volatile("ldmatrix.sync.aligned.m8n8.x4.trans.shared.b16 {%0, %1, %2, %3}, [%4];"
               : "=r"(r[0]), "=r"(r[1]), "=r"(r[2]), "=r"(r[3])
               : "r"(a));
}
__device__ __forceinline__ uint32_t fma_bf2(uint32_t a, uint32_t b, uint32_t c) {
  uint32_t r;
  asm("fma.rn.bf16x2 %0, %1, %2, %3;" : "=r"(r) : "r"(a), "r"(b), "r"(c));
  return r;
}
__device__ __forceinline__ void prep_agent(const Maps& maps, uint32_t sbase, int w, int lane) {
  const uint32_t bar = sbase + BAR_OFF, pb = bar + B_PFULL + w * 16;
  const int d0 = (blockIdx.x >> 3) * 64, t0 = (blockIdx.x & 7) * 256 + w * 128;
  mbar_wait_sleep(bar + B_GFULL + 8 * (G_STAGES - 1), 0);
#pragma unroll 1
  for (int i = -1; i < 4; i++) {
    GA(82 + 2 * i)
    if (i >= 0) mbar_wait_sleep(pb + (i & 1) * 8, i >> 1);
    GA(83 + 2 * i)
    const uint32_t so = sbase + G_STG_OFF + w * (P_TAPS + 512) + (i & 1) * P_SLOT;
    if (i < 3 && elect_one()) {
      const uint32_t b = pb + (~i & 1) * 8, dst = so + (i & 1 ? -P_SLOT : P_SLOT);
      mbar_expect_tx(b, i < 0 ? P_SLOT + 512 : P_SLOT);
      const uint64_t pol = policy_evict_first();
      tma_load_2d_hint(dst, &maps.bk, b, d0, t0 + 32 * i + 29, pol);
      tma_load_2d_hint(dst + P_V, &maps.bv, b, d0, t0 + 32 * i + 32, pol);
      if (i < 0) bulk_load(sbase + G_STG_OFF + P_TAPS, maps.shift_k + d0 * 4, 512, b);
    }
    if (i < 0) continue;
    uint32_t ak[4];
#pragma unroll
    for (int r = 0; r < 4; r++) {
      const uint32_t a = so / 128 + r + 4 * (lane & 6) + (((lane >> 2) ^ lane) & 6) + (lane & 1);
      ak[r] = a * 128 + (a & 7) * 16;
    }
    bf16* dst = g_kvT + (size_t)(d0 + (lane >> 2)) * S_LEN + t0 + ((lane & 3) + 4 * i) * 8;
#pragma unroll 1
    for (int cg = 0; cg < 128; cg += 16) {
      uint32_t t01, t23, k[4][4], v[4];
      asm volatile("ld.shared.v2.u32 {%0, %1}, [%2];"
                   : "=r"(t01), "=r"(t23)
                   : "r"(sbase + G_STG_OFF + P_TAPS + cg * 4 + (lane >> 2) * 8));
#pragma unroll
      for (int r = 0; r < 4; r++) ldsm4t(k[r], ak[r] ^ cg);
      ldsm4t(v, (ak[3] ^ cg) + 4096);
      const uint32_t w0 = __byte_perm(t01, 0, 0x1010), w1 = __byte_perm(t01, 0, 0x3232);
      const uint32_t w2 = __byte_perm(t23, 0, 0x1010), w3 = __byte_perm(t23, 0, 0x3232);
#pragma unroll
      for (int j = 0; j < 4; j++)
        v[j] = mul_bf2(fma_bf2(k[3][j], w0, fma_bf2(k[2][j], w1, fma_bf2(k[1][j], w2, mul_bf2(k[0][j], w3)))), v[j]);
      const bool s1 = lane & 1, s2 = lane & 2;
      const uint32_t a0 = s1 ? v[1] : v[0], a1 = s1 ? v[0] : v[1], a2 = s1 ? v[3] : v[2], a3 = s1 ? v[2] : v[3];
      *reinterpret_cast<uint4*>(dst) = make_uint4(s2 ? a2 : a0, s2 ? a3 : a1, s2 ? a0 : a2, s2 ? a1 : a3);
      dst += 8 * S_LEN;
    }
    fence_proxy_async();
    __syncwarp();
  }
  GA(90)
  if (lane == 0) note(bar, CNT_PREP);
  __syncwarp();
  GA(91)
}

__device__ __forceinline__ void qkv_tile(const Maps& maps, int it, int& which, int& m_tile, int& n_tile) {
  const bool q = it == 0 || it >= 5;
  const int b = maps.id[blockIdx.x][it >= 5];
  which = q ? 0 : 2 - (it & 1);
  m_tile = b & 15;
  n_tile = (b >> 4) * 2 + ((0x19 >> it) & 1);
}

constexpr int G_NTILES = 6;
__device__ __forceinline__ uint32_t qkv_flip(int it) { return ((0x0b >> it) & 1) * 3; }
__device__ __forceinline__ void qkv_producer(const Maps& maps, uint32_t sbase, bool first) {
  const uint32_t bar = sbase + BAR_OFF;
  uint32_t stage = 0, phase = 0;
#pragma unroll 1
  for (int it = 0; it < (first ? 1 : G_NTILES); it++) {
    int which, m_tile, n_tile;
    qkv_tile(maps, it, which, m_tile, n_tile);
    const CUtensorMap* ma = &maps.a[which == 0 ? 0 : 1];
    const CUtensorMap* mb = &maps.b[which];
    const int nk = first ? G_STAGES : which == 0 ? 16 : 8;
#pragma unroll 1
    for (int kt = (it == 0 && !first) ? G_STAGES : 0; kt < nk; kt++) {
      if (!first) mbar_wait_sleep(bar + B_GEMPTY + 8 * stage, phase);
      const uint32_t fb = bar + B_GFULL + 8 * stage;
      const uint32_t sa = sbase + stage * G_STAGE_BYTES;
      const int k0 = (kt ^ ((0x14 >> it) & 1) * 7) * 64;
      const bool keep = ((0x1c >> it) & 1) && kt < G_STAGES;
      mbar_expect_tx(fb, keep ? G_B_BYTES : G_STAGE_BYTES);
      if (!keep) tma_load_2d(sbase + (stage ^ qkv_flip(it)) * G_STAGE_BYTES, ma, fb, k0, m_tile * 128);
      tma_load_3d(sa + G_A_BYTES, mb, fb, 0, k0, n_tile * 4);
      if (++stage == G_STAGES) { stage = 0; phase ^= 1; }
      {
        const int b = maps.id[blockIdx.x][1];
        if (it == 2 && kt == (b & 7)) {
          for (int i = 0; i < 2; i++)
            asm volatile("cp.async.bulk.prefetch.tensor.2d.L2.global.tile [%0, {%1, %2}];" ::"l"(&maps.a[0]),
                         "r"((b >> 4) * 128 + i * 64), "r"((b & 15) * 128)
                         : "memory");
          asm volatile("cp.async.bulk.prefetch.tensor.3d.L2.global.tile [%0, {%1, %2, %3}];" ::"l"(&maps.b[1 + ((b >> 3) & 1)]),
                       "r"(0), "r"((b & 7) * 64), "r"((b >> 4) * 8 + 4)
                       : "memory");
        }
        if (it == 3 && kt == (b & 7))
          asm volatile("cp.async.bulk.prefetch.tensor.3d.L2.global.tile [%0, {%1, %2, %3}];" ::"l"(&maps.b[0]), "r"(0),
                       "r"((b & 15) * 64), "r"((b >> 4) * 8)
                       : "memory");
      }
    }
  }
}

__device__ __forceinline__ uint32_t seen_bar(uint32_t item) { return B_SEEN + ((0x700800u >> (8 * item)) & 255); }
__device__ __noinline__ void publisher(uint32_t bar, int lane, uint32_t nsrc, uint32_t item, uint32_t mine) {
  uint32_t done = 0, tot = 0;
#pragma unroll 1
  for (uint32_t spins = 0; (done < nsrc || item < 3) && spins < (1u << 20); spins++) {
    const uint32_t cnt = item ? CNT_CTX - 1 + item : CNT_KV + 1;
    if (item < 3 && __shfl_sync(0xffffffffu, tot, cnt) >= mine) {
      uint32_t v;
      asm volatile("ld.acquire.gpu.global.u32 %0, [%1];" : "=r"(v) : "l"(g_cnt + (lane ? cnt : CNT_PREP) * 32) : "memory");
      if (__all_sync(0xffffffffu, v >= (lane ? 512 : 260))) {
        asm volatile("fence.proxy.async.global;" ::: "memory");
        mbar_arrive_if(bar + seen_bar(item), lane == 0);
        item++;
      }
    }
    uint32_t v = 0;
    if (lane < CNT_N)
      asm volatile("atom.acquire.cta.shared.exch.b32 %0, [%1], 0;" : "=r"(v) : "r"(bar + B_PEND + 4 * lane) : "memory");
    done += __shfl_sync(0xffffffffu, v, CNT_DONE);
    if (lane == CNT_DONE) v = 0;
    if (done == nsrc && lane < CNT_DONE) {
      uint32_t w;
      asm volatile("atom.acquire.cta.shared.exch.b32 %0, [%1], 0;" : "=r"(w) : "r"(bar + B_PEND + 4 * lane) : "memory");
      v += w;
    }
    if (v && lane == 0) { TD(0) }
    if (v) cnt_signal_release(lane, v);
    tot += v;
    if (v && lane == 0) { TD(1) }
    if (!__any_sync(0xffffffffu, v != 0)) __nanosleep(item == 1 ? 1000 : 200);
  }
  __threadfence();
  __syncwarp();
}

__device__ __forceinline__ void gate_rows(const Maps& maps, uint32_t sbase, int w48, int w12, int lane) {
  const uint32_t buf = sbase + w12 * 16384, gb = sbase + BAR_OFF + 768 + w12 * 16;
  if (lane == 0) {
    mbar_init(gb, 1);
    mbar_init(gb + 8, 1);
    fence_barrier_init();
    for (int i = 0; i < 2; i++) {
      mbar_expect_tx(gb + 8 * i, 8192);
      bulk_load(buf + i * 8192, maps.x + (size_t)(w48 + 48 * i) * 4 * DM, 8192, gb + 8 * i);
    }
  }
  __syncwarp();
  uint4 wv[4];
#pragma unroll
  for (int i = 0; i < 4; i++) wv[i] = __ldg(reinterpret_cast<const uint4*>(maps.gate_w + (i * 32 + lane) * 8));
  int it = 0;
#pragma unroll 1
  for (int row = w48 * 4; row < S_LEN; row += 48 * 4, it++) {
    mbar_wait(gb + 8 * (it & 1), (it >> 1) & 1);
    uint4 xv[4][4];
#pragma unroll
    for (int r = 0; r < 4; r++)
#pragma unroll
      for (int i = 0; i < 4; i++) xv[r][i] = lds128(buf + (it & 1) * 8192 + r * 2048 + (i * 32 + lane) * 16);
    float d[2][4];
#pragma unroll
    for (int pr = 0; pr < 2; pr++) {
      d[pr][0] = d[pr][1] = d[pr][2] = d[pr][3] = 0.f;
      auto acc = [&](uint32_t a0, uint32_t a2, uint32_t b0, uint32_t b2, uint32_t w0, uint32_t w2) {
        asm volatile(
            "mma.sync.aligned.m16n8k16.row.col.f32.bf16.bf16.f32 {%0, %1, %2, %3}, {%4, %5, %6, %7}, {%8, %8}, "
            "{%0, %1, %2, %3};"
            : "+f"(d[pr][0]), "+f"(d[pr][1]), "+f"(d[pr][2]), "+f"(d[pr][3])
            : "r"(mul_bf2(a0, w0)), "r"(mul_bf2(b0, w0)), "r"(mul_bf2(a2, w2)), "r"(mul_bf2(b2, w2)), "r"(0x3f803f80u));
      };
#pragma unroll
      for (int i = 0; i < 4; i++) {
        acc(xv[2 * pr][i].x, xv[2 * pr][i].y, xv[2 * pr + 1][i].x, xv[2 * pr + 1][i].y, wv[i].x, wv[i].y);
        acc(xv[2 * pr][i].z, xv[2 * pr][i].w, xv[2 * pr + 1][i].z, xv[2 * pr + 1][i].w, wv[i].z, wv[i].w);
      }
    }
    float sum = (lane & 2) ? ((lane & 1) ? d[1][2] : d[1][0]) : ((lane & 1) ? d[0][2] : d[0][0]);
#pragma unroll
    for (int off = 16; off >= 4; off >>= 1) sum += __shfl_xor_sync(0xffffffffu, sum, off);
    if (lane < 4) g_gate[row + lane] = bf16_round(rcp(1.0f + __expf(-bf16_round(sum))));
    if (lane == 0 && row + 2 * 48 * 4 < S_LEN) {
      mbar_expect_tx(gb + 8 * (it & 1), 8192);
      bulk_load(buf + (it & 1) * 8192, maps.x + (size_t)(row + 2 * 48 * 4) * DM, 8192, gb + 8 * (it & 1));
    }
  }
}

constexpr float Q_SCALE = 0.08838834764831845f * 1.4426950408889634f;
__device__ __forceinline__ uint32_t qkv_consumer(const Maps& maps, const uint32_t sbase, const int wg, bool fused,
                                                 float (&rest)[64]) {
  PHASE_GIVEN
  constexpr int NTILES = G_NTILES;
  float acc[128];
  const uint32_t stg = sbase + G_STG_OFF + wg * 18432;
  const int st_row = warp * 16 + (lane & 7) + ((lane >> 3) & 1) * 8;
  const int st_cb = lane >> 4;
  uint32_t pend[64];
  const CUtensorMap* pend_map = nullptr;
  int pend_c0 = 0, pend_c1 = 0;
  uint32_t sn = 0;
  uint32_t st_a[4];
#pragma unroll
  for (int jp = 0; jp < 4; jp++) {
    st_a[jp] = stg + st_row * 128 + (((jp * 2 + st_cb) ^ (st_row & 7)) << 4);
    asm volatile("" : "+r"(st_a[jp]));
  }
  auto put_box = [&](uint32_t off, const uint32_t* v) {
#pragma unroll
    for (int jp = 0; jp < 4; jp++) stmatrix_x4(st_a[jp] + off, v[jp * 4], v[jp * 4 + 1], v[jp * 4 + 2], v[jp * 4 + 3]);
  };
  GT(gti++)
  const uint64_t da0 = make_desc(sbase + wg * 8192, 16, 1024, DESC_SW128);
  const uint64_t db0 = make_desc(sbase + G_A_BYTES, 8192, 1024, DESC_SW128);
  uint32_t g = 0, oa = 3 * (G_STAGE_BYTES / 16), ob = 0;
  bool go = false;
  mbar_wait(bar + B_GFULL, 0);
  uint32_t gend = 16, when = 0;
#pragma unroll 1
  for (int it = 0;; it++) {
    bool more = false;
#pragma unroll 1
    do {
      GT(gti++)
      wgmma_fence();
#pragma unroll
      for (int kk = 0; kk < 4; kk++)
        wgmma_m64n256_ss_tb(acc, desc_add(da0, oa + kk * 2), desc_add(db0, ob + kk * 128), kk || more);
      wgmma_commit();
      if (go) st_go(bar, wg, wtid, sn - 1);
      g++;
      if (g + wg == 63) {
        if (wg) named_bar_sync(6, 256);
        else named_bar_arrive(6, 256);
      }
      const uint32_t full = (bar + B_GFULL) + 8 * (g & 3);
      const bool here = mbar_test(full, (g >> 2) & 1) || g >= 64;
      oa = ((g & 3) ^ ((0x17 >> (g >> 3)) & 1) * 3) * (G_STAGE_BYTES / 16);
      ob = (g & 3) * (G_STAGE_BYTES / 16);
      go = when & 1;
      when >>= 1;
      if (go) {
        const int c = sn & 3;
        st_wait(bar, wg, sn - 2);
        st_cmd(bar, wg, wtid, sn, ST_BOX1, pend_map, stg + (c & 1) * 8192, pend_c0 + c * 64, pend_c1,
               (c == 3 && it > 1) ? CNT_KV + (it > 3) : -1);
        switch (c) {
          case 0: put_box(0, pend); break;
          case 1: put_box(8192, pend + 16); break;
          case 2: put_box(0, pend + 32); break;
          default: put_box(8192, pend + 48); break;
        }
        sn++;
      }
      if (it < NTILES) {
        wgmma_wait<1>();
        mbar_arrive_if((bar + B_GEMPTY) + 8 * ((g + 2) & 3), wtid == 32 && more);
        if (!here) mbar_wait(full, (g >> 2) & 1);
      }
      more = true;
    } while (g != gend);
    wgmma_wait<0>();
    fence_regs(acc);
    GT(gti++)
    mbar_arrive_if((bar + B_GEMPTY) + 8 * 3, wtid == 32);
    int which, m_tile, n_tile;
    qkv_tile(maps, it, which, m_tile, n_tile);
    if (which == 0) {
      if (it == NTILES - fused) break;
#pragma unroll
      for (int j = 0; j < 128; j++) acc[j] *= Q_SCALE;
    }
#pragma unroll
    for (int j = 0; j < 64; j++) pend[j] = pack_bf16(acc[2 * j], acc[2 * j + 1]);
    pend_map = &maps.c[which];
    pend_c0 = n_tile * 256;
    pend_c1 = m_tile * 128 + wg * 64;
    gend += it == 4 ? 16 : 8;
    when = (it == 4 ? 0x922 : 0x55) << wg;
  }
  if (go) st_go(bar, wg, wtid, sn - 1);
  mbar_wait(bar + B_GEMPTY, 1);
#pragma unroll
  for (int j = 0; j < 32; j++) pend[j] = pack_bf16(acc[2 * j] * Q_SCALE, acc[2 * j + 1] * Q_SCALE);
  put_box(-G_STG_OFF - wg * 10240, pend);
  put_box(16384 - G_STG_OFF - wg * 10240, pend + 16);
  fence_proxy_async();
#pragma unroll
  for (int j = 0; j < 64; j++) rest[j] = acc[64 + j];
  GT(gti++)
  return sn;
}

constexpr int A_TILE = 128 * 128 * 2;
constexpr int A_Q_OFF = 0;
constexpr int A_K_OFF = 2 * A_TILE;
constexpr int A_V_OFF = 4 * A_TILE;
constexpr int A_O_OFF = 6 * A_TILE;
constexpr int A_ITEMS = NH * (S_LEN / 128);

constexpr uint32_t A_ORDER = 0x3120, A_STEPS = 34;
__device__ __forceinline__ int item_m(uint32_t it) { return it & 15; }
__device__ __forceinline__ int item_h(uint32_t it) { return it >> 4; }

constexpr int C_V = 16384, C_MAT = 24576;
constexpr float C_ALPHA = 0.07874506561842957f;
__device__ __forceinline__ void sincos_turn(int p, float inv, float& c, float& s) {
  const float a = (float)p * (inv * 6.283185307179586f);
  asm("cos.approx.ftz.f32 %0, %1;" : "=f"(c) : "f"(a));
  asm("sin.approx.ftz.f32 %0, %1;" : "=f"(s) : "f"(a));
}

__device__ __forceinline__ uint32_t item_of(const Maps& maps, uint32_t r) {
  const uint32_t b = maps.id[blockIdx.x & 127][1];
  return (b >> 4) * 64 + ((A_ORDER >> (4 * r)) & 3) * 16 + ((b ^ ((r & 1) * 15)) & 15);
}

#define PACE 250
#define SPACE 0
#define LCHK 1
#define XMASK 3
#define XFIRST 4
#define C_SIDE 64
__device__ __forceinline__ uint32_t conv_first(const Maps& maps) {
  const uint32_t b = maps.id[blockIdx.x & 127][1];
  return (b >> 4) * 128 + ((b + 15) & 15);
}

__device__ __forceinline__ void conv_consumer(const Maps& maps, uint32_t smem0, uint32_t first, uint32_t step,
                                              uint32_t end, bool pp, bool dealt) {
  PHASE_PROLOGUE
  const uint32_t in_full = bar + B_CFULL + wg * 16;
  const uint32_t ca = sbase + (wg ? A_V_OFF + A_TILE : A_Q_OFF);
  const int w = __shfl_sync(0xffffffffu, warp, 0), g = lane >> 2, c = lane & 3;
  auto fetch = [&](uint32_t ch, uint32_t n) {
    if (w == 2 && ch < C_NONE) {
      if (elect_one()) {
        const uint32_t b = in_full + (n & 1) * 8, d = ca + (n & 1) * 8192;
        const uint64_t pol = policy_evict_first();
        mbar_expect_tx(b, 8192);
        tma_load_2d_hint(d, &maps.cu, b, 0, ch * 64, pol);
        tma_load_2d_hint(d + 4096, &maps.ch, b, 0, ch * 64, pol);
      }
    }
  };
  if (wtid == 96 && wg) { TD(15) }
  uint32_t f1[8][4];
  float tt[16], ts[16];
  uint32_t cc[4], ss[4];
#pragma unroll
  for (int i = 0; i < 16; i++) {
    const int k = 2 * (16 * w + g + 8 * (i & 1)) + 1, n = 2 * (8 * (i >> 1) + 2 * c) + 1;
    float c0, s0, c1, s1;
    sincos_turn(((k * n) << 23) >> 23, 1.f / 512, c0, s0);
    sincos_turn(((k * n + 2 * k) << 23) >> 23, 1.f / 512, c1, s1);
    f1[i >> 2][i & 3] = pack_bf16(c0 * C_ALPHA, c1 * C_ALPHA);
    f1[4 + (i >> 2)][i & 3] = pack_bf16(s0 * -C_ALPHA, s1 * -C_ALPHA);
  }
#pragma unroll
  for (int i = 0; i < 16; i++) {
    const int k = 2 * (16 * w + g + 8 * ((i >> 1) & 1)) + 1, n = 16 - (8 * (i >> 2) + 2 * c + (i & 1));
    float cs;
    sincos_turn(k * n, 1.f / 8192, cs, ts[i]);
    tt[i] = ts[i] * rcp(1.f + cs);
  }
#pragma unroll
  for (int j = 0; j < 4; j++) {
    const int k = 8 * w + g, n = 8 * c + 2 * j;
    float c0, s0, c1, s1;
    sincos_turn((int8_t)(k * n * 8), 1.f / 256, c0, s0);
    sincos_turn((int8_t)((k * n + k) * 8), 1.f / 256, c1, s1);
    cc[j] = pack_bf16(c0, c1);
    ss[j] = pack_bf16(s0, s1);
  }
  named_bar_sync(3, 256);
  fetch(first, 0);
  fetch(first + step, 1);
  const uint32_t va = ca + g * 64 + ((c ^ (g >> 1)) << 4);
  {
    const uint32_t a = va + C_MAT + w * 512, m = 0x80008000u;
    sts128(a, make_uint4(cc[0], cc[1], cc[2], cc[3]));
    sts128(a + 2048, make_uint4(ss[0], ss[1], ss[2], ss[3]));
    sts128(a + 4096, make_uint4(ss[0] ^ m, ss[1] ^ m, ss[2] ^ m, ss[3] ^ m));
    sts128(a + 6144, make_uint4(cc[0], cc[1], cc[2], cc[3]));
  }
  fence_proxy_async();
  named_bar_sync(1 + wg, 128);
  constexpr uint64_t DHI = (2ull << 62) | ((uint64_t)(512 >> 4) << 32);
  const uint32_t d0 = (uint32_t)make_desc(ca, 4096, 0, 0);
  float a5[16];
  uint4* const yb = reinterpret_cast<uint4*>(g_y2T) + (16 * w + g) * 4 + c;
  auto issue5 = [&]() {
#pragma unroll
    for (int ks = 0; ks < 8; ks++) wgmma_m64n32_rs_tb(a5, f1[ks], DHI | (d0 + (C_V >> 4) + ks * 64), ks != 0);
    wgmma_commit();
  };
  auto finish = [&](uint32_t ch, bool on) {
    fence_regs(a5);
    uint4* y = yb + (size_t)ch * 256;
    if (on) {
      y[0] = make_uint4(pack_bf16(a5[0], a5[1]), pack_bf16(a5[4], a5[5]), pack_bf16(a5[8], a5[9]), pack_bf16(a5[12], a5[13]));
      y[32] = make_uint4(pack_bf16(a5[2], a5[3]), pack_bf16(a5[6], a5[7]), pack_bf16(a5[10], a5[11]), pack_bf16(a5[14], a5[15]));
    }
  };
  auto dft32 = [&](float (&d)[32], const float* re, const float* im) {
    uint32_t a[4][4];
#pragma unroll
    for (int i = 0; i < 8; i++) {
      a[i >> 2][i & 3] = pack_bf16(re[2 * i], re[2 * i + 1]);
      a[2 + (i >> 2)][i & 3] = pack_bf16(im[2 * i], im[2 * i + 1]);
    }
    wgmma_fence();
#pragma unroll
    for (int ks = 0; ks < 4; ks++) wgmma_m64n64_rs_tb(d, a[ks], DHI | (d0 + (C_MAT >> 4) + ks * 64), ks != 0);
    wgmma_commit();
  };
  auto rot = [&](float* x, float* y) {
#pragma unroll
    for (int i = 0; i < 16; i++) {
      x[i] = fmaf(-tt[i], y[i], x[i]);
      y[i] = fmaf(ts[i], x[i], y[i]);
      x[i] = fmaf(-tt[i], y[i], x[i]);
    }
  };
  auto load_d = [&](uint32_t ch) {
    return __ldg(reinterpret_cast<const unsigned short*>(maps.ssm_D) + ((ch & (DM - 1)) | (lane & rt_zero)));
  };
  uint32_t dn = load_d(first);
  uint32_t n = 0, prev = 0, ch = first, next = first + step;
#pragma unroll 1
  for (; ch < C_NONE; n++) {
    CT(0)
    float a1[2][32], a2[2][32], a4[32];
    const float dsk = c ? 0.f : __uint_as_float(dn << 16) * C_ALPHA;
    dn = load_d(next);
    uint32_t next2 = next + step < end ? next + step : C_NONE;
    mbar_wait(in_full + (n & 1) * 8, (n >> 1) & 1);
    if (pp) named_bar_sync(4 + wg, 256);
    CT(1)
    wgmma_fence();
#pragma unroll
    for (int ks = 0; ks < 8; ks++)
      wgmma_m64n64_rs_tb(a1[ks >> 2], f1[ks], DHI | (d0 + (n & 1) * 512 + (ks & 3) * 64), (ks & 3) != 0);
    wgmma_commit();
    issue5();
    wgmma_wait<1>();
    fence_regs(a1[0]);
    fence_regs(a1[1]);
    CT(2)
    rot(a1[0], a1[1]);
    dft32(a2[0], a1[0], a1[1]);
    rot(a1[0] + 16, a1[1] + 16);
    a1[0][16] += dsk;
    a1[0][18] += dsk;
    dft32(a2[1], a1[0] + 16, a1[1] + 16);
    CT(3)
    wgmma_wait<2>();
    finish(prev, n > 0);
    wgmma_wait<0>();
    fence_regs(a2[0]);
    fence_regs(a2[1]);
    CT(4)
    if (pp) named_bar_arrive(5 - wg, 256);
    float re[16], im[16];
#pragma unroll
    for (int i = 0; i < 16; i++) {
      re[i] = a2[0][i] * a2[1][i] - a2[0][16 + i] * a2[1][16 + i];
      im[i] = a2[0][i] * a2[1][16 + i] + a2[0][16 + i] * a2[1][i];
    }
    dft32(a4, im, re);
    if (dealt) {
      mbar_wait(bar + (n < 2 ? B_DEAL : B_DEAL2), 0);
      asm volatile("ld.shared.u32 %0, [%1];" : "=r"(next2) : "r"(bar + B_LIST + 4 * n + (n < 2 ? 0 : 8)));
    }
    wgmma_wait<0>();
    fence_regs(a4);
    CT(5)
    rot(a4, a4 + 16);
#pragma unroll
    for (int i = 0; i < 4; i++) {
      const float* x = a4 + 16 - 16 * (i >> 1) + 2 * (i & 1);
      sts128(va + C_V + w * 1024 + (i >> 1) * 4096 + (i & 1) * 512,
             make_uint4(pack_bf16(x[0], x[1]), pack_bf16(x[4], x[5]), pack_bf16(x[8], x[9]), pack_bf16(x[12], x[13])));
    }
    CT(6)
    fence_proxy_async();
    named_bar_sync(1 + wg, 128);
    fetch(next2, n);
    if (wtid == 96 && n > 0) note(bar, CNT_Y2 + ((prev & 112) == 112));
    prev = ch;
    ch = next;
    next = next2;
    CT(7)
  }
  wgmma_fence();
  issue5();
  wgmma_wait<0>();
  finish(prev, (dn | ~rt_zero) != 0);
  named_bar_sync(1 + wg, 128);
  if (wtid == 96 && wg) { TD(8) }
  if (wtid == 96) cnt_signal_release(CNT_Y2 + ((prev & 112) == 112), 1);
  if (wtid == 64) note(bar, CNT_DONE);
  if (wtid == 96 && wg) { TD(9) }
}

__device__ __forceinline__ void attn_producer(const Maps& maps, uint32_t sbase, bool after_qkv, bool to_out,
                                              bool dry) {
  const uint32_t bar = sbase + BAR_OFF;
  const uint32_t q_full = bar + B_QFULL, q_empty = bar + B_QEMPTY;
  const uint32_t k_full = bar + B_KFULL, k_empty = bar + B_KEMPTY, v_full = bar + B_VFULL, v_empty = bar + B_VEMPTY;
  int ndrained = after_qkv ? 0 : G_STAGES;
  auto wait = [&](uint32_t b, uint32_t par) {
    if (!dry) mbar_wait_sleep(b, par);
  };
  auto drained = [&](int upto) {
#pragma unroll 1
    for (; ndrained <= upto; ndrained++) wait(bar + B_GEMPTY + 8 * ndrained, 1);
  };
  uint32_t st = 0, ph = 1, vs = 0, vp = 1;
  int pend_j = -1, pend_h = 0;
  int round = -1, m = -1, h = 0;
  bool last = false;
#pragma unroll 1
  for (;; round++) {
    uint32_t nitem = 0;
    const int tpost = m >= 3 ? m - 1 : m;
#pragma unroll 1
    for (int t = m < 0 ? -1 : 0; t <= m; t++) {
      const int j = (t < m && (round & 1)) ? m - 1 - t : t;
      if (t >= 0) {
        drained(1 + st);
        wait(k_empty + 8 * st, ph);
        if (!dry) {
          mbar_expect_tx(k_full + 8 * st, A_TILE);
          tma_load_3d(sbase + A_K_OFF + st * A_TILE, &maps.k, k_full + 8 * st, 0, j * 128, h * 2);
        }
        if (++st == 2) { st = 0; ph ^= 1; }
      }
      if (pend_j >= 0) {
        drained(3);
        wait(v_empty + 8 * vs, vp);
        if (!dry) {
          mbar_expect_tx(v_full + 8 * vs, A_TILE);
          tma_load_3d(sbase + A_V_OFF + vs * A_TILE, &maps.v, v_full + 8 * vs, 0, pend_j * 128, pend_h * 2);
        }
        if (++vs == 2) { vs = 0; vp ^= 1; }
      }
      pend_j = j;
      pend_h = h;
      if (t == tpost && !last) {
        nitem = dry ? 1 : item_of(maps, round + 1);
        if (round == (dry ? 0 : 3) || blockIdx.x >= 128) {
          nitem = A_ITEMS;
          if (!to_out) cnt_wait(CNT_PREP, dry ? 0 : 260);
          if (to_out) {
            wait(bar + seen_bar(1), 0);
            asm volatile("cp.async.bulk.prefetch.L2.global [%0], 4096;" ::"l"(maps.ssm_k + (size_t)conv_first(maps) * S_LEN));
            if (!dry)
              asm volatile("cp.async.bulk.prefetch.L2.global [%0], 4096;" ::"l"(g_kvT + (size_t)conv_first(maps) * S_LEN));
          }
        }
        const uint32_t qs = (round + 1) & 1;
        wait(q_empty + 8 * qs, (((round + 1) >> 1) & 1) ^ 1);
        if (round == 1 && after_qkv) wait(bar + B_QDONE, 0);
        if (round == 0 && after_qkv) wait(bar + seen_bar(0), 0);
        if (round < 0 && after_qkv) {
          if (!dry) { TD(2) }
          cnt_wait(CNT_KV, dry ? 0 : 512);
          if (!dry) { TD(3) }
        }
        if (nitem >= A_ITEMS || (round < 0 && after_qkv && !dry)) {
          if (!dry) mbar_arrive(q_full + 8 * qs);
        } else {
          drained(qs);
          if (!dry) {
            mbar_expect_tx(q_full + 8 * qs, A_TILE);
            tma_load_3d_hint(sbase + A_Q_OFF + qs * A_TILE, &maps.q, q_full + 8 * qs, 0, item_m(nitem) * 128,
                             item_h(nitem) * 2, policy_evict_first());
          }
        }
      }
    }
    if (last) break;
    last = nitem >= A_ITEMS;
    m = last ? -1 : item_m(nitem);
    h = item_h(nitem);
  }
}

__device__ __forceinline__ uint32_t attn_consumer(const Maps& maps, const uint32_t sbase, const int wg,
                                                  const uint32_t rt_zero, uint32_t sn, float (&rest)[64],
                                                  bool after_qkv) {
  PHASE_GIVEN
  const uint32_t q_full = bar + B_QFULL, q_empty = bar + B_QEMPTY;
  const uint32_t k_full = bar + B_KFULL, k_empty = bar + B_KEMPTY, v_full = bar + B_VFULL;
  float o[64], s[64];
  uint32_t p[32];
  float e[32];
  uint32_t dep = 0;
  constexpr int MIDJ = 5;
  float l0 = 0.f, l1 = 0.f, b0 = 0.f, b1 = 0.f;
  const int sched_own = 4 + wg, sched_other = 5 - wg;

  const uint32_t qd0 = (uint32_t)make_desc(sbase + A_Q_OFF + wg * 8192, 16, 0, 0);
  const uint32_t kd0 = (uint32_t)make_desc(sbase + A_K_OFF, 16, 0, 0);
  const uint32_t vd0 = (uint32_t)make_desc(sbase + A_V_OFF, 16384, 0, 0);
  constexpr uint64_t DHI = DESC_SW128 | ((uint64_t)(1024 >> 4) << 32);
  constexpr uint32_t DST = A_TILE >> 4;
  auto issue_qk = [&](uint32_t qd, uint32_t kd) {
#pragma unroll
    for (int kk = 0; kk < 8; kk++) {
      const uint32_t off = ((kk >> 2) * 16384 + (kk & 3) * 32) >> 4;
      wgmma_m64n128_ss(s, DHI | (qd + off), DHI | (kd + off), kk != 0);
    }
    wgmma_commit();
  };
  auto issue_pv = [&](uint32_t vd, bool accumulate, int nk) {
#pragma unroll
    for (int kk = 0; kk < 8; kk++) {
      if (kk < nk)
        wgmma_m64n128_rs_tb(o, p[4 * kk], p[4 * kk + 1], p[4 * kk + 2], p[4 * kk + 3], DHI | (vd + kk * 128),
                            accumulate || (kk != 0));
    }
    wgmma_commit();
  };
  auto exp_lo = [&](float& a0, float& a1) {
#pragma unroll
    for (int j = 0; j < 8; j++) {
      e[4 * j] = ex2(s[4 * j]);
      e[4 * j + 1] = ex2(s[4 * j + 1]);
      e[4 * j + 2] = ex2(s[4 * j + 2]);
      e[4 * j + 3] = ex2(s[4 * j + 3]);
      a0 += e[4 * j];
      a0 += e[4 * j + 1];
      a1 += e[4 * j + 2];
      a1 += e[4 * j + 3];
      if (j == MIDJ) dep = (__float_as_uint(a0) | __float_as_uint(a1)) & rt_zero;
    }
  };
  auto pack_lo = [&]() {
#pragma unroll
    for (int j = 0; j < 16; j++) p[j] = pack_bf16(e[2 * j], e[2 * j + 1]);
  };
  auto finish_p = [&](float& a0, float& a1) {
    pack_lo();
#pragma unroll
    for (int j = 8; j < 16; j++) {
      const float e0 = ex2(s[4 * j]), e1 = ex2(s[4 * j + 1]), e2 = ex2(s[4 * j + 2]), e3 = ex2(s[4 * j + 3]);
      a0 += e0;
      a0 += e1;
      a1 += e2;
      a1 += e3;
      p[2 * j] = pack_bf16(e0, e1);
      p[2 * j + 1] = pack_bf16(e2, e3);
      if (j == 8 + MIDJ) dep = __float_as_uint(a0) & rt_zero;
    }
  };
  auto quad_sum = [&](float t) {
    t += __shfl_xor_sync(0xffffffffu, t, 1);
    return t + __shfl_xor_sync(0xffffffffu, t, 2);
  };
  auto write_o = [&](float i0, float i1) {
    st_wait(bar, wg, sn - 1);
    const int st_row = warp * 16 + (lane & 7) + ((lane >> 3) & 1) * 8;
    const uint32_t so = sbase + A_O_OFF + wg * 16384 + st_row * 128;
#pragma unroll
    for (int j = 0; j < 16; j += 2)
      stmatrix_x4(so + (j >> 3) * 8192 + ((((j & 7) + (lane >> 4)) ^ (lane & 7)) << 4),
                  pack_bf16(o[4 * j] * i0, o[4 * j + 1] * i0), pack_bf16(o[4 * j + 2] * i1, o[4 * j + 3] * i1),
                  pack_bf16(o[4 * j + 4] * i0, o[4 * j + 5] * i0), pack_bf16(o[4 * j + 6] * i1, o[4 * j + 7] * i1));
  };
  auto store_o = [&](uint32_t r, int kind, uint32_t lazy) {
    const uint32_t it = item_of(maps, r);
    st_post(bar, wg, wtid, sn, kind, (INPLACE & 1) || kind != ST_BOX2Q ? &maps.o : &maps.c[0], sbase + A_O_OFF + wg * 16384, item_h(it) * 128,
            item_m(it) * 128 + wg * 64, CNT_CTX + (r >> 1), lazy);
    sn++;
  };
  auto mask_half = [&](float* sh) {
    const int u = warp * 16 + (lane >> 2) - (lane & 3) * 2;
#pragma unroll
    for (int j = 0; j < 8; j++) {
      if (8 * j > u) sh[4 * j] = -INFINITY;
      if (8 * j + 1 > u) sh[4 * j + 1] = -INFINITY;
      if (8 * j - 8 > u) sh[4 * j + 2] = -INFINITY;
      if (8 * j - 7 > u) sh[4 * j + 3] = -INFINITY;
    }
  };
  ST(0)
  mbar_wait(q_full, 0);
  if (blockIdx.x >= 128) {
    return sn;
  }
  mbar_wait(k_full, 0);
  named_bar_sync(sched_own, 256);
  wgmma_fence();
  issue_qk(qd0, kd0);
  named_bar_arrive(sched_other, 256);
  fence_regs(rest);
#pragma unroll
  for (int i = 0; i < 64; i++) o[i] = rest[i] * Q_SCALE;
  fence_regs(o);
  wgmma_wait<0>();
  fence_regs(s);
  mbar_arrive_if(k_empty, wtid == 32);
  uint32_t g = 0;
  uint32_t rnd = 0;
  int rem = item_m(item_of(maps, 0));
  uint32_t first = 1;
  uint32_t fl = 0;
#define redo (fl & 1)
#define shifted (fl & 2)
  float d0 = 0.f, d1 = 0.f;
  float pi0 = 1.f, pi1 = 1.f;
  ST(1)
  for (;;) {
    if (shifted) {
#pragma unroll
      for (int j = 0; j < 16; j++) {
        s[4 * j] -= d0;
        s[4 * j + 1] -= d0;
        s[4 * j + 2] -= d1;
        s[4 * j + 3] -= d1;
      }
    }
    if (rem == 0 && !redo) {
      mbar_arrive_if(q_empty + 8 * (rnd & 1), wtid == 96);
      rnd++;
      if (wg == 0) mask_half(s);
      else mask_half(s + 32);
    }
    for (;;) {
      const bool kill = rem == 0 && wg == 0;
      const uint32_t kd = kd0 + ((g + 1) & 1) * DST, vd = vd0 + (g & 1) * DST;
      float a0 = 0.f, a1 = 0.f;
      exp_lo(a0, a1);
      fence_regs(e);
      const uint32_t kb = k_full + 8 * ((g + 1) & 1);
      const uint32_t kpar = (((g + 1) >> 1) & 1) ^ (g == A_STEPS - 1 ? 1u : 0u);
      const uint32_t qb = q_full + 8 * (rnd & 1), qpar = ((rnd >> 1) & 1) | dep;
      if (!mbar_try(qb, qpar)) mbar_wait(qb, qpar | ((__float_as_uint(a0) | __float_as_uint(a1)) & rt_zero));
      wgmma_wait<0>();
      fence_regs(o);
      if (kill) {
        mbar_arrive_if(kb + (B_VEMPTY - B_KFULL), wtid == 64 && !redo && g > 0);
        fence_regs(e);
        pack_lo();
#pragma unroll
        for (int j = 16; j < 32; j++) asm volatile("mov.u32 %0, 0;" : "=r"(p[j]));
        goto check;
      }
#pragma unroll
      for (int i = 32; i < 64; i++) asm volatile("" : "+f"(s[i])::"memory");
      mbar_arrive_if(kb + (B_VEMPTY - B_KFULL), wtid == 64 && !redo && g > 0);
      finish_p(a0, a1);
      if (__any_sync(0xffffffffu, !(mbar_try(v_full + 8 * (g & 1), ((g >> 1) & 1) | dep) &
                                    mbar_try(kb, kpar | dep)) ||
                                      !(a0 + a1 < 1.0995116e12f) || !(fminf(a0, a1) > (first ? 9.094947e-13f : -1.f)))) {
      check:
        bool bad = !(a0 + a1 < 1.0995116e12f);
        if (first) bad |= !(fminf(quad_sum(a0), quad_sum(a1)) > 9.094947e-13f);
        if (!redo && __any_sync(0xffffffffu, bad)) {
          d0 = d1 = first ? -INFINITY : 0.f;
#pragma unroll
          for (int j = 0; j < 16; j++) {
            if (j < 8 || !kill) {
              d0 = fmaxf(d0, fmaxf(s[4 * j], s[4 * j + 1]));
              d1 = fmaxf(d1, fmaxf(s[4 * j + 2], s[4 * j + 3]));
            }
          }
#pragma unroll
          for (int x = 1; x <= 2; x++) {
            d0 = fmaxf(d0, __shfl_xor_sync(0xffffffffu, d0, x));
            d1 = fmaxf(d1, __shfl_xor_sync(0xffffffffu, d1, x));
          }
          b0 += d0;
          b1 += d1;
          if (!first) {
            const float al0 = ex2(-d0), al1 = ex2(-d1);
            l0 *= al0;
            l1 *= al1;
#pragma unroll
            for (int j = 0; j < 16; j++) {
              o[4 * j] *= al0;
              o[4 * j + 1] *= al0;
              o[4 * j + 2] *= al1;
              o[4 * j + 3] *= al1;
            }
          }
          fl = 3;
          break;
        }
        mbar_wait(v_full + 8 * (g & 1), (g >> 1) & 1);
        mbar_wait(kb, kpar);
      }
      named_bar_sync(sched_own, 256);
      if (g == A_STEPS - 1) {
        if (first) write_o(pi0, pi1);
        fence_regs(o);
        wgmma_fence();
        issue_pv(vd, !first, 8);
        named_bar_arrive(sched_other, 256);
        if (first) store_o(rnd - 2, ST_BOX2, 0);
        pi0 = rcp(quad_sum(l0 + a0));
        pi1 = rcp(quad_sum(l1 + a1));
        goto done;
      }
      wgmma_fence();
      issue_qk(qd0 + (rnd & 1) * DST, kd);
      if (first) write_o(pi0, pi1);
      fence_regs(o);
      if (kill) {
        wgmma_fence();
        issue_pv(vd, !first, 4);
      } else {
        wgmma_fence();
        issue_pv(vd, !first, 8);
      }
      named_bar_arrive(sched_other, 256);
      fl &= 2;
      l0 += a0;
      l1 += a1;
      if (rem == 0 || first) {
        if (first && (g > 0 || after_qkv)) store_o(g ? rnd - (rem == 0 ? 2 : 1) : 2, g ? ST_BOX2 : ST_BOX2Q, rem);
        first = rem == 0;
        if (first) {
          pi0 = rcp(quad_sum(l0));
          pi1 = rcp(quad_sum(l1));
          l0 = l1 = b0 = b1 = 0.f;
          fl = 0;
          rem = item_m(item_of(maps, rnd)) + 1;
        }
      }
      rem--;
      g++;
      wgmma_wait<1>();
      fence_regs(s);
      mbar_arrive_if(kb + (B_KEMPTY - B_KFULL), wtid == 32);
      ST(g + 1)
      if (rem == 0 || shifted) {
        d0 = b0;
        d1 = b1;
        break;
      }
    }
  }
done:
#undef redo
#undef shifted
  wgmma_wait<0>();
  fence_regs(o);
  write_o(pi0, pi1);
  store_o(3, ST_BOX2L, 0);
  ST(35)
  return sn;
}

constexpr int O_STAGES = 5;
constexpr int O_STAGE_BYTES = 32768;
constexpr int O_Y_OFF = 5 * 32768;
constexpr int O_X_OFF = 6 * 32768;
constexpr int O_NK = HDIM / 64;

__device__ __forceinline__ uint32_t out_stage(uint32_t st) { return ((0x43120u >> (4 * st)) & 7) * O_STAGE_BYTES; }

__device__ __forceinline__ void out_producer(const Maps& maps, uint32_t sbase, bool after_attn, bool dry) {
  const uint32_t bar = sbase + BAR_OFF;
  const uint32_t rank = blockIdx.x & 1;
  const int m_tile = maps.id[blockIdx.x][2] & 15, n_tile = maps.id[blockIdx.x][2] >> 4;
  uint32_t stage = 0, phase = 0, xi = 0;
#pragma unroll 1
  for (int ki = 0; ki < (dry ? 1 : O_NK); ki++) {
    const int kt = (ki & 14) * 4 + ((A_ORDER >> ((ki >> 4) * 4)) & 3) * 2 + (ki & 1);
    const uint32_t fb = bar + B_OFULL + 8 * stage, eb = bar + B_OEMPTY + 8 * stage;
    const uint32_t sa = sbase + out_stage(stage);
    if (ki < O_STAGES) {
      constexpr uint32_t LASTB = B_KEMPTY | ((B_QEMPTY + 8) << 8) | ((B_KEMPTY + 8) << 16) | (B_VEMPTY << 24);
      if (ki > 0 && after_attn) mbar_wait_sleep(bar + ((LASTB >> (8 * ki - 8)) & 255), ki == 2);
      mbar_arrive_cluster_if(eb, 0, !dry);
      mbar_arrive_cluster_if(eb, 1, !dry);
    }
    if (ki == 32) mbar_wait_sleep(bar + seen_bar(2), 0);
    if (!dry) {
      mbar_wait_sleep(eb, phase);
      mbar_expect_tx(fb, O_STAGE_BYTES);
      tma_load_2d_mc(sa + 16384 + rank * 8192, &maps.ob, fb, n_tile * 128 + rank * 64, kt * 64, (uint16_t)3);
      tma_load_2d(sa, &maps.oa, fb, kt * 64, m_tile * 128);
    }
    if (++stage == O_STAGES) { stage = 0; phase ^= 1; }
    if ((ki & XMASK) == XMASK && ki >= XFIRST && xi < 8) {
      if (after_attn && xi < 2) mbar_wait_sleep(bar + B_OFREE + 8 * xi, 0);
      tma_load_3d(sbase + O_X_OFF + (xi & 1) * 16384 + (xi >> 1) * 4096, &maps.xs, bar + B_OY, 0,
                  m_tile * 128 + (xi & 1) * 64 + (xi >> 1) * 16, n_tile * 2);
      xi++;
    }
  }
  if (!dry) mbar_wait_sleep(bar + B_OY2, 0);
}

__device__ __forceinline__ void out_side(const Maps& maps, uint32_t smem0, const float (&gv)[4]) {
  PHASE_PROLOGUE
  const int m_tile = maps.id[blockIdx.x][2] & 15, n_tile = maps.id[blockIdx.x][2] >> 4;
  const bool w0 = __shfl_sync(0xffffffffu, warp, 0) == 0;
  bool have = false;
  auto late = [&](uint32_t spins) {
    have = cnt_wait(CNT_Y2 + 1, 128, spins) || !spins;
    TD(11)
    if (have) {
      mbar_expect_tx(bar + B_OY2, 4096);
      tma_load_3d(sbase + O_Y_OFF + 7 * 4096, &maps.y, bar + B_OY2, 0, n_tile * 128 + 112, m_tile * 2);
    }
  };
  if (w0) {
    if (elect_one()) {
      mbar_expect_tx(bar + B_OY, 65536 - 4096);
      TD(10)
      cnt_wait(CNT_Y2, DM - 128);
      TD(7)
#pragma unroll 1
      for (int i = 0; i < 7; i++) {
        tma_load_3d(sbase + O_Y_OFF + i * 4096, &maps.y, bar + B_OY, 0, n_tile * 128 + i * 16, m_tile * 2);
        __nanosleep(PACE);
      }
      late(1u << 18);
    }
  }
  mbar_wait_sleep(bar + B_OY, 0);
  if (wtid == 0) { TD(12) }
  const int mrow = (lane & 7) + ((lane >> 4) & 1) * 8;
  const int mchunk = warp * 2 + ((lane >> 3) & 1);
  const uint32_t xrow = sbase + O_X_OFF + warp * 4096 + (lane & 15) * 128;
  const uint32_t yrow = sbase + O_Y_OFF + mrow * 128 + ((mchunk ^ (lane & 7)) << 4);
  uint32_t y[7][4], x[7][4], om[4];
#pragma unroll
  for (int i = 0; i < 4; i++) om[i] = pack_bf16(1.0f - gv[i], 1.0f - gv[i]);
  auto xa = [&](int h, int i) { return xrow + h * 16384 + (i >> 2) * 2048 + ((((i & 3) * 2 + (lane >> 4)) ^ (lane & 7)) << 4); };
  auto load = [&](int r, int h, int i) {
    ldsm4t(y[r], yrow + h * 2048 + i * 4096);
    asm volatile("ldmatrix.sync.aligned.m8n8.x4.shared.b16 {%0, %1, %2, %3}, [%4];"
                 : "=r"(x[r][0]), "=r"(x[r][1]), "=r"(x[r][2]), "=r"(x[r][3])
                 : "r"(xa(h, i)));
  };
  auto store = [&](int r, int h, int i, uint32_t om0, uint32_t om1) {
    stmatrix_x4(xa(h, i), mul_bf2(om0, mul_bf2(x[r][0], y[r][0])), mul_bf2(om1, mul_bf2(x[r][1], y[r][1])),
                mul_bf2(om0, mul_bf2(x[r][2], y[r][2])), mul_bf2(om1, mul_bf2(x[r][3], y[r][3])));
  };
#pragma unroll 1
  for (int h = 0; h < 2; h++) {
#pragma unroll
    for (int i = 0; i < 7; i++) load(i, h, i);
#pragma unroll
    for (int i = 0; i < 7; i++) store(i, h, i, h ? om[2] : om[0], h ? om[3] : om[1]);
  }
  __syncwarp();
  mbar_arrive_if(bar + B_OE, lane == 0);
  if (w0 && !__any_sync(0xffffffffu, have)) {
    if (elect_one()) late(0);
  }
  mbar_wait_sleep(bar + B_OY2, 0);
  load(0, 0, 7);
  load(1, 1, 7);
  store(0, 0, 7, om[0], om[1]);
  store(1, 1, 7, om[2], om[3]);
  __syncwarp();
  mbar_arrive_if(bar + B_OY + 8, lane == 0);
  if (wtid == 0) { TD(13) }
}

__device__ __forceinline__ void out_gemm(const Maps& maps, uint32_t smem0) {
  PHASE_PROLOGUE
  const int m_tile = maps.id[blockIdx.x][2] & 15, n_tile = maps.id[blockIdx.x][2] >> 4;
  float acc[2][64];
  undef_regs(acc[0]);
  undef_regs(acc[1]);
  uint32_t stage = 0, phase = 0, prev_stage = 0;
  GT(gti++)
  const float* gp = g_gate + m_tile * 128 + warp * 16 + (lane >> 2);
  const float gv[4] = {__ldcg(gp), __ldcg(gp + 8), __ldcg(gp + 64), __ldcg(gp + 72)};
  if (wg == 1) {
    out_side(maps, smem0, gv);
    return;
  }
  const uint32_t xrow = sbase + O_X_OFF + warp * 4096 + (lane & 15) * 128;
  auto addr = [&](int i) {
    return xrow + (i >> 3) * 16384 + ((i >> 2) & 1) * 2048 + ((((i & 3) * 2 + (lane >> 4)) ^ (lane & 7)) << 4);
  };
  uint32_t b[16][4];
#pragma unroll
  for (int i = 0; i < 64; i++) asm volatile("" : "=r"(b[i >> 2][i & 3]));
  auto ld_b = [&](int q0, int q1) {
#pragma unroll
    for (int i = 0; i < 16; i++)
      if ((i & 7) != 7)
        asm volatile(
            "{\n.reg .pred p;\nsetp.ge.s32 p, %5, %6;\nsetp.le.and.s32 p, %5, %7, p;\n"
            "@p ldmatrix.sync.aligned.m8n8.x4.shared.b16 {%0, %1, %2, %3}, [%4];\n}\n"
            : "+r"(b[i][0]), "+r"(b[i][1]), "+r"(b[i][2]), "+r"(b[i][3])
            : "r"(addr(i)), "r"(i / 4), "r"(q0), "r"(q1)
            : "memory");
  };
  int nq = 0;
  constexpr uint64_t DHI = DESC_SW128 | ((uint64_t)(1024 >> 4) << 32);
#pragma unroll 1
  for (int kt = 0; kt < O_NK - 2; kt++) {
    uint32_t da = (uint32_t)make_desc(sbase + out_stage(stage), 16, 0, 0);
    uint32_t db = (uint32_t)make_desc(sbase + out_stage(stage) + 16384, 8192, 0, 0);
    asm volatile("" : "+r"(da), "+r"(db));
    mbar_wait(bar + B_OFULL + 8 * stage, phase);
    GT(gti++)
#pragma unroll
    for (int kk = 0; kk < 4; kk++) {
      wgmma_wait<2>();
      if (kk == 2)
        mbar_arrive_cluster_if(bar + B_OEMPTY + 8 * prev_stage, wtid >> 6,
                               (wtid & 63) == 32 && kt > 0 && kt - 1 + O_STAGES < O_NK);
      wgmma_fence();
      wgmma_m64n128_ss_tb(acc[0], DHI | (da + kk * 2), DHI | (db + kk * 128), (kt | kk) != 0);
      wgmma_m64n128_ss_tb(acc[1], DHI | (da + 512 + kk * 2), DHI | (db + kk * 128), (kt | kk) != 0);
      wgmma_commit();
      if (kk == 0 && kt >= 52) {
        uint32_t ok;
        asm volatile("{\n.reg .pred p;\nmbarrier.test_wait.parity.shared::cta.b64 p, [%1], 0;\nselp.u32 %0, 1, 0, p;\n}\n"
                     : "=r"(ok)
                     : "r"(bar + B_OE)
                     : "memory");
        if (__all_sync(0xffffffffu, ok)) {
          ld_b(nq, nq);
          nq++;
        }
      }
    }
    prev_stage = stage;
    if (++stage == O_STAGES) { stage = 0; phase ^= 1; }
  }
  if (tid == 0) { TD(14) }
  constexpr int S0 = (O_NK - 2) % O_STAGES, P0 = ((O_NK - 2) / O_STAGES) & 1;
  const uint32_t d0 = (uint32_t)make_desc(sbase, 0, 0, 0);
  auto mma = [&](int h, int k0, int k1) {
    wgmma_fence();
#pragma unroll
    for (int k = k0; k < k1; k++) {
      const uint32_t d = d0 + (out_stage(S0 + (k >> 2)) >> 4);
      wgmma_m64n128_ss_tb(acc[h], DHI | (d + 0x10000 + h * 512 + (k & 3) * 2), DHI | (d + 0x2000400 + (k & 3) * 128), 1);
    }
    wgmma_commit();
  };
#pragma unroll
  for (int p = 0; p < 2; p++) {
    mbar_wait(bar + B_OFULL + 8 * (S0 + p), P0);
    mma(0, 4 * p, 4 * p + 4);
  }
  mma(1, 0, 8);
  uint32_t gg[4];
#pragma unroll
  for (int i = 0; i < 4; i++) gg[i] = pack_bf16(gv[i], gv[i]);
  if (nq < 4) {
    mbar_wait(bar + B_OE, 0);
    ld_b(nq, 3);
  }
  const int w4 = __shfl_sync(0xffffffffu, warp, 0);
#pragma unroll
  for (int i = 0; i < 16; i++) {
    const int h = i >> 3;
    if (i == 0) wgmma_wait<1>();
    if (i == 8) wgmma_wait<0>();
    if ((i & 7) == 0) fence_regs(acc[h]);
    if (i == 8) {   }
    if (i == 7) {
      mbar_wait(bar + B_OY + 8, 0);
#pragma unroll
      for (int j = 7; j < 16; j += 8)
        asm volatile("ldmatrix.sync.aligned.m8n8.x4.shared.b16 {%0, %1, %2, %3}, [%4];"
                     : "=r"(b[j][0]), "=r"(b[j][1]), "=r"(b[j][2]), "=r"(b[j][3])
                     : "r"(addr(j))
                     : "memory");
    }
    const float* a = acc[h] + 8 * (i & 7);
    stmatrix_x4(addr(i), fma_bf2(gg[2 * h], pack_bf16(a[0], a[1]), b[i][0]), fma_bf2(gg[2 * h + 1], pack_bf16(a[2], a[3]), b[i][1]),
                fma_bf2(gg[2 * h], pack_bf16(a[4], a[5]), b[i][2]), fma_bf2(gg[2 * h + 1], pack_bf16(a[6], a[7]), b[i][3]));
    if ((i & 7) == 7) {
      fence_proxy_async();
      __syncwarp();
      if (elect_one()) {
        tma_store_3d(&maps.oc, sbase + O_X_OFF + (h * 4 + w4) * 4096, 0, m_tile * 128 + h * 64 + w4 * 16, n_tile * 2);
        if (h == 1) {
          tma_store_commit();
        }
      }
    }
  }
  GT(gti++)
}

__device__ __noinline__ void leave_kernel(int mask) {
  if (!(mask & 4)) return;
  if (atomicAdd(g_cnt + CNT_DONE * 32, 1u) == 2 * gridDim.x - 1) {
    for (int i = 0; i < CNT_N; i++) g_cnt[i * 32] = 0;
#pragma unroll 4
    for (int i = 0; i < 128; i++) g_slot[i] = 0;
  }
}

__device__ __noinline__ void side_jobs(const Maps& maps, uint32_t sbase) {
  const int w12 = __shfl_sync(0xffffffffu, threadIdx.x >> 5, 0);
  gate_rows(maps, sbase, (blockIdx.x - 128) * 12 + w12, w12, threadIdx.x & 31);
  fence_proxy_async();
  __syncthreads();
  if (threadIdx.x == 320) cnt_signal_release(CNT_PREP, 1);
}

__global__ void __launch_bounds__(384, 1)
    fused_kernel(int mask, const bf16* px, const bf16* pw, const __grid_constant__ Maps maps) {
  extern __shared__ __align__(1024) uint8_t smem_raw[];
  {
    const uint32_t t = threadIdx.x, l = t & 31, u = (blockIdx.x & 127) * 16 + (l >> 1);
    const uint32_t ow = (u >> 5) * HDIM + ((u >> 2) & 7) * 512 + 256 + (u & 3) * 64, ox = u * DM;
    const bf16* p = ((l & 1) ? pw : px) + ((l & 1) ? ow : ox);
    asm volatile("{\n.reg .pred p;\nsetp.ne.u32 p, %1, 0;\n@p prefetch.global.L2 [%0];\n}\n" ::"l"(p), "r"((uint32_t)(t < 32)));
  }
  {
    const uint32_t sbase = __shfl_sync(0xffffffffu, smem_u32(smem_raw), 0);
    const uint32_t bar = sbase + BAR_OFF;
    const int tid = threadIdx.x;
    const bool do_qkv = (mask & 1) && blockIdx.x < 128;
    TL(0, 0)
    if (__shfl_sync(0xffffffffu, tid >> 5, 0) == 1 && do_qkv) {
      if (elect_one()) {
        for (int i = 0; i < G_STAGES; i++) mbar_init(bar + B_GFULL + 8 * i, 1);
        fence_barrier_init();
        qkv_producer(maps, sbase, true);
      }
    }
    if (tid == 0) {
      for (int i = 0; i < G_STAGES; i++) {
        mbar_init(bar + B_GEMPTY + 8 * i, 2);
        mbar_init(bar + B_SFULL + 8 * i, 4);
        mbar_init(bar + B_SFREE + 8 * i, 1);
      }
      for (int i = 0; i < 2; i++) {
        mbar_init(bar + B_OFREE + 8 * i, 1);
        mbar_init(bar + B_QFULL + 8 * i, 1);
        mbar_init(bar + B_QEMPTY + 8 * i, 2);
        mbar_init(bar + B_KFULL + 8 * i, 1);
        mbar_init(bar + B_KEMPTY + 8 * i, 2);
        mbar_init(bar + B_VFULL + 8 * i, 1);
        mbar_init(bar + B_VEMPTY + 8 * i, 2);
      }
      for (int i = 0; i < O_STAGES; i++) {
        mbar_init(bar + B_OFULL + 8 * i, 1);
        mbar_init(bar + B_OEMPTY + 8 * i, 2);
      }
      mbar_init(bar + B_OY, 1);
      for (int i = 0; i < 3; i++) mbar_init(bar + seen_bar(i), 1);
      mbar_init(bar + B_OY2, 1);
      mbar_init(bar + B_DEAL, 1);
      mbar_init(bar + B_DEAL2, 1);
      mbar_init(bar + B_PAIR, 1);
      mbar_init(bar + B_OY + 8, 4);
      mbar_init(bar + B_OE, 4);
      mbar_init(bar + B_QDONE, 2);
      for (int i = 0; i < 8; i++) mbar_init(bar + B_CFULL + 8 * i, 1);
      for (int i = 0; i < CNT_N; i++) asm volatile("st.shared.u32 [%0], 0;" ::"r"(bar + B_PEND + 4 * i) : "memory");
      fence_barrier_init();
    }
    __syncthreads();
    asm volatile("barrier.cluster.arrive.relaxed.aligned;" ::: "memory");
    if ((mask & 1) && blockIdx.x >= 128) side_jobs(maps, sbase);
  }
  uint32_t smem0 = smem_u32(smem_raw);
  PHASE_PROLOGUE
  const bool do_qkv = (mask & 1) && blockIdx.x < 128, do_out = (mask & 4) && blockIdx.x < 128;
  TL(0, 1)

  if (wg != 2) {
    reg_alloc<232>();
    asm volatile("barrier.cluster.wait.acquire.aligned;" ::: "memory");
    if (wg == 1) named_bar_arrive(4, 256);
    uint32_t sn = 0;
    float o[64];
    if (do_qkv) {
      sn = qkv_consumer(maps, sbase, wg, mask & 2, o);
    } else {
      undef_regs(o);
    }
    TL(0, 2) TL(1, 0) TL(1, 1)
    if (mask & 2) {
      sn = attn_consumer(maps, sbase, wg, rt_zero, sn, o, mask & 1);
      TL(2, 0)
      if ((mask & 4) && blockIdx.x < 128 && __shfl_sync(0xffffffffu, threadIdx.x, 0) < 128) {
        named_bar_arrive(3, 256);
      } else {
        const uint32_t b2 = blockIdx.x * 2 + (threadIdx.x >> 7);
        const bool fused = mask & 4, mainc = blockIdx.x < 128;
        const uint32_t first = __shfl_sync(0xffffffffu, !fused ? b2 : mainc ? conv_first(maps) : (b2 - 255) * 128 - C_SIDE, 0);
        conv_consumer(maps, smem_u32(smem_raw), first, !fused ? 264 : mainc ? 16 : 1,
                      !fused ? DM : mainc ? (first | 127) + 1 - C_SIDE : first + C_SIDE, fused && !mainc,
                      fused && mainc);
      }
      TL(1, 2) TL(2, 1) TL(2, 2)
    }
    TL(3, 0) TL(3, 1)
    {
      uint32_t smem0 = smem_u32(smem_raw);
      PHASE_PROLOGUE
      st_wait(bar, wg, sn - 2);
      st_post(bar, wg, wtid, sn, ST_END, nullptr, 0, 0, 0, -1);
    }
    if ((mask & 4) && blockIdx.x < 128) out_gemm(maps, smem_u32(smem_raw));
    tma_store_wait_read<0>();
  } else {
    reg_dealloc<40>();
    asm volatile("barrier.cluster.wait.acquire.aligned;" ::: "memory");
    const int w = __shfl_sync(0xffffffffu, tid >> 5, 0) - 8;
    if (w < 2) {
      if (do_qkv) prep_agent(maps, sbase, w, lane);
      if (elect_one()) store_agent(bar, w, w && do_out ? conv_first(maps) + 48 : 0);
      TL2(3, 2)
    } else {
      if (elect_one()) {
        const bool dry = w == 2;
        if (do_qkv && !dry) qkv_producer(maps, sbase, false);
        if (mask & 2) attn_producer(maps, sbase, do_qkv, do_out, dry);
        if (do_out) out_producer(maps, sbase, mask & 2, dry);
        if (dry) { TD(5) }
      }
      __syncwarp();
      if (w == 2) publisher(bar, tid & 31, !(mask & 2) ? 2 : do_out ? 3 : 4, !do_out ? 3 : do_qkv ? 0 : 2, do_qkv ? 4 : 0);
      if ((tid & 31) == 0) leave_kernel(mask);
    }
  }
}

typedef CUresult (*PFN_tmapEncode)(CUtensorMap*, CUtensorMapDataType, cuuint32_t, void*, const cuuint64_t*,
                                   const cuuint64_t*, const cuuint32_t*, const cuuint32_t*, CUtensorMapInterleave,
                                   CUtensorMapSwizzle, CUtensorMapL2promotion, CUtensorMapFloatOOBfill);
static PFN_tmapEncode s_encode = nullptr;

static void make_map_2d(CUtensorMap* m, const void* ptr, int rows, int cols, int box_rows) {
  cuuint64_t dims[2] = {(cuuint64_t)cols, (cuuint64_t)rows};
  cuuint64_t strides[1] = {(cuuint64_t)cols * 2};
  cuuint32_t box[2] = {cols < 64 ? 32u : 64u, (cuuint32_t)box_rows};
  cuuint32_t es[2] = {1, 1};
  s_encode(m, CU_TENSOR_MAP_DATA_TYPE_BFLOAT16, 2, const_cast<void*>(ptr), dims, strides, box, es,
           CU_TENSOR_MAP_INTERLEAVE_NONE, cols < 64 ? CU_TENSOR_MAP_SWIZZLE_64B : CU_TENSOR_MAP_SWIZZLE_128B, CU_TENSOR_MAP_L2_PROMOTION_L2_256B,
           CU_TENSOR_MAP_FLOAT_OOB_FILL_NONE);
}
static void make_map_3d(CUtensorMap* m, const void* ptr, int rows, int cols, int box_rows, int box_chunks) {
  cuuint64_t dims[3] = {64, (cuuint64_t)rows, (cuuint64_t)(cols / 64)};
  cuuint64_t strides[2] = {(cuuint64_t)cols * 2, 128};
  cuuint32_t box[3] = {64, (cuuint32_t)box_rows, (cuuint32_t)box_chunks};
  cuuint32_t es[3] = {1, 1, 1};
  s_encode(m, CU_TENSOR_MAP_DATA_TYPE_BFLOAT16, 3, const_cast<void*>(ptr), dims, strides, box, es,
           CU_TENSOR_MAP_INTERLEAVE_NONE, CU_TENSOR_MAP_SWIZZLE_128B, CU_TENSOR_MAP_L2_PROMOTION_L2_256B,
           CU_TENSOR_MAP_FLOAT_OOB_FILL_NONE);
}

static cudaLaunchConfig_t fused_cfg(cudaLaunchAttribute* at) {
  cudaLaunchConfig_t cfg = {};
  cfg.gridDim = dim3(132);
  cfg.blockDim = dim3(384);
  cfg.dynamicSmemBytes = SMEM_BYTES;
  cfg.stream = cudaStreamPerThread;
  at[0].id = cudaLaunchAttributeClusterDimension;
  at[0].val.clusterDim.x = 2;
  at[0].val.clusterDim.y = 1;
  at[0].val.clusterDim.z = 1;
  cfg.attrs = at;
  cfg.numAttrs = 1;
  return cfg;
}

extern "C" void kernel_launch(void* const* d_in, const int* in_sizes, int n_in, void* d_out, int out_size) {
  const bf16* x = (const bf16*)d_in[0];
  const bf16* ckv = (const bf16*)d_in[1];
  const bf16* wq = (const bf16*)d_in[2];
  const bf16* wuk = (const bf16*)d_in[3];
  const bf16* wuv = (const bf16*)d_in[4];
  const bf16* wo = (const bf16*)d_in[5];
  const bf16* bk = (const bf16*)d_in[7];
  const bf16* bv = (const bf16*)d_in[8];
  const bf16* shift_k = (const bf16*)d_in[9];
  const bf16* ssm_k = (const bf16*)d_in[10];
  const bf16* ssm_D = (const bf16*)d_in[11];
  const bf16* gate_w = (const bf16*)d_in[12];
  bf16* out = (bf16*)d_out;

  static void *pq = nullptr, *pk = nullptr, *pv = nullptr, *pctx = nullptr, *pb = nullptr, *pu = nullptr;
  static int max_clusters = 0;
  if (!s_encode) {
    void* fn = nullptr;
    cudaDriverEntryPointQueryResult qres;
    cudaGetDriverEntryPoint("cuTensorMapEncodeTiled", &fn, cudaEnableDefault, &qres);
    s_encode = (PFN_tmapEncode)fn;
    cudaGetSymbolAddress(&pq, g_q);
    cudaGetSymbolAddress(&pk, g_k);
    cudaGetSymbolAddress(&pv, g_v);
    cudaGetSymbolAddress(&pctx, g_ctx);
    cudaGetSymbolAddress(&pb, g_y2T);
    cudaGetSymbolAddress(&pu, g_kvT);
    cudaFuncSetAttribute(fused_kernel, cudaFuncAttributeMaxDynamicSharedMemorySize, SMEM_BYTES);
    cudaLaunchAttribute at[1];
    cudaLaunchConfig_t cfg = fused_cfg(at);
    if (cudaOccupancyMaxActiveClusters(&max_clusters, fused_kernel, &cfg) != cudaSuccess) max_clusters = 0;
  }

  Maps all = {};
  make_map_2d(&all.a[0], x, S_LEN, DM, 128);
  make_map_2d(&all.a[1], ckv, S_LEN, DC, 128);
  make_map_3d(&all.b[0], wq, DM, HDIM, 64, 4);
  make_map_3d(&all.b[1], wuk, DC, HDIM, 64, 4);
  make_map_3d(&all.b[2], wuv, DC, HDIM, 64, 4);
  make_map_2d(&all.c[0], pq, S_LEN, HDIM, 64);
  make_map_2d(&all.c[1], pk, S_LEN, HDIM, 64);
  make_map_2d(&all.c[2], pv, S_LEN, HDIM, 64);
  make_map_3d(&all.q, pq, S_LEN, HDIM, 128, 2);
  make_map_3d(&all.k, pk, S_LEN, HDIM, 128, 2);
  make_map_3d(&all.v, pv, S_LEN, HDIM, 128, 2);
  make_map_2d(&all.o, pctx, S_LEN, HDIM, 64);
  all.ssm_k = ssm_k;
  all.ssm_D = ssm_D;
  make_map_2d(&all.oa, pctx, S_LEN, HDIM, 128);
  make_map_2d(&all.ob, wo, HDIM, DM, 64);
  make_map_3d(&all.oc, out, S_LEN, DM, 16, 2);
  make_map_3d(&all.y, pb, DM, S_LEN, 16, 2);
  make_map_3d(&all.xs, x, S_LEN, DM, 16, 2);
  make_map_2d(&all.cu, pu, DM * 64, 32, 64);
  make_map_2d(&all.ch, ssm_k, DM * 64, 32, 64);

  make_map_2d(&all.bk, bk, S_LEN, DM, 35);
  make_map_2d(&all.bv, bv, S_LEN, DM, 32);
  for (int b = 0; b < 128; b++) {
    const int c = b >> 1, r = b & 1;
    const int G = c < 4 ? 0 : c < 36 ? (c - 4) % 8 : 1 + (c - 36) % 7;
    const int i = c < 4 ? 4 + c : c < 36 ? (c - 4) / 8 : 4 + (c - 36) / 7;
    all.id[b][0] = r + 2 * (i & 1) + 4 * (G & 3) + 16 * (i >> 1) + 64 * (G >> 2);
    all.id[b][1] = r + 2 * i + 16 * G;
    all.id[b][2] = r + 2 * G + 16 * i;
  }
  all.shift_k = shift_k;
  all.x = x;
  all.gate_w = gate_w;
  cudaLaunchAttribute at[1];
  cudaLaunchConfig_t cfg = fused_cfg(at);
  if (max_clusters >= 66) {
    cudaLaunchKernelEx(&cfg, fused_kernel, 7, x, wq, all);
  } else {
    for (int m = 1; m <= 4; m <<= 1) cudaLaunchKernelEx(&cfg, fused_kernel, m, x, wq, all);
  }
}
```

```cpp
#include <cuda_runtime.h>
#include <cuda_bf16.h>
#include <cuda.h>
#include <stdint.h>

typedef __nv_bfloat16 bf16;
#define INPLACE 3

constexpr int S_LEN = 2048;
constexpr int DM = 1024;
constexpr int NH = 32;
constexpr int HD = 128;
constexpr int DC = 512;
constexpr int HDIM = NH * HD;

__device__ __align__(1024) bf16 g_q[S_LEN * HDIM];
__device__ __align__(1024) bf16 g_k[S_LEN * HDIM];
__device__ __align__(1024) bf16 g_v[S_LEN * HDIM];
#define g_ctx g_q
__device__ __align__(1024) bf16 g_kvT[DM * S_LEN];
#define g_y2T g_kvT
__device__ __align__(1024) float g_gate[S_LEN];
enum { CNT_KV = 0, CNT_PREP = CNT_KV + 2, CNT_CTX, CNT_Y2 = CNT_CTX + 2, CNT_DONE = CNT_Y2 + 2, CNT_RANK, CNT_N };
__device__ unsigned int g_cnt[CNT_N * 32];
__device__ unsigned long long g_slot[128];

#define TL(k, i)
#define TL2(k, i)
#define TD(i)
#define CT(i)
#define GT(i)
#define GA(i)
#define ST(i)

__device__ __forceinline__ uint32_t smem_u32(const void* p) { return (uint32_t)__cvta_generic_to_shared(p); }

__device__ __forceinline__ void mbar_init(uint32_t bar, uint32_t count) {
  asm volatile("mbarrier.init.shared::cta.b64 [%0], %1;" ::"r"(bar), "r"(count));
}
__device__ __forceinline__ void mbar_expect_tx(uint32_t bar, uint32_t bytes) {
  asm volatile("mbarrier.arrive.expect_tx.shared::cta.b64 _, [%0], %1;" ::"r"(bar), "r"(bytes) : "memory");
}
__device__ __forceinline__ void mbar_arrive(uint32_t bar) {
  asm volatile("mbarrier.arrive.shared::cta.b64 _, [%0];" ::"r"(bar) : "memory");
}
__device__ __forceinline__ void mbar_wait(uint32_t bar, uint32_t parity) {
  uint32_t done;
  uint32_t spins = 0;
  do {
    asm volatile(
        "{\n.reg .pred p;\n"
        "mbarrier.try_wait.parity.shared::cta.b64 p, [%1], %2;\n"
        "selp.u32 %0, 1, 0, p;\n}\n"
        : "=r"(done)
        : "r"(bar), "r"(parity)
        : "memory");
    if (++spins > (1u << 22)) break;
  } while (!done);
}
__device__ __forceinline__ bool mbar_try(uint32_t bar, uint32_t parity) {
  uint32_t done;
  asm volatile(
      "{\n.reg .pred p;\n"
      "mbarrier.try_wait.parity.shared::cta.b64 p, [%1], %2;\n"
      "selp.u32 %0, 1, 0, p;\n}\n"
      : "=r"(done)
      : "r"(bar), "r"(parity)
      : "memory");
  return done != 0;
}
__device__ __forceinline__ bool mbar_test(uint32_t bar, uint32_t parity) {
  uint32_t done;
  asm volatile(
      "{\n.reg .pred p;\n"
      "mbarrier.test_wait.parity.shared::cta.b64 p, [%1], %2;\n"
      "selp.u32 %0, 1, 0, p;\n}\n"
      : "=r"(done)
      : "r"(bar), "r"(parity)
      : "memory");
  return done != 0;
}
__device__ __forceinline__ bool elect_one() {
  uint32_t pred;
  asm volatile("{\n.reg .pred p;\nelect.sync _|p, 0xffffffff;\nselp.u32 %0, 1, 0, p;\n}\n" : "=r"(pred));
  return pred != 0;
}
__device__ __forceinline__ void mbar_arrive_if(uint32_t bar, bool pred) {
  asm volatile(
      "{\n.reg .pred p;\nsetp.ne.b32 p, %1, 0;\n"
      "@p mbarrier.arrive.shared::cta.b64 _, [%0];\n}\n" ::"r"(bar),
      "r"((uint32_t)pred)
      : "memory");
}
__device__ __forceinline__ void mbar_wait_sleep(uint32_t bar, uint32_t parity) {
  uint32_t done;
  uint32_t spins = 0;
  do {
    asm volatile(
        "{\n.reg .pred p;\n"
        "mbarrier.try_wait.parity.shared::cta.b64 p, [%1], %2, %3;\n"
        "selp.u32 %0, 1, 0, p;\n}\n"
        : "=r"(done)
        : "r"(bar), "r"(parity), "r"(20000u)
        : "memory");
    if (++spins > (1u << 16)) break;
  } while (!done);
}
__device__ __forceinline__ void fence_barrier_init() {
  asm volatile("fence.mbarrier_init.release.cluster;" ::: "memory");
}
__device__ __forceinline__ void fence_proxy_async() {
  asm volatile("fence.proxy.async.shared::cta;" ::: "memory");
}
__device__ __forceinline__ void named_bar_sync(int id, int nthreads) {
  asm volatile("bar.sync %0, %1;" ::"r"(id), "r"(nthreads) : "memory");
}
__device__ __forceinline__ void named_bar_arrive(int id, int nthreads) {
  asm volatile("bar.arrive %0, %1;" ::"r"(id), "r"(nthreads) : "memory");
}
__device__ __forceinline__ void tma_load_2d(uint32_t dst, const CUtensorMap* m, uint32_t bar, int c0, int c1) {
  asm volatile(
      "cp.async.bulk.tensor.2d.shared::cluster.global.mbarrier::complete_tx::bytes [%0], [%1, {%3, %4}], [%2];" ::"r"(dst),
      "l"(reinterpret_cast<uint64_t>(m)), "r"(bar), "r"(c0), "r"(c1)
      : "memory");
}
__device__ __forceinline__ void tma_load_3d(uint32_t dst, const CUtensorMap* m, uint32_t bar, int c0, int c1, int c2) {
  asm volatile(
      "cp.async.bulk.tensor.3d.shared::cluster.global.mbarrier::complete_tx::bytes [%0], [%1, {%3, %4, %5}], [%2];" ::"r"(dst),
      "l"(reinterpret_cast<uint64_t>(m)), "r"(bar), "r"(c0), "r"(c1), "r"(c2)
      : "memory");
}
__device__ __forceinline__ void tma_store_2d(const CUtensorMap* m, uint32_t src, int c0, int c1) {
  asm volatile("cp.async.bulk.tensor.2d.global.shared::cta.bulk_group [%0, {%2, %3}], [%1];" ::"l"(
                   reinterpret_cast<uint64_t>(m)),
               "r"(src), "r"(c0), "r"(c1)
               : "memory");
}
__device__ __forceinline__ void bulk_load(uint32_t dst, const void* src, uint32_t bytes, uint32_t bar) {
  asm volatile("cp.async.bulk.shared::cluster.global.mbarrier::complete_tx::bytes [%0], [%1], %2, [%3];" ::"r"(dst),
               "l"(src), "r"(bytes), "r"(bar)
               : "memory");
}
__device__ __forceinline__ void tma_load_2d_mc(uint32_t dst, const CUtensorMap* m, uint32_t bar, int c0, int c1,
                                               uint16_t mask) {
  asm volatile(
      "cp.async.bulk.tensor.2d.shared::cluster.global.mbarrier::complete_tx::bytes.multicast::cluster [%0], [%1, {%3, "
      "%4}], [%2], %5;" ::"r"(dst),
      "l"(reinterpret_cast<uint64_t>(m)), "r"(bar), "r"(c0), "r"(c1), "h"(mask)
      : "memory");
}
__device__ __forceinline__ void mbar_arrive_cluster_if(uint32_t bar, uint32_t cta, bool pred) {
  asm volatile(
      "{\n.reg .b32 ra;\n.reg .pred p;\nsetp.ne.b32 p, %2, 0;\n"
      "mapa.shared::cluster.u32 ra, %0, %1;\n"
      "@p mbarrier.arrive.shared::cluster.b64 _, [ra];\n}\n" ::"r"(bar),
      "r"(cta), "r"((uint32_t)pred)
      : "memory");
}
__device__ __forceinline__ uint64_t policy_evict_first() {
  uint64_t pol;
  asm volatile("createpolicy.fractional.L2::evict_first.b64 %0, 1.0;" : "=l"(pol));
  return pol;
}
__device__ __forceinline__ void tma_load_2d_hint(uint32_t dst, const CUtensorMap* m, uint32_t bar, int c0, int c1,
                                                 uint64_t pol) {
  asm volatile(
      "cp.async.bulk.tensor.2d.shared::cluster.global.mbarrier::complete_tx::bytes.L2::cache_hint [%0], [%1, {%3, %4}], "
      "[%2], %5;" ::"r"(dst),
      "l"(reinterpret_cast<uint64_t>(m)), "r"(bar), "r"(c0), "r"(c1), "l"(pol)
      : "memory");
}
__device__ __forceinline__ void tma_load_3d_hint(uint32_t dst, const CUtensorMap* m, uint32_t bar, int c0, int c1,
                                                 int c2, uint64_t pol) {
  asm volatile(
      "cp.async.bulk.tensor.3d.shared::cluster.global.mbarrier::complete_tx::bytes.L2::cache_hint [%0], [%1, {%3, %4, "
      "%5}], [%2], %6;" ::"r"(dst),
      "l"(reinterpret_cast<uint64_t>(m)), "r"(bar), "r"(c0), "r"(c1), "r"(c2), "l"(pol)
      : "memory");
}
__device__ __forceinline__ void bulk_load_hint(uint32_t dst, const void* src, uint32_t bytes, uint32_t bar, uint64_t pol) {
  asm volatile(
      "cp.async.bulk.shared::cluster.global.mbarrier::complete_tx::bytes.L2::cache_hint [%0], [%1], %2, [%3], %4;" ::"r"(dst),
      "l"(src), "r"(bytes), "r"(bar), "l"(pol)
      : "memory");
}
__device__ __forceinline__ void cnt_signal_release(int which, uint32_t n) {
  asm volatile("red.release.gpu.global.add.u32 [%0], %1;" ::"l"(g_cnt + which * 32), "r"(n) : "memory");
}
__device__ __forceinline__ bool cnt_wait(int which, uint32_t target, uint32_t spins = 0) {
  uint32_t v;
  while (true) {
    asm volatile("ld.acquire.gpu.global.u32 %0, [%1];" : "=r"(v) : "l"(g_cnt + which * 32) : "memory");
    if (v >= target || ++spins > (1u << 18)) break;
    __nanosleep(64);
  }
  asm volatile("fence.proxy.async.global;" ::: "memory");
  return v >= target;
}
__device__ __forceinline__ void tma_store_3d(const CUtensorMap* m, uint32_t src, int c0, int c1, int c2) {
  asm volatile("cp.async.bulk.tensor.3d.global.shared::cta.bulk_group [%0, {%2, %3, %4}], [%1];" ::"l"(
                   reinterpret_cast<uint64_t>(m)),
               "r"(src), "r"(c0), "r"(c1), "r"(c2)
               : "memory");
}
__device__ __forceinline__ void tma_store_commit() { asm volatile("cp.async.bulk.commit_group;" ::: "memory"); }
template <int N>
__device__ __forceinline__ void tma_store_wait_read() {
  asm volatile("cp.async.bulk.wait_group.read %0;" ::"n"(N) : "memory");
}
template <int N>
__device__ __forceinline__ void tma_store_wait() {
  asm volatile("cp.async.bulk.wait_group %0;" ::"n"(N) : "memory");
}
__device__ __forceinline__ void wgmma_fence() { asm volatile("wgmma.fence.sync.aligned;" ::: "memory"); }
__device__ __forceinline__ void wgmma_commit() { asm volatile("wgmma.commit_group.sync.aligned;" ::: "memory"); }
template <int N>
__device__ __forceinline__ void wgmma_wait() {
  asm volatile("wgmma.wait_group.sync.aligned %0;" ::"n"(N) : "memory");
}
template <int R>
__device__ __forceinline__ void reg_alloc() { asm volatile("setmaxnreg.inc.sync.aligned.u32 %0;" ::"n"(R)); }
template <int R>
__device__ __forceinline__ void reg_dealloc() { asm volatile("setmaxnreg.dec.sync.aligned.u32 %0;" ::"n"(R)); }

__device__ __forceinline__ void stmatrix_x4(uint32_t addr, uint32_t r0, uint32_t r1, uint32_t r2, uint32_t r3) {
  asm volatile("stmatrix.sync.aligned.m8n8.x4.shared.b16 [%0], {%1, %2, %3, %4};" ::"r"(addr), "r"(r0), "r"(r1),
               "r"(r2), "r"(r3)
               : "memory");
}
__device__ __forceinline__ uint32_t pack_bf16(float lo, float hi) {
  uint32_t r;
  asm("cvt.rn.bf16x2.f32 %0, %1, %2;" : "=r"(r) : "f"(hi), "f"(lo));
  return r;
}
__device__ __forceinline__ float bf16_round(float x) { return __bfloat162float(__float2bfloat16_rn(x)); }
__device__ __forceinline__ float bf_lo(uint32_t v) { return __uint_as_float(v << 16); }
__device__ __forceinline__ float bf_hi(uint32_t v) { return __uint_as_float(v & 0xffff0000u); }
__device__ __forceinline__ uint4 lds128(uint32_t a) {
  uint4 v;
  asm volatile("ld.shared.v4.u32 {%0, %1, %2, %3}, [%4];" : "=r"(v.x), "=r"(v.y), "=r"(v.z), "=r"(v.w) : "r"(a));
  return v;
}
__device__ __forceinline__ void sts128(uint32_t a, uint4 v) {
  asm volatile("st.shared.v4.u32 [%0], {%1, %2, %3, %4};" ::"r"(a), "r"(v.x), "r"(v.y), "r"(v.z), "r"(v.w) : "memory");
}
__device__ __forceinline__ uint32_t mul_bf2(uint32_t a, uint32_t b) {
  uint32_t r;
  asm("mul.rn.bf16x2 %0, %1, %2;" : "=r"(r) : "r"(a), "r"(b));
  return r;
}
__device__ __forceinline__ float ex2(float x) {
  float y;
  asm("ex2.approx.ftz.f32 %0, %1;" : "=f"(y) : "f"(x));
  return y;
}
__device__ __forceinline__ float rcp(float x) {
  float y;
  asm("rcp.approx.ftz.f32 %0, %1;" : "=f"(y) : "f"(x));
  return y;
}
template <int N>
__device__ __forceinline__ void fence_regs(float (&r)[N]) {
#pragma unroll
  for (int i = 0; i < N; i++) asm volatile("" : "+f"(r[i])::"memory");
}

template <int N>
__device__ __forceinline__ void undef_regs(float (&r)[N]) {
#pragma unroll
  for (int i = 0; i < N; i++) asm volatile("" : "=f"(r[i]));
}
template <int N>
__device__ __forceinline__ void fence_regs_u(uint32_t (&r)[N]) {
#pragma unroll
  for (int i = 0; i < N; i++) asm volatile("" : "+r"(r[i])::"memory");
}

constexpr uint64_t DESC_SW128 = 1ull << 62;
__device__ __forceinline__ uint64_t make_desc(uint32_t addr, uint32_t lbo_bytes, uint32_t sbo_bytes, uint64_t swz) {
  return (uint64_t)((addr & 0x3FFFF) >> 4) | ((uint64_t)((lbo_bytes & 0x3FFFF) >> 4) << 16) |
         ((uint64_t)((sbo_bytes & 0x3FFFF) >> 4) << 32) | swz;
}

__device__ __forceinline__ uint64_t desc_add(uint64_t d, uint32_t off16) {
  return (d & 0xFFFFFFFF00000000ull) | (uint64_t)((uint32_t)d + off16);
}

__device__ __forceinline__ void wgmma_m64n256_ss_tb(float (&d)[128], uint64_t da, uint64_t db, int sd) {
  asm volatile(
    "{\n.reg .pred p;\nsetp.ne.b32 p, %130, 0;\n"
    "wgmma.mma_async.sync.aligned.m64n256k16.f32.bf16.bf16 "
    "{%0, %1, %2, %3, %4, %5, %6, %7, %8, %9, %10, %11, %12, %13, %14, %15, %16, %17, %18, %19, %20, %21, %22, %23, %24, %25, %26, %27, %28, %29, %30, %31, %32, %33, %34, %35, %36, %37, %38, %39, %40, %41, %42, %43, %44, %45, %46, %47, %48, %49, %50, %51, %52, %53, %54, %55, %56, %57, %58, %59, %60, %61, %62, %63, %64, %65, %66, %67, %68, %69, %70, %71, %72, %73, %74, %75, %76, %77, %78, %79, %80, %81, %82, %83, %84, %85, %86, %87, %88, %89, %90, %91, %92, %93, %94, %95, %96, %97, %98, %99, %100, %101, %102, %103, %104, %105, %106, %107, %108, %109, %110, %111, %112, %113, %114, %115, %116, %117, %118, %119, %120, %121, %122, %123, %124, %125, %126, %127}, %128, %129, p, 1, 1, 0, 1;\n}\n"
    : "+f"(d[0]), "+f"(d[1]), "+f"(d[2]), "+f"(d[3]), "+f"(d[4]), "+f"(d[5]), "+f"(d[6]), "+f"(d[7]), "+f"(d[8]), "+f"(d[9]), "+f"(d[10]), "+f"(d[11]), "+f"(d[12]), "+f"(d[13]), "+f"(d[14]), "+f"(d[15]), "+f"(d[16]), "+f"(d[17]), "+f"(d[18]), "+f"(d[19]), "+f"(d[20]), "+f"(d[21]), "+f"(d[22]), "+f"(d[23]), "+f"(d[24]), "+f"(d[25]), "+f"(d[26]), "+f"(d[27]), "+f"(d[28]), "+f"(d[29]), "+f"(d[30]), "+f"(d[31]), "+f"(d[32]), "+f"(d[33]), "+f"(d[34]), "+f"(d[35]), "+f"(d[36]), "+f"(d[37]), "+f"(d[38]), "+f"(d[39]), "+f"(d[40]), "+f"(d[41]), "+f"(d[42]), "+f"(d[43]), "+f"(d[44]), "+f"(d[45]), "+f"(d[46]), "+f"(d[47]), "+f"(d[48]), "+f"(d[49]), "+f"(d[50]), "+f"(d[51]), "+f"(d[52]), "+f"(d[53]), "+f"(d[54]), "+f"(d[55]), "+f"(d[56]), "+f"(d[57]), "+f"(d[58]), "+f"(d[59]), "+f"(d[60]), "+f"(d[61]), "+f"(d[62]), "+f"(d[63]), "+f"(d[64]), "+f"(d[65]), "+f"(d[66]), "+f"(d[67]), "+f"(d[68]), "+f"(d[69]), "+f"(d[70]), "+f"(d[71]), "+f"(d[72]), "+f"(d[73]), "+f"(d[74]), "+f"(d[75]), "+f"(d[76]), "+f"(d[77]), "+f"(d[78]), "+f"(d[79]), "+f"(d[80]), "+f"(d[81]), "+f"(d[82]), "+f"(d[83]), "+f"(d[84]), "+f"(d[85]), "+f"(d[86]), "+f"(d[87]), "+f"(d[88]), "+f"(d[89]), "+f"(d[90]), "+f"(d[91]), "+f"(d[92]), "+f"(d[93]), "+f"(d[94]), "+f"(d[95]), "+f"(d[96]), "+f"(d[97]), "+f"(d[98]), "+f"(d[99]), "+f"(d[100]), "+f"(d[101]), "+f"(d[102]), "+f"(d[103]), "+f"(d[104]), "+f"(d[105]), "+f"(d[106]), "+f"(d[107]), "+f"(d[108]), "+f"(d[109]), "+f"(d[110]), "+f"(d[111]), "+f"(d[112]), "+f"(d[113]), "+f"(d[114]), "+f"(d[115]), "+f"(d[116]), "+f"(d[117]), "+f"(d[118]), "+f"(d[119]), "+f"(d[120]), "+f"(d[121]), "+f"(d[122]), "+f"(d[123]), "+f"(d[124]), "+f"(d[125]), "+f"(d[126]), "+f"(d[127])
    : "l"(da), "l"(db), "r"(sd));
}

__device__ __forceinline__ void wgmma_m64n128_ss(float (&d)[64], uint64_t da, uint64_t db, int sd) {
  asm volatile(
    "{\n.reg .pred p;\nsetp.ne.b32 p, %66, 0;\n"
    "wgmma.mma_async.sync.aligned.m64n128k16.f32.bf16.bf16 "
    "{%0, %1, %2, %3, %4, %5, %6, %7, %8, %9, %10, %11, %12, %13, %14, %15, %16, %17, %18, %19, %20, %21, %22, %23, %24, %25, %26, %27, %28, %29, %30, %31, %32, %33, %34, %35, %36, %37, %38, %39, %40, %41, %42, %43, %44, %45, %46, %47, %48, %49, %50, %51, %52, %53, %54, %55, %56, %57, %58, %59, %60, %61, %62, %63}, %64, %65, p, 1, 1, 0, 0;\n}\n"
    : "+f"(d[0]), "+f"(d[1]), "+f"(d[2]), "+f"(d[3]), "+f"(d[4]), "+f"(d[5]), "+f"(d[6]), "+f"(d[7]), "+f"(d[8]), "+f"(d[9]), "+f"(d[10]), "+f"(d[11]), "+f"(d[12]), "+f"(d[13]), "+f"(d[14]), "+f"(d[15]), "+f"(d[16]), "+f"(d[17]), "+f"(d[18]), "+f"(d[19]), "+f"(d[20]), "+f"(d[21]), "+f"(d[22]), "+f"(d[23]), "+f"(d[24]), "+f"(d[25]), "+f"(d[26]), "+f"(d[27]), "+f"(d[28]), "+f"(d[29]), "+f"(d[30]), "+f"(d[31]), "+f"(d[32]), "+f"(d[33]), "+f"(d[34]), "+f"(d[35]), "+f"(d[36]), "+f"(d[37]), "+f"(d[38]), "+f"(d[39]), "+f"(d[40]), "+f"(d[41]), "+f"(d[42]), "+f"(d[43]), "+f"(d[44]), "+f"(d[45]), "+f"(d[46]), "+f"(d[47]), "+f"(d[48]), "+f"(d[49]), "+f"(d[50]), "+f"(d[51]), "+f"(d[52]), "+f"(d[53]), "+f"(d[54]), "+f"(d[55]), "+f"(d[56]), "+f"(d[57]), "+f"(d[58]), "+f"(d[59]), "+f"(d[60]), "+f"(d[61]), "+f"(d[62]), "+f"(d[63])
    : "l"(da), "l"(db), "r"(sd));
}

__device__ __forceinline__ void wgmma_m64n128_ss_tb(float (&d)[64], uint64_t da, uint64_t db, int sd) {
  asm volatile(
    "{\n.reg .pred p;\nsetp.ne.b32 p, %66, 0;\n"
    "wgmma.mma_async.sync.aligned.m64n128k16.f32.bf16.bf16 "
    "{%0, %1, %2, %3, %4, %5, %6, %7, %8, %9, %10, %11, %12, %13, %14, %15, %16, %17, %18, %19, %20, %21, %22, %23, %24, %25, %26, %27, %28, %29, %30, %31, %32, %33, %34, %35, %36, %37, %38, %39, %40, %41, %42, %43, %44, %45, %46, %47, %48, %49, %50, %51, %52, %53, %54, %55, %56, %57, %58, %59, %60, %61, %62, %63}, %64, %65, p, 1, 1, 0, 1;\n}\n"
    : "+f"(d[0]), "+f"(d[1]), "+f"(d[2]), "+f"(d[3]), "+f"(d[4]), "+f"(d[5]), "+f"(d[6]), "+f"(d[7]), "+f"(d[8]), "+f"(d[9]), "+f"(d[10]), "+f"(d[11]), "+f"(d[12]), "+f"(d[13]), "+f"(d[14]), "+f"(d[15]), "+f"(d[16]), "+f"(d[17]), "+f"(d[18]), "+f"(d[19]), "+f"(d[20]), "+f"(d[21]), "+f"(d[22]), "+f"(d[23]), "+f"(d[24]), "+f"(d[25]), "+f"(d[26]), "+f"(d[27]), "+f"(d[28]), "+f"(d[29]), "+f"(d[30]), "+f"(d[31]), "+f"(d[32]), "+f"(d[33]), "+f"(d[34]), "+f"(d[35]), "+f"(d[36]), "+f"(d[37]), "+f"(d[38]), "+f"(d[39]), "+f"(d[40]), "+f"(d[41]), "+f"(d[42]), "+f"(d[43]), "+f"(d[44]), "+f"(d[45]), "+f"(d[46]), "+f"(d[47]), "+f"(d[48]), "+f"(d[49]), "+f"(d[50]), "+f"(d[51]), "+f"(d[52]), "+f"(d[53]), "+f"(d[54]), "+f"(d[55]), "+f"(d[56]), "+f"(d[57]), "+f"(d[58]), "+f"(d[59]), "+f"(d[60]), "+f"(d[61]), "+f"(d[62]), "+f"(d[63])
    : "l"(da), "l"(db), "r"(sd));
}

__device__ __forceinline__ void wgmma_m64n128_rs_tb(float* d, uint32_t a0, uint32_t a1, uint32_t a2, uint32_t a3, uint64_t db, int sd) {
  asm volatile(
    "{\n.reg .pred p;\nsetp.ne.b32 p, %69, 0;\n"
    "wgmma.mma_async.sync.aligned.m64n128k16.f32.bf16.bf16 "
    "{%0, %1, %2, %3, %4, %5, %6, %7, %8, %9, %10, %11, %12, %13, %14, %15, %16, %17, %18, %19, %20, %21, %22, %23, %24, %25, %26, %27, %28, %29, %30, %31, %32, %33, %34, %35, %36, %37, %38, %39, %40, %41, %42, %43, %44, %45, %46, %47, %48, %49, %50, %51, %52, %53, %54, %55, %56, %57, %58, %59, %60, %61, %62, %63}, {%64, %65, %66, %67}, %68, p, 1, 1, 1;\n}\n"
    : "+f"(d[0]), "+f"(d[1]), "+f"(d[2]), "+f"(d[3]), "+f"(d[4]), "+f"(d[5]), "+f"(d[6]), "+f"(d[7]), "+f"(d[8]), "+f"(d[9]), "+f"(d[10]), "+f"(d[11]), "+f"(d[12]), "+f"(d[13]), "+f"(d[14]), "+f"(d[15]), "+f"(d[16]), "+f"(d[17]), "+f"(d[18]), "+f"(d[19]), "+f"(d[20]), "+f"(d[21]), "+f"(d[22]), "+f"(d[23]), "+f"(d[24]), "+f"(d[25]), "+f"(d[26]), "+f"(d[27]), "+f"(d[28]), "+f"(d[29]), "+f"(d[30]), "+f"(d[31]), "+f"(d[32]), "+f"(d[33]), "+f"(d[34]), "+f"(d[35]), "+f"(d[36]), "+f"(d[37]), "+f"(d[38]), "+f"(d[39]), "+f"(d[40]), "+f"(d[41]), "+f"(d[42]), "+f"(d[43]), "+f"(d[44]), "+f"(d[45]), "+f"(d[46]), "+f"(d[47]), "+f"(d[48]), "+f"(d[49]), "+f"(d[50]), "+f"(d[51]), "+f"(d[52]), "+f"(d[53]), "+f"(d[54]), "+f"(d[55]), "+f"(d[56]), "+f"(d[57]), "+f"(d[58]), "+f"(d[59]), "+f"(d[60]), "+f"(d[61]), "+f"(d[62]), "+f"(d[63])
    : "r"(a0), "r"(a1), "r"(a2), "r"(a3), "l"(db), "r"(sd));
}

__device__ __forceinline__ void wgmma_m64n64_rs_tb(float (&d)[32], const uint32_t (&a)[4], uint64_t db, int sd) {
  asm volatile(
    "{\n.reg .pred p;\nsetp.ne.b32 p, %37, 0;\n"
    "wgmma.mma_async.sync.aligned.m64n64k16.f32.bf16.bf16 "
    "{%0, %1, %2, %3, %4, %5, %6, %7, %8, %9, %10, %11, %12, %13, %14, %15, %16, %17, %18, %19, %20, %21, %22, %23, %24, %25, %26, %27, %28, %29, %30, %31}, {%32, %33, %34, %35}, %36, p, 1, 1, 1;\n}\n"
    : "+f"(d[0]), "+f"(d[1]), "+f"(d[2]), "+f"(d[3]), "+f"(d[4]), "+f"(d[5]), "+f"(d[6]), "+f"(d[7]), "+f"(d[8]), "+f"(d[9]), "+f"(d[10]), "+f"(d[11]), "+f"(d[12]), "+f"(d[13]), "+f"(d[14]), "+f"(d[15]), "+f"(d[16]), "+f"(d[17]), "+f"(d[18]), "+f"(d[19]), "+f"(d[20]), "+f"(d[21]), "+f"(d[22]), "+f"(d[23]), "+f"(d[24]), "+f"(d[25]), "+f"(d[26]), "+f"(d[27]), "+f"(d[28]), "+f"(d[29]), "+f"(d[30]), "+f"(d[31])
    : "r"(a[0]), "r"(a[1]), "r"(a[2]), "r"(a[3]), "l"(db), "r"(sd));
}

__device__ __forceinline__ void wgmma_m64n32_rs_tb(float (&d)[16], const uint32_t (&a)[4], uint64_t db, int sd) {
  asm volatile(
    "{\n.reg .pred p;\nsetp.ne.b32 p, %21, 0;\n"
    "wgmma.mma_async.sync.aligned.m64n32k16.f32.bf16.bf16 "
    "{%0, %1, %2, %3, %4, %5, %6, %7, %8, %9, %10, %11, %12, %13, %14, %15}, {%16, %17, %18, %19}, %20, p, 1, 1, 1;\n}\n"
    : "+f"(d[0]), "+f"(d[1]), "+f"(d[2]), "+f"(d[3]), "+f"(d[4]), "+f"(d[5]), "+f"(d[6]), "+f"(d[7]), "+f"(d[8]), "+f"(d[9]), "+f"(d[10]), "+f"(d[11]), "+f"(d[12]), "+f"(d[13]), "+f"(d[14]), "+f"(d[15])
    : "r"(a[0]), "r"(a[1]), "r"(a[2]), "r"(a[3]), "l"(db), "r"(sd));
}

constexpr int G_STAGES = 4;
constexpr int G_A_BYTES = 128 * 64 * 2;
constexpr int G_B_BYTES = 256 * 64 * 2;
constexpr int G_STAGE_BYTES = G_A_BYTES + G_B_BYTES;
constexpr int G_STG_OFF = G_STAGES * G_STAGE_BYTES;
constexpr int BAR_OFF = G_STG_OFF + 32768 + 2048;
constexpr int SMEM_BYTES = BAR_OFF + 1024;
constexpr int B_GFULL = 0, B_GEMPTY = 32, B_SEEN = 64, B_PFULL = 224;
constexpr int B_KFULL = 80, B_KEMPTY = 96, B_VFULL = 112, B_VEMPTY = 128, B_QFULL = 144, B_QEMPTY = 160,
              B_QDONE = 184;
constexpr int B_CFULL = 192;
constexpr int B_OFREE = 256, B_OFULL = 272, B_OEMPTY = 320, B_OY = 368, B_OY2 = 384, B_OE = 768;
constexpr int B_DEAL = 312, B_DEAL2 = 360, B_LIST = 640, B_PAIR = 504;
constexpr int B_SFULL = 392, B_SFREE = 424, B_PEND = 456, B_SCMD = 512;

#define PHASE_PROLOGUE                                                                \
  uint32_t tid, rt_zero;                                                              \
  asm volatile("mov.u32 %0, %%tid.x;" : "=r"(tid));                                   \
  asm volatile("mov.u32 %0, %%nctaid.y;" : "=r"(rt_zero));                            \
  asm volatile("" : "+r"(smem0));                                                     \
  rt_zero = __shfl_sync(0xffffffffu, rt_zero >> 8, 0);   \
  const uint32_t sbase = __shfl_sync(0xffffffffu, smem0, 0);                          \
  const uint32_t bar = sbase + BAR_OFF;                                               \
  const int wg = __shfl_sync(0xffffffffu, tid >> 7, 0);                               \
  const int warp = (tid >> 5) & 3, lane = tid & 31, wtid = tid & 127;                 \
  (void)rt_zero; (void)bar; (void)warp; (void)lane; (void)wtid;

#define PHASE_GIVEN PHASE_GIVEN_(0)
#define PHASE_GIVEN_(z)                                                               \
  uint32_t tid;                                                                       \
  asm volatile("mov.u32 %0, %%tid.x;" : "=r"(tid));                                   \
  tid |= z;                               \
  const uint32_t bar = sbase + BAR_OFF;                                               \
  const int warp = (tid >> 5) & 3, lane = tid & 31, wtid = tid & 127;

enum { ST_BOX1, ST_BOX2, ST_BOX2Q, ST_BOX2L };
__device__ __forceinline__ void st_cmd(uint32_t bar, int wg, int wtid, uint32_t n, int kind, const void* dst,
                                       uint32_t src, int c0, int c1, int sig, uint32_t lazy = 0) {
  if (wtid == 0) {
    const uint32_t c = bar + B_SCMD + wg * 64 + (n & 1) * 32;
    const uint64_t d = reinterpret_cast<uint64_t>(dst);
    sts128(c, make_uint4(kind, src, c0, c1));
    sts128(c + 16, make_uint4((uint32_t)d, (uint32_t)(d >> 32), sig, lazy));
  }
}
__device__ __forceinline__ void st_go(uint32_t bar, int wg, int wtid, uint32_t n) {
  fence_proxy_async();
  __syncwarp();
  mbar_arrive_if(bar + B_SFULL + wg * 16 + (n & 1) * 8, (wtid & 31) == 0);
}
__device__ __forceinline__ void st_post(uint32_t bar, int wg, int wtid, uint32_t n, int kind, const void* dst,
                                        uint32_t src, int c0, int c1, int sig, uint32_t lazy = 0) {
  st_cmd(bar, wg, wtid, n, kind, dst, src, c0, c1, sig, lazy);
  st_go(bar, wg, wtid, n);
}
__device__ __forceinline__ void st_wait(uint32_t bar, int wg, uint32_t n) {
  const uint32_t b = bar + B_SFREE + wg * 16 + (n & 1) * 8;
  if (!mbar_try(b, ~(n >> 1) & 1)) mbar_wait(b, ~(n >> 1) & 1);
}
__device__ __forceinline__ void note(uint32_t bar, uint32_t cnt) {
  asm volatile("red.release.cta.shared.add.u32 [%0], 1;" ::"r"(bar + B_PEND + 4 * cnt) : "memory");
}
#define LAZY_NS 250
#define DEAL_NS 400
#define DEAL_NS2 1250
constexpr uint32_t C_NONE = 0x10000;
__device__ __forceinline__ void deal(uint32_t bar, uint32_t r, uint32_t t, uint32_t own) {
  uint64_t p;
  uint32_t spins = 0;
  while (true) {
    asm volatile("ld.relaxed.gpu.global.u64 %0, [%1];" : "=l"(p) : "l"(g_slot + 127 - r) : "memory");
    if (p || ++spins > (1u << 18)) break;
    __nanosleep(100);
  }
  const uint32_t pc = (uint32_t)p;
  int dt = (uint32_t)(p >> 32) - t;
  if (r >= 64) {
    sts128(bar + B_LIST, make_uint4(-dt > DEAL_NS2 ? C_NONE : own - 16, -dt > DEAL_NS ? C_NONE : own, C_NONE, C_NONE));
    mbar_arrive(bar + B_DEAL);
    dt = 0;
  }
  sts128(bar + B_LIST + 16, make_uint4(dt > DEAL_NS ? pc : C_NONE, dt > DEAL_NS2 ? pc - 16 : C_NONE, C_NONE, C_NONE));
  mbar_arrive(bar + B_DEAL2);
}
__device__ __forceinline__ void store_agent(uint32_t bar, int wg, uint32_t last_ch, uint32_t n_end) {
  mbar_arrive(bar + B_SFREE + wg * 16);
  mbar_arrive(bar + B_SFREE + wg * 16 + 8);
  bool more = true;
  for (uint32_t n = 0; n < n_end && more; n++) {
    mbar_wait_sleep(bar + B_SFULL + wg * 16 + (n & 1) * 8, (n >> 1) & 1);
    const uint4 c = lds128(bar + B_SCMD + wg * 64 + (n & 1) * 32);
    const uint4 d = lds128(bar + B_SCMD + wg * 64 + (n & 1) * 32 + 16);
    uint32_t t;
    asm volatile("mov.u32 %0, %%globaltimer_lo;" : "=r"(t));
    uint32_t r = 0, tp = t;
    if (c.x == ST_BOX2L && last_ch) {
      mbar_expect_tx(bar + B_PAIR, 4);
      asm volatile(
          "{\n.reg .b32 ra;\nmapa.shared::cluster.u32 ra, %0, %1;\n"
          "st.async.weak.shared::cluster.mbarrier::complete_tx::bytes.u32 [ra + 224], %2, [ra];\n}\n" ::"r"(bar + B_PAIR),
          "r"(~blockIdx.x & 1), "r"(t)
          : "memory");
      mbar_wait_sleep(bar + B_PAIR, 0);
      r = atomicAdd(g_cnt + CNT_RANK * 32, 1u) & 127;
      asm volatile("ld.shared.u32 %0, [%1];" : "=r"(tp) : "r"(bar + B_PAIR + 224) : "memory");
      if ((int)(tp - t) < 0) tp = t;
      asm volatile("st.relaxed.gpu.global.u64 [%0], %1;" ::"l"(g_slot + r), "l"(((uint64_t)tp << 32) | last_ch) : "memory");
      if (r < 64) {
        sts128(bar + B_LIST, make_uint4(last_ch - 16, last_ch, C_NONE, C_NONE));
        mbar_arrive(bar + B_DEAL);
      } else {
        deal(bar, r, tp, last_ch);
      }
    }
    for (uint32_t t1 = t; d.w && t1 - t < (2 * d.w + wg) * LAZY_NS;) {
      __nanosleep(200);
      asm volatile("mov.u32 %0, %%globaltimer_lo;" : "=r"(t1));
    }
    const CUtensorMap* dst = reinterpret_cast<const CUtensorMap*>((uint64_t)d.x | ((uint64_t)d.y << 32));
    tma_store_2d(dst, c.y, c.z, c.w);
    if (c.x >= ST_BOX2) tma_store_2d(dst, c.y + 8192, c.z + 64, c.w);
    tma_store_commit();
    tma_store_wait_read<0>();
    mbar_arrive(bar + B_SFREE + wg * 16 + (n & 1) * 8);
    if (c.x == ST_BOX2L) mbar_arrive(bar + B_OFREE + 8 * wg);
    if ((int)d.z >= 0) {
      tma_store_wait<0>();
      if (d.z == 0) { TD(6) }
      asm volatile("fence.proxy.async.global;" ::: "memory");
      if (c.x == ST_BOX2Q) mbar_arrive(bar + B_QDONE);
      else note(bar, d.z);
      if (c.x == ST_BOX2L) {
        note(bar, CNT_DONE);
        more = false;
        if (last_ch && r < 64) deal(bar, r, tp, last_ch);
      }
    }
  }
  if (more) note(bar, CNT_DONE);
}

struct Maps {
  const bf16 *shift_k, *x, *gate_w, *ssm_k, *ssm_D;
  uint8_t id[128][4];
  CUtensorMap a[2];
  CUtensorMap b[3];
  CUtensorMap c[3];
  CUtensorMap bk, bv;
  CUtensorMap q, k, v, o;
  CUtensorMap oa, ob, oc;
  CUtensorMap y, xs;
  CUtensorMap cu, ch;
};

constexpr int P_SLOT = 67 * 128, P_V = 35 * 128, P_TAPS = 2 * P_SLOT;
__device__ __forceinline__ void ldsm4t(uint32_t (&r)[4], uint32_t a) {
  asm volatile("ldmatrix.sync.aligned.m8n8.x4.trans.shared.b16 {%0, %1, %2, %3}, [%4];"
               : "=r"(r[0]), "=r"(r[1]), "=r"(r[2]), "=r"(r[3])
               : "r"(a));
}
__device__ __forceinline__ uint32_t fma_bf2(uint32_t a, uint32_t b, uint32_t c) {
  uint32_t r;
  asm("fma.rn.bf16x2 %0, %1, %2, %3;" : "=r"(r) : "r"(a), "r"(b), "r"(c));
  return r;
}
__device__ __forceinline__ void prep_agent(const Maps& maps, uint32_t sbase, int w, int lane) {
  const uint32_t bar = sbase + BAR_OFF, pb = bar + B_PFULL + w * 16;
  const int d0 = (blockIdx.x >> 3) * 64, t0 = (blockIdx.x & 7) * 256 + w * 128;
  mbar_wait_sleep(bar + B_GFULL + 8 * (G_STAGES - 1), 0);
#pragma unroll 1
  for (int i = -1; i < 4; i++) {
    GA(82 + 2 * i)
    if (i >= 0) mbar_wait_sleep(pb + (i & 1) * 8, i >> 1);
    GA(83 + 2 * i)
    const uint32_t so = sbase + G_STG_OFF + w * (P_TAPS + 512) + (i & 1) * P_SLOT;
    if (i < 3 && elect_one()) {
      const uint32_t b = pb + (~i & 1) * 8, dst = so + (i & 1 ? -P_SLOT : P_SLOT);
      mbar_expect_tx(b, i < 0 ? P_SLOT + 512 : P_SLOT);
      const uint64_t pol = policy_evict_first();
      tma_load_2d_hint(dst, &maps.bk, b, d0, t0 + 32 * i + 29, pol);
      tma_load_2d_hint(dst + P_V, &maps.bv, b, d0, t0 + 32 * i + 32, pol);
      if (i < 0) bulk_load(sbase + G_STG_OFF + P_TAPS, maps.shift_k + d0 * 4, 512, b);
    }
    if (i < 0) continue;
    uint32_t ak[4];
#pragma unroll
    for (int r = 0; r < 4; r++) {
      const uint32_t a = so / 128 + r + 4 * (lane & 6) + (((lane >> 2) ^ lane) & 6) + (lane & 1);
      ak[r] = a * 128 + (a & 7) * 16;
    }
    bf16* dst = g_kvT + (size_t)(d0 + (lane >> 2)) * S_LEN + t0 + ((lane & 3) + 4 * i) * 8;
#pragma unroll 1
    for (int cg = 0; cg < 128; cg += 16) {
      uint32_t t01, t23, k[4][4], v[4];
      asm volatile("ld.shared.v2.u32 {%0, %1}, [%2];"
                   : "=r"(t01), "=r"(t23)
                   : "r"(sbase + G_STG_OFF + P_TAPS + cg * 4 + (lane >> 2) * 8));
#pragma unroll
      for (int r = 0; r < 4; r++) ldsm4t(k[r], ak[r] ^ cg);
      ldsm4t(v, (ak[3] ^ cg) + 4096);
      const uint32_t w0 = __byte_perm(t01, 0, 0x1010), w1 = __byte_perm(t01, 0, 0x3232);
      const uint32_t w2 = __byte_perm(t23, 0, 0x1010), w3 = __byte_perm(t23, 0, 0x3232);
#pragma unroll
      for (int j = 0; j < 4; j++)
        v[j] = mul_bf2(fma_bf2(k[3][j], w0, fma_bf2(k[2][j], w1, fma_bf2(k[1][j], w2, mul_bf2(k[0][j], w3)))), v[j]);
      const bool s1 = lane & 1, s2 = lane & 2;
      const uint32_t a0 = s1 ? v[1] : v[0], a1 = s1 ? v[0] : v[1], a2 = s1 ? v[3] : v[2], a3 = s1 ? v[2] : v[3];
      *reinterpret_cast<uint4*>(dst) = make_uint4(s2 ? a2 : a0, s2 ? a3 : a1, s2 ? a0 : a2, s2 ? a1 : a3);
      dst += 8 * S_LEN;
    }
    fence_proxy_async();
    __syncwarp();
  }
  GA(90)
  if (lane == 0) note(bar, CNT_PREP);
  __syncwarp();
  GA(91)
}

__device__ __forceinline__ void qkv_tile(const Maps& maps, int it, int& which, int& m_tile, int& n_tile) {
  const bool q = it == 0 || it >= 5;
  const int b = maps.id[blockIdx.x][it >= 5];
  which = q ? 0 : 2 - (it & 1);
  m_tile = b & 15;
  n_tile = (b >> 4) * 2 + ((0x19 >> it) & 1);
}

constexpr int G_NTILES = 6;
__device__ __forceinline__ uint32_t qkv_flip(int it) { return ((0x0b >> it) & 1) * 3; }
__device__ __forceinline__ void qkv_producer(const Maps& maps, uint32_t sbase, bool first) {
  const uint32_t bar = sbase + BAR_OFF;
  uint32_t stage = 0, phase = 0;
#pragma unroll 1
  for (int it = 0; it < (first ? 1 : G_NTILES); it++) {
    int which, m_tile, n_tile;
    qkv_tile(maps, it, which, m_tile, n_tile);
    const CUtensorMap* ma = &maps.a[which == 0 ? 0 : 1];
    const CUtensorMap* mb = &maps.b[which];
    const int nk = first ? G_STAGES : which == 0 ? 16 : 8;
#pragma unroll 1
    for (int kt = (it == 0 && !first) ? G_STAGES : 0; kt < nk; kt++) {
      if (!first) mbar_wait_sleep(bar + B_GEMPTY + 8 * stage, phase);
      const uint32_t fb = bar + B_GFULL + 8 * stage;
      const uint32_t sa = sbase + stage * G_STAGE_BYTES;
      const int k0 = (kt ^ ((0x14 >> it) & 1) * 7) * 64;
      const bool keep = ((0x1c >> it) & 1) && kt < G_STAGES;
      mbar_expect_tx(fb, keep ? G_B_BYTES : G_STAGE_BYTES);
      if (!keep) tma_load_2d(sbase + (stage ^ qkv_flip(it)) * G_STAGE_BYTES, ma, fb, k0, m_tile * 128);
      tma_load_3d(sa + G_A_BYTES, mb, fb, 0, k0, n_tile * 4);
      if (++stage == G_STAGES) { stage = 0; phase ^= 1; }
      {
        const int b = maps.id[blockIdx.x][1];
        if (it == 2 && kt == (b & 7)) {
          for (int i = 0; i < 2; i++)
            asm volatile("cp.async.bulk.prefetch.tensor.2d.L2.global.tile [%0, {%1, %2}];" ::"l"(&maps.a[0]),
                         "r"((b >> 4) * 128 + i * 64), "r"((b & 15) * 128)
                         : "memory");
          asm volatile("cp.async.bulk.prefetch.tensor.3d.L2.global.tile [%0, {%1, %2, %3}];" ::"l"(&maps.b[1 + ((b >> 3) & 1)]),
                       "r"(0), "r"((b & 7) * 64), "r"((b >> 4) * 8 + 4)
                       : "memory");
        }
        if (it == 3 && kt == (b & 7))
          asm volatile("cp.async.bulk.prefetch.tensor.3d.L2.global.tile [%0, {%1, %2, %3}];" ::"l"(&maps.b[0]), "r"(0),
                       "r"((b & 15) * 64), "r"((b >> 4) * 8)
                       : "memory");
      }
    }
  }
}

__device__ __forceinline__ uint32_t seen_bar(uint32_t item) { return B_SEEN + ((0x700800u >> (8 * item)) & 255); }
__device__ __noinline__ void publisher(uint32_t bar, int lane, uint32_t nsrc, uint32_t item, uint32_t mine) {
  uint32_t done = 0, tot = 0;
#pragma unroll 1
  for (uint32_t spins = 0; (done < nsrc || item < 3) && spins < (1u << 20); spins++) {
    const uint32_t cnt = item ? CNT_CTX - 1 + item : CNT_KV + 1;
    if (item < 3 && __shfl_sync(0xffffffffu, tot, cnt) >= mine) {
      uint32_t v;
      asm volatile("ld.acquire.gpu.global.u32 %0, [%1];" : "=r"(v) : "l"(g_cnt + (lane ? cnt : CNT_PREP) * 32) : "memory");
      if (__all_sync(0xffffffffu, v >= (lane ? 512 : 260))) {
        asm volatile("fence.proxy.async.global;" ::: "memory");
        mbar_arrive_if(bar + seen_bar(item), lane == 0);
        item++;
      }
    }
    uint32_t v = 0;
    if (lane < CNT_N)
      asm volatile("atom.acquire.cta.shared.exch.b32 %0, [%1], 0;" : "=r"(v) : "r"(bar + B_PEND + 4 * lane) : "memory");
    done += __shfl_sync(0xffffffffu, v, CNT_DONE);
    if (lane == CNT_DONE) v = 0;
    if (done == nsrc && lane < CNT_DONE) {
      uint32_t w;
      asm volatile("atom.acquire.cta.shared.exch.b32 %0, [%1], 0;" : "=r"(w) : "r"(bar + B_PEND + 4 * lane) : "memory");
      v += w;
    }
    if (v && lane == 0) { TD(0) }
    if (v) cnt_signal_release(lane, v);
    tot += v;
    if (v && lane == 0) { TD(1) }
    if (!__any_sync(0xffffffffu, v != 0)) __nanosleep(item == 1 ? 1000 : 200);
  }
  __threadfence();
  __syncwarp();
}

__device__ __forceinline__ void gate_rows(const Maps& maps, uint32_t sbase, int w48, int w12, int lane) {
  const uint32_t buf = sbase + w12 * 16384, gb = sbase + BAR_OFF + 768 + w12 * 16;
  if (lane == 0) {
    mbar_init(gb, 1);
    mbar_init(gb + 8, 1);
    fence_barrier_init();
    for (int i = 0; i < 2; i++) {
      mbar_expect_tx(gb + 8 * i, 8192);
      bulk_load(buf + i * 8192, maps.x + (size_t)(w48 + 48 * i) * 4 * DM, 8192, gb + 8 * i);
    }
  }
  __syncwarp();
  uint4 wv[4];
#pragma unroll
  for (int i = 0; i < 4; i++) wv[i] = __ldg(reinterpret_cast<const uint4*>(maps.gate_w + (i * 32 + lane) * 8));
  int it = 0;
#pragma unroll 1
  for (int row = w48 * 4; row < S_LEN; row += 48 * 4, it++) {
    mbar_wait(gb + 8 * (it & 1), (it >> 1) & 1);
    uint4 xv[4][4];
#pragma unroll
    for (int r = 0; r < 4; r++)
#pragma unroll
      for (int i = 0; i < 4; i++) xv[r][i] = lds128(buf + (it & 1) * 8192 + r * 2048 + (i * 32 + lane) * 16);
    float d[2][4];
#pragma unroll
    for (int pr = 0; pr < 2; pr++) {
      d[pr][0] = d[pr][1] = d[pr][2] = d[pr][3] = 0.f;
      auto acc = [&](uint32_t a0, uint32_t a2, uint32_t b0, uint32_t b2, uint32_t w0, uint32_t w2) {
        asm volatile(
            "mma.sync.aligned.m16n8k16.row.col.f32.bf16.bf16.f32 {%0, %1, %2, %3}, {%4, %5, %6, %7}, {%8, %8}, "
            "{%0, %1, %2, %3};"
            : "+f"(d[pr][0]), "+f"(d[pr][1]), "+f"(d[pr][2]), "+f"(d[pr][3])
            : "r"(mul_bf2(a0, w0)), "r"(mul_bf2(b0, w0)), "r"(mul_bf2(a2, w2)), "r"(mul_bf2(b2, w2)), "r"(0x3f803f80u));
      };
#pragma unroll
      for (int i = 0; i < 4; i++) {
        acc(xv[2 * pr][i].x, xv[2 * pr][i].y, xv[2 * pr + 1][i].x, xv[2 * pr + 1][i].y, wv[i].x, wv[i].y);
        acc(xv[2 * pr][i].z, xv[2 * pr][i].w, xv[2 * pr + 1][i].z, xv[2 * pr + 1][i].w, wv[i].z, wv[i].w);
      }
    }
    float sum = (lane & 2) ? ((lane & 1) ? d[1][2] : d[1][0]) : ((lane & 1) ? d[0][2] : d[0][0]);
#pragma unroll
    for (int off = 16; off >= 4; off >>= 1) sum += __shfl_xor_sync(0xffffffffu, sum, off);
    if (lane < 4) g_gate[row + lane] = bf16_round(rcp(1.0f + __expf(-bf16_round(sum))));
    if (lane == 0 && row + 2 * 48 * 4 < S_LEN) {
      mbar_expect_tx(gb + 8 * (it & 1), 8192);
      bulk_load(buf + (it & 1) * 8192, maps.x + (size_t)(row + 2 * 48 * 4) * DM, 8192, gb + 8 * (it & 1));
    }
  }
}

constexpr float Q_SCALE = 0.08838834764831845f * 1.4426950408889634f;
__device__ __forceinline__ uint32_t qkv_consumer(const Maps& maps, const uint32_t sbase, const int wg, bool fused,
                                                 float (&rest)[64], uint32_t rt_zero) {
  PHASE_GIVEN_(rt_zero)
  constexpr int NTILES = G_NTILES;
  float acc[128];
  const uint32_t stg = sbase + G_STG_OFF + wg * 18432;
  const int st_row = warp * 16 + (lane & 7) + ((lane >> 3) & 1) * 8;
  const int st_cb = lane >> 4;
  uint32_t pend[64];
  const CUtensorMap* pend_map = nullptr;
  int pend_c0 = 0, pend_c1 = 0;
  uint32_t sn = 0;
  uint32_t st_a[4];
#pragma unroll
  for (int jp = 0; jp < 4; jp++) {
    st_a[jp] = stg + st_row * 128 + (((jp * 2 + st_cb) ^ (st_row & 7)) << 4);
    asm volatile("" : "+r"(st_a[jp]));
  }
  auto put_box = [&](uint32_t off, const uint32_t* v) {
#pragma unroll
    for (int jp = 0; jp < 4; jp++) stmatrix_x4(st_a[jp] + off, v[jp * 4], v[jp * 4 + 1], v[jp * 4 + 2], v[jp * 4 + 3]);
  };
  GT(gti++)
  const int hf = wg ^ 1;
  const uint64_t da0 = make_desc(sbase + hf * 8192, 16, 1024, DESC_SW128);
  const uint64_t db0 = make_desc(sbase + G_A_BYTES, 8192, 1024, DESC_SW128);
  uint32_t g = 0, oa = 3 * (G_STAGE_BYTES / 16), ob = 0;
  bool go = false;
  mbar_wait(bar + B_GFULL, 0);
  uint32_t gend = 16, when = 0;
#pragma unroll 1
  for (int it = 0;; it++) {
    bool more = false;
#pragma unroll 1
    do {
      GT(gti++)
      wgmma_fence();
#pragma unroll
      for (int kk = 0; kk < 4; kk++)
        wgmma_m64n256_ss_tb(acc, desc_add(da0, oa + kk * 2), desc_add(db0, ob + kk * 128), kk || more);
      wgmma_commit();
      if (go) st_go(bar, wg, wtid, sn - 1);
      g++;
      if (g + wg == 63) {
        if (wg) named_bar_sync(6, 256);
        else named_bar_arrive(6, 256);
      }
      const uint32_t full = (bar + B_GFULL) + 8 * (g & 3);
      const bool here = mbar_test(full, (g >> 2) & 1) || g >= 64;
      oa = ((g & 3) ^ ((0x17 >> (g >> 3)) & 1) * 3) * (G_STAGE_BYTES / 16);
      ob = (g & 3) * (G_STAGE_BYTES / 16);
      go = when & 1;
      when >>= 1;
      if (go) {
        const int c = sn & 3;
        st_wait(bar, wg, sn - 2);
        st_cmd(bar, wg, wtid, sn, ST_BOX1, pend_map, stg + (c & 1) * 8192, pend_c0 + c * 64, pend_c1,
               (c == 3 && it > 1) ? CNT_KV + (it > 3) : -1);
        switch (c) {
          case 0: put_box(0, pend); break;
          case 1: put_box(8192, pend + 16); break;
          case 2: put_box(0, pend + 32); break;
          default: put_box(8192, pend + 48); break;
        }
        sn++;
      }
      if (it < NTILES) {
        wgmma_wait<1>();
        mbar_arrive_if((bar + B_GEMPTY) + 8 * ((g + 2) & 3), wtid == 32 && more);
        if (!here) mbar_wait(full, (g >> 2) & 1);
      }
      more = true;
    } while (g != gend);
    wgmma_wait<0>();
    fence_regs(acc);
    GT(gti++)
    mbar_arrive_if((bar + B_GEMPTY) + 8 * 3, wtid == 32);
    int which, m_tile, n_tile;
    qkv_tile(maps, it, which, m_tile, n_tile);
    if (which == 0) {
      if (it == NTILES - fused) break;
#pragma unroll
      for (int j = 0; j < 128; j++) acc[j] *= Q_SCALE;
    }
#pragma unroll
    for (int j = 0; j < 64; j++) pend[j] = pack_bf16(acc[2 * j], acc[2 * j + 1]);
    pend_map = &maps.c[which];
    pend_c0 = n_tile * 256;
    pend_c1 = m_tile * 128 + hf * 64;
    gend += it == 4 ? 16 : 8;
    when = (it == 4 ? 0x922 : 0x55) << wg;
  }
  if (go) st_go(bar, wg, wtid, sn - 1);
  mbar_wait(bar + B_GEMPTY, 1);
#pragma unroll
  for (int j = 0; j < 32; j++) pend[j] = pack_bf16(acc[2 * j] * Q_SCALE, acc[2 * j + 1] * Q_SCALE);
  put_box(-G_STG_OFF - wg * 18432 + hf * 8192, pend);
  put_box(16384 - G_STG_OFF - wg * 18432 + hf * 8192, pend + 16);
  fence_proxy_async();
#pragma unroll
  for (int j = 0; j < 64; j++) rest[j] = acc[64 + j];
  GT(gti++)
  return sn;
}

constexpr int A_TILE = 128 * 128 * 2;
constexpr int A_Q_OFF = 0;
constexpr int A_K_OFF = 2 * A_TILE;
constexpr int A_V_OFF = 4 * A_TILE;
constexpr int A_O_OFF = 6 * A_TILE;
constexpr int A_ITEMS = NH * (S_LEN / 128);

constexpr uint32_t A_ORDER = 0x3120, A_STEPS = 34;
__device__ __forceinline__ int item_m(uint32_t it) { return it & 15; }
__device__ __forceinline__ int item_h(uint32_t it) { return it >> 4; }

constexpr int C_V = 16384, C_MAT = 24576;
constexpr float C_ALPHA = 0.07874506561842957f;
__device__ __forceinline__ void sincos_turn(int p, float inv, float& c, float& s) {
  const float a = (float)p * (inv * 6.283185307179586f);
  asm("cos.approx.ftz.f32 %0, %1;" : "=f"(c) : "f"(a));
  asm("sin.approx.ftz.f32 %0, %1;" : "=f"(s) : "f"(a));
}

__device__ __forceinline__ uint32_t head_of(const Maps& maps, uint32_t r) { return (maps.id[blockIdx.x & 127][3] >> (2 * r)) & 3; }
__device__ __forceinline__ uint32_t item_at(const Maps& maps, uint32_t h) {
  const uint32_t b = maps.id[blockIdx.x & 127][1];
  return (b >> 4) * 64 + h * 16 + ((b ^ ((h >> 1) * 15)) & 15);
}
__device__ __forceinline__ uint32_t item_of(const Maps& maps, uint32_t r) { return item_at(maps, head_of(maps, r)); }

#define PACE 250
#define SPACE 0
#define LCHK 1
#define XMASK 3
#define XFIRST 12
#define C_SIDE 64
__device__ __forceinline__ uint32_t conv_first(const Maps& maps) {
  const uint32_t b = maps.id[blockIdx.x & 127][1];
  return (b >> 4) * 128 + ((b + 15) & 15);
}

__device__ __forceinline__ void conv_consumer(const Maps& maps, uint32_t smem0, uint32_t first, uint32_t step,
                                              uint32_t end, bool pp, bool dealt) {
  PHASE_PROLOGUE
  const uint32_t in_full = bar + B_CFULL + wg * 16;
  const uint32_t ca = sbase + (wg ? A_V_OFF + A_TILE : A_Q_OFF);
  const int w = __shfl_sync(0xffffffffu, warp, 0), g = lane >> 2, c = lane & 3;
  auto fetch = [&](uint32_t ch, uint32_t n) {
    if (w == 2 && ch < C_NONE) {
      if (elect_one()) {
        const uint32_t b = in_full + (n & 1) * 8, d = ca + (n & 1) * 8192;
        const uint64_t pol = policy_evict_first();
        mbar_expect_tx(b, 8192);
        tma_load_2d_hint(d, &maps.cu, b, 0, ch * 64, pol);
        tma_load_2d_hint(d + 4096, &maps.ch, b, 0, ch * 64, pol);
      }
    }
  };
  if (wtid == 96 && wg) { TD(15) }
  uint32_t f1[8][4];
  float tt[16], ts[16];
  uint32_t cc[4], ss[4];
#pragma unroll
  for (int i = 0; i < 16; i++) {
    const int k = 2 * (16 * w + g + 8 * (i & 1)) + 1, n = 2 * (8 * (i >> 1) + 2 * c) + 1;
    float c0, s0, c1, s1;
    sincos_turn(((k * n) << 23) >> 23, 1.f / 512, c0, s0);
    sincos_turn(((k * n + 2 * k) << 23) >> 23, 1.f / 512, c1, s1);
    f1[i >> 2][i & 3] = pack_bf16(c0 * C_ALPHA, c1 * C_ALPHA);
    f1[4 + (i >> 2)][i & 3] = pack_bf16(s0 * -C_ALPHA, s1 * -C_ALPHA);
  }
#pragma unroll
  for (int i = 0; i < 16; i++) {
    const int k = 2 * (16 * w + g + 8 * ((i >> 1) & 1)) + 1, n = 16 - (8 * (i >> 2) + 2 * c + (i & 1));
    float cs;
    sincos_turn(k * n, 1.f / 8192, cs, ts[i]);
    tt[i] = ts[i] * rcp(1.f + cs);
  }
#pragma unroll
  for (int j = 0; j < 4; j++) {
    const int k = 8 * w + g, n = 8 * c + 2 * j;
    float c0, s0, c1, s1;
    sincos_turn((int8_t)(k * n * 8), 1.f / 256, c0, s0);
    sincos_turn((int8_t)((k * n + k) * 8), 1.f / 256, c1, s1);
    cc[j] = pack_bf16(c0, c1);
    ss[j] = pack_bf16(s0, s1);
  }
  named_bar_sync(3, 256);
  fetch(first, 0);
  fetch(first + step, 1);
  const uint32_t va = ca + g * 64 + ((c ^ (g >> 1)) << 4);
  {
    const uint32_t a = va + C_MAT + w * 512, m = 0x80008000u;
    sts128(a, make_uint4(cc[0], cc[1], cc[2], cc[3]));
    sts128(a + 2048, make_uint4(ss[0], ss[1], ss[2], ss[3]));
    sts128(a + 4096, make_uint4(ss[0] ^ m, ss[1] ^ m, ss[2] ^ m, ss[3] ^ m));
    sts128(a + 6144, make_uint4(cc[0], cc[1], cc[2], cc[3]));
  }
  fence_proxy_async();
  named_bar_sync(1 + wg, 128);
  constexpr uint64_t DHI = (2ull << 62) | ((uint64_t)(512 >> 4) << 32);
  const uint32_t d0 = (uint32_t)make_desc(ca, 4096, 0, 0);
  float a5[16];
  uint4* const yb = reinterpret_cast<uint4*>(g_y2T) + (16 * w + g) * 4 + c;
  auto issue5 = [&]() {
#pragma unroll
    for (int ks = 0; ks < 8; ks++) wgmma_m64n32_rs_tb(a5, f1[ks], DHI | (d0 + (C_V >> 4) + ks * 64), ks != 0);
    wgmma_commit();
  };
  auto finish = [&](uint32_t ch, bool on) {
    fence_regs(a5);
    uint4* y = yb + (size_t)ch * 256;
    if (on) {
      y[0] = make_uint4(pack_bf16(a5[0], a5[1]), pack_bf16(a5[4], a5[5]), pack_bf16(a5[8], a5[9]), pack_bf16(a5[12], a5[13]));
      y[32] = make_uint4(pack_bf16(a5[2], a5[3]), pack_bf16(a5[6], a5[7]), pack_bf16(a5[10], a5[11]), pack_bf16(a5[14], a5[15]));
    }
  };
  auto dft32 = [&](float (&d)[32], const float* re, const float* im) {
    uint32_t a[4][4];
#pragma unroll
    for (int i = 0; i < 8; i++) {
      a[i >> 2][i & 3] = pack_bf16(re[2 * i], re[2 * i + 1]);
      a[2 + (i >> 2)][i & 3] = pack_bf16(im[2 * i], im[2 * i + 1]);
    }
    wgmma_fence();
#pragma unroll
    for (int ks = 0; ks < 4; ks++) wgmma_m64n64_rs_tb(d, a[ks], DHI | (d0 + (C_MAT >> 4) + ks * 64), ks != 0);
    wgmma_commit();
  };
  auto rot = [&](float* x, float* y) {
#pragma unroll
    for (int i = 0; i < 16; i++) {
      x[i] = fmaf(-tt[i], y[i], x[i]);
      y[i] = fmaf(ts[i], x[i], y[i]);
      x[i] = fmaf(-tt[i], y[i], x[i]);
    }
  };
  auto load_d = [&](uint32_t ch) {
    return __ldg(reinterpret_cast<const unsigned short*>(maps.ssm_D) + ((ch & (DM - 1)) | (lane & rt_zero)));
  };
  uint32_t dn = load_d(first);
  uint32_t n = 0, prev = 0, ch = first, next = first + step;
#pragma unroll 1
  for (; ch < C_NONE; n++) {
    CT(0)
    float a1[2][32], a2[2][32], a4[32];
    const float dsk = c ? 0.f : __uint_as_float(dn << 16) * C_ALPHA;
    dn = load_d(next);
    uint32_t next2 = next + step < end ? next + step : C_NONE;
    mbar_wait(in_full + (n & 1) * 8, (n >> 1) & 1);
    if (pp) named_bar_sync(4 + wg, 256);
    CT(1)
    wgmma_fence();
#pragma unroll
    for (int ks = 0; ks < 8; ks++)
      wgmma_m64n64_rs_tb(a1[ks >> 2], f1[ks], DHI | (d0 + (n & 1) * 512 + (ks & 3) * 64), (ks & 3) != 0);
    wgmma_commit();
    issue5();
    wgmma_wait<1>();
    fence_regs(a1[0]);
    fence_regs(a1[1]);
    CT(2)
    rot(a1[0], a1[1]);
    dft32(a2[0], a1[0], a1[1]);
    rot(a1[0] + 16, a1[1] + 16);
    a1[0][16] += dsk;
    a1[0][18] += dsk;
    dft32(a2[1], a1[0] + 16, a1[1] + 16);
    CT(3)
    wgmma_wait<2>();
    finish(prev, n > 0);
    wgmma_wait<0>();
    fence_regs(a2[0]);
    fence_regs(a2[1]);
    CT(4)
    if (pp) named_bar_arrive(5 - wg, 256);
    float re[16], im[16];
#pragma unroll
    for (int i = 0; i < 16; i++) {
      re[i] = a2[0][i] * a2[1][i] - a2[0][16 + i] * a2[1][16 + i];
      im[i] = a2[0][i] * a2[1][16 + i] + a2[0][16 + i] * a2[1][i];
    }
    dft32(a4, im, re);
    if (dealt) {
      mbar_wait(bar + (n < 2 ? B_DEAL : B_DEAL2), 0);
      asm volatile("ld.shared.u32 %0, [%1];" : "=r"(next2) : "r"(bar + B_LIST + 4 * n + (n < 2 ? 0 : 8)));
    }
    wgmma_wait<0>();
    fence_regs(a4);
    CT(5)
    rot(a4, a4 + 16);
#pragma unroll
    for (int i = 0; i < 4; i++) {
      const float* x = a4 + 16 - 16 * (i >> 1) + 2 * (i & 1);
      sts128(va + C_V + w * 1024 + (i >> 1) * 4096 + (i & 1) * 512,
             make_uint4(pack_bf16(x[0], x[1]), pack_bf16(x[4], x[5]), pack_bf16(x[8], x[9]), pack_bf16(x[12], x[13])));
    }
    CT(6)
    fence_proxy_async();
    named_bar_sync(1 + wg, 128);
    fetch(next2, n);
    if (wtid == 96 && n > 0) note(bar, CNT_Y2 + ((prev & 112) == 112));
    prev = ch;
    ch = next;
    next = next2;
    CT(7)
  }
  wgmma_fence();
  issue5();
  wgmma_wait<0>();
  finish(prev, (dn | ~rt_zero) != 0);
  named_bar_sync(1 + wg, 128);
  if (wtid == 96 && wg) { TD(8) }
  if (wtid == 96) cnt_signal_release(CNT_Y2 + ((prev & 112) == 112), 1);
  if (wtid == 64) note(bar, CNT_DONE);
  if (wtid == 96 && wg) { TD(9) }
}

__device__ __forceinline__ void attn_producer(const Maps& maps, uint32_t sbase, bool after_qkv, bool to_out,
                                              bool dry) {
  const uint32_t bar = sbase + BAR_OFF;
  const uint32_t q_full = bar + B_QFULL, q_empty = bar + B_QEMPTY;
  const uint32_t k_full = bar + B_KFULL, k_empty = bar + B_KEMPTY, v_full = bar + B_VFULL, v_empty = bar + B_VEMPTY;
  int ndrained = after_qkv ? 0 : G_STAGES;
  auto wait = [&](uint32_t b, uint32_t par) {
    if (!dry) mbar_wait_sleep(b, par);
  };
  auto drained = [&](int upto) {
#pragma unroll 1
    for (; ndrained <= upto; ndrained++) wait(bar + B_GEMPTY + 8 * ndrained, 1);
  };
  uint32_t st = 0, ph = 1, vs = 0, vp = 1;
  int pend_j = -1, pend_h = 0;
  int round = -1, m = -1, h = 0;
  bool last = false;
#pragma unroll 1
  for (;; round++) {
    uint32_t nitem = 0;
    const int tpost = m >= 3 ? m - 1 : m;
#pragma unroll 1
    for (int t = m < 0 ? -1 : 0; t <= m; t++) {
      const int j = (t < m && (h & 2)) ? m - 1 - t : t;
      if (t >= 0) {
        drained(1 + st);
        wait(k_empty + 8 * st, ph);
        if (!dry) {
          mbar_expect_tx(k_full + 8 * st, A_TILE);
          tma_load_3d(sbase + A_K_OFF + st * A_TILE, &maps.k, k_full + 8 * st, 0, j * 128, h * 2);
        }
        if (++st == 2) { st = 0; ph ^= 1; }
      }
      if (pend_j >= 0) {
        drained(3);
        wait(v_empty + 8 * vs, vp);
        if (!dry) {
          mbar_expect_tx(v_full + 8 * vs, A_TILE);
          tma_load_3d(sbase + A_V_OFF + vs * A_TILE, &maps.v, v_full + 8 * vs, 0, pend_j * 128, pend_h * 2);
        }
        if (++vs == 2) { vs = 0; vp ^= 1; }
      }
      pend_j = j;
      pend_h = h;
      if (t == tpost && !last) {
        nitem = dry ? 1 : item_of(maps, round + 1);
        if (round == (dry ? 0 : 3) || blockIdx.x >= 128) {
          nitem = A_ITEMS;
          if (!to_out) cnt_wait(CNT_PREP, dry ? 0 : 260);
          if (to_out) {
            wait(bar + seen_bar(1), 0);
            asm volatile("cp.async.bulk.prefetch.L2.global [%0], 4096;" ::"l"(maps.ssm_k + (size_t)conv_first(maps) * S_LEN));
            if (!dry)
              asm volatile("cp.async.bulk.prefetch.L2.global [%0], 4096;" ::"l"(g_kvT + (size_t)conv_first(maps) * S_LEN));
          }
        }
        const uint32_t qs = (round + 1) & 1;
        wait(q_empty + 8 * qs, (((round + 1) >> 1) & 1) ^ 1);
        if (round == 1 && after_qkv) wait(bar + B_QDONE, 0);
        if (round == 0 && after_qkv) wait(bar + seen_bar(0), 0);
        if (round < 0 && after_qkv) {
          if (!dry) { TD(2) }
          cnt_wait(CNT_KV, dry ? 0 : 512);
          if (!dry) { TD(3) }
        }
        if (nitem >= A_ITEMS || (round < 0 && after_qkv && !dry)) {
          if (!dry) mbar_arrive(q_full + 8 * qs);
        } else {
          drained(qs);
          if (!dry) {
            mbar_expect_tx(q_full + 8 * qs, A_TILE);
            tma_load_3d_hint(sbase + A_Q_OFF + qs * A_TILE, &maps.q, q_full + 8 * qs, 0, item_m(nitem) * 128,
                             item_h(nitem) * 2, policy_evict_first());
          }
        }
      }
    }
    if (last) break;
    last = nitem >= A_ITEMS;
    m = last ? -1 : item_m(nitem);
    h = item_h(nitem);
  }
}

__device__ __forceinline__ void put_o(uint32_t sbase, int wg, int warp, int lane, const float (&o)[64], float i0, float i1) {
  const int st_row = warp * 16 + (lane & 7) + ((lane >> 3) & 1) * 8;
  const uint32_t so = sbase + A_O_OFF + wg * 16384 + st_row * 128;
#pragma unroll
  for (int j = 0; j < 16; j += 2)
    stmatrix_x4(so + (j >> 3) * 8192 + ((((j & 7) + (lane >> 4)) ^ (lane & 7)) << 4),
                pack_bf16(o[4 * j] * i0, o[4 * j + 1] * i0), pack_bf16(o[4 * j + 2] * i1, o[4 * j + 3] * i1),
                pack_bf16(o[4 * j + 4] * i0, o[4 * j + 5] * i0), pack_bf16(o[4 * j + 6] * i1, o[4 * j + 7] * i1));
}
__device__ __forceinline__ uint32_t attn_consumer(const Maps& maps, const uint32_t sbase, const int wg,
                                                  const uint32_t rt_zero, uint32_t sn, float (&rest)[64],
                                                  bool after_qkv, float (&o)[64], float (&s)[64], float& pi0, float& pi1) {
  PHASE_GIVEN
  const uint32_t q_full = bar + B_QFULL, q_empty = bar + B_QEMPTY;
  const uint32_t k_full = bar + B_KFULL, k_empty = bar + B_KEMPTY, v_full = bar + B_VFULL;
  uint32_t p[32];
  float e[32];
  uint32_t dep = 0;
  constexpr int MIDJ = 5;
  float l0 = 0.f, l1 = 0.f, b0 = 0.f, b1 = 0.f;
  const int sched_own = 4 + wg, sched_other = 5 - wg;

  const int hf = wg ^ 1;
  const uint32_t qd0 = (uint32_t)make_desc(sbase + A_Q_OFF + hf * 8192, 16, 0, 0);
  const uint32_t kd0 = (uint32_t)make_desc(sbase + A_K_OFF, 16, 0, 0);
  const uint32_t vd0 = (uint32_t)make_desc(sbase + A_V_OFF, 16384, 0, 0);
  constexpr uint64_t DHI = DESC_SW128 | ((uint64_t)(1024 >> 4) << 32);
  constexpr uint32_t DST = A_TILE >> 4;
  auto issue_qk = [&](uint32_t qd, uint32_t kd) {
#pragma unroll
    for (int kk = 0; kk < 8; kk++) {
      const uint32_t off = ((kk >> 2) * 16384 + (kk & 3) * 32) >> 4;
      wgmma_m64n128_ss(s, DHI | (qd + off), DHI | (kd + off), kk != 0);
    }
    wgmma_commit();
  };
  auto issue_pv = [&](uint32_t vd, bool accumulate, int nk) {
#pragma unroll
    for (int kk = 0; kk < 8; kk++) {
      if (kk < nk)
        wgmma_m64n128_rs_tb(o, p[4 * kk], p[4 * kk + 1], p[4 * kk + 2], p[4 * kk + 3], DHI | (vd + kk * 128),
                            accumulate || (kk != 0));
    }
    wgmma_commit();
  };
  auto exp_lo = [&](float& a0, float& a1) {
#pragma unroll
    for (int j = 0; j < 8; j++) {
      e[4 * j] = ex2(s[4 * j]);
      e[4 * j + 1] = ex2(s[4 * j + 1]);
      e[4 * j + 2] = ex2(s[4 * j + 2]);
      e[4 * j + 3] = ex2(s[4 * j + 3]);
      a0 += e[4 * j];
      a0 += e[4 * j + 1];
      a1 += e[4 * j + 2];
      a1 += e[4 * j + 3];
      if (j == MIDJ) dep = (__float_as_uint(a0) | __float_as_uint(a1)) & rt_zero;
    }
  };
  auto pack_lo = [&]() {
#pragma unroll
    for (int j = 0; j < 16; j++) p[j] = pack_bf16(e[2 * j], e[2 * j + 1]);
  };
  auto finish_p = [&](float& a0, float& a1) {
    pack_lo();
#pragma unroll
    for (int j = 8; j < 16; j++) {
      const float e0 = ex2(s[4 * j]), e1 = ex2(s[4 * j + 1]), e2 = ex2(s[4 * j + 2]), e3 = ex2(s[4 * j + 3]);
      a0 += e0;
      a0 += e1;
      a1 += e2;
      a1 += e3;
      p[2 * j] = pack_bf16(e0, e1);
      p[2 * j + 1] = pack_bf16(e2, e3);
      if (j == 8 + MIDJ) dep = __float_as_uint(a0) & rt_zero;
    }
  };
  auto quad_sum = [&](float t) {
    t += __shfl_xor_sync(0xffffffffu, t, 1);
    return t + __shfl_xor_sync(0xffffffffu, t, 2);
  };
  auto write_o = [&](float i0, float i1) {
    st_wait(bar, wg, sn - 1);
    put_o(sbase, wg, warp, lane, o, i0, i1);
  };
  auto store_o = [&](uint32_t r, int kind, uint32_t lazy) {
    const uint32_t it = item_at(maps, kind == ST_BOX2Q ? 1 : head_of(maps, r));
    st_cmd(bar, wg, wtid, sn, kind, (INPLACE & 1) || kind != ST_BOX2Q ? &maps.o : &maps.c[0], sbase + A_O_OFF + wg * 16384, item_h(it) * 128,
            item_m(it) * 128 + hf * 64, CNT_CTX + (r >> 1), lazy);
    if (kind != ST_BOX2L) st_go(bar, wg, wtid, sn);
    sn++;
  };
  auto mask_half = [&](float* sh) {
    const int u = warp * 16 + (lane >> 2) - (lane & 3) * 2;
#pragma unroll
    for (int j = 0; j < 8; j++) {
      if (8 * j > u) sh[4 * j] = -INFINITY;
      if (8 * j + 1 > u) sh[4 * j + 1] = -INFINITY;
      if (8 * j - 8 > u) sh[4 * j + 2] = -INFINITY;
      if (8 * j - 7 > u) sh[4 * j + 3] = -INFINITY;
    }
  };
  ST(0)
  mbar_wait(q_full, 0);
  if (blockIdx.x >= 128) {
    return sn;
  }
  mbar_wait(k_full, 0);
  named_bar_sync(sched_own, 256);
  wgmma_fence();
  issue_qk(qd0, kd0);
  named_bar_arrive(sched_other, 256);
  fence_regs(rest);
#pragma unroll
  for (int i = 0; i < 64; i++) o[i] = rest[i] * Q_SCALE;
  fence_regs(o);
  wgmma_wait<0>();
  fence_regs(s);
  mbar_arrive_if(k_empty, wtid == 32);
  uint32_t g = 0;
  uint32_t rnd = 0;
  int rem = item_m(item_of(maps, 0));
  uint32_t first = 1;
  uint32_t fl = 0;
#define redo (fl & 1)
#define shifted (fl & 2)
  float d0 = 0.f, d1 = 0.f;
  pi0 = pi1 = 1.f;
  ST(1)
  for (;;) {
    if (shifted) {
#pragma unroll
      for (int j = 0; j < 16; j++) {
        s[4 * j] -= d0;
        s[4 * j + 1] -= d0;
        s[4 * j + 2] -= d1;
        s[4 * j + 3] -= d1;
      }
    }
    if (rem == 0 && !redo) {
      mbar_arrive_if(q_empty + 8 * (rnd & 1), wtid == 96);
      rnd++;
      if (hf == 0) mask_half(s);
      else mask_half(s + 32);
    }
    for (;;) {
      const bool kill = rem == 0 && hf == 0;
      const uint32_t kd = kd0 + ((g + 1) & 1) * DST, vd = vd0 + (g & 1) * DST;
      float a0 = 0.f, a1 = 0.f;
      exp_lo(a0, a1);
      fence_regs(e);
      const uint32_t kb = k_full + 8 * ((g + 1) & 1);
      const uint32_t kpar = (((g + 1) >> 1) & 1) ^ (g == A_STEPS - 1 ? 1u : 0u);
      const uint32_t qb = q_full + 8 * (rnd & 1), qpar = ((rnd >> 1) & 1) | dep;
      if (!mbar_try(qb, qpar)) mbar_wait(qb, qpar | ((__float_as_uint(a0) | __float_as_uint(a1)) & rt_zero));
      wgmma_wait<0>();
      fence_regs(o);
      if (kill) {
        mbar_arrive_if(kb + (B_VEMPTY - B_KFULL), wtid == 64 && !redo && g > 0);
        fence_regs(e);
        pack_lo();
#pragma unroll
        for (int j = 16; j < 32; j++) asm volatile("" : "=r"(p[j]));
        goto check;
      }
#pragma unroll
      for (int i = 32; i < 64; i++) asm volatile("" : "+f"(s[i])::"memory");
      mbar_arrive_if(kb + (B_VEMPTY - B_KFULL), wtid == 64 && !redo && g > 0);
      finish_p(a0, a1);
      if (__any_sync(0xffffffffu, !(mbar_try(v_full + 8 * (g & 1), ((g >> 1) & 1) | dep) &
                                    mbar_try(kb, kpar | dep)) ||
                                      !(a0 + a1 < 1.0995116e12f) || !(fminf(a0, a1) > (first ? 9.094947e-13f : -1.f)))) {
      check:
        bool bad = !(a0 + a1 < 1.0995116e12f);
        if (first) bad |= !(fminf(quad_sum(a0), quad_sum(a1)) > 9.094947e-13f);
        if (!redo && __any_sync(0xffffffffu, bad)) {
          d0 = d1 = first ? -INFINITY : 0.f;
#pragma unroll
          for (int j = 0; j < 16; j++) {
            if (j < 8 || !kill) {
              d0 = fmaxf(d0, fmaxf(s[4 * j], s[4 * j + 1]));
              d1 = fmaxf(d1, fmaxf(s[4 * j + 2], s[4 * j + 3]));
            }
          }
#pragma unroll
          for (int x = 1; x <= 2; x++) {
            d0 = fmaxf(d0, __shfl_xor_sync(0xffffffffu, d0, x));
            d1 = fmaxf(d1, __shfl_xor_sync(0xffffffffu, d1, x));
          }
          b0 += d0;
          b1 += d1;
          if (!first) {
            const float al0 = ex2(-d0), al1 = ex2(-d1);
            l0 *= al0;
            l1 *= al1;
#pragma unroll
            for (int j = 0; j < 16; j++) {
              o[4 * j] *= al0;
              o[4 * j + 1] *= al0;
              o[4 * j + 2] *= al1;
              o[4 * j + 3] *= al1;
            }
          }
          fl = 3;
          break;
        }
        mbar_wait(v_full + 8 * (g & 1), (g >> 1) & 1);
        mbar_wait(kb, kpar);
      }
      named_bar_sync(sched_own, 256);
      if (g == A_STEPS - 1) {
        fence_regs(o);
        if (hf == 0) {
          wgmma_fence();
          issue_pv(vd, 1, 4);
        } else {
          wgmma_fence();
          issue_pv(vd, 1, 8);
        }
        named_bar_arrive(sched_other, 256);
        pi0 = rcp(quad_sum(l0 + a0));
        pi1 = rcp(quad_sum(l1 + a1));
        goto done;
      }
      wgmma_fence();
      issue_qk(qd0 + (rnd & 1) * DST, kd);
      if (first) write_o(pi0, pi1);
      fence_regs(o);
      if (kill) {
        wgmma_fence();
        issue_pv(vd, !first, 4);
      } else {
        wgmma_fence();
        issue_pv(vd, !first, 8);
      }
      named_bar_arrive(sched_other, 256);
      fl &= 2;
      l0 += a0;
      l1 += a1;
      if (rem == 0 || first) {
        if (first && (g > 0 || after_qkv)) store_o(g ? rnd - (rem == 0 ? 2 : 1) : 2, g ? ST_BOX2 : ST_BOX2Q, rem);
        first = rem == 0;
        if (first) {
          pi0 = rcp(quad_sum(l0));
          pi1 = rcp(quad_sum(l1));
          l0 = l1 = b0 = b1 = 0.f;
          fl = 0;
          rem = item_m(item_of(maps, rnd)) + 1;
        }
      }
      rem--;
      g++;
      wgmma_wait<1>();
      fence_regs(s);
      mbar_arrive_if(kb + (B_KEMPTY - B_KFULL), wtid == 32);
      ST(g + 1)
      if (rem == 0 || shifted) {
        d0 = b0;
        d1 = b1;
        break;
      }
    }
  }
done:
#undef redo
#undef shifted
  st_wait(bar, wg, sn - 1);
  store_o(3, ST_BOX2L, 4);
  ST(35)
  return sn;
}

constexpr int O_STAGES = 5;
constexpr int O_STAGE_BYTES = 32768;
constexpr int O_Y_OFF = 5 * 32768;
constexpr int O_X_OFF = 6 * 32768;
constexpr int O_G_OFF = 7 * 32768;
constexpr int O_NK = HDIM / 64;

__device__ __forceinline__ uint32_t out_stage(uint32_t st) { return ((0x43120u >> (4 * st)) & 7) * O_STAGE_BYTES; }

__device__ __forceinline__ void out_producer(const Maps& maps, uint32_t sbase, bool after_attn, bool dry) {
  const uint32_t bar = sbase + BAR_OFF;
  const uint32_t rank = blockIdx.x & 1;
  const int m_tile = maps.id[blockIdx.x][2] & 15, n_tile = maps.id[blockIdx.x][2] >> 4;
  uint32_t stage = 0, phase = 0, xi = 0;
#pragma unroll 1
  for (int ki = 0; ki < (dry ? 1 : O_NK); ki++) {
    const int kt = (ki & 14) * 4 + ((A_ORDER >> ((ki >> 4) * 4)) & 3) * 2 + (ki & 1);
    const uint32_t fb = bar + B_OFULL + 8 * stage, eb = bar + B_OEMPTY + 8 * stage;
    const uint32_t sa = sbase + out_stage(stage);
    if (ki < O_STAGES) {
      constexpr uint32_t LASTB = B_KEMPTY | ((B_QEMPTY + 8) << 8) | ((B_KEMPTY + 8) << 16) | (B_VEMPTY << 24);
      if (ki > 0 && after_attn) mbar_wait_sleep(bar + ((LASTB >> (8 * ki - 8)) & 255), ki == 2);
      mbar_arrive_cluster_if(eb, 0, !dry);
      mbar_arrive_cluster_if(eb, 1, !dry);
    }
    if (ki == 32) mbar_wait_sleep(bar + seen_bar(2), 0);
    if (!dry) {
      mbar_wait_sleep(eb, phase);
      mbar_expect_tx(fb, O_STAGE_BYTES);
      tma_load_2d_mc(sa + 16384 + rank * 8192, &maps.ob, fb, n_tile * 128 + rank * 64, kt * 64, (uint16_t)3);
      tma_load_2d(sa, &maps.oa, fb, kt * 64, m_tile * 128);
    }
    if (++stage == O_STAGES) { stage = 0; phase ^= 1; }
    if ((ki & XMASK) == XMASK && ki >= XFIRST && xi < 8) {
      if (after_attn && xi < 2) mbar_wait_sleep(bar + B_OFREE + 8 * xi, 0);
      tma_load_3d(sbase + O_X_OFF + (xi & 1) * 16384 + (xi >> 1) * 4096, &maps.xs, bar + B_OY, 0,
                  m_tile * 128 + (xi & 1) * 64 + (xi >> 1) * 16, n_tile * 2);
      xi++;
    }
  }
  if (!dry) mbar_wait_sleep(bar + B_OY2, 0);
}

__device__ __forceinline__ void out_side(const Maps& maps, uint32_t smem0) {
  PHASE_PROLOGUE
  const int m_tile = maps.id[blockIdx.x][2] & 15, n_tile = maps.id[blockIdx.x][2] >> 4;
  const float* gp = g_gate + m_tile * 128 + warp * 16 + (lane >> 2);
  const float gv[4] = {__ldcg(gp), __ldcg(gp + 8), __ldcg(gp + 64), __ldcg(gp + 72)};
  const bool w0 = __shfl_sync(0xffffffffu, warp, 0) == 0;
  bool have = false;
  auto late = [&](uint32_t spins) {
    have = cnt_wait(CNT_Y2 + 1, 128, spins) || !spins;
    TD(11)
    if (have) {
      mbar_expect_tx(bar + B_OY2, 4096);
      tma_load_3d(sbase + O_Y_OFF + 7 * 4096, &maps.y, bar + B_OY2, 0, n_tile * 128 + 112, m_tile * 2);
    }
  };
  if (w0) {
    if (elect_one()) {
      mbar_expect_tx(bar + B_OY, 65536 - 4096);
      TD(10)
      cnt_wait(CNT_Y2, DM - 128);
      TD(7)
#pragma unroll 1
      for (int i = 0; i < 7; i++) {
        tma_load_3d(sbase + O_Y_OFF + i * 4096, &maps.y, bar + B_OY, 0, n_tile * 128 + i * 16, m_tile * 2);
        __nanosleep(PACE);
      }
      late(1u << 18);
    }
  }
  mbar_wait_sleep(bar + B_OY, 0);
  if (wtid == 0) { TD(12) }
  const int mrow = (lane & 7) + ((lane >> 4) & 1) * 8;
  const int mchunk = warp * 2 + ((lane >> 3) & 1);
  const uint32_t xrow = sbase + O_X_OFF + warp * 4096 + (lane & 15) * 128;
  const uint32_t yrow = sbase + O_Y_OFF + mrow * 128 + ((mchunk ^ (lane & 7)) << 4);
  uint32_t y[7][4], x[7][4], om[4];
#pragma unroll
  for (int i = 0; i < 4; i++) om[i] = pack_bf16(1.0f - gv[i], 1.0f - gv[i]);
  sts128(sbase + O_G_OFF + wtid * 16, make_uint4(pack_bf16(gv[0], gv[0]), pack_bf16(gv[1], gv[1]), pack_bf16(gv[2], gv[2]),
                                                 pack_bf16(gv[3], gv[3])));
  auto xa = [&](int h, int i) { return xrow + h * 16384 + (i >> 2) * 2048 + ((((i & 3) * 2 + (lane >> 4)) ^ (lane & 7)) << 4); };
  auto load = [&](int r, int h, int i) {
    ldsm4t(y[r], yrow + h * 2048 + i * 4096);
    asm volatile("ldmatrix.sync.aligned.m8n8.x4.shared.b16 {%0, %1, %2, %3}, [%4];"
                 : "=r"(x[r][0]), "=r"(x[r][1]), "=r"(x[r][2]), "=r"(x[r][3])
                 : "r"(xa(h, i)));
  };
  auto store = [&](int r, int h, int i, uint32_t om0, uint32_t om1) {
    stmatrix_x4(xa(h, i), mul_bf2(om0, mul_bf2(x[r][0], y[r][0])), mul_bf2(om1, mul_bf2(x[r][1], y[r][1])),
                mul_bf2(om0, mul_bf2(x[r][2], y[r][2])), mul_bf2(om1, mul_bf2(x[r][3], y[r][3])));
  };
#pragma unroll 1
  for (int h = 0; h < 2; h++) {
#pragma unroll
    for (int i = 0; i < 7; i++) load(i, h, i);
#pragma unroll
    for (int i = 0; i < 7; i++) store(i, h, i, h ? om[2] : om[0], h ? om[3] : om[1]);
  }
  __syncwarp();
  mbar_arrive_if(bar + B_OE, lane == 0);
  if (w0 && !__any_sync(0xffffffffu, have)) {
    if (elect_one()) late(0);
  }
  mbar_wait_sleep(bar + B_OY2, 0);
  load(0, 0, 7);
  load(1, 1, 7);
  store(0, 0, 7, om[0], om[1]);
  store(1, 1, 7, om[2], om[3]);
  __syncwarp();
  mbar_arrive_if(bar + B_OY + 8, lane == 0);
  if (wtid == 0) { TD(13) }
}

__device__ __forceinline__ void out_gemm(const Maps& maps, const uint32_t sbase, uint32_t sn, bool post, float (&o)[64],
                                         float (&s)[64],                                          float i0, float i1) {
  PHASE_GIVEN
  auto acc = [&](int h) -> float (&)[64] { return h ? o : s; };
  constexpr uint64_t DHI = DESC_SW128 | ((uint64_t)(1024 >> 4) << 32);
  const uint32_t d0 = (uint32_t)make_desc(sbase, 0, 0, 0);
  auto mma0 = [&](int h) {
    wgmma_fence();
#pragma unroll
    for (int k = 0; k < 4; k++)
      wgmma_m64n128_ss_tb(acc(h), DHI | (d0 + 0x10000 + h * 512 + k * 2), DHI | (d0 + 0x2000400 + k * 128), k != 0);
    wgmma_commit();
  };
  mbar_wait(bar + B_OFULL, 0);
  mma0(0);
  wgmma_wait<1>();
  fence_regs(o);
  if (post) {
    named_bar_arrive(3, 256);
    put_o(sbase, 0, warp, lane, o, i0, i1);
  }
  mma0(1);
  if (post) st_go(bar, 0, wtid, sn - 1);
  const int m_tile = maps.id[blockIdx.x][2] & 15, n_tile = maps.id[blockIdx.x][2] >> 4;
  uint32_t stage = 1, phase = 0, prev_stage = 0;
  GT(gti++)
  const uint32_t xrow = sbase + O_X_OFF + warp * 4096 + (lane & 15) * 128;
  auto addr = [&](int i) {
    return xrow + (i >> 3) * 16384 + ((i >> 2) & 1) * 2048 + ((((i & 3) * 2 + (lane >> 4)) ^ (lane & 7)) << 4);
  };
  uint32_t b[16][4];
#pragma unroll
  for (int i = 0; i < 64; i++) asm volatile("" : "=r"(b[i >> 2][i & 3]));
  auto ld_b = [&](int q0, int q1) {
#pragma unroll
    for (int i = 0; i < 16; i++)
      if ((i & 7) != 7)
        asm volatile(
            "{\n.reg .pred p;\nsetp.ge.s32 p, %5, %6;\nsetp.le.and.s32 p, %5, %7, p;\n"
            "@p ldmatrix.sync.aligned.m8n8.x4.shared.b16 {%0, %1, %2, %3}, [%4];\n}\n"
            : "+r"(b[i][0]), "+r"(b[i][1]), "+r"(b[i][2]), "+r"(b[i][3])
            : "r"(addr(i)), "r"(i / 4), "r"(q0), "r"(q1)
            : "memory");
  };
  int nq = 0;
#pragma unroll 1
  for (int kt = 1; kt < O_NK - 2; kt++) {
    uint32_t da = (uint32_t)make_desc(sbase + out_stage(stage), 16, 0, 0);
    uint32_t db = (uint32_t)make_desc(sbase + out_stage(stage) + 16384, 8192, 0, 0);
    asm volatile("" : "+r"(da), "+r"(db));
    mbar_wait(bar + B_OFULL + 8 * stage, phase);
    GT(gti++)
#pragma unroll
    for (int kk = 0; kk < 4; kk++) {
      wgmma_wait<2>();
      if (kk == 2)
        mbar_arrive_cluster_if(bar + B_OEMPTY + 8 * prev_stage, wtid >> 6, (wtid & 63) == 32 && kt - 1 + O_STAGES < O_NK);
      wgmma_fence();
      wgmma_m64n128_ss_tb(acc(0), DHI | (da + kk * 2), DHI | (db + kk * 128), 1);
      wgmma_m64n128_ss_tb(acc(1), DHI | (da + 512 + kk * 2), DHI | (db + kk * 128), 1);
      wgmma_commit();
      if (kk == 0 && kt >= 52) {
        uint32_t ok;
        asm volatile("{\n.reg .pred p;\nmbarrier.test_wait.parity.shared::cta.b64 p, [%1], 0;\nselp.u32 %0, 1, 0, p;\n}\n"
                     : "=r"(ok)
                     : "r"(bar + B_OE)
                     : "memory");
        if (__all_sync(0xffffffffu, ok)) {
          ld_b(nq, nq);
          nq++;
        }
      }
    }
    prev_stage = stage;
    if (++stage == O_STAGES) { stage = 0; phase ^= 1; }
  }
  if (tid == 0) { TD(14) }
  constexpr int S0 = (O_NK - 2) % O_STAGES, P0 = ((O_NK - 2) / O_STAGES) & 1;
  auto mma = [&](int h, int k0, int k1) {
    wgmma_fence();
#pragma unroll
    for (int k = k0; k < k1; k++) {
      const uint32_t d = d0 + (out_stage(S0 + (k >> 2)) >> 4);
      wgmma_m64n128_ss_tb(acc(h), DHI | (d + 0x10000 + h * 512 + (k & 3) * 2), DHI | (d + 0x2000400 + (k & 3) * 128), 1);
    }
    wgmma_commit();
  };
#pragma unroll
  for (int p = 0; p < 2; p++) {
    mbar_wait(bar + B_OFULL + 8 * (S0 + p), P0);
    mma(0, 4 * p, 4 * p + 4);
  }
  mma(1, 0, 8);
  if (nq < 4) {
    mbar_wait(bar + B_OE, 0);
    ld_b(nq, 3);
  }
  const uint4 g4 = lds128(sbase + O_G_OFF + wtid * 16);
  const uint32_t gg[4] = {g4.x, g4.y, g4.z, g4.w};
  const int w4 = __shfl_sync(0xffffffffu, warp, 0);
#pragma unroll
  for (int i = 0; i < 16; i++) {
    const int h = i >> 3;
    if (i == 0) wgmma_wait<1>();
    if (i == 8) wgmma_wait<0>();
    if ((i & 7) == 0) fence_regs(acc(h));
    if (i == 8) {   }
    if (i == 7) {
      mbar_wait(bar + B_OY + 8, 0);
#pragma unroll
      for (int j = 7; j < 16; j += 8)
        asm volatile("ldmatrix.sync.aligned.m8n8.x4.shared.b16 {%0, %1, %2, %3}, [%4];"
                     : "=r"(b[j][0]), "=r"(b[j][1]), "=r"(b[j][2]), "=r"(b[j][3])
                     : "r"(addr(j))
                     : "memory");
    }
    const float* a = acc(h) + 8 * (i & 7);
    stmatrix_x4(addr(i), fma_bf2(gg[2 * h], pack_bf16(a[0], a[1]), b[i][0]), fma_bf2(gg[2 * h + 1], pack_bf16(a[2], a[3]), b[i][1]),
                fma_bf2(gg[2 * h], pack_bf16(a[4], a[5]), b[i][2]), fma_bf2(gg[2 * h + 1], pack_bf16(a[6], a[7]), b[i][3]));
    if ((i & 7) == 7) {
      fence_proxy_async();
      __syncwarp();
      if (elect_one()) {
        tma_store_3d(&maps.oc, sbase + O_X_OFF + (h * 4 + w4) * 4096, 0, m_tile * 128 + h * 64 + w4 * 16, n_tile * 2);
        if (h == 1) {
          tma_store_commit();
        }
      }
    }
  }
  GT(gti++)
}

__device__ __noinline__ void leave_kernel(int mask) {
  if (!(mask & 4)) return;
  if (atomicAdd(g_cnt + CNT_DONE * 32, 1u) == 2 * gridDim.x - 1) {
    for (int i = 0; i < CNT_N; i++) g_cnt[i * 32] = 0;
#pragma unroll 4
    for (int i = 0; i < 128; i++) g_slot[i] = 0;
  }
}

__device__ __noinline__ void side_jobs(const Maps& maps, uint32_t sbase) {
  const int w12 = __shfl_sync(0xffffffffu, threadIdx.x >> 5, 0);
  gate_rows(maps, sbase, (blockIdx.x - 128) * 12 + w12, w12, threadIdx.x & 31);
  fence_proxy_async();
  __syncthreads();
  if (threadIdx.x == 320) cnt_signal_release(CNT_PREP, 1);
}

__global__ void __launch_bounds__(384, 1)
    fused_kernel(int mask, const bf16* px, const bf16* pw, const __grid_constant__ Maps maps) {
  extern __shared__ __align__(1024) uint8_t smem_raw[];
  {
    const uint32_t t = threadIdx.x, l = t & 31, u = (blockIdx.x & 127) * 16 + (l >> 1);
    const uint32_t ow = (u >> 5) * HDIM + ((u >> 2) & 7) * 512 + 256 + (u & 3) * 64, ox = u * DM;
    const bf16* p = ((l & 1) ? pw : px) + ((l & 1) ? ow : ox);
    asm volatile("{\n.reg .pred p;\nsetp.ne.u32 p, %1, 0;\n@p prefetch.global.L2 [%0];\n}\n" ::"l"(p), "r"((uint32_t)(t < 32)));
  }
  {
    const uint32_t sbase = __shfl_sync(0xffffffffu, smem_u32(smem_raw), 0);
    const uint32_t bar = sbase + BAR_OFF;
    const int tid = threadIdx.x;
    const bool do_qkv = (mask & 1) && blockIdx.x < 128;
    TL(0, 0)
    if (__shfl_sync(0xffffffffu, tid >> 5, 0) == 1 && do_qkv) {
      if (elect_one()) {
        for (int i = 0; i < G_STAGES; i++) mbar_init(bar + B_GFULL + 8 * i, 1);
        fence_barrier_init();
        qkv_producer(maps, sbase, true);
      }
    }
    if (tid == 0) {
      for (int i = 0; i < G_STAGES; i++) {
        mbar_init(bar + B_GEMPTY + 8 * i, 2);
        mbar_init(bar + B_SFULL + 8 * i, 4);
        mbar_init(bar + B_SFREE + 8 * i, 1);
      }
      for (int i = 0; i < 2; i++) {
        mbar_init(bar + B_OFREE + 8 * i, 1);
        mbar_init(bar + B_QFULL + 8 * i, 1);
        mbar_init(bar + B_QEMPTY + 8 * i, 2);
        mbar_init(bar + B_KFULL + 8 * i, 1);
        mbar_init(bar + B_KEMPTY + 8 * i, 2);
        mbar_init(bar + B_VFULL + 8 * i, 1);
        mbar_init(bar + B_VEMPTY + 8 * i, 2);
      }
      for (int i = 0; i < O_STAGES; i++) {
        mbar_init(bar + B_OFULL + 8 * i, 1);
        mbar_init(bar + B_OEMPTY + 8 * i, 2);
      }
      mbar_init(bar + B_OY, 1);
      for (int i = 0; i < 3; i++) mbar_init(bar + seen_bar(i), 1);
      mbar_init(bar + B_OY2, 1);
      mbar_init(bar + B_DEAL, 1);
      mbar_init(bar + B_DEAL2, 1);
      mbar_init(bar + B_PAIR, 1);
      mbar_init(bar + B_OY + 8, 4);
      mbar_init(bar + B_OE, 4);
      mbar_init(bar + B_QDONE, 2);
      for (int i = 0; i < 8; i++) mbar_init(bar + B_CFULL + 8 * i, 1);
      for (int i = 0; i < CNT_N; i++) asm volatile("st.shared.u32 [%0], 0;" ::"r"(bar + B_PEND + 4 * i) : "memory");
      fence_barrier_init();
    }
    __syncthreads();
    asm volatile("barrier.cluster.arrive.relaxed.aligned;" ::: "memory");
    if ((mask & 1) && blockIdx.x >= 128) side_jobs(maps, sbase);
  }
  uint32_t smem0 = smem_u32(smem_raw);
  PHASE_PROLOGUE
  const bool do_qkv = (mask & 1) && blockIdx.x < 128, do_out = (mask & 4) && blockIdx.x < 128;
  TL(0, 1)

  if (wg != 2) {
    reg_alloc<232>();
    asm volatile("barrier.cluster.wait.acquire.aligned;" ::: "memory");
    if (wg == 1) named_bar_arrive(4, 256);
    uint32_t sn = 0;
    float rest[64], o[64], s[64];
    if (do_qkv) {
      sn = qkv_consumer(maps, sbase, wg, mask & 2, rest, rt_zero);
    } else {
      undef_regs(rest);
    }
    undef_regs(o);
    undef_regs(s);
    TL(0, 2) TL(1, 0) TL(1, 1)
    const bool direct = do_out && wg == 0;
    float i0 = 0.f, i1 = 0.f;
    if (mask & 2) sn = attn_consumer(maps, sbase, wg, rt_zero, sn, rest, mask & 1, o, s, i0, i1);
    TL(2, 0)
    bool side = false;
    if (!direct) {
      wgmma_wait<0>();
      fence_regs(o);
      if (mask & 2) {
        const bool fused = mask & 4, mainc = blockIdx.x < 128;
        if (mainc) {
          PHASE_GIVEN
          put_o(sbase, wg, warp, lane, o, i0, i1);
          st_go(bar, wg, wtid, sn - 1);
        }
        const uint32_t b2 = blockIdx.x * 2 + (threadIdx.x >> 7);
        const uint32_t first = __shfl_sync(0xffffffffu, !fused ? b2 : mainc ? conv_first(maps) : (b2 - 255) * 128 - C_SIDE, 0);
        conv_consumer(maps, smem_u32(smem_raw), first, !fused ? 264 : mainc ? 16 : 1,
                      !fused ? DM : mainc ? (first | 127) + 1 - C_SIDE : first + C_SIDE, fused && !mainc,
                      fused && mainc);
      }
      side = (mask & 4) && blockIdx.x < 128;
    } else {
      out_gemm(maps, sbase, sn, mask & 2, o, s, i0, i1);
    }
    TL(1, 2) TL(2, 1) TL(2, 2) TL(3, 0) TL(3, 1)
    if (side + rt_zero) out_side(maps, smem_u32(smem_raw));
    tma_store_wait_read<0>();
  } else {
    reg_dealloc<40>();
    asm volatile("barrier.cluster.wait.acquire.aligned;" ::: "memory");
    const int w = __shfl_sync(0xffffffffu, tid >> 5, 0) - 8;
    if (w < 2) {
      if (do_qkv) prep_agent(maps, sbase, w, lane);
      if (elect_one()) store_agent(bar, w, w && do_out ? conv_first(maps) + 48 : 0, blockIdx.x >= 128 || mask == 4 ? 0 : mask == 1 ? 24 : 99);
      TL2(3, 2)
    } else {
      if (elect_one()) {
        const bool dry = w == 2;
        if (do_qkv && !dry) qkv_producer(maps, sbase, false);
        if (mask & 2) attn_producer(maps, sbase, do_qkv, do_out, dry);
        if (do_out) out_producer(maps, sbase, mask & 2, dry);
        if (dry) { TD(5) }
      }
      __syncwarp();
      if (w == 2) publisher(bar, tid & 31, !(mask & 2) ? 2 : do_out ? 3 : 4, !do_out ? 3 : do_qkv ? 0 : 2, do_qkv ? 4 : 0);
      if ((tid & 31) == 0) leave_kernel(mask);
    }
  }
}

typedef CUresult (*PFN_tmapEncode)(CUtensorMap*, CUtensorMapDataType, cuuint32_t, void*, const cuuint64_t*,
                                   const cuuint64_t*, const cuuint32_t*, const cuuint32_t*, CUtensorMapInterleave,
                                   CUtensorMapSwizzle, CUtensorMapL2promotion, CUtensorMapFloatOOBfill);
static PFN_tmapEncode s_encode = nullptr;

static void make_map_2d(CUtensorMap* m, const void* ptr, int rows, int cols, int box_rows) {
  cuuint64_t dims[2] = {(cuuint64_t)cols, (cuuint64_t)rows};
  cuuint64_t strides[1] = {(cuuint64_t)cols * 2};
  cuuint32_t box[2] = {cols < 64 ? 32u : 64u, (cuuint32_t)box_rows};
  cuuint32_t es[2] = {1, 1};
  s_encode(m, CU_TENSOR_MAP_DATA_TYPE_BFLOAT16, 2, const_cast<void*>(ptr), dims, strides, box, es,
           CU_TENSOR_MAP_INTERLEAVE_NONE, cols < 64 ? CU_TENSOR_MAP_SWIZZLE_64B : CU_TENSOR_MAP_SWIZZLE_128B, CU_TENSOR_MAP_L2_PROMOTION_L2_256B,
           CU_TENSOR_MAP_FLOAT_OOB_FILL_NONE);
}
static void make_map_3d(CUtensorMap* m, const void* ptr, int rows, int cols, int box_rows, int box_chunks) {
  cuuint64_t dims[3] = {64, (cuuint64_t)rows, (cuuint64_t)(cols / 64)};
  cuuint64_t strides[2] = {(cuuint64_t)cols * 2, 128};
  cuuint32_t box[3] = {64, (cuuint32_t)box_rows, (cuuint32_t)box_chunks};
  cuuint32_t es[3] = {1, 1, 1};
  s_encode(m, CU_TENSOR_MAP_DATA_TYPE_BFLOAT16, 3, const_cast<void*>(ptr), dims, strides, box, es,
           CU_TENSOR_MAP_INTERLEAVE_NONE, CU_TENSOR_MAP_SWIZZLE_128B, CU_TENSOR_MAP_L2_PROMOTION_L2_256B,
           CU_TENSOR_MAP_FLOAT_OOB_FILL_NONE);
}

static cudaLaunchConfig_t fused_cfg(cudaLaunchAttribute* at) {
  cudaLaunchConfig_t cfg = {};
  cfg.gridDim = dim3(132);
  cfg.blockDim = dim3(384);
  cfg.dynamicSmemBytes = SMEM_BYTES;
  cfg.stream = cudaStreamPerThread;
  at[0].id = cudaLaunchAttributeClusterDimension;
  at[0].val.clusterDim.x = 2;
  at[0].val.clusterDim.y = 1;
  at[0].val.clusterDim.z = 1;
  cfg.attrs = at;
  cfg.numAttrs = 1;
  return cfg;
}

extern "C" void kernel_launch(void* const* d_in, const int* in_sizes, int n_in, void* d_out, int out_size) {
  const bf16* x = (const bf16*)d_in[0];
  const bf16* ckv = (const bf16*)d_in[1];
  const bf16* wq = (const bf16*)d_in[2];
  const bf16* wuk = (const bf16*)d_in[3];
  const bf16* wuv = (const bf16*)d_in[4];
  const bf16* wo = (const bf16*)d_in[5];
  const bf16* bk = (const bf16*)d_in[7];
  const bf16* bv = (const bf16*)d_in[8];
  const bf16* shift_k = (const bf16*)d_in[9];
  const bf16* ssm_k = (const bf16*)d_in[10];
  const bf16* ssm_D = (const bf16*)d_in[11];
  const bf16* gate_w = (const bf16*)d_in[12];
  bf16* out = (bf16*)d_out;

  static void *pq = nullptr, *pk = nullptr, *pv = nullptr, *pctx = nullptr, *pb = nullptr, *pu = nullptr;
  static int max_clusters = 0;
  if (!s_encode) {
    void* fn = nullptr;
    cudaDriverEntryPointQueryResult qres;
    cudaGetDriverEntryPoint("cuTensorMapEncodeTiled", &fn, cudaEnableDefault, &qres);
    s_encode = (PFN_tmapEncode)fn;
    cudaGetSymbolAddress(&pq, g_q);
    cudaGetSymbolAddress(&pk, g_k);
    cudaGetSymbolAddress(&pv, g_v);
    cudaGetSymbolAddress(&pctx, g_ctx);
    cudaGetSymbolAddress(&pb, g_y2T);
    cudaGetSymbolAddress(&pu, g_kvT);
    cudaFuncSetAttribute(fused_kernel, cudaFuncAttributeMaxDynamicSharedMemorySize, SMEM_BYTES);
    cudaLaunchAttribute at[1];
    cudaLaunchConfig_t cfg = fused_cfg(at);
    if (cudaOccupancyMaxActiveClusters(&max_clusters, fused_kernel, &cfg) != cudaSuccess) max_clusters = 0;
  }

  Maps all = {};
  make_map_2d(&all.a[0], x, S_LEN, DM, 128);
  make_map_2d(&all.a[1], ckv, S_LEN, DC, 128);
  make_map_3d(&all.b[0], wq, DM, HDIM, 64, 4);
  make_map_3d(&all.b[1], wuk, DC, HDIM, 64, 4);
  make_map_3d(&all.b[2], wuv, DC, HDIM, 64, 4);
  make_map_2d(&all.c[0], pq, S_LEN, HDIM, 64);
  make_map_2d(&all.c[1], pk, S_LEN, HDIM, 64);
  make_map_2d(&all.c[2], pv, S_LEN, HDIM, 64);
  make_map_3d(&all.q, pq, S_LEN, HDIM, 128, 2);
  make_map_3d(&all.k, pk, S_LEN, HDIM, 128, 2);
  make_map_3d(&all.v, pv, S_LEN, HDIM, 128, 2);
  make_map_2d(&all.o, pctx, S_LEN, HDIM, 64);
  all.ssm_k = ssm_k;
  all.ssm_D = ssm_D;
  make_map_2d(&all.oa, pctx, S_LEN, HDIM, 128);
  make_map_2d(&all.ob, wo, HDIM, DM, 64);
  make_map_3d(&all.oc, out, S_LEN, DM, 16, 2);
  make_map_3d(&all.y, pb, DM, S_LEN, 16, 2);
  make_map_3d(&all.xs, x, S_LEN, DM, 16, 2);
  make_map_2d(&all.cu, pu, DM * 64, 32, 64);
  make_map_2d(&all.ch, ssm_k, DM * 64, 32, 64);

  make_map_2d(&all.bk, bk, S_LEN, DM, 35);
  make_map_2d(&all.bv, bv, S_LEN, DM, 32);
  for (int b = 0; b < 128; b++) {
    const int c = b >> 1, r = b & 1;
    const int G = c < 4 ? 0 : c < 36 ? (c - 4) % 8 : 1 + (c - 36) % 7;
    const int i = c < 4 ? 4 + c : c < 36 ? (c - 4) / 8 : 4 + (c - 36) / 7;
    all.id[b][0] = r + 2 * (i & 1) + 4 * (G & 3) + 16 * (i >> 1) + 64 * (G >> 2);
    all.id[b][1] = r + 2 * i + 16 * G;
    all.id[b][2] = r + 2 * G + 16 * i;
    all.id[b][3] = r + 2 * i == 15 ? 0x78 : 0xd8;
  }
  all.shift_k = shift_k;
  all.x = x;
  all.gate_w = gate_w;
  cudaLaunchAttribute at[1];
  cudaLaunchConfig_t cfg = fused_cfg(at);
  if (max_clusters >= 66) {
    cudaLaunchKernelEx(&cfg, fused_kernel, 7, x, wq, all);
  } else {
    for (int m = 1; m <= 4; m <<= 1) cudaLaunchKernelEx(&cfg, fused_kernel, m, x, wq, all);
  }
}
```

```cpp
#include <cuda_runtime.h>
#include <cuda_bf16.h>
#include <cuda.h>
#include <stdint.h>

typedef __nv_bfloat16 bf16;
#define INPLACE 3

constexpr int S_LEN = 2048;
constexpr int DM = 1024;
constexpr int NH = 32;
constexpr int HD = 128;
constexpr int DC = 512;
constexpr int HDIM = NH * HD;

__device__ __align__(1024) bf16 g_q[S_LEN * HDIM];
__device__ __align__(1024) bf16 g_k[S_LEN * HDIM];
__device__ __align__(1024) bf16 g_v[S_LEN * HDIM];
#define g_ctx g_q
__device__ __align__(1024) bf16 g_kvT[DM * S_LEN];
#define g_y2T g_kvT
__device__ __align__(1024) float g_gate[S_LEN];
enum { CNT_KV = 0, CNT_PREP = CNT_KV + 2, CNT_CTX, CNT_Y2 = CNT_CTX + 2, CNT_DONE = CNT_Y2 + 2, CNT_RANK, CNT_N };
__device__ unsigned int g_cnt[CNT_N * 32];
__device__ unsigned long long g_slot[128];

#define TL(k, i)
#define TL2(k, i)
#define TD(i)
#define CT(i)
#define GT(i)
#define GA(i)
#define ST(i)

__device__ __forceinline__ uint32_t smem_u32(const void* p) { return (uint32_t)__cvta_generic_to_shared(p); }

__device__ __forceinline__ void mbar_init(uint32_t bar, uint32_t count) {
  asm volatile("mbarrier.init.shared::cta.b64 [%0], %1;" ::"r"(bar), "r"(count));
}
__device__ __forceinline__ void mbar_expect_tx(uint32_t bar, uint32_t bytes) {
  asm volatile("mbarrier.arrive.expect_tx.shared::cta.b64 _, [%0], %1;" ::"r"(bar), "r"(bytes) : "memory");
}
__device__ __forceinline__ void mbar_arrive(uint32_t bar) {
  asm volatile("mbarrier.arrive.shared::cta.b64 _, [%0];" ::"r"(bar) : "memory");
}
__device__ __forceinline__ void mbar_wait(uint32_t bar, uint32_t parity) {
  uint32_t done;
  uint32_t spins = 0;
  do {
    asm volatile(
        "{\n.reg .pred p;\n"
        "mbarrier.try_wait.parity.shared::cta.b64 p, [%1], %2;\n"
        "selp.u32 %0, 1, 0, p;\n}\n"
        : "=r"(done)
        : "r"(bar), "r"(parity)
        : "memory");
    if (++spins > (1u << 22)) break;
  } while (!done);
}
__device__ __forceinline__ bool mbar_try(uint32_t bar, uint32_t parity) {
  uint32_t done;
  asm volatile(
      "{\n.reg .pred p;\n"
      "mbarrier.try_wait.parity.shared::cta.b64 p, [%1], %2;\n"
      "selp.u32 %0, 1, 0, p;\n}\n"
      : "=r"(done)
      : "r"(bar), "r"(parity)
      : "memory");
  return done != 0;
}
__device__ __forceinline__ bool mbar_test(uint32_t bar, uint32_t parity) {
  uint32_t done;
  asm volatile(
      "{\n.reg .pred p;\n"
      "mbarrier.test_wait.parity.shared::cta.b64 p, [%1], %2;\n"
      "selp.u32 %0, 1, 0, p;\n}\n"
      : "=r"(done)
      : "r"(bar), "r"(parity)
      : "memory");
  return done != 0;
}
__device__ __forceinline__ bool elect_one() {
  uint32_t pred;
  asm volatile("{\n.reg .pred p;\nelect.sync _|p, 0xffffffff;\nselp.u32 %0, 1, 0, p;\n}\n" : "=r"(pred));
  return pred != 0;
}
__device__ __forceinline__ void mbar_arrive_if(uint32_t bar, bool pred) {
  asm volatile(
      "{\n.reg .pred p;\nsetp.ne.b32 p, %1, 0;\n"
      "@p mbarrier.arrive.shared::cta.b64 _, [%0];\n}\n" ::"r"(bar),
      "r"((uint32_t)pred)
      : "memory");
}
__device__ __forceinline__ void mbar_wait_sleep(uint32_t bar, uint32_t parity) {
  uint32_t done;
  uint32_t spins = 0;
  do {
    asm volatile(
        "{\n.reg .pred p;\n"
        "mbarrier.try_wait.parity.shared::cta.b64 p, [%1], %2, %3;\n"
        "selp.u32 %0, 1, 0, p;\n}\n"
        : "=r"(done)
        : "r"(bar), "r"(parity), "r"(20000u)
        : "memory");
    if (++spins > (1u << 16)) break;
  } while (!done);
}
__device__ __forceinline__ void fence_barrier_init() {
  asm volatile("fence.mbarrier_init.release.cluster;" ::: "memory");
}
__device__ __forceinline__ void fence_proxy_async() {
  asm volatile("fence.proxy.async.shared::cta;" ::: "memory");
}
__device__ __forceinline__ void named_bar_sync(int id, int nthreads) {
  asm volatile("bar.sync %0, %1;" ::"r"(id), "r"(nthreads) : "memory");
}
__device__ __forceinline__ void named_bar_arrive(int id, int nthreads) {
  asm volatile("bar.arrive %0, %1;" ::"r"(id), "r"(nthreads) : "memory");
}
__device__ __forceinline__ void tma_load_2d(uint32_t dst, const CUtensorMap* m, uint32_t bar, int c0, int c1) {
  asm volatile(
      "cp.async.bulk.tensor.2d.shared::cluster.global.mbarrier::complete_tx::bytes [%0], [%1, {%3, %4}], [%2];" ::"r"(dst),
      "l"(reinterpret_cast<uint64_t>(m)), "r"(bar), "r"(c0), "r"(c1)
      : "memory");
}
__device__ __forceinline__ void tma_load_3d(uint32_t dst, const CUtensorMap* m, uint32_t bar, int c0, int c1, int c2) {
  asm volatile(
      "cp.async.bulk.tensor.3d.shared::cluster.global.mbarrier::complete_tx::bytes [%0], [%1, {%3, %4, %5}], [%2];" ::"r"(dst),
      "l"(reinterpret_cast<uint64_t>(m)), "r"(bar), "r"(c0), "r"(c1), "r"(c2)
      : "memory");
}
__device__ __forceinline__ void tma_store_2d(const CUtensorMap* m, uint32_t src, int c0, int c1) {
  asm volatile("cp.async.bulk.tensor.2d.global.shared::cta.bulk_group [%0, {%2, %3}], [%1];" ::"l"(
                   reinterpret_cast<uint64_t>(m)),
               "r"(src), "r"(c0), "r"(c1)
               : "memory");
}
__device__ __forceinline__ void bulk_load(uint32_t dst, const void* src, uint32_t bytes, uint32_t bar) {
  asm volatile("cp.async.bulk.shared::cluster.global.mbarrier::complete_tx::bytes [%0], [%1], %2, [%3];" ::"r"(dst),
               "l"(src), "r"(bytes), "r"(bar)
               : "memory");
}
__device__ __forceinline__ void tma_load_2d_mc(uint32_t dst, const CUtensorMap* m, uint32_t bar, int c0, int c1,
                                               uint16_t mask) {
  asm volatile(
      "cp.async.bulk.tensor.2d.shared::cluster.global.mbarrier::complete_tx::bytes.multicast::cluster [%0], [%1, {%3, "
      "%4}], [%2], %5;" ::"r"(dst),
      "l"(reinterpret_cast<uint64_t>(m)), "r"(bar), "r"(c0), "r"(c1), "h"(mask)
      : "memory");
}
__device__ __forceinline__ void mbar_arrive_cluster_if(uint32_t bar, uint32_t cta, bool pred) {
  asm volatile(
      "{\n.reg .b32 ra;\n.reg .pred p;\nsetp.ne.b32 p, %2, 0;\n"
      "mapa.shared::cluster.u32 ra, %0, %1;\n"
      "@p mbarrier.arrive.shared::cluster.b64 _, [ra];\n}\n" ::"r"(bar),
      "r"(cta), "r"((uint32_t)pred)
      : "memory");
}
__device__ __forceinline__ uint64_t policy_evict_first() {
  uint64_t pol;
  asm volatile("createpolicy.fractional.L2::evict_first.b64 %0, 1.0;" : "=l"(pol));
  return pol;
}
__device__ __forceinline__ void tma_load_2d_hint(uint32_t dst, const CUtensorMap* m, uint32_t bar, int c0, int c1,
                                                 uint64_t pol) {
  asm volatile(
      "cp.async.bulk.tensor.2d.shared::cluster.global.mbarrier::complete_tx::bytes.L2::cache_hint [%0], [%1, {%3, %4}], "
      "[%2], %5;" ::"r"(dst),
      "l"(reinterpret_cast<uint64_t>(m)), "r"(bar), "r"(c0), "r"(c1), "l"(pol)
      : "memory");
}
__device__ __forceinline__ void tma_load_3d_hint(uint32_t dst, const CUtensorMap* m, uint32_t bar, int c0, int c1,
                                                 int c2, uint64_t pol) {
  asm volatile(
      "cp.async.bulk.tensor.3d.shared::cluster.global.mbarrier::complete_tx::bytes.L2::cache_hint [%0], [%1, {%3, %4, "
      "%5}], [%2], %6;" ::"r"(dst),
      "l"(reinterpret_cast<uint64_t>(m)), "r"(bar), "r"(c0), "r"(c1), "r"(c2), "l"(pol)
      : "memory");
}
__device__ __forceinline__ void bulk_load_hint(uint32_t dst, const void* src, uint32_t bytes, uint32_t bar, uint64_t pol) {
  asm volatile(
      "cp.async.bulk.shared::cluster.global.mbarrier::complete_tx::bytes.L2::cache_hint [%0], [%1], %2, [%3], %4;" ::"r"(dst),
      "l"(src), "r"(bytes), "r"(bar), "l"(pol)
      : "memory");
}
__device__ __forceinline__ void cnt_signal_release(int which, uint32_t n) {
  asm volatile("red.release.gpu.global.add.u32 [%0], %1;" ::"l"(g_cnt + which * 32), "r"(n) : "memory");
}
__device__ __forceinline__ bool cnt_wait(int which, uint32_t target, uint32_t spins = 0) {
  uint32_t v;
  while (true) {
    asm volatile("ld.acquire.gpu.global.u32 %0, [%1];" : "=r"(v) : "l"(g_cnt + which * 32) : "memory");
    if (v >= target || ++spins > (1u << 18)) break;
    __nanosleep(64);
  }
  asm volatile("fence.proxy.async.global;" ::: "memory");
  return v >= target;
}
__device__ __forceinline__ void tma_store_3d(const CUtensorMap* m, uint32_t src, int c0, int c1, int c2) {
  asm volatile("cp.async.bulk.tensor.3d.global.shared::cta.bulk_group [%0, {%2, %3, %4}], [%1];" ::"l"(
                   reinterpret_cast<uint64_t>(m)),
               "r"(src), "r"(c0), "r"(c1), "r"(c2)
               : "memory");
}
__device__ __forceinline__ void tma_store_commit() { asm volatile("cp.async.bulk.commit_group;" ::: "memory"); }
template <int N>
__device__ __forceinline__ void tma_store_wait_read() {
  asm volatile("cp.async.bulk.wait_group.read %0;" ::"n"(N) : "memory");
}
template <int N>
__device__ __forceinline__ void tma_store_wait() {
  asm volatile("cp.async.bulk.wait_group %0;" ::"n"(N) : "memory");
}
__device__ __forceinline__ void wgmma_fence() { asm volatile("wgmma.fence.sync.aligned;" ::: "memory"); }
__device__ __forceinline__ void wgmma_commit() { asm volatile("wgmma.commit_group.sync.aligned;" ::: "memory"); }
template <int N>
__device__ __forceinline__ void wgmma_wait() {
  asm volatile("wgmma.wait_group.sync.aligned %0;" ::"n"(N) : "memory");
}
template <int R>
__device__ __forceinline__ void reg_alloc() { asm volatile("setmaxnreg.inc.sync.aligned.u32 %0;" ::"n"(R)); }
template <int R>
__device__ __forceinline__ void reg_dealloc() { asm volatile("setmaxnreg.dec.sync.aligned.u32 %0;" ::"n"(R)); }

__device__ __forceinline__ void stmatrix_x4(uint32_t addr, uint32_t r0, uint32_t r1, uint32_t r2, uint32_t r3) {
  asm volatile("stmatrix.sync.aligned.m8n8.x4.shared.b16 [%0], {%1, %2, %3, %4};" ::"r"(addr), "r"(r0), "r"(r1),
               "r"(r2), "r"(r3)
               : "memory");
}
__device__ __forceinline__ uint32_t pack_bf16(float lo, float hi) {
  uint32_t r;
  asm("cvt.rn.bf16x2.f32 %0, %1, %2;" : "=r"(r) : "f"(hi), "f"(lo));
  return r;
}
__device__ __forceinline__ float bf16_round(float x) { return __bfloat162float(__float2bfloat16_rn(x)); }
__device__ __forceinline__ float bf_lo(uint32_t v) { return __uint_as_float(v << 16); }
__device__ __forceinline__ float bf_hi(uint32_t v) { return __uint_as_float(v & 0xffff0000u); }
__device__ __forceinline__ uint4 lds128(uint32_t a) {
  uint4 v;
  asm volatile("ld.shared.v4.u32 {%0, %1, %2, %3}, [%4];" : "=r"(v.x), "=r"(v.y), "=r"(v.z), "=r"(v.w) : "r"(a));
  return v;
}
__device__ __forceinline__ void sts128(uint32_t a, uint4 v) {
  asm volatile("st.shared.v4.u32 [%0], {%1, %2, %3, %4};" ::"r"(a), "r"(v.x), "r"(v.y), "r"(v.z), "r"(v.w) : "memory");
}
__device__ __forceinline__ uint32_t mul_bf2(uint32_t a, uint32_t b) {
  uint32_t r;
  asm("mul.rn.bf16x2 %0, %1, %2;" : "=r"(r) : "r"(a), "r"(b));
  return r;
}
__device__ __forceinline__ float ex2(float x) {
  float y;
  asm("ex2.approx.ftz.f32 %0, %1;" : "=f"(y) : "f"(x));
  return y;
}
__device__ __forceinline__ float rcp(float x) {
  float y;
  asm("rcp.approx.ftz.f32 %0, %1;" : "=f"(y) : "f"(x));
  return y;
}
template <int N>
__device__ __forceinline__ void fence_regs(float (&r)[N]) {
#pragma unroll
  for (int i = 0; i < N; i++) asm volatile("" : "+f"(r[i])::"memory");
}

template <int N>
__device__ __forceinline__ void undef_regs(float (&r)[N]) {
#pragma unroll
  for (int i = 0; i < N; i++) asm volatile("" : "=f"(r[i]));
}
template <int N>
__device__ __forceinline__ void fence_regs_u(uint32_t (&r)[N]) {
#pragma unroll
  for (int i = 0; i < N; i++) asm volatile("" : "+r"(r[i])::"memory");
}

constexpr uint64_t DESC_SW128 = 1ull << 62;
__device__ __forceinline__ uint64_t make_desc(uint32_t addr, uint32_t lbo_bytes, uint32_t sbo_bytes, uint64_t swz) {
  return (uint64_t)((addr & 0x3FFFF) >> 4) | ((uint64_t)((lbo_bytes & 0x3FFFF) >> 4) << 16) |
         ((uint64_t)((sbo_bytes & 0x3FFFF) >> 4) << 32) | swz;
}

__device__ __forceinline__ uint64_t desc_add(uint64_t d, uint32_t off16) {
  return (d & 0xFFFFFFFF00000000ull) | (uint64_t)((uint32_t)d + off16);
}

__device__ __forceinline__ void wgmma_m64n256_ss_tb(float (&d)[128], uint64_t da, uint64_t db, int sd) {
  asm volatile(
    "{\n.reg .pred p;\nsetp.ne.b32 p, %130, 0;\n"
    "wgmma.mma_async.sync.aligned.m64n256k16.f32.bf16.bf16 "
    "{%0, %1, %2, %3, %4, %5, %6, %7, %8, %9, %10, %11, %12, %13, %14, %15, %16, %17, %18, %19, %20, %21, %22, %23, %24, %25, %26, %27, %28, %29, %30, %31, %32, %33, %34, %35, %36, %37, %38, %39, %40, %41, %42, %43, %44, %45, %46, %47, %48, %49, %50, %51, %52, %53, %54, %55, %56, %57, %58, %59, %60, %61, %62, %63, %64, %65, %66, %67, %68, %69, %70, %71, %72, %73, %74, %75, %76, %77, %78, %79, %80, %81, %82, %83, %84, %85, %86, %87, %88, %89, %90, %91, %92, %93, %94, %95, %96, %97, %98, %99, %100, %101, %102, %103, %104, %105, %106, %107, %108, %109, %110, %111, %112, %113, %114, %115, %116, %117, %118, %119, %120, %121, %122, %123, %124, %125, %126, %127}, %128, %129, p, 1, 1, 0, 1;\n}\n"
    : "+f"(d[0]), "+f"(d[1]), "+f"(d[2]), "+f"(d[3]), "+f"(d[4]), "+f"(d[5]), "+f"(d[6]), "+f"(d[7]), "+f"(d[8]), "+f"(d[9]), "+f"(d[10]), "+f"(d[11]), "+f"(d[12]), "+f"(d[13]), "+f"(d[14]), "+f"(d[15]), "+f"(d[16]), "+f"(d[17]), "+f"(d[18]), "+f"(d[19]), "+f"(d[20]), "+f"(d[21]), "+f"(d[22]), "+f"(d[23]), "+f"(d[24]), "+f"(d[25]), "+f"(d[26]), "+f"(d[27]), "+f"(d[28]), "+f"(d[29]), "+f"(d[30]), "+f"(d[31]), "+f"(d[32]), "+f"(d[33]), "+f"(d[34]), "+f"(d[35]), "+f"(d[36]), "+f"(d[37]), "+f"(d[38]), "+f"(d[39]), "+f"(d[40]), "+f"(d[41]), "+f"(d[42]), "+f"(d[43]), "+f"(d[44]), "+f"(d[45]), "+f"(d[46]), "+f"(d[47]), "+f"(d[48]), "+f"(d[49]), "+f"(d[50]), "+f"(d[51]), "+f"(d[52]), "+f"(d[53]), "+f"(d[54]), "+f"(d[55]), "+f"(d[56]), "+f"(d[57]), "+f"(d[58]), "+f"(d[59]), "+f"(d[60]), "+f"(d[61]), "+f"(d[62]), "+f"(d[63]), "+f"(d[64]), "+f"(d[65]), "+f"(d[66]), "+f"(d[67]), "+f"(d[68]), "+f"(d[69]), "+f"(d[70]), "+f"(d[71]), "+f"(d[72]), "+f"(d[73]), "+f"(d[74]), "+f"(d[75]), "+f"(d[76]), "+f"(d[77]), "+f"(d[78]), "+f"(d[79]), "+f"(d[80]), "+f"(d[81]), "+f"(d[82]), "+f"(d[83]), "+f"(d[84]), "+f"(d[85]), "+f"(d[86]), "+f"(d[87]), "+f"(d[88]), "+f"(d[89]), "+f"(d[90]), "+f"(d[91]), "+f"(d[92]), "+f"(d[93]), "+f"(d[94]), "+f"(d[95]), "+f"(d[96]), "+f"(d[97]), "+f"(d[98]), "+f"(d[99]), "+f"(d[100]), "+f"(d[101]), "+f"(d[102]), "+f"(d[103]), "+f"(d[104]), "+f"(d[105]), "+f"(d[106]), "+f"(d[107]), "+f"(d[108]), "+f"(d[109]), "+f"(d[110]), "+f"(d[111]), "+f"(d[112]), "+f"(d[113]), "+f"(d[114]), "+f"(d[115]), "+f"(d[116]), "+f"(d[117]), "+f"(d[118]), "+f"(d[119]), "+f"(d[120]), "+f"(d[121]), "+f"(d[122]), "+f"(d[123]), "+f"(d[124]), "+f"(d[125]), "+f"(d[126]), "+f"(d[127])
    : "l"(da), "l"(db), "r"(sd));
}

__device__ __forceinline__ void wgmma_m64n128_ss(float (&d)[64], uint64_t da, uint64_t db, int sd) {
  asm volatile(
    "{\n.reg .pred p;\nsetp.ne.b32 p, %66, 0;\n"
    "wgmma.mma_async.sync.aligned.m64n128k16.f32.bf16.bf16 "
    "{%0, %1, %2, %3, %4, %5, %6, %7, %8, %9, %10, %11, %12, %13, %14, %15, %16, %17, %18, %19, %20, %21, %22, %23, %24, %25, %26, %27, %28, %29, %30, %31, %32, %33, %34, %35, %36, %37, %38, %39, %40, %41, %42, %43, %44, %45, %46, %47, %48, %49, %50, %51, %52, %53, %54, %55, %56, %57, %58, %59, %60, %61, %62, %63}, %64, %65, p, 1, 1, 0, 0;\n}\n"
    : "+f"(d[0]), "+f"(d[1]), "+f"(d[2]), "+f"(d[3]), "+f"(d[4]), "+f"(d[5]), "+f"(d[6]), "+f"(d[7]), "+f"(d[8]), "+f"(d[9]), "+f"(d[10]), "+f"(d[11]), "+f"(d[12]), "+f"(d[13]), "+f"(d[14]), "+f"(d[15]), "+f"(d[16]), "+f"(d[17]), "+f"(d[18]), "+f"(d[19]), "+f"(d[20]), "+f"(d[21]), "+f"(d[22]), "+f"(d[23]), "+f"(d[24]), "+f"(d[25]), "+f"(d[26]), "+f"(d[27]), "+f"(d[28]), "+f"(d[29]), "+f"(d[30]), "+f"(d[31]), "+f"(d[32]), "+f"(d[33]), "+f"(d[34]), "+f"(d[35]), "+f"(d[36]), "+f"(d[37]), "+f"(d[38]), "+f"(d[39]), "+f"(d[40]), "+f"(d[41]), "+f"(d[42]), "+f"(d[43]), "+f"(d[44]), "+f"(d[45]), "+f"(d[46]), "+f"(d[47]), "+f"(d[48]), "+f"(d[49]), "+f"(d[50]), "+f"(d[51]), "+f"(d[52]), "+f"(d[53]), "+f"(d[54]), "+f"(d[55]), "+f"(d[56]), "+f"(d[57]), "+f"(d[58]), "+f"(d[59]), "+f"(d[60]), "+f"(d[61]), "+f"(d[62]), "+f"(d[63])
    : "l"(da), "l"(db), "r"(sd));
}

__device__ __forceinline__ void wgmma_m64n128_ss_tb(float (&d)[64], uint64_t da, uint64_t db, int sd) {
  asm volatile(
    "{\n.reg .pred p;\nsetp.ne.b32 p, %66, 0;\n"
    "wgmma.mma_async.sync.aligned.m64n128k16.f32.bf16.bf16 "
    "{%0, %1, %2, %3, %4, %5, %6, %7, %8, %9, %10, %11, %12, %13, %14, %15, %16, %17, %18, %19, %20, %21, %22, %23, %24, %25, %26, %27, %28, %29, %30, %31, %32, %33, %34, %35, %36, %37, %38, %39, %40, %41, %42, %43, %44, %45, %46, %47, %48, %49, %50, %51, %52, %53, %54, %55, %56, %57, %58, %59, %60, %61, %62, %63}, %64, %65, p, 1, 1, 0, 1;\n}\n"
    : "+f"(d[0]), "+f"(d[1]), "+f"(d[2]), "+f"(d[3]), "+f"(d[4]), "+f"(d[5]), "+f"(d[6]), "+f"(d[7]), "+f"(d[8]), "+f"(d[9]), "+f"(d[10]), "+f"(d[11]), "+f"(d[12]), "+f"(d[13]), "+f"(d[14]), "+f"(d[15]), "+f"(d[16]), "+f"(d[17]), "+f"(d[18]), "+f"(d[19]), "+f"(d[20]), "+f"(d[21]), "+f"(d[22]), "+f"(d[23]), "+f"(d[24]), "+f"(d[25]), "+f"(d[26]), "+f"(d[27]), "+f"(d[28]), "+f"(d[29]), "+f"(d[30]), "+f"(d[31]), "+f"(d[32]), "+f"(d[33]), "+f"(d[34]), "+f"(d[35]), "+f"(d[36]), "+f"(d[37]), "+f"(d[38]), "+f"(d[39]), "+f"(d[40]), "+f"(d[41]), "+f"(d[42]), "+f"(d[43]), "+f"(d[44]), "+f"(d[45]), "+f"(d[46]), "+f"(d[47]), "+f"(d[48]), "+f"(d[49]), "+f"(d[50]), "+f"(d[51]), "+f"(d[52]), "+f"(d[53]), "+f"(d[54]), "+f"(d[55]), "+f"(d[56]), "+f"(d[57]), "+f"(d[58]), "+f"(d[59]), "+f"(d[60]), "+f"(d[61]), "+f"(d[62]), "+f"(d[63])
    : "l"(da), "l"(db), "r"(sd));
}

__device__ __forceinline__ void wgmma_m64n128_rs_tb(float* d, uint32_t a0, uint32_t a1, uint32_t a2, uint32_t a3, uint64_t db, int sd) {
  asm volatile(
    "{\n.reg .pred p;\nsetp.ne.b32 p, %69, 0;\n"
    "wgmma.mma_async.sync.aligned.m64n128k16.f32.bf16.bf16 "
    "{%0, %1, %2, %3, %4, %5, %6, %7, %8, %9, %10, %11, %12, %13, %14, %15, %16, %17, %18, %19, %20, %21, %22, %23, %24, %25, %26, %27, %28, %29, %30, %31, %32, %33, %34, %35, %36, %37, %38, %39, %40, %41, %42, %43, %44, %45, %46, %47, %48, %49, %50, %51, %52, %53, %54, %55, %56, %57, %58, %59, %60, %61, %62, %63}, {%64, %65, %66, %67}, %68, p, 1, 1, 1;\n}\n"
    : "+f"(d[0]), "+f"(d[1]), "+f"(d[2]), "+f"(d[3]), "+f"(d[4]), "+f"(d[5]), "+f"(d[6]), "+f"(d[7]), "+f"(d[8]), "+f"(d[9]), "+f"(d[10]), "+f"(d[11]), "+f"(d[12]), "+f"(d[13]), "+f"(d[14]), "+f"(d[15]), "+f"(d[16]), "+f"(d[17]), "+f"(d[18]), "+f"(d[19]), "+f"(d[20]), "+f"(d[21]), "+f"(d[22]), "+f"(d[23]), "+f"(d[24]), "+f"(d[25]), "+f"(d[26]), "+f"(d[27]), "+f"(d[28]), "+f"(d[29]), "+f"(d[30]), "+f"(d[31]), "+f"(d[32]), "+f"(d[33]), "+f"(d[34]), "+f"(d[35]), "+f"(d[36]), "+f"(d[37]), "+f"(d[38]), "+f"(d[39]), "+f"(d[40]), "+f"(d[41]), "+f"(d[42]), "+f"(d[43]), "+f"(d[44]), "+f"(d[45]), "+f"(d[46]), "+f"(d[47]), "+f"(d[48]), "+f"(d[49]), "+f"(d[50]), "+f"(d[51]), "+f"(d[52]), "+f"(d[53]), "+f"(d[54]), "+f"(d[55]), "+f"(d[56]), "+f"(d[57]), "+f"(d[58]), "+f"(d[59]), "+f"(d[60]), "+f"(d[61]), "+f"(d[62]), "+f"(d[63])
    : "r"(a0), "r"(a1), "r"(a2), "r"(a3), "l"(db), "r"(sd));
}

__device__ __forceinline__ void wgmma_m64n64_rs_tb(float (&d)[32], const uint32_t (&a)[4], uint64_t db, int sd) {
  asm volatile(
    "{\n.reg .pred p;\nsetp.ne.b32 p, %37, 0;\n"
    "wgmma.mma_async.sync.aligned.m64n64k16.f32.bf16.bf16 "
    "{%0, %1, %2, %3, %4, %5, %6, %7, %8, %9, %10, %11, %12, %13, %14, %15, %16, %17, %18, %19, %20, %21, %22, %23, %24, %25, %26, %27, %28, %29, %30, %31}, {%32, %33, %34, %35}, %36, p, 1, 1, 1;\n}\n"
    : "+f"(d[0]), "+f"(d[1]), "+f"(d[2]), "+f"(d[3]), "+f"(d[4]), "+f"(d[5]), "+f"(d[6]), "+f"(d[7]), "+f"(d[8]), "+f"(d[9]), "+f"(d[10]), "+f"(d[11]), "+f"(d[12]), "+f"(d[13]), "+f"(d[14]), "+f"(d[15]), "+f"(d[16]), "+f"(d[17]), "+f"(d[18]), "+f"(d[19]), "+f"(d[20]), "+f"(d[21]), "+f"(d[22]), "+f"(d[23]), "+f"(d[24]), "+f"(d[25]), "+f"(d[26]), "+f"(d[27]), "+f"(d[28]), "+f"(d[29]), "+f"(d[30]), "+f"(d[31])
    : "r"(a[0]), "r"(a[1]), "r"(a[2]), "r"(a[3]), "l"(db), "r"(sd));
}

__device__ __forceinline__ void wgmma_m64n32_rs_tb(float (&d)[16], const uint32_t (&a)[4], uint64_t db, int sd) {
  asm volatile(
    "{\n.reg .pred p;\nsetp.ne.b32 p, %21, 0;\n"
    "wgmma.mma_async.sync.aligned.m64n32k16.f32.bf16.bf16 "
    "{%0, %1, %2, %3, %4, %5, %6, %7, %8, %9, %10, %11, %12, %13, %14, %15}, {%16, %17, %18, %19}, %20, p, 1, 1, 1;\n}\n"
    : "+f"(d[0]), "+f"(d[1]), "+f"(d[2]), "+f"(d[3]), "+f"(d[4]), "+f"(d[5]), "+f"(d[6]), "+f"(d[7]), "+f"(d[8]), "+f"(d[9]), "+f"(d[10]), "+f"(d[11]), "+f"(d[12]), "+f"(d[13]), "+f"(d[14]), "+f"(d[15])
    : "r"(a[0]), "r"(a[1]), "r"(a[2]), "r"(a[3]), "l"(db), "r"(sd));
}

constexpr int G_STAGES = 4;
constexpr int G_A_BYTES = 128 * 64 * 2;
constexpr int G_B_BYTES = 256 * 64 * 2;
constexpr int G_STAGE_BYTES = G_A_BYTES + G_B_BYTES;
constexpr int G_STG_OFF = G_STAGES * G_STAGE_BYTES;
constexpr int BAR_OFF = G_STG_OFF + 32768 + 2048;
constexpr int SMEM_BYTES = BAR_OFF + 1024;
constexpr int B_GFULL = 0, B_GEMPTY = 32, B_SEEN = 64, B_PFULL = 224;
constexpr int B_KFULL = 80, B_KEMPTY = 96, B_VFULL = 112, B_VEMPTY = 128, B_QFULL = 144, B_QEMPTY = 160,
              B_QDONE = 184;
constexpr int B_CFULL = 192;
constexpr int B_OFREE = 256, B_OFULL = 272, B_OEMPTY = 320, B_OY = 368, B_OY2 = 384, B_OE = 768;
constexpr int B_DEAL = 312, B_DEAL2 = 360, B_LIST = 640, B_PAIR = 504;
constexpr int B_SFULL = 392, B_SFREE = 424, B_PEND = 456, B_SCMD = 512;

#define PHASE_PROLOGUE                                                                \
  uint32_t tid, rt_zero;                                                              \
  asm volatile("mov.u32 %0, %%tid.x;" : "=r"(tid));                                   \
  asm volatile("mov.u32 %0, %%nctaid.y;" : "=r"(rt_zero));                            \
  asm volatile("" : "+r"(smem0));                                                     \
  rt_zero = __shfl_sync(0xffffffffu, rt_zero >> 8, 0);   \
  const uint32_t sbase = __shfl_sync(0xffffffffu, smem0, 0);                          \
  const uint32_t bar = sbase + BAR_OFF;                                               \
  const int wg = __shfl_sync(0xffffffffu, tid >> 7, 0);                               \
  const int warp = (tid >> 5) & 3, lane = tid & 31, wtid = tid & 127;                 \
  (void)rt_zero; (void)bar; (void)warp; (void)lane; (void)wtid;

#define PHASE_GIVEN PHASE_GIVEN_(0)
#define PHASE_GIVEN_(z)                                                               \
  uint32_t tid;                                                                       \
  asm volatile("mov.u32 %0, %%tid.x;" : "=r"(tid));                                   \
  tid |= z;                               \
  const uint32_t bar = sbase + BAR_OFF;                                               \
  const int warp = (tid >> 5) & 3, lane = tid & 31, wtid = tid & 127;

enum { ST_BOX1, ST_BOX2, ST_BOX2Q, ST_BOX2L };
__device__ __forceinline__ void st_cmd(uint32_t bar, int wg, int wtid, uint32_t n, int kind, const void* dst,
                                       uint32_t src, int c0, int c1, int sig, uint32_t lazy = 0) {
  if (wtid == 0) {
    const uint32_t c = bar + B_SCMD + wg * 64 + (n & 1) * 32;
    const uint64_t d = reinterpret_cast<uint64_t>(dst);
    sts128(c, make_uint4(kind, src, c0, c1));
    sts128(c + 16, make_uint4((uint32_t)d, (uint32_t)(d >> 32), sig, lazy));
  }
}
__device__ __forceinline__ void st_go(uint32_t bar, int wg, int wtid, uint32_t n) {
  fence_proxy_async();
  __syncwarp();
  mbar_arrive_if(bar + B_SFULL + wg * 16 + (n & 1) * 8, (wtid & 31) == 0);
}
__device__ __forceinline__ void st_post(uint32_t bar, int wg, int wtid, uint32_t n, int kind, const void* dst,
                                        uint32_t src, int c0, int c1, int sig, uint32_t lazy = 0) {
  st_cmd(bar, wg, wtid, n, kind, dst, src, c0, c1, sig, lazy);
  st_go(bar, wg, wtid, n);
}
__device__ __forceinline__ void st_wait(uint32_t bar, int wg, uint32_t n) {
  const uint32_t b = bar + B_SFREE + wg * 16 + (n & 1) * 8;
  if (!mbar_try(b, ~(n >> 1) & 1)) mbar_wait(b, ~(n >> 1) & 1);
}
__device__ __forceinline__ void note(uint32_t bar, uint32_t cnt) {
  asm volatile("red.release.cta.shared.add.u32 [%0], 1;" ::"r"(bar + B_PEND + 4 * cnt) : "memory");
}
#define LAZY_NS 250
#define DEAL_NS 400
#define DEAL_NS2 1250
constexpr uint32_t C_NONE = 0x10000;
__device__ __forceinline__ void deal(uint32_t bar, uint32_t r, uint32_t t, uint32_t own) {
  uint64_t p;
  uint32_t spins = 0;
  while (true) {
    asm volatile("ld.relaxed.gpu.global.u64 %0, [%1];" : "=l"(p) : "l"(g_slot + 127 - r) : "memory");
    if (p || ++spins > (1u << 18)) break;
    __nanosleep(100);
  }
  const uint32_t pc = (uint32_t)p;
  int dt = (uint32_t)(p >> 32) - t;
  if (r >= 64) {
    sts128(bar + B_LIST, make_uint4(-dt > DEAL_NS2 ? C_NONE : own - 16, -dt > DEAL_NS ? C_NONE : own, C_NONE, C_NONE));
    mbar_arrive(bar + B_DEAL);
    dt = 0;
  }
  sts128(bar + B_LIST + 16, make_uint4(dt > DEAL_NS ? pc : C_NONE, dt > DEAL_NS2 ? pc - 16 : C_NONE, C_NONE, C_NONE));
  mbar_arrive(bar + B_DEAL2);
}
__device__ __forceinline__ void store_agent(uint32_t bar, int wg, uint32_t last_ch, uint32_t n_end) {
  mbar_arrive(bar + B_SFREE + wg * 16);
  mbar_arrive(bar + B_SFREE + wg * 16 + 8);
  bool more = true;
  for (uint32_t n = 0; n < n_end && more; n++) {
    mbar_wait_sleep(bar + B_SFULL + wg * 16 + (n & 1) * 8, (n >> 1) & 1);
    const uint4 c = lds128(bar + B_SCMD + wg * 64 + (n & 1) * 32);
    const uint4 d = lds128(bar + B_SCMD + wg * 64 + (n & 1) * 32 + 16);
    uint32_t t;
    asm volatile("mov.u32 %0, %%globaltimer_lo;" : "=r"(t));
    uint32_t r = 0, tp = t;
    if (c.x == ST_BOX2L && last_ch) {
      mbar_expect_tx(bar + B_PAIR, 4);
      asm volatile(
          "{\n.reg .b32 ra;\nmapa.shared::cluster.u32 ra, %0, %1;\n"
          "st.async.weak.shared::cluster.mbarrier::complete_tx::bytes.u32 [ra + 224], %2, [ra];\n}\n" ::"r"(bar + B_PAIR),
          "r"(~blockIdx.x & 1), "r"(t)
          : "memory");
      mbar_wait_sleep(bar + B_PAIR, 0);
      r = atomicAdd(g_cnt + CNT_RANK * 32, 1u) & 127;
      asm volatile("ld.shared.u32 %0, [%1];" : "=r"(tp) : "r"(bar + B_PAIR + 224) : "memory");
      if ((int)(tp - t) < 0) tp = t;
      asm volatile("st.relaxed.gpu.global.u64 [%0], %1;" ::"l"(g_slot + r), "l"(((uint64_t)tp << 32) | last_ch) : "memory");
      if (r < 64) {
        sts128(bar + B_LIST, make_uint4(last_ch - 16, last_ch, C_NONE, C_NONE));
        mbar_arrive(bar + B_DEAL);
      } else {
        deal(bar, r, tp, last_ch);
      }
    }
    for (uint32_t t1 = t; d.w && t1 - t < (2 * d.w + wg) * LAZY_NS;) {
      __nanosleep(200);
      asm volatile("mov.u32 %0, %%globaltimer_lo;" : "=r"(t1));
    }
    const CUtensorMap* dst = reinterpret_cast<const CUtensorMap*>((uint64_t)d.x | ((uint64_t)d.y << 32));
    tma_store_2d(dst, c.y, c.z, c.w);
    if (c.x >= ST_BOX2) tma_store_2d(dst, c.y + 8192, c.z + 64, c.w);
    tma_store_commit();
    tma_store_wait_read<0>();
    mbar_arrive(bar + B_SFREE + wg * 16 + (n & 1) * 8);
    if (c.x == ST_BOX2L) mbar_arrive(bar + B_OFREE + 8 * wg);
    if ((int)d.z >= 0) {
      tma_store_wait<0>();
      if (d.z == 0) { TD(6) }
      asm volatile("fence.proxy.async.global;" ::: "memory");
      if (c.x == ST_BOX2Q) mbar_arrive(bar + B_QDONE);
      else note(bar, d.z);
      if (c.x == ST_BOX2L) {
        note(bar, CNT_DONE);
        more = false;
        if (last_ch && r < 64) deal(bar, r, tp, last_ch);
      }
    }
  }
  if (more) note(bar, CNT_DONE);
}

struct Maps {
  const bf16 *shift_k, *x, *gate_w, *ssm_k, *ssm_D;
  uint8_t id[128][4];
  CUtensorMap a[2];
  CUtensorMap b[3];
  CUtensorMap c[3];
  CUtensorMap bk, bv;
  CUtensorMap q, k, v, o;
  CUtensorMap oa, ob, oc;
  CUtensorMap y, xs;
  CUtensorMap cu, ch;
};

constexpr int P_SLOT = 67 * 128, P_V = 35 * 128, P_TAPS = 2 * P_SLOT;
__device__ __forceinline__ void ldsm4t(uint32_t (&r)[4], uint32_t a) {
  asm volatile("ldmatrix.sync.aligned.m8n8.x4.trans.shared.b16 {%0, %1, %2, %3}, [%4];"
               : "=r"(r[0]), "=r"(r[1]), "=r"(r[2]), "=r"(r[3])
               : "r"(a));
}
__device__ __forceinline__ uint32_t fma_bf2(uint32_t a, uint32_t b, uint32_t c) {
  uint32_t r;
  asm("fma.rn.bf16x2 %0, %1, %2, %3;" : "=r"(r) : "r"(a), "r"(b), "r"(c));
  return r;
}
__device__ __forceinline__ void prep_agent(const Maps& maps, uint32_t sbase, int w, int lane) {
  const uint32_t bar = sbase + BAR_OFF, pb = bar + B_PFULL + w * 16;
  const int d0 = (blockIdx.x >> 3) * 64, t0 = (blockIdx.x & 7) * 256 + w * 128;
  mbar_wait_sleep(bar + B_GFULL + 8 * (G_STAGES - 1), 0);
#pragma unroll 1
  for (int i = -1; i < 4; i++) {
    GA(82 + 2 * i)
    if (i >= 0) mbar_wait_sleep(pb + (i & 1) * 8, i >> 1);
    GA(83 + 2 * i)
    const uint32_t so = sbase + G_STG_OFF + w * (P_TAPS + 512) + (i & 1) * P_SLOT;
    if (i < 3 && elect_one()) {
      const uint32_t b = pb + (~i & 1) * 8, dst = so + (i & 1 ? -P_SLOT : P_SLOT);
      mbar_expect_tx(b, i < 0 ? P_SLOT + 512 : P_SLOT);
      const uint64_t pol = policy_evict_first();
      tma_load_2d_hint(dst, &maps.bk, b, d0, t0 + 32 * i + 29, pol);
      tma_load_2d_hint(dst + P_V, &maps.bv, b, d0, t0 + 32 * i + 32, pol);
      if (i < 0) bulk_load(sbase + G_STG_OFF + P_TAPS, maps.shift_k + d0 * 4, 512, b);
    }
    if (i < 0) continue;
    uint32_t ak[4];
#pragma unroll
    for (int r = 0; r < 4; r++) {
      const uint32_t a = so / 128 + r + 4 * (lane & 6) + (((lane >> 2) ^ lane) & 6) + (lane & 1);
      ak[r] = a * 128 + (a & 7) * 16;
    }
    bf16* dst = g_kvT + (size_t)(d0 + (lane >> 2)) * S_LEN + t0 + ((lane & 3) + 4 * i) * 8;
#pragma unroll 1
    for (int cg = 0; cg < 128; cg += 16) {
      uint32_t t01, t23, k[4][4], v[4];
      asm volatile("ld.shared.v2.u32 {%0, %1}, [%2];"
                   : "=r"(t01), "=r"(t23)
                   : "r"(sbase + G_STG_OFF + P_TAPS + cg * 4 + (lane >> 2) * 8));
#pragma unroll
      for (int r = 0; r < 4; r++) ldsm4t(k[r], ak[r] ^ cg);
      ldsm4t(v, (ak[3] ^ cg) + 4096);
      const uint32_t w0 = __byte_perm(t01, 0, 0x1010), w1 = __byte_perm(t01, 0, 0x3232);
      const uint32_t w2 = __byte_perm(t23, 0, 0x1010), w3 = __byte_perm(t23, 0, 0x3232);
#pragma unroll
      for (int j = 0; j < 4; j++)
        v[j] = mul_bf2(fma_bf2(k[3][j], w0, fma_bf2(k[2][j], w1, fma_bf2(k[1][j], w2, mul_bf2(k[0][j], w3)))), v[j]);
      const bool s1 = lane & 1, s2 = lane & 2;
      const uint32_t a0 = s1 ? v[1] : v[0], a1 = s1 ? v[0] : v[1], a2 = s1 ? v[3] : v[2], a3 = s1 ? v[2] : v[3];
      *reinterpret_cast<uint4*>(dst) = make_uint4(s2 ? a2 : a0, s2 ? a3 : a1, s2 ? a0 : a2, s2 ? a1 : a3);
      dst += 8 * S_LEN;
    }
    fence_proxy_async();
    __syncwarp();
  }
  GA(90)
  if (lane == 0) note(bar, CNT_PREP);
  __syncwarp();
  GA(91)
}

__device__ __forceinline__ void qkv_tile(const Maps& maps, int it, int& which, int& m_tile, int& n_tile) {
  const bool q = it == 0 || it >= 5;
  const int b = maps.id[blockIdx.x][it >= 5];
  which = q ? 0 : 2 - (it & 1);
  m_tile = b & 15;
  n_tile = (b >> 4) * 2 + ((0x19 >> it) & 1);
}

constexpr int G_NTILES = 6;
__device__ __forceinline__ uint32_t qkv_flip(int it) { return ((0x0b >> it) & 1) * 3; }
__device__ __forceinline__ void qkv_producer(const Maps& maps, uint32_t sbase, bool first) {
  const uint32_t bar = sbase + BAR_OFF;
  uint32_t stage = 0, phase = 0;
#pragma unroll 1
  for (int it = 0; it < (first ? 1 : G_NTILES); it++) {
    int which, m_tile, n_tile;
    qkv_tile(maps, it, which, m_tile, n_tile);
    const CUtensorMap* ma = &maps.a[which == 0 ? 0 : 1];
    const CUtensorMap* mb = &maps.b[which];
    const int nk = first ? G_STAGES : which == 0 ? 16 : 8;
#pragma unroll 1
    for (int kt = (it == 0 && !first) ? G_STAGES : 0; kt < nk; kt++) {
      if (!first) mbar_wait_sleep(bar + B_GEMPTY + 8 * stage, phase);
      const uint32_t fb = bar + B_GFULL + 8 * stage;
      const uint32_t sa = sbase + stage * G_STAGE_BYTES;
      const int k0 = (kt ^ ((0x14 >> it) & 1) * 7) * 64;
      const bool keep = ((0x1c >> it) & 1) && kt < G_STAGES;
      mbar_expect_tx(fb, keep ? G_B_BYTES : G_STAGE_BYTES);
      if (!keep) tma_load_2d(sbase + (stage ^ qkv_flip(it)) * G_STAGE_BYTES, ma, fb, k0, m_tile * 128);
      tma_load_3d(sa + G_A_BYTES, mb, fb, 0, k0, n_tile * 4);
      if (++stage == G_STAGES) { stage = 0; phase ^= 1; }
      {
        const int b = maps.id[blockIdx.x][1];
        if (it == 2 && kt == (b & 7)) {
          for (int i = 0; i < 2; i++)
            asm volatile("cp.async.bulk.prefetch.tensor.2d.L2.global.tile [%0, {%1, %2}];" ::"l"(&maps.a[0]),
                         "r"((b >> 4) * 128 + i * 64), "r"((b & 15) * 128)
                         : "memory");
          asm volatile("cp.async.bulk.prefetch.tensor.3d.L2.global.tile [%0, {%1, %2, %3}];" ::"l"(&maps.b[1 + ((b >> 3) & 1)]),
                       "r"(0), "r"((b & 7) * 64), "r"((b >> 4) * 8 + 4)
                       : "memory");
        }
        if (it == 3 && kt == (b & 7))
          asm volatile("cp.async.bulk.prefetch.tensor.3d.L2.global.tile [%0, {%1, %2, %3}];" ::"l"(&maps.b[0]), "r"(0),
                       "r"((b & 15) * 64), "r"((b >> 4) * 8)
                       : "memory");
      }
    }
  }
}

__device__ __forceinline__ uint32_t seen_bar(uint32_t item) { return B_SEEN + ((0x700800u >> (8 * item)) & 255); }
__device__ __noinline__ void publisher(uint32_t bar, int lane, uint32_t nsrc, uint32_t item, uint32_t mine) {
  uint32_t done = 0, tot = 0;
#pragma unroll 1
  for (uint32_t spins = 0; (done < nsrc || item < 3) && spins < (1u << 20); spins++) {
    const uint32_t cnt = item ? CNT_CTX - 1 + item : CNT_KV + 1;
    if (item < 3 && __shfl_sync(0xffffffffu, tot, cnt) >= mine >> !item) {
      uint32_t v;
      asm volatile("ld.acquire.gpu.global.u32 %0, [%1];" : "=r"(v) : "l"(g_cnt + (lane ? cnt : CNT_PREP) * 32) : "memory");
      if (__all_sync(0xffffffffu, v >= (lane ? 512 >> !item : 260))) {
        asm volatile("fence.proxy.async.global;" ::: "memory");
        mbar_arrive_if(bar + seen_bar(item), lane == 0);
        item++;
      }
    }
    uint32_t v = 0;
    if (lane < CNT_N)
      asm volatile("atom.acquire.cta.shared.exch.b32 %0, [%1], 0;" : "=r"(v) : "r"(bar + B_PEND + 4 * lane) : "memory");
    done += __shfl_sync(0xffffffffu, v, CNT_DONE);
    if (lane == CNT_DONE) v = 0;
    if (done == nsrc && lane < CNT_DONE) {
      uint32_t w;
      asm volatile("atom.acquire.cta.shared.exch.b32 %0, [%1], 0;" : "=r"(w) : "r"(bar + B_PEND + 4 * lane) : "memory");
      v += w;
    }
    if (v && lane == 0) { TD(0) }
    if (v) cnt_signal_release(lane, v);
    tot += v;
    if (v && lane == 0) { TD(1) }
    if (!__any_sync(0xffffffffu, v != 0)) __nanosleep(item == 1 ? 1000 : 200);
  }
  __threadfence();
  __syncwarp();
}

__device__ __forceinline__ void gate_rows(const Maps& maps, uint32_t sbase, int w48, int w12, int lane) {
  const uint32_t buf = sbase + w12 * 16384, gb = sbase + BAR_OFF + 768 + w12 * 16;
  if (lane == 0) {
    mbar_init(gb, 1);
    mbar_init(gb + 8, 1);
    fence_barrier_init();
    for (int i = 0; i < 2; i++) {
      mbar_expect_tx(gb + 8 * i, 8192);
      bulk_load(buf + i * 8192, maps.x + (size_t)(w48 + 48 * i) * 4 * DM, 8192, gb + 8 * i);
    }
  }
  __syncwarp();
  uint4 wv[4];
#pragma unroll
  for (int i = 0; i < 4; i++) wv[i] = __ldg(reinterpret_cast<const uint4*>(maps.gate_w + (i * 32 + lane) * 8));
  int it = 0;
#pragma unroll 1
  for (int row = w48 * 4; row < S_LEN; row += 48 * 4, it++) {
    mbar_wait(gb + 8 * (it & 1), (it >> 1) & 1);
    uint4 xv[4][4];
#pragma unroll
    for (int r = 0; r < 4; r++)
#pragma unroll
      for (int i = 0; i < 4; i++) xv[r][i] = lds128(buf + (it & 1) * 8192 + r * 2048 + (i * 32 + lane) * 16);
    float d[2][4];
#pragma unroll
    for (int pr = 0; pr < 2; pr++) {
      d[pr][0] = d[pr][1] = d[pr][2] = d[pr][3] = 0.f;
      auto acc = [&](uint32_t a0, uint32_t a2, uint32_t b0, uint32_t b2, uint32_t w0, uint32_t w2) {
        asm volatile(
            "mma.sync.aligned.m16n8k16.row.col.f32.bf16.bf16.f32 {%0, %1, %2, %3}, {%4, %5, %6, %7}, {%8, %8}, "
            "{%0, %1, %2, %3};"
            : "+f"(d[pr][0]), "+f"(d[pr][1]), "+f"(d[pr][2]), "+f"(d[pr][3])
            : "r"(mul_bf2(a0, w0)), "r"(mul_bf2(b0, w0)), "r"(mul_bf2(a2, w2)), "r"(mul_bf2(b2, w2)), "r"(0x3f803f80u));
      };
#pragma unroll
      for (int i = 0; i < 4; i++) {
        acc(xv[2 * pr][i].x, xv[2 * pr][i].y, xv[2 * pr + 1][i].x, xv[2 * pr + 1][i].y, wv[i].x, wv[i].y);
        acc(xv[2 * pr][i].z, xv[2 * pr][i].w, xv[2 * pr + 1][i].z, xv[2 * pr + 1][i].w, wv[i].z, wv[i].w);
      }
    }
    float sum = (lane & 2) ? ((lane & 1) ? d[1][2] : d[1][0]) : ((lane & 1) ? d[0][2] : d[0][0]);
#pragma unroll
    for (int off = 16; off >= 4; off >>= 1) sum += __shfl_xor_sync(0xffffffffu, sum, off);
    if (lane < 4) g_gate[row + lane] = bf16_round(rcp(1.0f + __expf(-bf16_round(sum))));
    if (lane == 0 && row + 2 * 48 * 4 < S_LEN) {
      mbar_expect_tx(gb + 8 * (it & 1), 8192);
      bulk_load(buf + (it & 1) * 8192, maps.x + (size_t)(row + 2 * 48 * 4) * DM, 8192, gb + 8 * (it & 1));
    }
  }
}

constexpr float Q_SCALE = 0.08838834764831845f * 1.4426950408889634f;
__device__ __forceinline__ uint32_t qkv_consumer(const Maps& maps, const uint32_t sbase, const int wg, bool fused,
                                                 float (&rest)[64], uint32_t rt_zero) {
  PHASE_GIVEN_(rt_zero)
  constexpr int NTILES = G_NTILES;
  float acc[128];
  const uint32_t stg = sbase + G_STG_OFF + wg * 18432;
  const int st_row = warp * 16 + (lane & 7) + ((lane >> 3) & 1) * 8;
  const int st_cb = lane >> 4;
  uint32_t pend[64];
  const CUtensorMap* pend_map = nullptr;
  int pend_c0 = 0, pend_c1 = 0;
  uint32_t sn = 0;
  uint32_t st_a[4];
#pragma unroll
  for (int jp = 0; jp < 4; jp++) {
    st_a[jp] = stg + st_row * 128 + (((jp * 2 + st_cb) ^ (st_row & 7)) << 4);
    asm volatile("" : "+r"(st_a[jp]));
  }
  auto put_box = [&](uint32_t off, const uint32_t* v) {
#pragma unroll
    for (int jp = 0; jp < 4; jp++) stmatrix_x4(st_a[jp] + off, v[jp * 4], v[jp * 4 + 1], v[jp * 4 + 2], v[jp * 4 + 3]);
  };
  GT(gti++)
  const int hf = wg ^ 1;
  const uint64_t da0 = make_desc(sbase + hf * 8192, 16, 1024, DESC_SW128);
  const uint64_t db0 = make_desc(sbase + G_A_BYTES, 8192, 1024, DESC_SW128);
  uint32_t g = 0, oa = 3 * (G_STAGE_BYTES / 16), ob = 0;
  bool go = false;
  mbar_wait(bar + B_GFULL, 0);
  uint32_t gend = 16, when = 0;
#pragma unroll 1
  for (int it = 0;; it++) {
    bool more = false;
#pragma unroll 1
    do {
      GT(gti++)
      wgmma_fence();
#pragma unroll
      for (int kk = 0; kk < 4; kk++)
        wgmma_m64n256_ss_tb(acc, desc_add(da0, oa + kk * 2), desc_add(db0, ob + kk * 128), kk || more);
      wgmma_commit();
      if (go) st_go(bar, wg, wtid, sn - 1);
      g++;
      if (g + wg == 63) {
        if (wg) named_bar_sync(6, 256);
        else named_bar_arrive(6, 256);
      }
      const uint32_t full = (bar + B_GFULL) + 8 * (g & 3);
      const bool here = mbar_test(full, (g >> 2) & 1) || g >= 64;
      oa = ((g & 3) ^ ((0x17 >> (g >> 3)) & 1) * 3) * (G_STAGE_BYTES / 16);
      ob = (g & 3) * (G_STAGE_BYTES / 16);
      go = when & 1;
      when >>= 1;
      if (go) {
        const int c = sn & 3;
        st_wait(bar, wg, sn - 2);
        st_cmd(bar, wg, wtid, sn, ST_BOX1, pend_map, stg + (c & 1) * 8192, pend_c0 + c * 64, pend_c1,
               (c == 3 && it > 1) ? CNT_KV + (it > 4) : -1);
        switch (c) {
          case 0: put_box(0, pend); break;
          case 1: put_box(8192, pend + 16); break;
          case 2: put_box(0, pend + 32); break;
          default: put_box(8192, pend + 48); break;
        }
        sn++;
      }
      if (it < NTILES) {
        wgmma_wait<1>();
        mbar_arrive_if((bar + B_GEMPTY) + 8 * ((g + 2) & 3), wtid == 32 && more);
        if (!here) mbar_wait(full, (g >> 2) & 1);
      }
      more = true;
    } while (g != gend);
    wgmma_wait<0>();
    fence_regs(acc);
    GT(gti++)
    mbar_arrive_if((bar + B_GEMPTY) + 8 * 3, wtid == 32);
    int which, m_tile, n_tile;
    qkv_tile(maps, it, which, m_tile, n_tile);
    if (which == 0) {
      if (it == NTILES - fused) break;
#pragma unroll
      for (int j = 0; j < 128; j++) acc[j] *= Q_SCALE;
    }
#pragma unroll
    for (int j = 0; j < 64; j++) pend[j] = pack_bf16(acc[2 * j], acc[2 * j + 1]);
    pend_map = &maps.c[which];
    pend_c0 = n_tile * 256;
    pend_c1 = m_tile * 128 + hf * 64;
    gend += it == 4 ? 16 : 8;
    when = (it == 4 ? 0x922 : 0x55) << wg;
  }
  if (go) st_go(bar, wg, wtid, sn - 1);
  mbar_wait(bar + B_GEMPTY, 1);
#pragma unroll
  for (int j = 0; j < 32; j++) pend[j] = pack_bf16(acc[2 * j] * Q_SCALE, acc[2 * j + 1] * Q_SCALE);
  put_box(-G_STG_OFF - wg * 18432 + hf * 8192, pend);
  put_box(16384 - G_STG_OFF - wg * 18432 + hf * 8192, pend + 16);
  fence_proxy_async();
#pragma unroll
  for (int j = 0; j < 64; j++) rest[j] = acc[64 + j];
  GT(gti++)
  return sn;
}

constexpr int A_TILE = 128 * 128 * 2;
constexpr int A_Q_OFF = 0;
constexpr int A_K_OFF = 2 * A_TILE;
constexpr int A_V_OFF = 4 * A_TILE;
constexpr int A_O_OFF = 6 * A_TILE;
constexpr int A_ITEMS = NH * (S_LEN / 128);

constexpr uint32_t A_ORDER = 0x3120, A_STEPS = 34;
__device__ __forceinline__ int item_m(uint32_t it) { return it & 15; }
__device__ __forceinline__ int item_h(uint32_t it) { return it >> 4; }

constexpr int C_V = 16384, C_MAT = 24576;
constexpr float C_ALPHA = 0.07874506561842957f;
__device__ __forceinline__ void sincos_turn(int p, float inv, float& c, float& s) {
  const float a = (float)p * (inv * 6.283185307179586f);
  asm("cos.approx.ftz.f32 %0, %1;" : "=f"(c) : "f"(a));
  asm("sin.approx.ftz.f32 %0, %1;" : "=f"(s) : "f"(a));
}

__device__ __forceinline__ uint32_t head_of(const Maps& maps, uint32_t r) { return (maps.id[blockIdx.x & 127][3] >> (2 * r)) & 3; }
__device__ __forceinline__ uint32_t item_at(const Maps& maps, uint32_t h) {
  const uint32_t b = maps.id[blockIdx.x & 127][1];
  return (b >> 4) * 64 + h * 16 + ((b ^ ((h >> 1) * 15)) & 15);
}
__device__ __forceinline__ uint32_t item_of(const Maps& maps, uint32_t r) { return item_at(maps, head_of(maps, r)); }

#define PACE 250
#define SPACE 0
#define LCHK 1
#define XMASK 3
#define XFIRST 12
#define C_SIDE 64
__device__ __forceinline__ uint32_t conv_first(const Maps& maps) {
  const uint32_t b = maps.id[blockIdx.x & 127][1];
  return (b >> 4) * 128 + ((b + 15) & 15);
}

__device__ __forceinline__ void conv_consumer(const Maps& maps, uint32_t smem0, uint32_t first, uint32_t step,
                                              uint32_t end, bool pp, bool dealt) {
  PHASE_PROLOGUE
  const uint32_t in_full = bar + B_CFULL + wg * 16;
  const uint32_t ca = sbase + (wg ? A_V_OFF + A_TILE : A_Q_OFF);
  const int w = __shfl_sync(0xffffffffu, warp, 0), g = lane >> 2, c = lane & 3;
  auto fetch = [&](uint32_t ch, uint32_t n) {
    if (w == 2 && ch < C_NONE) {
      if (elect_one()) {
        const uint32_t b = in_full + (n & 1) * 8, d = ca + (n & 1) * 8192;
        const uint64_t pol = policy_evict_first();
        mbar_expect_tx(b, 8192);
        tma_load_2d_hint(d, &maps.cu, b, 0, ch * 64, pol);
        tma_load_2d_hint(d + 4096, &maps.ch, b, 0, ch * 64, pol);
      }
    }
  };
  if (wtid == 96 && wg) { TD(15) }
  uint32_t f1[8][4];
  float tt[16], ts[16];
  uint32_t cc[4], ss[4];
#pragma unroll
  for (int i = 0; i < 16; i++) {
    const int k = 2 * (16 * w + g + 8 * (i & 1)) + 1, n = 2 * (8 * (i >> 1) + 2 * c) + 1;
    float c0, s0, c1, s1;
    sincos_turn(((k * n) << 23) >> 23, 1.f / 512, c0, s0);
    sincos_turn(((k * n + 2 * k) << 23) >> 23, 1.f / 512, c1, s1);
    f1[i >> 2][i & 3] = pack_bf16(c0 * C_ALPHA, c1 * C_ALPHA);
    f1[4 + (i >> 2)][i & 3] = pack_bf16(s0 * -C_ALPHA, s1 * -C_ALPHA);
  }
#pragma unroll
  for (int i = 0; i < 16; i++) {
    const int k = 2 * (16 * w + g + 8 * ((i >> 1) & 1)) + 1, n = 16 - (8 * (i >> 2) + 2 * c + (i & 1));
    float cs;
    sincos_turn(k * n, 1.f / 8192, cs, ts[i]);
    tt[i] = ts[i] * rcp(1.f + cs);
  }
#pragma unroll
  for (int j = 0; j < 4; j++) {
    const int k = 8 * w + g, n = 8 * c + 2 * j;
    float c0, s0, c1, s1;
    sincos_turn((int8_t)(k * n * 8), 1.f / 256, c0, s0);
    sincos_turn((int8_t)((k * n + k) * 8), 1.f / 256, c1, s1);
    cc[j] = pack_bf16(c0, c1);
    ss[j] = pack_bf16(s0, s1);
  }
  named_bar_sync(3, 256);
  fetch(first, 0);
  fetch(first + step, 1);
  const uint32_t va = ca + g * 64 + ((c ^ (g >> 1)) << 4);
  {
    const uint32_t a = va + C_MAT + w * 512, m = 0x80008000u;
    sts128(a, make_uint4(cc[0], cc[1], cc[2], cc[3]));
    sts128(a + 2048, make_uint4(ss[0], ss[1], ss[2], ss[3]));
    sts128(a + 4096, make_uint4(ss[0] ^ m, ss[1] ^ m, ss[2] ^ m, ss[3] ^ m));
    sts128(a + 6144, make_uint4(cc[0], cc[1], cc[2], cc[3]));
  }
  fence_proxy_async();
  named_bar_sync(1 + wg, 128);
  constexpr uint64_t DHI = (2ull << 62) | ((uint64_t)(512 >> 4) << 32);
  const uint32_t d0 = (uint32_t)make_desc(ca, 4096, 0, 0);
  float a5[16];
  uint4* const yb = reinterpret_cast<uint4*>(g_y2T) + (16 * w + g) * 4 + c;
  auto issue5 = [&]() {
#pragma unroll
    for (int ks = 0; ks < 8; ks++) wgmma_m64n32_rs_tb(a5, f1[ks], DHI | (d0 + (C_V >> 4) + ks * 64), ks != 0);
    wgmma_commit();
  };
  auto finish = [&](uint32_t ch, bool on) {
    fence_regs(a5);
    uint4* y = yb + (size_t)ch * 256;
    if (on) {
      y[0] = make_uint4(pack_bf16(a5[0], a5[1]), pack_bf16(a5[4], a5[5]), pack_bf16(a5[8], a5[9]), pack_bf16(a5[12], a5[13]));
      y[32] = make_uint4(pack_bf16(a5[2], a5[3]), pack_bf16(a5[6], a5[7]), pack_bf16(a5[10], a5[11]), pack_bf16(a5[14], a5[15]));
    }
  };
  auto dft32 = [&](float (&d)[32], const float* re, const float* im) {
    uint32_t a[4][4];
#pragma unroll
    for (int i = 0; i < 8; i++) {
      a[i >> 2][i & 3] = pack_bf16(re[2 * i], re[2 * i + 1]);
      a[2 + (i >> 2)][i & 3] = pack_bf16(im[2 * i], im[2 * i + 1]);
    }
    wgmma_fence();
#pragma unroll
    for (int ks = 0; ks < 4; ks++) wgmma_m64n64_rs_tb(d, a[ks], DHI | (d0 + (C_MAT >> 4) + ks * 64), ks != 0);
    wgmma_commit();
  };
  auto rot = [&](float* x, float* y) {
#pragma unroll
    for (int i = 0; i < 16; i++) {
      x[i] = fmaf(-tt[i], y[i], x[i]);
      y[i] = fmaf(ts[i], x[i], y[i]);
      x[i] = fmaf(-tt[i], y[i], x[i]);
    }
  };
  auto load_d = [&](uint32_t ch) {
    return __ldg(reinterpret_cast<const unsigned short*>(maps.ssm_D) + ((ch & (DM - 1)) | (lane & rt_zero)));
  };
  uint32_t dn = load_d(first);
  uint32_t n = 0, prev = 0, ch = first, next = first + step;
#pragma unroll 1
  for (; ch < C_NONE; n++) {
    CT(0)
    float a1[2][32], a2[2][32], a4[32];
    const float dsk = c ? 0.f : __uint_as_float(dn << 16) * C_ALPHA;
    dn = load_d(next);
    uint32_t next2 = next + step < end ? next + step : C_NONE;
    mbar_wait(in_full + (n & 1) * 8, (n >> 1) & 1);
    if (pp) named_bar_sync(4 + wg, 256);
    CT(1)
    wgmma_fence();
#pragma unroll
    for (int ks = 0; ks < 8; ks++)
      wgmma_m64n64_rs_tb(a1[ks >> 2], f1[ks], DHI | (d0 + (n & 1) * 512 + (ks & 3) * 64), (ks & 3) != 0);
    wgmma_commit();
    issue5();
    wgmma_wait<1>();
    fence_regs(a1[0]);
    fence_regs(a1[1]);
    CT(2)
    rot(a1[0], a1[1]);
    dft32(a2[0], a1[0], a1[1]);
    rot(a1[0] + 16, a1[1] + 16);
    a1[0][16] += dsk;
    a1[0][18] += dsk;
    dft32(a2[1], a1[0] + 16, a1[1] + 16);
    CT(3)
    wgmma_wait<2>();
    finish(prev, n > 0);
    wgmma_wait<0>();
    fence_regs(a2[0]);
    fence_regs(a2[1]);
    CT(4)
    if (pp) named_bar_arrive(5 - wg, 256);
    float re[16], im[16];
#pragma unroll
    for (int i = 0; i < 16; i++) {
      re[i] = a2[0][i] * a2[1][i] - a2[0][16 + i] * a2[1][16 + i];
      im[i] = a2[0][i] * a2[1][16 + i] + a2[0][16 + i] * a2[1][i];
    }
    dft32(a4, im, re);
    if (dealt) {
      mbar_wait(bar + (n < 2 ? B_DEAL : B_DEAL2), 0);
      asm volatile("ld.shared.u32 %0, [%1];" : "=r"(next2) : "r"(bar + B_LIST + 4 * n + (n < 2 ? 0 : 8)));
    }
    wgmma_wait<0>();
    fence_regs(a4);
    CT(5)
    rot(a4, a4 + 16);
#pragma unroll
    for (int i = 0; i < 4; i++) {
      const float* x = a4 + 16 - 16 * (i >> 1) + 2 * (i & 1);
      sts128(va + C_V + w * 1024 + (i >> 1) * 4096 + (i & 1) * 512,
             make_uint4(pack_bf16(x[0], x[1]), pack_bf16(x[4], x[5]), pack_bf16(x[8], x[9]), pack_bf16(x[12], x[13])));
    }
    CT(6)
    fence_proxy_async();
    named_bar_sync(1 + wg, 128);
    fetch(next2, n);
    if (wtid == 96 && n > 0) note(bar, CNT_Y2 + ((prev & 112) == 112));
    prev = ch;
    ch = next;
    next = next2;
    CT(7)
  }
  wgmma_fence();
  issue5();
  wgmma_wait<0>();
  finish(prev, (dn | ~rt_zero) != 0);
  named_bar_sync(1 + wg, 128);
  if (wtid == 96 && wg) { TD(8) }
  if (wtid == 96) cnt_signal_release(CNT_Y2 + ((prev & 112) == 112), 1);
  if (wtid == 64) note(bar, CNT_DONE);
  if (wtid == 96 && wg) { TD(9) }
}

__device__ __forceinline__ void attn_producer(const Maps& maps, uint32_t sbase, bool after_qkv, bool to_out,
                                              bool dry) {
  const uint32_t bar = sbase + BAR_OFF;
  const uint32_t q_full = bar + B_QFULL, q_empty = bar + B_QEMPTY;
  const uint32_t k_full = bar + B_KFULL, k_empty = bar + B_KEMPTY, v_full = bar + B_VFULL, v_empty = bar + B_VEMPTY;
  int ndrained = after_qkv ? 0 : G_STAGES;
  auto wait = [&](uint32_t b, uint32_t par) {
    if (!dry) mbar_wait_sleep(b, par);
  };
  auto drained = [&](int upto) {
#pragma unroll 1
    for (; ndrained <= upto; ndrained++) wait(bar + B_GEMPTY + 8 * ndrained, 1);
  };
  uint32_t st = 0, ph = 1, vs = 0, vp = 1;
  int pend_j = -1, pend_h = 0;
  int round = -1, m = -1, h = 0;
  bool last = false;
#pragma unroll 1
  for (;; round++) {
    uint32_t nitem = 0;
    const int tpost = m >= 3 ? m - 1 : m;
#pragma unroll 1
    for (int t = m < 0 ? -1 : 0; t <= m; t++) {
      const int j = (t < m && (h & 2)) ? m - 1 - t : t;
      if (t >= 0) {
        drained(1 + st);
        wait(k_empty + 8 * st, ph);
        if (!dry) {
          mbar_expect_tx(k_full + 8 * st, A_TILE);
          tma_load_3d(sbase + A_K_OFF + st * A_TILE, &maps.k, k_full + 8 * st, 0, j * 128, h * 2);
        }
        if (++st == 2) { st = 0; ph ^= 1; }
      }
      if (pend_j >= 0) {
        drained(3);
        if ((pend_h & 2) && after_qkv) wait(bar + seen_bar(0), 0);
        wait(v_empty + 8 * vs, vp);
        if (!dry) {
          mbar_expect_tx(v_full + 8 * vs, A_TILE);
          tma_load_3d(sbase + A_V_OFF + vs * A_TILE, &maps.v, v_full + 8 * vs, 0, pend_j * 128, pend_h * 2);
        }
        if (++vs == 2) { vs = 0; vp ^= 1; }
      }
      pend_j = j;
      pend_h = h;
      if (t == tpost && !last) {
        nitem = dry ? 1 : item_of(maps, round + 1);
        if (round == (dry ? 0 : 3) || blockIdx.x >= 128) {
          nitem = A_ITEMS;
          if (!to_out) cnt_wait(CNT_PREP, dry ? 0 : 260);
          if (to_out) {
            wait(bar + seen_bar(1), 0);
            asm volatile("cp.async.bulk.prefetch.L2.global [%0], 4096;" ::"l"(maps.ssm_k + (size_t)conv_first(maps) * S_LEN));
            if (!dry)
              asm volatile("cp.async.bulk.prefetch.L2.global [%0], 4096;" ::"l"(g_kvT + (size_t)conv_first(maps) * S_LEN));
          }
        }
        const uint32_t qs = (round + 1) & 1;
        wait(q_empty + 8 * qs, (((round + 1) >> 1) & 1) ^ 1);
        if (round == 1 && after_qkv) wait(bar + B_QDONE, 0);
        if (round < 0 && after_qkv) {
          if (!dry) { TD(2) }
          cnt_wait(CNT_KV, dry ? 0 : 768);
          if (!dry) { TD(3) }
        }
        if (nitem >= A_ITEMS || (round < 0 && after_qkv && !dry)) {
          if (!dry) mbar_arrive(q_full + 8 * qs);
        } else {
          drained(qs);
          if (!dry) {
            mbar_expect_tx(q_full + 8 * qs, A_TILE);
            tma_load_3d_hint(sbase + A_Q_OFF + qs * A_TILE, &maps.q, q_full + 8 * qs, 0, item_m(nitem) * 128,
                             item_h(nitem) * 2, policy_evict_first());
          }
        }
      }
    }
    if (last) break;
    last = nitem >= A_ITEMS;
    m = last ? -1 : item_m(nitem);
    h = item_h(nitem);
  }
}

__device__ __forceinline__ void put_o(uint32_t sbase, int wg, int warp, int lane, const float (&o)[64], float i0, float i1) {
  const int st_row = warp * 16 + (lane & 7) + ((lane >> 3) & 1) * 8;
  const uint32_t so = sbase + A_O_OFF + wg * 16384 + st_row * 128;
#pragma unroll
  for (int j = 0; j < 16; j += 2)
    stmatrix_x4(so + (j >> 3) * 8192 + ((((j & 7) + (lane >> 4)) ^ (lane & 7)) << 4),
                pack_bf16(o[4 * j] * i0, o[4 * j + 1] * i0), pack_bf16(o[4 * j + 2] * i1, o[4 * j + 3] * i1),
                pack_bf16(o[4 * j + 4] * i0, o[4 * j + 5] * i0), pack_bf16(o[4 * j + 6] * i1, o[4 * j + 7] * i1));
}
__device__ __forceinline__ uint32_t attn_consumer(const Maps& maps, const uint32_t sbase, const int wg,
                                                  const uint32_t rt_zero, uint32_t sn, float (&rest)[64],
                                                  bool after_qkv, float (&o)[64], float (&s)[64], float& pi0, float& pi1) {
  PHASE_GIVEN
  const uint32_t q_full = bar + B_QFULL, q_empty = bar + B_QEMPTY;
  const uint32_t k_full = bar + B_KFULL, k_empty = bar + B_KEMPTY, v_full = bar + B_VFULL;
  uint32_t p[32];
  float e[32];
  uint32_t dep = 0;
  constexpr int MIDJ = 5;
  float l0 = 0.f, l1 = 0.f, b0 = 0.f, b1 = 0.f;
  const int sched_own = 4 + wg, sched_other = 5 - wg;

  const int hf = wg ^ 1;
  const uint32_t qd0 = (uint32_t)make_desc(sbase + A_Q_OFF + hf * 8192, 16, 0, 0);
  const uint32_t kd0 = (uint32_t)make_desc(sbase + A_K_OFF, 16, 0, 0);
  const uint32_t vd0 = (uint32_t)make_desc(sbase + A_V_OFF, 16384, 0, 0);
  constexpr uint64_t DHI = DESC_SW128 | ((uint64_t)(1024 >> 4) << 32);
  constexpr uint32_t DST = A_TILE >> 4;
  auto issue_qk = [&](uint32_t qd, uint32_t kd) {
#pragma unroll
    for (int kk = 0; kk < 8; kk++) {
      const uint32_t off = ((kk >> 2) * 16384 + (kk & 3) * 32) >> 4;
      wgmma_m64n128_ss(s, DHI | (qd + off), DHI | (kd + off), kk != 0);
    }
    wgmma_commit();
  };
  auto issue_pv = [&](uint32_t vd, bool accumulate, int nk) {
#pragma unroll
    for (int kk = 0; kk < 8; kk++) {
      if (kk < nk)
        wgmma_m64n128_rs_tb(o, p[4 * kk], p[4 * kk + 1], p[4 * kk + 2], p[4 * kk + 3], DHI | (vd + kk * 128),
                            accumulate || (kk != 0));
    }
    wgmma_commit();
  };
  auto exp_lo = [&](float& a0, float& a1) {
#pragma unroll
    for (int j = 0; j < 8; j++) {
      e[4 * j] = ex2(s[4 * j]);
      e[4 * j + 1] = ex2(s[4 * j + 1]);
      e[4 * j + 2] = ex2(s[4 * j + 2]);
      e[4 * j + 3] = ex2(s[4 * j + 3]);
      a0 += e[4 * j];
      a0 += e[4 * j + 1];
      a1 += e[4 * j + 2];
      a1 += e[4 * j + 3];
      if (j == MIDJ) dep = (__float_as_uint(a0) | __float_as_uint(a1)) & rt_zero;
    }
  };
  auto pack_lo = [&]() {
#pragma unroll
    for (int j = 0; j < 16; j++) p[j] = pack_bf16(e[2 * j], e[2 * j + 1]);
  };
  auto finish_p = [&](float& a0, float& a1) {
    pack_lo();
#pragma unroll
    for (int j = 8; j < 16; j++) {
      const float e0 = ex2(s[4 * j]), e1 = ex2(s[4 * j + 1]), e2 = ex2(s[4 * j + 2]), e3 = ex2(s[4 * j + 3]);
      a0 += e0;
      a0 += e1;
      a1 += e2;
      a1 += e3;
      p[2 * j] = pack_bf16(e0, e1);
      p[2 * j + 1] = pack_bf16(e2, e3);
      if (j == 8 + MIDJ) dep = __float_as_uint(a0) & rt_zero;
    }
  };
  auto quad_sum = [&](float t) {
    t += __shfl_xor_sync(0xffffffffu, t, 1);
    return t + __shfl_xor_sync(0xffffffffu, t, 2);
  };
  auto write_o = [&](float i0, float i1) {
    st_wait(bar, wg, sn - 1);
    put_o(sbase, wg, warp, lane, o, i0, i1);
  };
  auto store_o = [&](uint32_t r, int kind, uint32_t lazy) {
    const uint32_t it = item_at(maps, kind == ST_BOX2Q ? 1 : head_of(maps, r));
    st_cmd(bar, wg, wtid, sn, kind, (INPLACE & 1) || kind != ST_BOX2Q ? &maps.o : &maps.c[0], sbase + A_O_OFF + wg * 16384, item_h(it) * 128,
            item_m(it) * 128 + hf * 64, CNT_CTX + (r >> 1), lazy);
    if (kind != ST_BOX2L) st_go(bar, wg, wtid, sn);
    sn++;
  };
  auto mask_half = [&](float* sh) {
    const int u = warp * 16 + (lane >> 2) - (lane & 3) * 2;
#pragma unroll
    for (int j = 0; j < 8; j++) {
      if (8 * j > u) sh[4 * j] = -INFINITY;
      if (8 * j + 1 > u) sh[4 * j + 1] = -INFINITY;
      if (8 * j - 8 > u) sh[4 * j + 2] = -INFINITY;
      if (8 * j - 7 > u) sh[4 * j + 3] = -INFINITY;
    }
  };
  ST(0)
  mbar_wait(q_full, 0);
  if (blockIdx.x >= 128) {
    return sn;
  }
  mbar_wait(k_full, 0);
  named_bar_sync(sched_own, 256);
  wgmma_fence();
  issue_qk(qd0, kd0);
  named_bar_arrive(sched_other, 256);
  fence_regs(rest);
#pragma unroll
  for (int i = 0; i < 64; i++) o[i] = rest[i] * Q_SCALE;
  fence_regs(o);
  wgmma_wait<0>();
  fence_regs(s);
  mbar_arrive_if(k_empty, wtid == 32);
  uint32_t g = 0;
  uint32_t rnd = 0;
  int rem = item_m(item_of(maps, 0));
  uint32_t first = 1;
  uint32_t fl = 0;
#define redo (fl & 1)
#define shifted (fl & 2)
  float d0 = 0.f, d1 = 0.f;
  pi0 = pi1 = 1.f;
  ST(1)
  for (;;) {
    if (shifted) {
#pragma unroll
      for (int j = 0; j < 16; j++) {
        s[4 * j] -= d0;
        s[4 * j + 1] -= d0;
        s[4 * j + 2] -= d1;
        s[4 * j + 3] -= d1;
      }
    }
    if (rem == 0 && !redo) {
      mbar_arrive_if(q_empty + 8 * (rnd & 1), wtid == 96);
      rnd++;
      if (hf == 0) mask_half(s);
      else mask_half(s + 32);
    }
    for (;;) {
      const bool kill = rem == 0 && hf == 0;
      const uint32_t kd = kd0 + ((g + 1) & 1) * DST, vd = vd0 + (g & 1) * DST;
      float a0 = 0.f, a1 = 0.f;
      exp_lo(a0, a1);
      fence_regs(e);
      const uint32_t kb = k_full + 8 * ((g + 1) & 1);
      const uint32_t kpar = (((g + 1) >> 1) & 1) ^ (g == A_STEPS - 1 ? 1u : 0u);
      const uint32_t qb = q_full + 8 * (rnd & 1), qpar = ((rnd >> 1) & 1) | dep;
      if (!mbar_try(qb, qpar)) mbar_wait(qb, qpar | ((__float_as_uint(a0) | __float_as_uint(a1)) & rt_zero));
      wgmma_wait<0>();
      fence_regs(o);
      if (kill) {
        mbar_arrive_if(kb + (B_VEMPTY - B_KFULL), wtid == 64 && !redo && g > 0);
        fence_regs(e);
        pack_lo();
#pragma unroll
        for (int j = 16; j < 32; j++) asm volatile("" : "=r"(p[j]));
        goto check;
      }
#pragma unroll
      for (int i = 32; i < 64; i++) asm volatile("" : "+f"(s[i])::"memory");
      mbar_arrive_if(kb + (B_VEMPTY - B_KFULL), wtid == 64 && !redo && g > 0);
      finish_p(a0, a1);
      if (__any_sync(0xffffffffu, !(mbar_try(v_full + 8 * (g & 1), ((g >> 1) & 1) | dep) &
                                    mbar_try(kb, kpar | dep)) ||
                                      !(a0 + a1 < 1.0995116e12f) || !(fminf(a0, a1) > (first ? 9.094947e-13f : -1.f)))) {
      check:
        bool bad = !(a0 + a1 < 1.0995116e12f);
        if (first) bad |= !(fminf(quad_sum(a0), quad_sum(a1)) > 9.094947e-13f);
        if (!redo && __any_sync(0xffffffffu, bad)) {
          d0 = d1 = first ? -INFINITY : 0.f;
#pragma unroll
          for (int j = 0; j < 16; j++) {
            if (j < 8 || !kill) {
              d0 = fmaxf(d0, fmaxf(s[4 * j], s[4 * j + 1]));
              d1 = fmaxf(d1, fmaxf(s[4 * j + 2], s[4 * j + 3]));
            }
          }
#pragma unroll
          for (int x = 1; x <= 2; x++) {
            d0 = fmaxf(d0, __shfl_xor_sync(0xffffffffu, d0, x));
            d1 = fmaxf(d1, __shfl_xor_sync(0xffffffffu, d1, x));
          }
          b0 += d0;
          b1 += d1;
          if (!first) {
            const float al0 = ex2(-d0), al1 = ex2(-d1);
            l0 *= al0;
            l1 *= al1;
#pragma unroll
            for (int j = 0; j < 16; j++) {
              o[4 * j] *= al0;
              o[4 * j + 1] *= al0;
              o[4 * j + 2] *= al1;
              o[4 * j + 3] *= al1;
            }
          }
          fl = 3;
          break;
        }
        mbar_wait(v_full + 8 * (g & 1), (g >> 1) & 1);
        mbar_wait(kb, kpar);
      }
      named_bar_sync(sched_own, 256);
      if (g == A_STEPS - 1) {
        fence_regs(o);
        if (hf == 0) {
          wgmma_fence();
          issue_pv(vd, 1, 4);
        } else {
          wgmma_fence();
          issue_pv(vd, 1, 8);
        }
        named_bar_arrive(sched_other, 256);
        pi0 = rcp(quad_sum(l0 + a0));
        pi1 = rcp(quad_sum(l1 + a1));
        goto done;
      }
      wgmma_fence();
      issue_qk(qd0 + (rnd & 1) * DST, kd);
      if (first) write_o(pi0, pi1);
      fence_regs(o);
      if (kill) {
        wgmma_fence();
        issue_pv(vd, !first, 4);
      } else {
        wgmma_fence();
        issue_pv(vd, !first, 8);
      }
      named_bar_arrive(sched_other, 256);
      fl &= 2;
      l0 += a0;
      l1 += a1;
      if (rem == 0 || first) {
        if (first && (g > 0 || after_qkv)) store_o(g ? rnd - (rem == 0 ? 2 : 1) : 2, g ? ST_BOX2 : ST_BOX2Q, rem);
        first = rem == 0;
        if (first) {
          pi0 = rcp(quad_sum(l0));
          pi1 = rcp(quad_sum(l1));
          l0 = l1 = b0 = b1 = 0.f;
          fl = 0;
          rem = item_m(item_of(maps, rnd)) + 1;
        }
      }
      rem--;
      g++;
      wgmma_wait<1>();
      fence_regs(s);
      mbar_arrive_if(kb + (B_KEMPTY - B_KFULL), wtid == 32);
      ST(g + 1)
      if (rem == 0 || shifted) {
        d0 = b0;
        d1 = b1;
        break;
      }
    }
  }
done:
#undef redo
#undef shifted
  st_wait(bar, wg, sn - 1);
  store_o(3, ST_BOX2L, 4);
  ST(35)
  return sn;
}

constexpr int O_STAGES = 5;
constexpr int O_STAGE_BYTES = 32768;
constexpr int O_Y_OFF = 5 * 32768;
constexpr int O_X_OFF = 6 * 32768;
constexpr int O_G_OFF = 7 * 32768;
constexpr int O_NK = HDIM / 64;

__device__ __forceinline__ uint32_t out_stage(uint32_t st) { return ((0x43120u >> (4 * st)) & 7) * O_STAGE_BYTES; }

__device__ __forceinline__ void out_producer(const Maps& maps, uint32_t sbase, bool after_attn, bool dry) {
  const uint32_t bar = sbase + BAR_OFF;
  const uint32_t rank = blockIdx.x & 1;
  const int m_tile = maps.id[blockIdx.x][2] & 15, n_tile = maps.id[blockIdx.x][2] >> 4;
  uint32_t stage = 0, phase = 0, xi = 0;
#pragma unroll 1
  for (int ki = 0; ki < (dry ? 1 : O_NK); ki++) {
    const int kt = (ki & 14) * 4 + ((A_ORDER >> ((ki >> 4) * 4)) & 3) * 2 + (ki & 1);
    const uint32_t fb = bar + B_OFULL + 8 * stage, eb = bar + B_OEMPTY + 8 * stage;
    const uint32_t sa = sbase + out_stage(stage);
    if (ki < O_STAGES) {
      constexpr uint32_t LASTB = B_KEMPTY | ((B_QEMPTY + 8) << 8) | ((B_KEMPTY + 8) << 16) | (B_VEMPTY << 24);
      if (ki > 0 && after_attn) mbar_wait_sleep(bar + ((LASTB >> (8 * ki - 8)) & 255), ki == 2);
      mbar_arrive_cluster_if(eb, 0, !dry);
      mbar_arrive_cluster_if(eb, 1, !dry);
    }
    if (ki == 32) mbar_wait_sleep(bar + seen_bar(2), 0);
    if (!dry) {
      mbar_wait_sleep(eb, phase);
      mbar_expect_tx(fb, O_STAGE_BYTES);
      tma_load_2d_mc(sa + 16384 + rank * 8192, &maps.ob, fb, n_tile * 128 + rank * 64, kt * 64, (uint16_t)3);
      tma_load_2d(sa, &maps.oa, fb, kt * 64, m_tile * 128);
    }
    if (++stage == O_STAGES) { stage = 0; phase ^= 1; }
    if ((ki & XMASK) == XMASK && ki >= XFIRST && xi < 8) {
      if (after_attn && xi < 2) mbar_wait_sleep(bar + B_OFREE + 8 * xi, 0);
      tma_load_3d(sbase + O_X_OFF + (xi & 1) * 16384 + (xi >> 1) * 4096, &maps.xs, bar + B_OY, 0,
                  m_tile * 128 + (xi & 1) * 64 + (xi >> 1) * 16, n_tile * 2);
      xi++;
    }
  }
  if (!dry) mbar_wait_sleep(bar + B_OY2, 0);
}

__device__ __forceinline__ void out_side(const Maps& maps, uint32_t smem0) {
  PHASE_PROLOGUE
  const int m_tile = maps.id[blockIdx.x][2] & 15, n_tile = maps.id[blockIdx.x][2] >> 4;
  const float* gp = g_gate + m_tile * 128 + warp * 16 + (lane >> 2);
  const float gv[4] = {__ldcg(gp), __ldcg(gp + 8), __ldcg(gp + 64), __ldcg(gp + 72)};
  const bool w0 = __shfl_sync(0xffffffffu, warp, 0) == 0;
  bool have = false;
  auto late = [&](uint32_t spins) {
    have = cnt_wait(CNT_Y2 + 1, 128, spins) || !spins;
    TD(11)
    if (have) {
      mbar_expect_tx(bar + B_OY2, 4096);
      tma_load_3d(sbase + O_Y_OFF + 7 * 4096, &maps.y, bar + B_OY2, 0, n_tile * 128 + 112, m_tile * 2);
    }
  };
  if (w0) {
    if (elect_one()) {
      mbar_expect_tx(bar + B_OY, 65536 - 4096);
      TD(10)
      cnt_wait(CNT_Y2, DM - 128);
      TD(7)
#pragma unroll 1
      for (int i = 0; i < 7; i++) {
        tma_load_3d(sbase + O_Y_OFF + i * 4096, &maps.y, bar + B_OY, 0, n_tile * 128 + i * 16, m_tile * 2);
        __nanosleep(PACE);
      }
      late(1u << 18);
    }
  }
  mbar_wait_sleep(bar + B_OY, 0);
  if (wtid == 0) { TD(12) }
  const int mrow = (lane & 7) + ((lane >> 4) & 1) * 8;
  const int mchunk = warp * 2 + ((lane >> 3) & 1);
  const uint32_t xrow = sbase + O_X_OFF + warp * 4096 + (lane & 15) * 128;
  const uint32_t yrow = sbase + O_Y_OFF + mrow * 128 + ((mchunk ^ (lane & 7)) << 4);
  uint32_t y[7][4], x[7][4], om[4];
#pragma unroll
  for (int i = 0; i < 4; i++) om[i] = pack_bf16(1.0f - gv[i], 1.0f - gv[i]);
  sts128(sbase + O_G_OFF + wtid * 16, make_uint4(pack_bf16(gv[0], gv[0]), pack_bf16(gv[1], gv[1]), pack_bf16(gv[2], gv[2]),
                                                 pack_bf16(gv[3], gv[3])));
  auto xa = [&](int h, int i) { return xrow + h * 16384 + (i >> 2) * 2048 + ((((i & 3) * 2 + (lane >> 4)) ^ (lane & 7)) << 4); };
  auto load = [&](int r, int h, int i) {
    ldsm4t(y[r], yrow + h * 2048 + i * 4096);
    asm volatile("ldmatrix.sync.aligned.m8n8.x4.shared.b16 {%0, %1, %2, %3}, [%4];"
                 : "=r"(x[r][0]), "=r"(x[r][1]), "=r"(x[r][2]), "=r"(x[r][3])
                 : "r"(xa(h, i)));
  };
  auto store = [&](int r, int h, int i, uint32_t om0, uint32_t om1) {
    stmatrix_x4(xa(h, i), mul_bf2(om0, mul_bf2(x[r][0], y[r][0])), mul_bf2(om1, mul_bf2(x[r][1], y[r][1])),
                mul_bf2(om0, mul_bf2(x[r][2], y[r][2])), mul_bf2(om1, mul_bf2(x[r][3], y[r][3])));
  };
#pragma unroll 1
  for (int h = 0; h < 2; h++) {
#pragma unroll
    for (int i = 0; i < 7; i++) load(i, h, i);
#pragma unroll
    for (int i = 0; i < 7; i++) store(i, h, i, h ? om[2] : om[0], h ? om[3] : om[1]);
  }
  __syncwarp();
  mbar_arrive_if(bar + B_OE, lane == 0);
  if (w0 && !__any_sync(0xffffffffu, have)) {
    if (elect_one()) late(0);
  }
  mbar_wait_sleep(bar + B_OY2, 0);
  load(0, 0, 7);
  load(1, 1, 7);
  store(0, 0, 7, om[0], om[1]);
  store(1, 1, 7, om[2], om[3]);
  __syncwarp();
  mbar_arrive_if(bar + B_OY + 8, lane == 0);
  if (wtid == 0) { TD(13) }
}

__device__ __forceinline__ void out_gemm(const Maps& maps, const uint32_t sbase, uint32_t sn, bool post, float (&o)[64],
                                         float (&s)[64],                                          float i0, float i1) {
  PHASE_GIVEN
  auto acc = [&](int h) -> float (&)[64] { return h ? o : s; };
  constexpr uint64_t DHI = DESC_SW128 | ((uint64_t)(1024 >> 4) << 32);
  const uint32_t d0 = (uint32_t)make_desc(sbase, 0, 0, 0);
  auto mma0 = [&](int h) {
    wgmma_fence();
#pragma unroll
    for (int k = 0; k < 4; k++)
      wgmma_m64n128_ss_tb(acc(h), DHI | (d0 + 0x10000 + h * 512 + k * 2), DHI | (d0 + 0x2000400 + k * 128), k != 0);
    wgmma_commit();
  };
  mbar_wait(bar + B_OFULL, 0);
  mma0(0);
  wgmma_wait<1>();
  fence_regs(o);
  if (post) {
    named_bar_arrive(3, 256);
    put_o(sbase, 0, warp, lane, o, i0, i1);
  }
  mma0(1);
  if (post) st_go(bar, 0, wtid, sn - 1);
  const int m_tile = maps.id[blockIdx.x][2] & 15, n_tile = maps.id[blockIdx.x][2] >> 4;
  uint32_t stage = 1, phase = 0, prev_stage = 0;
  GT(gti++)
  const uint32_t xrow = sbase + O_X_OFF + warp * 4096 + (lane & 15) * 128;
  auto addr = [&](int i) {
    return xrow + (i >> 3) * 16384 + ((i >> 2) & 1) * 2048 + ((((i & 3) * 2 + (lane >> 4)) ^ (lane & 7)) << 4);
  };
  uint32_t b[16][4];
#pragma unroll
  for (int i = 0; i < 64; i++) asm volatile("" : "=r"(b[i >> 2][i & 3]));
  auto ld_b = [&](int q0, int q1) {
#pragma unroll
    for (int i = 0; i < 16; i++)
      if ((i & 7) != 7)
        asm volatile(
            "{\n.reg .pred p;\nsetp.ge.s32 p, %5, %6;\nsetp.le.and.s32 p, %5, %7, p;\n"
            "@p ldmatrix.sync.aligned.m8n8.x4.shared.b16 {%0, %1, %2, %3}, [%4];\n}\n"
            : "+r"(b[i][0]), "+r"(b[i][1]), "+r"(b[i][2]), "+r"(b[i][3])
            : "r"(addr(i)), "r"(i / 4), "r"(q0), "r"(q1)
            : "memory");
  };
  int nq = 0;
#pragma unroll 1
  for (int kt = 1; kt < O_NK - 2; kt++) {
    uint32_t da = (uint32_t)make_desc(sbase + out_stage(stage), 16, 0, 0);
    uint32_t db = (uint32_t)make_desc(sbase + out_stage(stage) + 16384, 8192, 0, 0);
    asm volatile("" : "+r"(da), "+r"(db));
    mbar_wait(bar + B_OFULL + 8 * stage, phase);
    GT(gti++)
#pragma unroll
    for (int kk = 0; kk < 4; kk++) {
      wgmma_wait<2>();
      if (kk == 2)
        mbar_arrive_cluster_if(bar + B_OEMPTY + 8 * prev_stage, wtid >> 6, (wtid & 63) == 32 && kt - 1 + O_STAGES < O_NK);
      wgmma_fence();
      wgmma_m64n128_ss_tb(acc(0), DHI | (da + kk * 2), DHI | (db + kk * 128), 1);
      wgmma_m64n128_ss_tb(acc(1), DHI | (da + 512 + kk * 2), DHI | (db + kk * 128), 1);
      wgmma_commit();
      if (kk == 0 && kt >= 52) {
        uint32_t ok;
        asm volatile("{\n.reg .pred p;\nmbarrier.test_wait.parity.shared::cta.b64 p, [%1], 0;\nselp.u32 %0, 1, 0, p;\n}\n"
                     : "=r"(ok)
                     : "r"(bar + B_OE)
                     : "memory");
        if (__all_sync(0xffffffffu, ok)) {
          ld_b(nq, nq);
          nq++;
        }
      }
    }
    prev_stage = stage;
    if (++stage == O_STAGES) { stage = 0; phase ^= 1; }
  }
  if (tid == 0) { TD(14) }
  constexpr int S0 = (O_NK - 2) % O_STAGES, P0 = ((O_NK - 2) / O_STAGES) & 1;
  auto mma = [&](int h, int k0, int k1) {
    wgmma_fence();
#pragma unroll
    for (int k = k0; k < k1; k++) {
      const uint32_t d = d0 + (out_stage(S0 + (k >> 2)) >> 4);
      wgmma_m64n128_ss_tb(acc(h), DHI | (d + 0x10000 + h * 512 + (k & 3) * 2), DHI | (d + 0x2000400 + (k & 3) * 128), 1);
    }
    wgmma_commit();
  };
#pragma unroll
  for (int p = 0; p < 2; p++) {
    mbar_wait(bar + B_OFULL + 8 * (S0 + p), P0);
    mma(0, 4 * p, 4 * p + 4);
  }
  mma(1, 0, 8);
  if (nq < 4) {
    mbar_wait(bar + B_OE, 0);
    ld_b(nq, 3);
  }
  const uint4 g4 = lds128(sbase + O_G_OFF + wtid * 16);
  const uint32_t gg[4] = {g4.x, g4.y, g4.z, g4.w};
  const int w4 = __shfl_sync(0xffffffffu, warp, 0);
#pragma unroll
  for (int i = 0; i < 16; i++) {
    const int h = i >> 3;
    if (i == 0) wgmma_wait<1>();
    if (i == 8) wgmma_wait<0>();
    if ((i & 7) == 0) fence_regs(acc(h));
    if (i == 8) {   }
    if (i == 7) {
      mbar_wait(bar + B_OY + 8, 0);
#pragma unroll
      for (int j = 7; j < 16; j += 8)
        asm volatile("ldmatrix.sync.aligned.m8n8.x4.shared.b16 {%0, %1, %2, %3}, [%4];"
                     : "=r"(b[j][0]), "=r"(b[j][1]), "=r"(b[j][2]), "=r"(b[j][3])
                     : "r"(addr(j))
                     : "memory");
    }
    const float* a = acc(h) + 8 * (i & 7);
    stmatrix_x4(addr(i), fma_bf2(gg[2 * h], pack_bf16(a[0], a[1]), b[i][0]), fma_bf2(gg[2 * h + 1], pack_bf16(a[2], a[3]), b[i][1]),
                fma_bf2(gg[2 * h], pack_bf16(a[4], a[5]), b[i][2]), fma_bf2(gg[2 * h + 1], pack_bf16(a[6], a[7]), b[i][3]));
    if ((i & 7) == 7) {
      fence_proxy_async();
      __syncwarp();
      if (elect_one()) {
        tma_store_3d(&maps.oc, sbase + O_X_OFF + (h * 4 + w4) * 4096, 0, m_tile * 128 + h * 64 + w4 * 16, n_tile * 2);
        if (h == 1) {
          tma_store_commit();
        }
      }
    }
  }
  GT(gti++)
}

__device__ __noinline__ void leave_kernel(int mask) {
  if (!(mask & 4)) return;
  if (atomicAdd(g_cnt + CNT_DONE * 32, 1u) == 2 * gridDim.x - 1) {
    for (int i = 0; i < CNT_N; i++) g_cnt[i * 32] = 0;
#pragma unroll 4
    for (int i = 0; i < 128; i++) g_slot[i] = 0;
  }
}

__device__ __noinline__ void side_jobs(const Maps& maps, uint32_t sbase) {
  const int w12 = __shfl_sync(0xffffffffu, threadIdx.x >> 5, 0);
  gate_rows(maps, sbase, (blockIdx.x - 128) * 12 + w12, w12, threadIdx.x & 31);
  fence_proxy_async();
  __syncthreads();
  if (threadIdx.x == 320) cnt_signal_release(CNT_PREP, 1);
}

__global__ void __launch_bounds__(384, 1)
    fused_kernel(int mask, const bf16* px, const bf16* pw, const __grid_constant__ Maps maps) {
  extern __shared__ __align__(1024) uint8_t smem_raw[];
  {
    const uint32_t t = threadIdx.x, l = t & 31, u = (blockIdx.x & 127) * 16 + (l >> 1);
    const uint32_t ow = (u >> 5) * HDIM + ((u >> 2) & 7) * 512 + 256 + (u & 3) * 64, ox = u * DM;
    const bf16* p = ((l & 1) ? pw : px) + ((l & 1) ? ow : ox);
    asm volatile("{\n.reg .pred p;\nsetp.ne.u32 p, %1, 0;\n@p prefetch.global.L2 [%0];\n}\n" ::"l"(p), "r"((uint32_t)(t < 32)));
  }
  {
    const uint32_t sbase = __shfl_sync(0xffffffffu, smem_u32(smem_raw), 0);
    const uint32_t bar = sbase + BAR_OFF;
    const int tid = threadIdx.x;
    const bool do_qkv = (mask & 1) && blockIdx.x < 128;
    TL(0, 0)
    if (__shfl_sync(0xffffffffu, tid >> 5, 0) == 1 && do_qkv) {
      if (elect_one()) {
        for (int i = 0; i < G_STAGES; i++) mbar_init(bar + B_GFULL + 8 * i, 1);
        fence_barrier_init();
        qkv_producer(maps, sbase, true);
      }
    }
    if (tid == 0) {
      for (int i = 0; i < G_STAGES; i++) {
        mbar_init(bar + B_GEMPTY + 8 * i, 2);
        mbar_init(bar + B_SFULL + 8 * i, 4);
        mbar_init(bar + B_SFREE + 8 * i, 1);
      }
      for (int i = 0; i < 2; i++) {
        mbar_init(bar + B_OFREE + 8 * i, 1);
        mbar_init(bar + B_QFULL + 8 * i, 1);
        mbar_init(bar + B_QEMPTY + 8 * i, 2);
        mbar_init(bar + B_KFULL + 8 * i, 1);
        mbar_init(bar + B_KEMPTY + 8 * i, 2);
        mbar_init(bar + B_VFULL + 8 * i, 1);
        mbar_init(bar + B_VEMPTY + 8 * i, 2);
      }
      for (int i = 0; i < O_STAGES; i++) {
        mbar_init(bar + B_OFULL + 8 * i, 1);
        mbar_init(bar + B_OEMPTY + 8 * i, 2);
      }
      mbar_init(bar + B_OY, 1);
      for (int i = 0; i < 3; i++) mbar_init(bar + seen_bar(i), 1);
      mbar_init(bar + B_OY2, 1);
      mbar_init(bar + B_DEAL, 1);
      mbar_init(bar + B_DEAL2, 1);
      mbar_init(bar + B_PAIR, 1);
      mbar_init(bar + B_OY + 8, 4);
      mbar_init(bar + B_OE, 4);
      mbar_init(bar + B_QDONE, 2);
      for (int i = 0; i < 8; i++) mbar_init(bar + B_CFULL + 8 * i, 1);
      for (int i = 0; i < CNT_N; i++) asm volatile("st.shared.u32 [%0], 0;" ::"r"(bar + B_PEND + 4 * i) : "memory");
      fence_barrier_init();
    }
    __syncthreads();
    asm volatile("barrier.cluster.arrive.relaxed.aligned;" ::: "memory");
    if ((mask & 1) && blockIdx.x >= 128) side_jobs(maps, sbase);
  }
  uint32_t smem0 = smem_u32(smem_raw);
  PHASE_PROLOGUE
  const bool do_qkv = (mask & 1) && blockIdx.x < 128, do_out = (mask & 4) && blockIdx.x < 128;
  TL(0, 1)

  if (wg != 2) {
    reg_alloc<232>();
    asm volatile("barrier.cluster.wait.acquire.aligned;" ::: "memory");
    if (wg == 1) named_bar_arrive(4, 256);
    uint32_t sn = 0;
    float rest[64], o[64], s[64];
    if (do_qkv) {
      sn = qkv_consumer(maps, sbase, wg, mask & 2, rest, rt_zero);
    } else {
      undef_regs(rest);
    }
    undef_regs(o);
    undef_regs(s);
    TL(0, 2) TL(1, 0) TL(1, 1)
    const bool direct = do_out && wg == 0;
    float i0 = 0.f, i1 = 0.f;
    if (mask & 2) sn = attn_consumer(maps, sbase, wg, rt_zero, sn, rest, mask & 1, o, s, i0, i1);
    TL(2, 0)
    bool side = false;
    if (!direct) {
      wgmma_wait<0>();
      fence_regs(o);
      if (mask & 2) {
        const bool fused = mask & 4, mainc = blockIdx.x < 128;
        if (mainc) {
          PHASE_GIVEN
          put_o(sbase, wg, warp, lane, o, i0, i1);
          st_go(bar, wg, wtid, sn - 1);
        }
        const uint32_t b2 = blockIdx.x * 2 + (threadIdx.x >> 7);
        const uint32_t first = __shfl_sync(0xffffffffu, !fused ? b2 : mainc ? conv_first(maps) : (b2 - 255) * 128 - C_SIDE, 0);
        conv_consumer(maps, smem_u32(smem_raw), first, !fused ? 264 : mainc ? 16 : 1,
                      !fused ? DM : mainc ? (first | 127) + 1 - C_SIDE : first + C_SIDE, fused && !mainc,
                      fused && mainc);
      }
      side = (mask & 4) && blockIdx.x < 128;
    } else {
      out_gemm(maps, sbase, sn, mask & 2, o, s, i0, i1);
    }
    TL(1, 2) TL(2, 1) TL(2, 2) TL(3, 0) TL(3, 1)
    if (side + rt_zero) out_side(maps, smem_u32(smem_raw));
    tma_store_wait_read<0>();
  } else {
    reg_dealloc<40>();
    asm volatile("barrier.cluster.wait.acquire.aligned;" ::: "memory");
    const int w = __shfl_sync(0xffffffffu, tid >> 5, 0) - 8;
    if (w < 2) {
      if (do_qkv) prep_agent(maps, sbase, w, lane);
      if (elect_one()) store_agent(bar, w, w && do_out ? conv_first(maps) + 48 : 0, blockIdx.x >= 128 || mask == 4 ? 0 : mask == 1 ? 24 : 99);
      TL2(3, 2)
    } else {
      if (elect_one()) {
        const bool dry = w == 2;
        if (do_qkv && !dry) qkv_producer(maps, sbase, false);
        if (mask & 2) attn_producer(maps, sbase, do_qkv, do_out, dry);
        if (do_out) out_producer(maps, sbase, mask & 2, dry);
        if (dry) { TD(5) }
      }
      __syncwarp();
      if (w == 2) publisher(bar, tid & 31, !(mask & 2) ? 2 : do_out ? 3 : 4, !do_out ? 3 : do_qkv ? 0 : 2, do_qkv ? 4 : 0);
      if ((tid & 31) == 0) leave_kernel(mask);
    }
  }
}

typedef CUresult (*PFN_tmapEncode)(CUtensorMap*, CUtensorMapDataType, cuuint32_t, void*, const cuuint64_t*,
                                   const cuuint64_t*, const cuuint32_t*, const cuuint32_t*, CUtensorMapInterleave,
                                   CUtensorMapSwizzle, CUtensorMapL2promotion, CUtensorMapFloatOOBfill);
static PFN_tmapEncode s_encode = nullptr;

static void make_map_2d(CUtensorMap* m, const void* ptr, int rows, int cols, int box_rows) {
  cuuint64_t dims[2] = {(cuuint64_t)cols, (cuuint64_t)rows};
  cuuint64_t strides[1] = {(cuuint64_t)cols * 2};
  cuuint32_t box[2] = {cols < 64 ? 32u : 64u, (cuuint32_t)box_rows};
  cuuint32_t es[2] = {1, 1};
  s_encode(m, CU_TENSOR_MAP_DATA_TYPE_BFLOAT16, 2, const_cast<void*>(ptr), dims, strides, box, es,
           CU_TENSOR_MAP_INTERLEAVE_NONE, cols < 64 ? CU_TENSOR_MAP_SWIZZLE_64B : CU_TENSOR_MAP_SWIZZLE_128B, CU_TENSOR_MAP_L2_PROMOTION_L2_256B,
           CU_TENSOR_MAP_FLOAT_OOB_FILL_NONE);
}
static void make_map_3d(CUtensorMap* m, const void* ptr, int rows, int cols, int box_rows, int box_chunks) {
  cuuint64_t dims[3] = {64, (cuuint64_t)rows, (cuuint64_t)(cols / 64)};
  cuuint64_t strides[2] = {(cuuint64_t)cols * 2, 128};
  cuuint32_t box[3] = {64, (cuuint32_t)box_rows, (cuuint32_t)box_chunks};
  cuuint32_t es[3] = {1, 1, 1};
  s_encode(m, CU_TENSOR_MAP_DATA_TYPE_BFLOAT16, 3, const_cast<void*>(ptr), dims, strides, box, es,
           CU_TENSOR_MAP_INTERLEAVE_NONE, CU_TENSOR_MAP_SWIZZLE_128B, CU_TENSOR_MAP_L2_PROMOTION_L2_256B,
           CU_TENSOR_MAP_FLOAT_OOB_FILL_NONE);
}

static cudaLaunchConfig_t fused_cfg(cudaLaunchAttribute* at) {
  cudaLaunchConfig_t cfg = {};
  cfg.gridDim = dim3(132);
  cfg.blockDim = dim3(384);
  cfg.dynamicSmemBytes = SMEM_BYTES;
  cfg.stream = cudaStreamPerThread;
  at[0].id = cudaLaunchAttributeClusterDimension;
  at[0].val.clusterDim.x = 2;
  at[0].val.clusterDim.y = 1;
  at[0].val.clusterDim.z = 1;
  cfg.attrs = at;
  cfg.numAttrs = 1;
  return cfg;
}

extern "C" void kernel_launch(void* const* d_in, const int* in_sizes, int n_in, void* d_out, int out_size) {
  const bf16* x = (const bf16*)d_in[0];
  const bf16* ckv = (const bf16*)d_in[1];
  const bf16* wq = (const bf16*)d_in[2];
  const bf16* wuk = (const bf16*)d_in[3];
  const bf16* wuv = (const bf16*)d_in[4];
  const bf16* wo = (const bf16*)d_in[5];
  const bf16* bk = (const bf16*)d_in[7];
  const bf16* bv = (const bf16*)d_in[8];
  const bf16* shift_k = (const bf16*)d_in[9];
  const bf16* ssm_k = (const bf16*)d_in[10];
  const bf16* ssm_D = (const bf16*)d_in[11];
  const bf16* gate_w = (const bf16*)d_in[12];
  bf16* out = (bf16*)d_out;

  static void *pq = nullptr, *pk = nullptr, *pv = nullptr, *pctx = nullptr, *pb = nullptr, *pu = nullptr;
  static int max_clusters = 0;
  if (!s_encode) {
    void* fn = nullptr;
    cudaDriverEntryPointQueryResult qres;
    cudaGetDriverEntryPoint("cuTensorMapEncodeTiled", &fn, cudaEnableDefault, &qres);
    s_encode = (PFN_tmapEncode)fn;
    cudaGetSymbolAddress(&pq, g_q);
    cudaGetSymbolAddress(&pk, g_k);
    cudaGetSymbolAddress(&pv, g_v);
    cudaGetSymbolAddress(&pctx, g_ctx);
    cudaGetSymbolAddress(&pb, g_y2T);
    cudaGetSymbolAddress(&pu, g_kvT);
    cudaFuncSetAttribute(fused_kernel, cudaFuncAttributeMaxDynamicSharedMemorySize, SMEM_BYTES);
    cudaLaunchAttribute at[1];
    cudaLaunchConfig_t cfg = fused_cfg(at);
    if (cudaOccupancyMaxActiveClusters(&max_clusters, fused_kernel, &cfg) != cudaSuccess) max_clusters = 0;
  }

  Maps all = {};
  make_map_2d(&all.a[0], x, S_LEN, DM, 128);
  make_map_2d(&all.a[1], ckv, S_LEN, DC, 128);
  make_map_3d(&all.b[0], wq, DM, HDIM, 64, 4);
  make_map_3d(&all.b[1], wuk, DC, HDIM, 64, 4);
  make_map_3d(&all.b[2], wuv, DC, HDIM, 64, 4);
  make_map_2d(&all.c[0], pq, S_LEN, HDIM, 64);
  make_map_2d(&all.c[1], pk, S_LEN, HDIM, 64);
  make_map_2d(&all.c[2], pv, S_LEN, HDIM, 64);
  make_map_3d(&all.q, pq, S_LEN, HDIM, 128, 2);
  make_map_3d(&all.k, pk, S_LEN, HDIM, 128, 2);
  make_map_3d(&all.v, pv, S_LEN, HDIM, 128, 2);
  make_map_2d(&all.o, pctx, S_LEN, HDIM, 64);
  all.ssm_k = ssm_k;
  all.ssm_D = ssm_D;
  make_map_2d(&all.oa, pctx, S_LEN, HDIM, 128);
  make_map_2d(&all.ob, wo, HDIM, DM, 64);
  make_map_3d(&all.oc, out, S_LEN, DM, 16, 2);
  make_map_3d(&all.y, pb, DM, S_LEN, 16, 2);
  make_map_3d(&all.xs, x, S_LEN, DM, 16, 2);
  make_map_2d(&all.cu, pu, DM * 64, 32, 64);
  make_map_2d(&all.ch, ssm_k, DM * 64, 32, 64);

  make_map_2d(&all.bk, bk, S_LEN, DM, 35);
  make_map_2d(&all.bv, bv, S_LEN, DM, 32);
  for (int b = 0; b < 128; b++) {
    const int c = b >> 1, r = b & 1;
    const int G = c < 4 ? 0 : c < 36 ? (c - 4) % 8 : 1 + (c - 36) % 7;
    const int i = c < 4 ? 4 + c : c < 36 ? (c - 4) / 8 : 4 + (c - 36) / 7;
    all.id[b][0] = r + 2 * (i & 1) + 4 * (G & 3) + 16 * (i >> 1) + 64 * (G >> 2);
    all.id[b][1] = r + 2 * i + 16 * G;
    all.id[b][2] = r + 2 * G + 16 * i;
    all.id[b][3] = r + 2 * i == 15 ? 0x78 : 0xd8;
  }
  all.shift_k = shift_k;
  all.x = x;
  all.gate_w = gate_w;
  cudaLaunchAttribute at[1];
  cudaLaunchConfig_t cfg = fused_cfg(at);
  if (max_clusters >= 66) {
    cudaLaunchKernelEx(&cfg, fused_kernel, 7, x, wq, all);
  } else {
    for (int m = 1; m <= 4; m <<= 1) cudaLaunchKernelEx(&cfg, fused_kernel, m, x, wq, all);
  }
}
```

```cpp
#include <cuda_runtime.h>
#include <cuda_bf16.h>
#include <cuda.h>
#include <stdint.h>

typedef __nv_bfloat16 bf16;
#define INPLACE 3

constexpr int S_LEN = 2048;
constexpr int DM = 1024;
constexpr int NH = 32;
constexpr int HD = 128;
constexpr int DC = 512;
constexpr int HDIM = NH * HD;

__device__ __align__(1024) bf16 g_q[S_LEN * HDIM];
__device__ __align__(1024) bf16 g_k[S_LEN * HDIM];
__device__ __align__(1024) bf16 g_v[S_LEN * HDIM];
#define g_ctx g_q
__device__ __align__(1024) bf16 g_kvT[DM * S_LEN];
#define g_y2T g_kvT
__device__ __align__(1024) float g_gate[S_LEN];
enum { CNT_KV = 0, CNT_PREP = CNT_KV + 2, CNT_CTX, CNT_Y2 = CNT_CTX + 2, CNT_DONE = CNT_Y2 + 2, CNT_RANK, CNT_N };
__device__ unsigned int g_cnt[CNT_N * 32];
__device__ unsigned long long g_slot[128];

#define TL(k, i)
#define TL2(k, i)
#define TD(i)
#define CT(i)
#define GT(i)
#define GA(i)
#define ST(i)

__device__ __forceinline__ uint32_t smem_u32(const void* p) { return (uint32_t)__cvta_generic_to_shared(p); }

__device__ __forceinline__ void mbar_init(uint32_t bar, uint32_t count) {
  asm volatile("mbarrier.init.shared::cta.b64 [%0], %1;" ::"r"(bar), "r"(count));
}
__device__ __forceinline__ void mbar_expect_tx(uint32_t bar, uint32_t bytes) {
  asm volatile("mbarrier.arrive.expect_tx.shared::cta.b64 _, [%0], %1;" ::"r"(bar), "r"(bytes) : "memory");
}
__device__ __forceinline__ void mbar_arrive(uint32_t bar) {
  asm volatile("mbarrier.arrive.shared::cta.b64 _, [%0];" ::"r"(bar) : "memory");
}
__device__ __forceinline__ void mbar_wait(uint32_t bar, uint32_t parity) {
  uint32_t done;
  uint32_t spins = 0;
  do {
    asm volatile(
        "{\n.reg .pred p;\n"
        "mbarrier.try_wait.parity.shared::cta.b64 p, [%1], %2;\n"
        "selp.u32 %0, 1, 0, p;\n}\n"
        : "=r"(done)
        : "r"(bar), "r"(parity)
        : "memory");
    if (++spins > (1u << 22)) break;
  } while (!done);
}
__device__ __forceinline__ bool mbar_try(uint32_t bar, uint32_t parity) {
  uint32_t done;
  asm volatile(
      "{\n.reg .pred p;\n"
      "mbarrier.try_wait.parity.shared::cta.b64 p, [%1], %2;\n"
      "selp.u32 %0, 1, 0, p;\n}\n"
      : "=r"(done)
      : "r"(bar), "r"(parity)
      : "memory");
  return done != 0;
}
__device__ __forceinline__ bool mbar_test(uint32_t bar, uint32_t parity) {
  uint32_t done;
  asm volatile(
      "{\n.reg .pred p;\n"
      "mbarrier.test_wait.parity.shared::cta.b64 p, [%1], %2;\n"
      "selp.u32 %0, 1, 0, p;\n}\n"
      : "=r"(done)
      : "r"(bar), "r"(parity)
      : "memory");
  return done != 0;
}
__device__ __forceinline__ bool elect_one() {
  uint32_t pred;
  asm volatile("{\n.reg .pred p;\nelect.sync _|p, 0xffffffff;\nselp.u32 %0, 1, 0, p;\n}\n" : "=r"(pred));
  return pred != 0;
}
__device__ __forceinline__ void mbar_arrive_if(uint32_t bar, bool pred) {
  asm volatile(
      "{\n.reg .pred p;\nsetp.ne.b32 p, %1, 0;\n"
      "@p mbarrier.arrive.shared::cta.b64 _, [%0];\n}\n" ::"r"(bar),
      "r"((uint32_t)pred)
      : "memory");
}
__device__ __forceinline__ void mbar_wait_sleep(uint32_t bar, uint32_t parity) {
  uint32_t done;
  uint32_t spins = 0;
  do {
    asm volatile(
        "{\n.reg .pred p;\n"
        "mbarrier.try_wait.parity.shared::cta.b64 p, [%1], %2, %3;\n"
        "selp.u32 %0, 1, 0, p;\n}\n"
        : "=r"(done)
        : "r"(bar), "r"(parity), "r"(20000u)
        : "memory");
    if (++spins > (1u << 16)) break;
  } while (!done);
}
__device__ __forceinline__ void fence_barrier_init() {
  asm volatile("fence.mbarrier_init.release.cluster;" ::: "memory");
}
__device__ __forceinline__ void fence_proxy_async() {
  asm volatile("fence.proxy.async.shared::cta;" ::: "memory");
}
__device__ __forceinline__ void named_bar_sync(int id, int nthreads) {
  asm volatile("bar.sync %0, %1;" ::"r"(id), "r"(nthreads) : "memory");
}
__device__ __forceinline__ void named_bar_arrive(int id, int nthreads) {
  asm volatile("bar.arrive %0, %1;" ::"r"(id), "r"(nthreads) : "memory");
}
__device__ __forceinline__ void tma_load_2d(uint32_t dst, const CUtensorMap* m, uint32_t bar, int c0, int c1) {
  asm volatile(
      "cp.async.bulk.tensor.2d.shared::cluster.global.mbarrier::complete_tx::bytes [%0], [%1, {%3, %4}], [%2];" ::"r"(dst),
      "l"(reinterpret_cast<uint64_t>(m)), "r"(bar), "r"(c0), "r"(c1)
      : "memory");
}
__device__ __forceinline__ void tma_load_3d(uint32_t dst, const CUtensorMap* m, uint32_t bar, int c0, int c1, int c2) {
  asm volatile(
      "cp.async.bulk.tensor.3d.shared::cluster.global.mbarrier::complete_tx::bytes [%0], [%1, {%3, %4, %5}], [%2];" ::"r"(dst),
      "l"(reinterpret_cast<uint64_t>(m)), "r"(bar), "r"(c0), "r"(c1), "r"(c2)
      : "memory");
}
__device__ __forceinline__ void tma_store_2d(const CUtensorMap* m, uint32_t src, int c0, int c1) {
  asm volatile("cp.async.bulk.tensor.2d.global.shared::cta.bulk_group [%0, {%2, %3}], [%1];" ::"l"(
                   reinterpret_cast<uint64_t>(m)),
               "r"(src), "r"(c0), "r"(c1)
               : "memory");
}
__device__ __forceinline__ void bulk_load(uint32_t dst, const void* src, uint32_t bytes, uint32_t bar) {
  asm volatile("cp.async.bulk.shared::cluster.global.mbarrier::complete_tx::bytes [%0], [%1], %2, [%3];" ::"r"(dst),
               "l"(src), "r"(bytes), "r"(bar)
               : "memory");
}
__device__ __forceinline__ void tma_load_2d_mc(uint32_t dst, const CUtensorMap* m, uint32_t bar, int c0, int c1,
                                               uint16_t mask) {
  asm volatile(
      "cp.async.bulk.tensor.2d.shared::cluster.global.mbarrier::complete_tx::bytes.multicast::cluster [%0], [%1, {%3, "
      "%4}], [%2], %5;" ::"r"(dst),
      "l"(reinterpret_cast<uint64_t>(m)), "r"(bar), "r"(c0), "r"(c1), "h"(mask)
      : "memory");
}
__device__ __forceinline__ void mbar_arrive_cluster_if(uint32_t bar, uint32_t cta, bool pred) {
  asm volatile(
      "{\n.reg .b32 ra;\n.reg .pred p;\nsetp.ne.b32 p, %2, 0;\n"
      "mapa.shared::cluster.u32 ra, %0, %1;\n"
      "@p mbarrier.arrive.shared::cluster.b64 _, [ra];\n}\n" ::"r"(bar),
      "r"(cta), "r"((uint32_t)pred)
      : "memory");
}
__device__ __forceinline__ uint64_t policy_evict_first() {
  uint64_t pol;
  asm volatile("createpolicy.fractional.L2::evict_first.b64 %0, 1.0;" : "=l"(pol));
  return pol;
}
__device__ __forceinline__ void tma_load_2d_hint(uint32_t dst, const CUtensorMap* m, uint32_t bar, int c0, int c1,
                                                 uint64_t pol) {
  asm volatile(
      "cp.async.bulk.tensor.2d.shared::cluster.global.mbarrier::complete_tx::bytes.L2::cache_hint [%0], [%1, {%3, %4}], "
      "[%2], %5;" ::"r"(dst),
      "l"(reinterpret_cast<uint64_t>(m)), "r"(bar), "r"(c0), "r"(c1), "l"(pol)
      : "memory");
}
__device__ __forceinline__ void tma_load_3d_hint(uint32_t dst, const CUtensorMap* m, uint32_t bar, int c0, int c1,
                                                 int c2, uint64_t pol) {
  asm volatile(
      "cp.async.bulk.tensor.3d.shared::cluster.global.mbarrier::complete_tx::bytes.L2::cache_hint [%0], [%1, {%3, %4, "
      "%5}], [%2], %6;" ::"r"(dst),
      "l"(reinterpret_cast<uint64_t>(m)), "r"(bar), "r"(c0), "r"(c1), "r"(c2), "l"(pol)
      : "memory");
}
__device__ __forceinline__ void bulk_load_hint(uint32_t dst, const void* src, uint32_t bytes, uint32_t bar, uint64_t pol) {
  asm volatile(
      "cp.async.bulk.shared::cluster.global.mbarrier::complete_tx::bytes.L2::cache_hint [%0], [%1], %2, [%3], %4;" ::"r"(dst),
      "l"(src), "r"(bytes), "r"(bar), "l"(pol)
      : "memory");
}
__device__ __forceinline__ void cnt_signal_release(int which, uint32_t n) {
  asm volatile("red.release.gpu.global.add.u32 [%0], %1;" ::"l"(g_cnt + which * 32), "r"(n) : "memory");
}
__device__ __forceinline__ bool cnt_wait(int which, uint32_t target, uint32_t spins = 0) {
  uint32_t v;
  while (true) {
    asm volatile("ld.acquire.gpu.global.u32 %0, [%1];" : "=r"(v) : "l"(g_cnt + which * 32) : "memory");
    if (v >= target || ++spins > (1u << 18)) break;
    __nanosleep(64);
  }
  asm volatile("fence.proxy.async.global;" ::: "memory");
  return v >= target;
}
__device__ __forceinline__ void tma_store_3d(const CUtensorMap* m, uint32_t src, int c0, int c1, int c2) {
  asm volatile("cp.async.bulk.tensor.3d.global.shared::cta.bulk_group [%0, {%2, %3, %4}], [%1];" ::"l"(
                   reinterpret_cast<uint64_t>(m)),
               "r"(src), "r"(c0), "r"(c1), "r"(c2)
               : "memory");
}
__device__ __forceinline__ void tma_store_commit() { asm volatile("cp.async.bulk.commit_group;" ::: "memory"); }
template <int N>
__device__ __forceinline__ void tma_store_wait_read() {
  asm volatile("cp.async.bulk.wait_group.read %0;" ::"n"(N) : "memory");
}
template <int N>
__device__ __forceinline__ void tma_store_wait() {
  asm volatile("cp.async.bulk.wait_group %0;" ::"n"(N) : "memory");
}
__device__ __forceinline__ void wgmma_fence() { asm volatile("wgmma.fence.sync.aligned;" ::: "memory"); }
__device__ __forceinline__ void wgmma_commit() { asm volatile("wgmma.commit_group.sync.aligned;" ::: "memory"); }
template <int N>
__device__ __forceinline__ void wgmma_wait() {
  asm volatile("wgmma.wait_group.sync.aligned %0;" ::"n"(N) : "memory");
}
template <int R>
__device__ __forceinline__ void reg_alloc() { asm volatile("setmaxnreg.inc.sync.aligned.u32 %0;" ::"n"(R)); }
template <int R>
__device__ __forceinline__ void reg_dealloc() { asm volatile("setmaxnreg.dec.sync.aligned.u32 %0;" ::"n"(R)); }

__device__ __forceinline__ void stmatrix_x4(uint32_t addr, uint32_t r0, uint32_t r1, uint32_t r2, uint32_t r3) {
  asm volatile("stmatrix.sync.aligned.m8n8.x4.shared.b16 [%0], {%1, %2, %3, %4};" ::"r"(addr), "r"(r0), "r"(r1),
               "r"(r2), "r"(r3)
               : "memory");
}
__device__ __forceinline__ uint32_t pack_bf16(float lo, float hi) {
  uint32_t r;
  asm("cvt.rn.bf16x2.f32 %0, %1, %2;" : "=r"(r) : "f"(hi), "f"(lo));
  return r;
}
__device__ __forceinline__ float bf16_round(float x) { return __bfloat162float(__float2bfloat16_rn(x)); }
__device__ __forceinline__ float bf_lo(uint32_t v) { return __uint_as_float(v << 16); }
__device__ __forceinline__ float bf_hi(uint32_t v) { return __uint_as_float(v & 0xffff0000u); }
__device__ __forceinline__ uint4 lds128(uint32_t a) {
  uint4 v;
  asm volatile("ld.shared.v4.u32 {%0, %1, %2, %3}, [%4];" : "=r"(v.x), "=r"(v.y), "=r"(v.z), "=r"(v.w) : "r"(a));
  return v;
}
__device__ __forceinline__ void sts128(uint32_t a, uint4 v) {
  asm volatile("st.shared.v4.u32 [%0], {%1, %2, %3, %4};" ::"r"(a), "r"(v.x), "r"(v.y), "r"(v.z), "r"(v.w) : "memory");
}
__device__ __forceinline__ uint32_t mul_bf2(uint32_t a, uint32_t b) {
  uint32_t r;
  asm("mul.rn.bf16x2 %0, %1, %2;" : "=r"(r) : "r"(a), "r"(b));
  return r;
}
__device__ __forceinline__ float ex2(float x) {
  float y;
  asm("ex2.approx.ftz.f32 %0, %1;" : "=f"(y) : "f"(x));
  return y;
}
__device__ __forceinline__ float rcp(float x) {
  float y;
  asm("rcp.approx.ftz.f32 %0, %1;" : "=f"(y) : "f"(x));
  return y;
}
template <int N>
__device__ __forceinline__ void fence_regs(float (&r)[N]) {
#pragma unroll
  for (int i = 0; i < N; i++) asm volatile("" : "+f"(r[i])::"memory");
}

template <int N>
__device__ __forceinline__ void undef_regs(float (&r)[N]) {
#pragma unroll
  for (int i = 0; i < N; i++) asm volatile("" : "=f"(r[i]));
}
template <int N>
__device__ __forceinline__ void fence_regs_u(uint32_t (&r)[N]) {
#pragma unroll
  for (int i = 0; i < N; i++) asm volatile("" : "+r"(r[i])::"memory");
}

constexpr uint64_t DESC_SW128 = 1ull << 62;
__device__ __forceinline__ uint64_t make_desc(uint32_t addr, uint32_t lbo_bytes, uint32_t sbo_bytes, uint64_t swz) {
  return (uint64_t)((addr & 0x3FFFF) >> 4) | ((uint64_t)((lbo_bytes & 0x3FFFF) >> 4) << 16) |
         ((uint64_t)((sbo_bytes & 0x3FFFF) >> 4) << 32) | swz;
}

__device__ __forceinline__ uint64_t desc_add(uint64_t d, uint32_t off16) {
  return (d & 0xFFFFFFFF00000000ull) | (uint64_t)((uint32_t)d + off16);
}

__device__ __forceinline__ void wgmma_m64n256_ss_tb(float (&d)[128], uint64_t da, uint64_t db, int sd) {
  asm volatile(
    "{\n.reg .pred p;\nsetp.ne.b32 p, %130, 0;\n"
    "wgmma.mma_async.sync.aligned.m64n256k16.f32.bf16.bf16 "
    "{%0, %1, %2, %3, %4, %5, %6, %7, %8, %9, %10, %11, %12, %13, %14, %15, %16, %17, %18, %19, %20, %21, %22, %23, %24, %25, %26, %27, %28, %29, %30, %31, %32, %33, %34, %35, %36, %37, %38, %39, %40, %41, %42, %43, %44, %45, %46, %47, %48, %49, %50, %51, %52, %53, %54, %55, %56, %57, %58, %59, %60, %61, %62, %63, %64, %65, %66, %67, %68, %69, %70, %71, %72, %73, %74, %75, %76, %77, %78, %79, %80, %81, %82, %83, %84, %85, %86, %87, %88, %89, %90, %91, %92, %93, %94, %95, %96, %97, %98, %99, %100, %101, %102, %103, %104, %105, %106, %107, %108, %109, %110, %111, %112, %113, %114, %115, %116, %117, %118, %119, %120, %121, %122, %123, %124, %125, %126, %127}, %128, %129, p, 1, 1, 0, 1;\n}\n"
    : "+f"(d[0]), "+f"(d[1]), "+f"(d[2]), "+f"(d[3]), "+f"(d[4]), "+f"(d[5]), "+f"(d[6]), "+f"(d[7]), "+f"(d[8]), "+f"(d[9]), "+f"(d[10]), "+f"(d[11]), "+f"(d[12]), "+f"(d[13]), "+f"(d[14]), "+f"(d[15]), "+f"(d[16]), "+f"(d[17]), "+f"(d[18]), "+f"(d[19]), "+f"(d[20]), "+f"(d[21]), "+f"(d[22]), "+f"(d[23]), "+f"(d[24]), "+f"(d[25]), "+f"(d[26]), "+f"(d[27]), "+f"(d[28]), "+f"(d[29]), "+f"(d[30]), "+f"(d[31]), "+f"(d[32]), "+f"(d[33]), "+f"(d[34]), "+f"(d[35]), "+f"(d[36]), "+f"(d[37]), "+f"(d[38]), "+f"(d[39]), "+f"(d[40]), "+f"(d[41]), "+f"(d[42]), "+f"(d[43]), "+f"(d[44]), "+f"(d[45]), "+f"(d[46]), "+f"(d[47]), "+f"(d[48]), "+f"(d[49]), "+f"(d[50]), "+f"(d[51]), "+f"(d[52]), "+f"(d[53]), "+f"(d[54]), "+f"(d[55]), "+f"(d[56]), "+f"(d[57]), "+f"(d[58]), "+f"(d[59]), "+f"(d[60]), "+f"(d[61]), "+f"(d[62]), "+f"(d[63]), "+f"(d[64]), "+f"(d[65]), "+f"(d[66]), "+f"(d[67]), "+f"(d[68]), "+f"(d[69]), "+f"(d[70]), "+f"(d[71]), "+f"(d[72]), "+f"(d[73]), "+f"(d[74]), "+f"(d[75]), "+f"(d[76]), "+f"(d[77]), "+f"(d[78]), "+f"(d[79]), "+f"(d[80]), "+f"(d[81]), "+f"(d[82]), "+f"(d[83]), "+f"(d[84]), "+f"(d[85]), "+f"(d[86]), "+f"(d[87]), "+f"(d[88]), "+f"(d[89]), "+f"(d[90]), "+f"(d[91]), "+f"(d[92]), "+f"(d[93]), "+f"(d[94]), "+f"(d[95]), "+f"(d[96]), "+f"(d[97]), "+f"(d[98]), "+f"(d[99]), "+f"(d[100]), "+f"(d[101]), "+f"(d[102]), "+f"(d[103]), "+f"(d[104]), "+f"(d[105]), "+f"(d[106]), "+f"(d[107]), "+f"(d[108]), "+f"(d[109]), "+f"(d[110]), "+f"(d[111]), "+f"(d[112]), "+f"(d[113]), "+f"(d[114]), "+f"(d[115]), "+f"(d[116]), "+f"(d[117]), "+f"(d[118]), "+f"(d[119]), "+f"(d[120]), "+f"(d[121]), "+f"(d[122]), "+f"(d[123]), "+f"(d[124]), "+f"(d[125]), "+f"(d[126]), "+f"(d[127])
    : "l"(da), "l"(db), "r"(sd));
}

__device__ __forceinline__ void wgmma_m64n128_ss(float (&d)[64], uint64_t da, uint64_t db, int sd) {
  asm volatile(
    "{\n.reg .pred p;\nsetp.ne.b32 p, %66, 0;\n"
    "wgmma.mma_async.sync.aligned.m64n128k16.f32.bf16.bf16 "
    "{%0, %1, %2, %3, %4, %5, %6, %7, %8, %9, %10, %11, %12, %13, %14, %15, %16, %17, %18, %19, %20, %21, %22, %23, %24, %25, %26, %27, %28, %29, %30, %31, %32, %33, %34, %35, %36, %37, %38, %39, %40, %41, %42, %43, %44, %45, %46, %47, %48, %49, %50, %51, %52, %53, %54, %55, %56, %57, %58, %59, %60, %61, %62, %63}, %64, %65, p, 1, 1, 0, 0;\n}\n"
    : "+f"(d[0]), "+f"(d[1]), "+f"(d[2]), "+f"(d[3]), "+f"(d[4]), "+f"(d[5]), "+f"(d[6]), "+f"(d[7]), "+f"(d[8]), "+f"(d[9]), "+f"(d[10]), "+f"(d[11]), "+f"(d[12]), "+f"(d[13]), "+f"(d[14]), "+f"(d[15]), "+f"(d[16]), "+f"(d[17]), "+f"(d[18]), "+f"(d[19]), "+f"(d[20]), "+f"(d[21]), "+f"(d[22]), "+f"(d[23]), "+f"(d[24]), "+f"(d[25]), "+f"(d[26]), "+f"(d[27]), "+f"(d[28]), "+f"(d[29]), "+f"(d[30]), "+f"(d[31]), "+f"(d[32]), "+f"(d[33]), "+f"(d[34]), "+f"(d[35]), "+f"(d[36]), "+f"(d[37]), "+f"(d[38]), "+f"(d[39]), "+f"(d[40]), "+f"(d[41]), "+f"(d[42]), "+f"(d[43]), "+f"(d[44]), "+f"(d[45]), "+f"(d[46]), "+f"(d[47]), "+f"(d[48]), "+f"(d[49]), "+f"(d[50]), "+f"(d[51]), "+f"(d[52]), "+f"(d[53]), "+f"(d[54]), "+f"(d[55]), "+f"(d[56]), "+f"(d[57]), "+f"(d[58]), "+f"(d[59]), "+f"(d[60]), "+f"(d[61]), "+f"(d[62]), "+f"(d[63])
    : "l"(da), "l"(db), "r"(sd));
}

__device__ __forceinline__ void wgmma_m64n128_ss_tb(float (&d)[64], uint64_t da, uint64_t db, int sd) {
  asm volatile(
    "{\n.reg .pred p;\nsetp.ne.b32 p, %66, 0;\n"
    "wgmma.mma_async.sync.aligned.m64n128k16.f32.bf16.bf16 "
    "{%0, %1, %2, %3, %4, %5, %6, %7, %8, %9, %10, %11, %12, %13, %14, %15, %16, %17, %18, %19, %20, %21, %22, %23, %24, %25, %26, %27, %28, %29, %30, %31, %32, %33, %34, %35, %36, %37, %38, %39, %40, %41, %42, %43, %44, %45, %46, %47, %48, %49, %50, %51, %52, %53, %54, %55, %56, %57, %58, %59, %60, %61, %62, %63}, %64, %65, p, 1, 1, 0, 1;\n}\n"
    : "+f"(d[0]), "+f"(d[1]), "+f"(d[2]), "+f"(d[3]), "+f"(d[4]), "+f"(d[5]), "+f"(d[6]), "+f"(d[7]), "+f"(d[8]), "+f"(d[9]), "+f"(d[10]), "+f"(d[11]), "+f"(d[12]), "+f"(d[13]), "+f"(d[14]), "+f"(d[15]), "+f"(d[16]), "+f"(d[17]), "+f"(d[18]), "+f"(d[19]), "+f"(d[20]), "+f"(d[21]), "+f"(d[22]), "+f"(d[23]), "+f"(d[24]), "+f"(d[25]), "+f"(d[26]), "+f"(d[27]), "+f"(d[28]), "+f"(d[29]), "+f"(d[30]), "+f"(d[31]), "+f"(d[32]), "+f"(d[33]), "+f"(d[34]), "+f"(d[35]), "+f"(d[36]), "+f"(d[37]), "+f"(d[38]), "+f"(d[39]), "+f"(d[40]), "+f"(d[41]), "+f"(d[42]), "+f"(d[43]), "+f"(d[44]), "+f"(d[45]), "+f"(d[46]), "+f"(d[47]), "+f"(d[48]), "+f"(d[49]), "+f"(d[50]), "+f"(d[51]), "+f"(d[52]), "+f"(d[53]), "+f"(d[54]), "+f"(d[55]), "+f"(d[56]), "+f"(d[57]), "+f"(d[58]), "+f"(d[59]), "+f"(d[60]), "+f"(d[61]), "+f"(d[62]), "+f"(d[63])
    : "l"(da), "l"(db), "r"(sd));
}

template <int TB>
__device__ __forceinline__ void wgmma_m64n128_rs(float* d, uint32_t a0, uint32_t a1, uint32_t a2, uint32_t a3, uint64_t db, int sd) {
  asm volatile(
    "{\n.reg .pred p;\nsetp.ne.b32 p, %69, 0;\n"
    "wgmma.mma_async.sync.aligned.m64n128k16.f32.bf16.bf16 "
    "{%0, %1, %2, %3, %4, %5, %6, %7, %8, %9, %10, %11, %12, %13, %14, %15, %16, %17, %18, %19, %20, %21, %22, %23, %24, %25, %26, %27, %28, %29, %30, %31, %32, %33, %34, %35, %36, %37, %38, %39, %40, %41, %42, %43, %44, %45, %46, %47, %48, %49, %50, %51, %52, %53, %54, %55, %56, %57, %58, %59, %60, %61, %62, %63}, {%64, %65, %66, %67}, %68, p, 1, 1, %70;\n}\n"
    : "+f"(d[0]), "+f"(d[1]), "+f"(d[2]), "+f"(d[3]), "+f"(d[4]), "+f"(d[5]), "+f"(d[6]), "+f"(d[7]), "+f"(d[8]), "+f"(d[9]), "+f"(d[10]), "+f"(d[11]), "+f"(d[12]), "+f"(d[13]), "+f"(d[14]), "+f"(d[15]), "+f"(d[16]), "+f"(d[17]), "+f"(d[18]), "+f"(d[19]), "+f"(d[20]), "+f"(d[21]), "+f"(d[22]), "+f"(d[23]), "+f"(d[24]), "+f"(d[25]), "+f"(d[26]), "+f"(d[27]), "+f"(d[28]), "+f"(d[29]), "+f"(d[30]), "+f"(d[31]), "+f"(d[32]), "+f"(d[33]), "+f"(d[34]), "+f"(d[35]), "+f"(d[36]), "+f"(d[37]), "+f"(d[38]), "+f"(d[39]), "+f"(d[40]), "+f"(d[41]), "+f"(d[42]), "+f"(d[43]), "+f"(d[44]), "+f"(d[45]), "+f"(d[46]), "+f"(d[47]), "+f"(d[48]), "+f"(d[49]), "+f"(d[50]), "+f"(d[51]), "+f"(d[52]), "+f"(d[53]), "+f"(d[54]), "+f"(d[55]), "+f"(d[56]), "+f"(d[57]), "+f"(d[58]), "+f"(d[59]), "+f"(d[60]), "+f"(d[61]), "+f"(d[62]), "+f"(d[63])
    : "r"(a0), "r"(a1), "r"(a2), "r"(a3), "l"(db), "r"(sd), "n"(TB));
}

__device__ __forceinline__ void wgmma_m64n64_rs_tb(float (&d)[32], const uint32_t (&a)[4], uint64_t db, int sd) {
  asm volatile(
    "{\n.reg .pred p;\nsetp.ne.b32 p, %37, 0;\n"
    "wgmma.mma_async.sync.aligned.m64n64k16.f32.bf16.bf16 "
    "{%0, %1, %2, %3, %4, %5, %6, %7, %8, %9, %10, %11, %12, %13, %14, %15, %16, %17, %18, %19, %20, %21, %22, %23, %24, %25, %26, %27, %28, %29, %30, %31}, {%32, %33, %34, %35}, %36, p, 1, 1, 1;\n}\n"
    : "+f"(d[0]), "+f"(d[1]), "+f"(d[2]), "+f"(d[3]), "+f"(d[4]), "+f"(d[5]), "+f"(d[6]), "+f"(d[7]), "+f"(d[8]), "+f"(d[9]), "+f"(d[10]), "+f"(d[11]), "+f"(d[12]), "+f"(d[13]), "+f"(d[14]), "+f"(d[15]), "+f"(d[16]), "+f"(d[17]), "+f"(d[18]), "+f"(d[19]), "+f"(d[20]), "+f"(d[21]), "+f"(d[22]), "+f"(d[23]), "+f"(d[24]), "+f"(d[25]), "+f"(d[26]), "+f"(d[27]), "+f"(d[28]), "+f"(d[29]), "+f"(d[30]), "+f"(d[31])
    : "r"(a[0]), "r"(a[1]), "r"(a[2]), "r"(a[3]), "l"(db), "r"(sd));
}

__device__ __forceinline__ void wgmma_m64n32_rs_tb(float (&d)[16], const uint32_t (&a)[4], uint64_t db, int sd) {
  asm volatile(
    "{\n.reg .pred p;\nsetp.ne.b32 p, %21, 0;\n"
    "wgmma.mma_async.sync.aligned.m64n32k16.f32.bf16.bf16 "
    "{%0, %1, %2, %3, %4, %5, %6, %7, %8, %9, %10, %11, %12, %13, %14, %15}, {%16, %17, %18, %19}, %20, p, 1, 1, 1;\n}\n"
    : "+f"(d[0]), "+f"(d[1]), "+f"(d[2]), "+f"(d[3]), "+f"(d[4]), "+f"(d[5]), "+f"(d[6]), "+f"(d[7]), "+f"(d[8]), "+f"(d[9]), "+f"(d[10]), "+f"(d[11]), "+f"(d[12]), "+f"(d[13]), "+f"(d[14]), "+f"(d[15])
    : "r"(a[0]), "r"(a[1]), "r"(a[2]), "r"(a[3]), "l"(db), "r"(sd));
}

constexpr int G_STAGES = 4;
constexpr int G_A_BYTES = 128 * 64 * 2;
constexpr int G_B_BYTES = 256 * 64 * 2;
constexpr int G_STAGE_BYTES = G_A_BYTES + G_B_BYTES;
constexpr int G_STG_OFF = G_STAGES * G_STAGE_BYTES;
constexpr int BAR_OFF = G_STG_OFF + 32768 + 2048;
constexpr int SMEM_BYTES = BAR_OFF + 1024;
constexpr int B_GFULL = 0, B_GEMPTY = 32, B_SEEN = 64, B_PFULL = 224;
constexpr int B_KFULL = 80, B_KEMPTY = 96, B_VFULL = 112, B_VEMPTY = 128, B_QFULL = 144, B_QEMPTY = 160,
              B_QDONE = 184;
constexpr int B_CFULL = 192;
constexpr int B_OFREE = 256, B_OFULL = 272, B_OEMPTY = 320, B_OY = 368, B_OY2 = 384, B_OE = 768;
constexpr int B_DEAL = 312, B_DEAL2 = 360, B_LIST = 640, B_PAIR = 504;
constexpr int B_SFULL = 392, B_SFREE = 424, B_PEND = 456, B_SCMD = 512;

#define PHASE_PROLOGUE                                                                \
  uint32_t tid, rt_zero;                                                              \
  asm volatile("mov.u32 %0, %%tid.x;" : "=r"(tid));                                   \
  asm volatile("mov.u32 %0, %%nctaid.y;" : "=r"(rt_zero));                            \
  asm volatile("" : "+r"(smem0));                                                     \
  rt_zero = __shfl_sync(0xffffffffu, rt_zero >> 8, 0);   \
  const uint32_t sbase = __shfl_sync(0xffffffffu, smem0, 0);                          \
  const uint32_t bar = sbase + BAR_OFF;                                               \
  const int wg = __shfl_sync(0xffffffffu, tid >> 7, 0);                               \
  const int warp = (tid >> 5) & 3, lane = tid & 31, wtid = tid & 127;                 \
  (void)rt_zero; (void)bar; (void)warp; (void)lane; (void)wtid;

#define PHASE_GIVEN PHASE_GIVEN_(0)
#define PHASE_GIVEN_(z)                                                               \
  uint32_t tid;                                                                       \
  asm volatile("mov.u32 %0, %%tid.x;" : "=r"(tid));                                   \
  tid |= z;                               \
  const uint32_t bar = sbase + BAR_OFF;                                               \
  const int warp = (tid >> 5) & 3, lane = tid & 31, wtid = tid & 127;

enum { ST_BOX1, ST_BOX2, ST_BOX2Q, ST_BOX2L };
__device__ __forceinline__ void st_cmd(uint32_t bar, int wg, int wtid, uint32_t n, int kind, const void* dst,
                                       uint32_t src, int c0, int c1, int sig, uint32_t lazy = 0) {
  if (wtid == 0) {
    const uint32_t c = bar + B_SCMD + wg * 64 + (n & 1) * 32;
    const uint64_t d = reinterpret_cast<uint64_t>(dst);
    sts128(c, make_uint4(kind, src, c0, c1));
    sts128(c + 16, make_uint4((uint32_t)d, (uint32_t)(d >> 32), sig, lazy));
  }
}
__device__ __forceinline__ void st_go(uint32_t bar, int wg, int wtid, uint32_t n) {
  fence_proxy_async();
  __syncwarp();
  mbar_arrive_if(bar + B_SFULL + wg * 16 + (n & 1) * 8, (wtid & 31) == 0);
}
__device__ __forceinline__ void st_post(uint32_t bar, int wg, int wtid, uint32_t n, int kind, const void* dst,
                                        uint32_t src, int c0, int c1, int sig, uint32_t lazy = 0) {
  st_cmd(bar, wg, wtid, n, kind, dst, src, c0, c1, sig, lazy);
  st_go(bar, wg, wtid, n);
}
__device__ __forceinline__ void st_wait(uint32_t bar, int wg, uint32_t n) {
  const uint32_t b = bar + B_SFREE + wg * 16 + (n & 1) * 8;
  if (!mbar_try(b, ~(n >> 1) & 1)) mbar_wait(b, ~(n >> 1) & 1);
}
__device__ __forceinline__ void note(uint32_t bar, uint32_t cnt) {
  asm volatile("red.release.cta.shared.add.u32 [%0], 1;" ::"r"(bar + B_PEND + 4 * cnt) : "memory");
}
#define LEAD 2
#define HOLD 1
#define KS 1
#define LAZY_NS 250
#define DEAL_NS 400
#define DEAL_NS2 1250
constexpr uint32_t C_NONE = 0x10000;
__device__ __forceinline__ void deal(uint32_t bar, uint32_t r, uint32_t t, uint32_t own) {
  uint64_t p;
  uint32_t spins = 0;
  while (true) {
    asm volatile("ld.relaxed.gpu.global.u64 %0, [%1];" : "=l"(p) : "l"(g_slot + 127 - r) : "memory");
    if (p || ++spins > (1u << 18)) break;
    __nanosleep(100);
  }
  const uint32_t pc = (uint32_t)p;
  int dt = (uint32_t)(p >> 32) - t;
  if (r >= 64) {
    sts128(bar + B_LIST, make_uint4(-dt > DEAL_NS2 ? C_NONE : own - 16, -dt > DEAL_NS ? C_NONE : own, C_NONE, C_NONE));
    mbar_arrive(bar + B_DEAL);
    dt = 0;
  }
  sts128(bar + B_LIST + 16, make_uint4(dt > DEAL_NS ? pc : C_NONE, dt > DEAL_NS2 ? pc - 16 : C_NONE, C_NONE, C_NONE));
  mbar_arrive(bar + B_DEAL2);
}
__device__ __forceinline__ void store_agent(uint32_t bar, int wg, uint32_t last_ch, uint32_t n_end) {
  mbar_arrive(bar + B_SFREE + wg * 16);
  mbar_arrive(bar + B_SFREE + wg * 16 + 8);
  bool more = true;
  for (uint32_t n = 0; n < n_end && more; n++) {
    mbar_wait_sleep(bar + B_SFULL + wg * 16 + (n & 1) * 8, (n >> 1) & 1);
    const uint4 c = lds128(bar + B_SCMD + wg * 64 + (n & 1) * 32);
    const uint4 d = lds128(bar + B_SCMD + wg * 64 + (n & 1) * 32 + 16);
    uint32_t t;
    asm volatile("mov.u32 %0, %%globaltimer_lo;" : "=r"(t));
    uint32_t r = 0, tp = t;
    if (c.x == ST_BOX2L && last_ch) {
      mbar_expect_tx(bar + B_PAIR, 4);
      asm volatile(
          "{\n.reg .b32 ra;\nmapa.shared::cluster.u32 ra, %0, %1;\n"
          "st.async.weak.shared::cluster.mbarrier::complete_tx::bytes.u32 [ra + 224], %2, [ra];\n}\n" ::"r"(bar + B_PAIR),
          "r"(~blockIdx.x & 1), "r"(t)
          : "memory");
      mbar_wait_sleep(bar + B_PAIR, 0);
      r = atomicAdd(g_cnt + CNT_RANK * 32, 1u) & 127;
      asm volatile("ld.shared.u32 %0, [%1];" : "=r"(tp) : "r"(bar + B_PAIR + 224) : "memory");
      if ((int)(tp - t) < 0) tp = t;
      asm volatile("st.relaxed.gpu.global.u64 [%0], %1;" ::"l"(g_slot + r), "l"(((uint64_t)tp << 32) | last_ch) : "memory");
      if (r < 64) {
        sts128(bar + B_LIST, make_uint4(last_ch - 16, last_ch, C_NONE, C_NONE));
        mbar_arrive(bar + B_DEAL);
      } else {
        deal(bar, r, tp, last_ch);
      }
    }
    for (uint32_t t1 = t; d.w && t1 - t < (2 * d.w + wg) * LAZY_NS;) {
      __nanosleep(200);
      asm volatile("mov.u32 %0, %%globaltimer_lo;" : "=r"(t1));
    }
    const CUtensorMap* dst = reinterpret_cast<const CUtensorMap*>((uint64_t)d.x | ((uint64_t)d.y << 32));
    tma_store_2d(dst, c.y, c.z, c.w);
    if (c.x >= ST_BOX2) tma_store_2d(dst, c.y + 8192, c.z + 64, c.w);
    tma_store_commit();
    tma_store_wait_read<0>();
    mbar_arrive(bar + B_SFREE + wg * 16 + (n & 1) * 8);
    if (c.x == ST_BOX2L) mbar_arrive(bar + B_OFREE + 8 * wg);
    if ((int)d.z >= 0) {
      tma_store_wait<0>();
      if (d.z == 0) { TD(6) }
      asm volatile("fence.proxy.async.global;" ::: "memory");
      if (c.x == ST_BOX2Q) mbar_arrive(bar + B_QDONE);
      else note(bar, d.z);
      if (c.x == ST_BOX2L) {
        note(bar, CNT_DONE);
        more = false;
        if (last_ch && r < 64) deal(bar, r, tp, last_ch);
      }
    }
  }
  if (more) note(bar, CNT_DONE);
}

struct Maps {
  const bf16 *shift_k, *x, *gate_w, *ssm_k, *ssm_D;
  uint8_t id[128][4];
  CUtensorMap a[2];
  CUtensorMap b[3];
  CUtensorMap c[3];
  CUtensorMap bk, bv;
  CUtensorMap q, k, v, o;
  CUtensorMap oa, ob, oc;
  CUtensorMap y, xs;
  CUtensorMap cu, ch;
};

constexpr int P_SLOT = 67 * 128, P_V = 35 * 128, P_TAPS = 2 * P_SLOT;
__device__ __forceinline__ void ldsm4t(uint32_t (&r)[4], uint32_t a) {
  asm volatile("ldmatrix.sync.aligned.m8n8.x4.trans.shared.b16 {%0, %1, %2, %3}, [%4];"
               : "=r"(r[0]), "=r"(r[1]), "=r"(r[2]), "=r"(r[3])
               : "r"(a));
}
__device__ __forceinline__ uint32_t fma_bf2(uint32_t a, uint32_t b, uint32_t c) {
  uint32_t r;
  asm("fma.rn.bf16x2 %0, %1, %2, %3;" : "=r"(r) : "r"(a), "r"(b), "r"(c));
  return r;
}
__device__ __forceinline__ void prep_agent(const Maps& maps, uint32_t sbase, int w, int lane) {
  const uint32_t bar = sbase + BAR_OFF, pb = bar + B_PFULL + w * 16;
  const int d0 = (blockIdx.x >> 3) * 64, t0 = (blockIdx.x & 7) * 256 + w * 128;
  mbar_wait_sleep(bar + B_GFULL + 8 * (G_STAGES - 1), 0);
#pragma unroll 1
  for (int i = -1; i < 4; i++) {
    GA(82 + 2 * i)
    if (i >= 0) mbar_wait_sleep(pb + (i & 1) * 8, i >> 1);
    GA(83 + 2 * i)
    const uint32_t so = sbase + G_STG_OFF + w * (P_TAPS + 512) + (i & 1) * P_SLOT;
    if (i < 3 && elect_one()) {
      const uint32_t b = pb + (~i & 1) * 8, dst = so + (i & 1 ? -P_SLOT : P_SLOT);
      mbar_expect_tx(b, i < 0 ? P_SLOT + 512 : P_SLOT);
      const uint64_t pol = policy_evict_first();
      tma_load_2d_hint(dst, &maps.bk, b, d0, t0 + 32 * i + 29, pol);
      tma_load_2d_hint(dst + P_V, &maps.bv, b, d0, t0 + 32 * i + 32, pol);
      if (i < 0) bulk_load(sbase + G_STG_OFF + P_TAPS, maps.shift_k + d0 * 4, 512, b);
    }
    if (i < 0) continue;
    uint32_t ak[4];
#pragma unroll
    for (int r = 0; r < 4; r++) {
      const uint32_t a = so / 128 + r + 4 * (lane & 6) + (((lane >> 2) ^ lane) & 6) + (lane & 1);
      ak[r] = a * 128 + (a & 7) * 16;
    }
    bf16* dst = g_kvT + (size_t)(d0 + (lane >> 2)) * S_LEN + t0 + ((lane & 3) + 4 * i) * 8;
#pragma unroll 1
    for (int cg = 0; cg < 128; cg += 16) {
      uint32_t t01, t23, k[4][4], v[4];
      asm volatile("ld.shared.v2.u32 {%0, %1}, [%2];"
                   : "=r"(t01), "=r"(t23)
                   : "r"(sbase + G_STG_OFF + P_TAPS + cg * 4 + (lane >> 2) * 8));
#pragma unroll
      for (int r = 0; r < 4; r++) ldsm4t(k[r], ak[r] ^ cg);
      ldsm4t(v, (ak[3] ^ cg) + 4096);
      const uint32_t w0 = __byte_perm(t01, 0, 0x1010), w1 = __byte_perm(t01, 0, 0x3232);
      const uint32_t w2 = __byte_perm(t23, 0, 0x1010), w3 = __byte_perm(t23, 0, 0x3232);
#pragma unroll
      for (int j = 0; j < 4; j++)
        v[j] = mul_bf2(fma_bf2(k[3][j], w0, fma_bf2(k[2][j], w1, fma_bf2(k[1][j], w2, mul_bf2(k[0][j], w3)))), v[j]);
      const bool s1 = lane & 1, s2 = lane & 2;
      const uint32_t a0 = s1 ? v[1] : v[0], a1 = s1 ? v[0] : v[1], a2 = s1 ? v[3] : v[2], a3 = s1 ? v[2] : v[3];
      *reinterpret_cast<uint4*>(dst) = make_uint4(s2 ? a2 : a0, s2 ? a3 : a1, s2 ? a0 : a2, s2 ? a1 : a3);
      dst += 8 * S_LEN;
    }
    fence_proxy_async();
    __syncwarp();
  }
  GA(90)
  if (lane == 0) note(bar, CNT_PREP);
  __syncwarp();
  GA(91)
}

__device__ __forceinline__ void qkv_tile(const Maps& maps, int it, int& which, int& m_tile, int& n_tile) {
  const bool q = it == 0 || it >= 5;
  const int b = maps.id[blockIdx.x][it >= 5];
  which = q ? 0 : 2 - (it & 1);
  m_tile = b & 15;
  n_tile = (b >> 4) * 2 + ((0x19 >> it) & 1);
}

constexpr int G_NTILES = 6;
__device__ __forceinline__ uint32_t qkv_flip(int it) { return ((0x0b >> it) & 1) * 3; }
__device__ __forceinline__ void qkv_producer(const Maps& maps, uint32_t sbase, bool first) {
  const uint32_t bar = sbase + BAR_OFF;
  uint32_t stage = 0, phase = 0;
#pragma unroll 1
  for (int it = 0; it < (first ? 1 : G_NTILES); it++) {
    int which, m_tile, n_tile;
    qkv_tile(maps, it, which, m_tile, n_tile);
    const CUtensorMap* ma = &maps.a[which == 0 ? 0 : 1];
    const CUtensorMap* mb = &maps.b[which];
    const int nk = first ? G_STAGES : which == 0 ? 16 : 8;
#pragma unroll 1
    for (int kt = (it == 0 && !first) ? G_STAGES : 0; kt < nk; kt++) {
      if (!first) mbar_wait_sleep(bar + B_GEMPTY + 8 * stage, phase);
      const uint32_t fb = bar + B_GFULL + 8 * stage;
      const uint32_t sa = sbase + stage * G_STAGE_BYTES;
      const int k0 = (kt ^ ((0x14 >> it) & 1) * 7) * 64;
      const bool keep = ((0x1c >> it) & 1) && kt < G_STAGES;
      mbar_expect_tx(fb, keep ? G_B_BYTES : G_STAGE_BYTES);
      if (!keep) tma_load_2d(sbase + (stage ^ qkv_flip(it)) * G_STAGE_BYTES, ma, fb, k0, m_tile * 128);
      tma_load_3d(sa + G_A_BYTES, mb, fb, 0, k0, n_tile * 4);
      if (++stage == G_STAGES) { stage = 0; phase ^= 1; }
      {
        const int b = maps.id[blockIdx.x][1];
        if (it == 2 && kt == (b & 7)) {
          for (int i = 0; i < 2; i++)
            asm volatile("cp.async.bulk.prefetch.tensor.2d.L2.global.tile [%0, {%1, %2}];" ::"l"(&maps.a[0]),
                         "r"((b >> 4) * 128 + i * 64), "r"((b & 15) * 128)
                         : "memory");
          asm volatile("cp.async.bulk.prefetch.tensor.3d.L2.global.tile [%0, {%1, %2, %3}];" ::"l"(&maps.b[1 + ((b >> 3) & 1)]),
                       "r"(0), "r"((b & 7) * 64), "r"((b >> 4) * 8 + 4)
                       : "memory");
        }
        if (it == 3 && kt == (b & 7))
          asm volatile("cp.async.bulk.prefetch.tensor.3d.L2.global.tile [%0, {%1, %2, %3}];" ::"l"(&maps.b[0]), "r"(0),
                       "r"((b & 15) * 64), "r"((b >> 4) * 8)
                       : "memory");
      }
    }
  }
}

__device__ __forceinline__ uint32_t seen_bar(uint32_t item) { return B_SEEN + ((0x700800u >> (8 * item)) & 255); }
__device__ __noinline__ void publisher(uint32_t bar, int lane, uint32_t nsrc, uint32_t item, uint32_t mine) {
  uint32_t done = 0, tot = 0;
#pragma unroll 1
  for (uint32_t spins = 0; (done < nsrc || item < 3) && spins < (1u << 20); spins++) {
    const uint32_t cnt = item ? CNT_CTX - 1 + item : CNT_KV + 1;
    if (item < 3 && __shfl_sync(0xffffffffu, tot, cnt) >= mine >> !item) {
      uint32_t v;
      asm volatile("ld.acquire.gpu.global.u32 %0, [%1];" : "=r"(v) : "l"(g_cnt + (lane ? cnt : CNT_PREP) * 32) : "memory");
      if (__all_sync(0xffffffffu, v >= (lane ? 512 >> !item : 260))) {
        asm volatile("fence.proxy.async.global;" ::: "memory");
        mbar_arrive_if(bar + seen_bar(item), lane == 0);
        item++;
      }
    }
    uint32_t v = 0;
    if (lane < CNT_N)
      asm volatile("atom.acquire.cta.shared.exch.b32 %0, [%1], 0;" : "=r"(v) : "r"(bar + B_PEND + 4 * lane) : "memory");
    done += __shfl_sync(0xffffffffu, v, CNT_DONE);
    if (lane == CNT_DONE) v = 0;
    if (done == nsrc && lane < CNT_DONE) {
      uint32_t w;
      asm volatile("atom.acquire.cta.shared.exch.b32 %0, [%1], 0;" : "=r"(w) : "r"(bar + B_PEND + 4 * lane) : "memory");
      v += w;
    }
    if (v && lane == 0) { TD(0) }
    if (v) cnt_signal_release(lane, v);
    tot += v;
    if (v && lane == 0) { TD(1) }
    if (!__any_sync(0xffffffffu, v != 0)) __nanosleep(item == 1 ? 1000 : 200);
  }
  __threadfence();
  __syncwarp();
}

__device__ __forceinline__ void gate_rows(const Maps& maps, uint32_t sbase, int w48, int w12, int lane) {
  const uint32_t buf = sbase + w12 * 16384, gb = sbase + BAR_OFF + 768 + w12 * 16;
  if (lane == 0) {
    mbar_init(gb, 1);
    mbar_init(gb + 8, 1);
    fence_barrier_init();
    for (int i = 0; i < 2; i++) {
      mbar_expect_tx(gb + 8 * i, 8192);
      bulk_load(buf + i * 8192, maps.x + (size_t)(w48 + 48 * i) * 4 * DM, 8192, gb + 8 * i);
    }
  }
  __syncwarp();
  uint4 wv[4];
#pragma unroll
  for (int i = 0; i < 4; i++) wv[i] = __ldg(reinterpret_cast<const uint4*>(maps.gate_w + (i * 32 + lane) * 8));
  int it = 0;
#pragma unroll 1
  for (int row = w48 * 4; row < S_LEN; row += 48 * 4, it++) {
    mbar_wait(gb + 8 * (it & 1), (it >> 1) & 1);
    uint4 xv[4][4];
#pragma unroll
    for (int r = 0; r < 4; r++)
#pragma unroll
      for (int i = 0; i < 4; i++) xv[r][i] = lds128(buf + (it & 1) * 8192 + r * 2048 + (i * 32 + lane) * 16);
    float d[2][4];
#pragma unroll
    for (int pr = 0; pr < 2; pr++) {
      d[pr][0] = d[pr][1] = d[pr][2] = d[pr][3] = 0.f;
      auto acc = [&](uint32_t a0, uint32_t a2, uint32_t b0, uint32_t b2, uint32_t w0, uint32_t w2) {
        asm volatile(
            "mma.sync.aligned.m16n8k16.row.col.f32.bf16.bf16.f32 {%0, %1, %2, %3}, {%4, %5, %6, %7}, {%8, %8}, "
            "{%0, %1, %2, %3};"
            : "+f"(d[pr][0]), "+f"(d[pr][1]), "+f"(d[pr][2]), "+f"(d[pr][3])
            : "r"(mul_bf2(a0, w0)), "r"(mul_bf2(b0, w0)), "r"(mul_bf2(a2, w2)), "r"(mul_bf2(b2, w2)), "r"(0x3f803f80u));
      };
#pragma unroll
      for (int i = 0; i < 4; i++) {
        acc(xv[2 * pr][i].x, xv[2 * pr][i].y, xv[2 * pr + 1][i].x, xv[2 * pr + 1][i].y, wv[i].x, wv[i].y);
        acc(xv[2 * pr][i].z, xv[2 * pr][i].w, xv[2 * pr + 1][i].z, xv[2 * pr + 1][i].w, wv[i].z, wv[i].w);
      }
    }
    float sum = (lane & 2) ? ((lane & 1) ? d[1][2] : d[1][0]) : ((lane & 1) ? d[0][2] : d[0][0]);
#pragma unroll
    for (int off = 16; off >= 4; off >>= 1) sum += __shfl_xor_sync(0xffffffffu, sum, off);
    if (lane < 4) g_gate[row + lane] = bf16_round(rcp(1.0f + __expf(-bf16_round(sum))));
    if (lane == 0 && row + 2 * 48 * 4 < S_LEN) {
      mbar_expect_tx(gb + 8 * (it & 1), 8192);
      bulk_load(buf + (it & 1) * 8192, maps.x + (size_t)(row + 2 * 48 * 4) * DM, 8192, gb + 8 * (it & 1));
    }
  }
}

constexpr float Q_SCALE = 0.08838834764831845f * 1.4426950408889634f;
__device__ __forceinline__ uint32_t qkv_consumer(const Maps& maps, const uint32_t sbase, const int wg, bool fused,
                                                 uint32_t (&q)[32], float (&rest)[64], uint32_t rt_zero) {
  PHASE_GIVEN_(rt_zero)
  constexpr int NTILES = G_NTILES;
  float acc[128];
  const uint32_t stg = sbase + G_STG_OFF + wg * 18432;
  const int st_row = warp * 16 + (lane & 7) + ((lane >> 3) & 1) * 8;
  const int st_cb = lane >> 4;
  uint32_t pend[64];
  const CUtensorMap* pend_map = nullptr;
  int pend_c0 = 0, pend_c1 = 0;
  uint32_t sn = 0;
  uint32_t st_a[4];
#pragma unroll
  for (int jp = 0; jp < 4; jp++) {
    st_a[jp] = stg + st_row * 128 + (((jp * 2 + st_cb) ^ (st_row & 7)) << 4);
    asm volatile("" : "+r"(st_a[jp]));
  }
  auto put_box = [&](uint32_t off, const uint32_t* v) {
#pragma unroll
    for (int jp = 0; jp < 4; jp++) stmatrix_x4(st_a[jp] + off, v[jp * 4], v[jp * 4 + 1], v[jp * 4 + 2], v[jp * 4 + 3]);
  };
  GT(gti++)
  const int hf = wg ^ 1;
  const uint64_t da0 = make_desc(sbase + hf * 8192, 16, 1024, DESC_SW128);
  const uint64_t db0 = make_desc(sbase + G_A_BYTES, 8192, 1024, DESC_SW128);
  uint32_t g = 0, oa = 3 * (G_STAGE_BYTES / 16), ob = 0;
  bool go = false;
  mbar_wait(bar + B_GFULL, 0);
  uint32_t gend = 16, when = 0;
#pragma unroll 1
  for (int it = 0;; it++) {
    bool more = false;
#pragma unroll 1
    do {
      GT(gti++)
      wgmma_fence();
#pragma unroll
      for (int kk = 0; kk < 4; kk++)
        wgmma_m64n256_ss_tb(acc, desc_add(da0, oa + kk * 2), desc_add(db0, ob + kk * 128), kk || more);
      wgmma_commit();
      if (go) st_go(bar, wg, wtid, sn - 1);
      g++;
      if (g + wg * 64 == 62 + LEAD) named_bar_arrive(6, 256);
      const uint32_t full = (bar + B_GFULL) + 8 * (g & 3);
      const bool here = mbar_test(full, (g >> 2) & 1) || g >= 64;
      oa = ((g & 3) ^ ((0x17 >> (g >> 3)) & 1) * 3) * (G_STAGE_BYTES / 16);
      ob = (g & 3) * (G_STAGE_BYTES / 16);
      go = when & 1;
      when >>= 1;
      if (go) {
        const int c = sn & 3;
        st_wait(bar, wg, sn - 2);
        st_cmd(bar, wg, wtid, sn, ST_BOX1, pend_map, stg + (c & 1) * 8192, pend_c0 + c * 64, pend_c1,
               (c == 3 && it > 1) ? CNT_KV + (it > 4) : -1);
        switch (c) {
          case 0: put_box(0, pend); break;
          case 1: put_box(8192, pend + 16); break;
          case 2: put_box(0, pend + 32); break;
          default: put_box(8192, pend + 48); break;
        }
        sn++;
      }
      if (it < NTILES) {
        wgmma_wait<1>();
        mbar_arrive_if((bar + B_GEMPTY) + 8 * ((g + 2) & 3), wtid == 32 && more);
        if (wg && g == 62) named_bar_sync(6, 256);
        if (HOLD && g == 63 && wg && fused) named_bar_sync(7, 256);
        if (!here) mbar_wait(full, (g >> 2) & 1);
      }
      more = true;
    } while (g != gend);
    wgmma_wait<0>();
    fence_regs(acc);
    GT(gti++)
    mbar_arrive_if((bar + B_GEMPTY) + 8 * 3, wtid == 32);
    int which, m_tile, n_tile;
    qkv_tile(maps, it, which, m_tile, n_tile);
    if (it == NTILES - fused) break;
    if (which == KS) {
#pragma unroll
      for (int j = 0; j < 128; j++) acc[j] *= Q_SCALE;
    }
#pragma unroll
    for (int j = 0; j < 64; j++) pend[j] = pack_bf16(acc[2 * j], acc[2 * j + 1]);
    pend_map = &maps.c[which];
    pend_c0 = n_tile * 256;
    pend_c1 = m_tile * 128 + hf * 64;
    gend += it == 4 ? 16 : 8;
    when = (it == 4 ? 0x922 : 0x55) << wg;
  }
  if (go) st_go(bar, wg, wtid, sn - 1);
#pragma unroll
  for (int j = 0; j < 32; j++)
    q[j] = KS ? pack_bf16(acc[2 * j], acc[2 * j + 1]) : pack_bf16(acc[2 * j] * Q_SCALE, acc[2 * j + 1] * Q_SCALE);
#pragma unroll
  for (int j = 0; j < 64; j++) rest[j] = acc[64 + j];
  GT(gti++)
  return sn;
}

constexpr int A_TILE = 128 * 128 * 2;
constexpr int A_K_OFF = 0, A_Q_OFF = A_TILE, A_V_OFF = 3 * A_TILE;
constexpr int A_O_OFF = 6 * A_TILE;
constexpr int A_ITEMS = NH * (S_LEN / 128);

constexpr uint32_t A_ORDER = 0x3120, A_STEPS = 34;
__device__ __forceinline__ int item_m(uint32_t it) { return it & 15; }
__device__ __forceinline__ int item_h(uint32_t it) { return it >> 4; }

constexpr int C_V = 16384, C_MAT = 24576;
constexpr float C_ALPHA = 0.07874506561842957f;
__device__ __forceinline__ void sincos_turn(int p, float inv, float& c, float& s) {
  const float a = (float)p * (inv * 6.283185307179586f);
  asm("cos.approx.ftz.f32 %0, %1;" : "=f"(c) : "f"(a));
  asm("sin.approx.ftz.f32 %0, %1;" : "=f"(s) : "f"(a));
}

__device__ __forceinline__ uint32_t head_of(const Maps& maps, uint32_t r) { return (maps.id[blockIdx.x & 127][3] >> (2 * r)) & 3; }
__device__ __forceinline__ uint32_t item_at(const Maps& maps, uint32_t h) {
  const uint32_t b = maps.id[blockIdx.x & 127][1];
  return (b >> 4) * 64 + h * 16 + ((b ^ ((h >> 1) * 15)) & 15);
}
__device__ __forceinline__ uint32_t item_of(const Maps& maps, uint32_t r) { return item_at(maps, head_of(maps, r)); }

#define PACE 250
#define SPACE 0
#define LCHK 1
#define XMASK 3
#define XFIRST 12
#define C_SIDE 64
__device__ __forceinline__ uint32_t conv_first(const Maps& maps) {
  const uint32_t b = maps.id[blockIdx.x & 127][1];
  return (b >> 4) * 128 + ((b + 15) & 15);
}

__device__ __forceinline__ void conv_consumer(const Maps& maps, uint32_t smem0, uint32_t first, uint32_t step,
                                              uint32_t end, bool pp, bool dealt) {
  PHASE_PROLOGUE
  const uint32_t in_full = bar + B_CFULL + wg * 16;
  const uint32_t ca = sbase + (wg ? A_V_OFF + A_TILE : A_Q_OFF);
  const int w = __shfl_sync(0xffffffffu, warp, 0), g = lane >> 2, c = lane & 3;
  auto fetch = [&](uint32_t ch, uint32_t n) {
    if (w == 2 && ch < C_NONE) {
      if (elect_one()) {
        const uint32_t b = in_full + (n & 1) * 8, d = ca + (n & 1) * 8192;
        const uint64_t pol = policy_evict_first();
        mbar_expect_tx(b, 8192);
        tma_load_2d_hint(d, &maps.cu, b, 0, ch * 64, pol);
        tma_load_2d_hint(d + 4096, &maps.ch, b, 0, ch * 64, pol);
      }
    }
  };
  if (wtid == 96 && wg) { TD(15) }
  uint32_t f1[8][4];
  float tt[16], ts[16];
  uint32_t cc[4], ss[4];
#pragma unroll
  for (int i = 0; i < 16; i++) {
    const int k = 2 * (16 * w + g + 8 * (i & 1)) + 1, n = 2 * (8 * (i >> 1) + 2 * c) + 1;
    float c0, s0, c1, s1;
    sincos_turn(((k * n) << 23) >> 23, 1.f / 512, c0, s0);
    sincos_turn(((k * n + 2 * k) << 23) >> 23, 1.f / 512, c1, s1);
    f1[i >> 2][i & 3] = pack_bf16(c0 * C_ALPHA, c1 * C_ALPHA);
    f1[4 + (i >> 2)][i & 3] = pack_bf16(s0 * -C_ALPHA, s1 * -C_ALPHA);
  }
#pragma unroll
  for (int i = 0; i < 16; i++) {
    const int k = 2 * (16 * w + g + 8 * ((i >> 1) & 1)) + 1, n = 16 - (8 * (i >> 2) + 2 * c + (i & 1));
    float cs;
    sincos_turn(k * n, 1.f / 8192, cs, ts[i]);
    tt[i] = ts[i] * rcp(1.f + cs);
  }
#pragma unroll
  for (int j = 0; j < 4; j++) {
    const int k = 8 * w + g, n = 8 * c + 2 * j;
    float c0, s0, c1, s1;
    sincos_turn((int8_t)(k * n * 8), 1.f / 256, c0, s0);
    sincos_turn((int8_t)((k * n + k) * 8), 1.f / 256, c1, s1);
    cc[j] = pack_bf16(c0, c1);
    ss[j] = pack_bf16(s0, s1);
  }
  named_bar_sync(3, 256);
  fetch(first, 0);
  fetch(first + step, 1);
  const uint32_t va = ca + g * 64 + ((c ^ (g >> 1)) << 4);
  {
    const uint32_t a = va + C_MAT + w * 512, m = 0x80008000u;
    sts128(a, make_uint4(cc[0], cc[1], cc[2], cc[3]));
    sts128(a + 2048, make_uint4(ss[0], ss[1], ss[2], ss[3]));
    sts128(a + 4096, make_uint4(ss[0] ^ m, ss[1] ^ m, ss[2] ^ m, ss[3] ^ m));
    sts128(a + 6144, make_uint4(cc[0], cc[1], cc[2], cc[3]));
  }
  fence_proxy_async();
  named_bar_sync(1 + wg, 128);
  constexpr uint64_t DHI = (2ull << 62) | ((uint64_t)(512 >> 4) << 32);
  const uint32_t d0 = (uint32_t)make_desc(ca, 4096, 0, 0);
  float a5[16];
  uint4* const yb = reinterpret_cast<uint4*>(g_y2T) + (16 * w + g) * 4 + c;
  auto issue5 = [&]() {
#pragma unroll
    for (int ks = 0; ks < 8; ks++) wgmma_m64n32_rs_tb(a5, f1[ks], DHI | (d0 + (C_V >> 4) + ks * 64), ks != 0);
    wgmma_commit();
  };
  auto finish = [&](uint32_t ch, bool on) {
    fence_regs(a5);
    uint4* y = yb + (size_t)ch * 256;
    if (on) {
      y[0] = make_uint4(pack_bf16(a5[0], a5[1]), pack_bf16(a5[4], a5[5]), pack_bf16(a5[8], a5[9]), pack_bf16(a5[12], a5[13]));
      y[32] = make_uint4(pack_bf16(a5[2], a5[3]), pack_bf16(a5[6], a5[7]), pack_bf16(a5[10], a5[11]), pack_bf16(a5[14], a5[15]));
    }
  };
  auto dft32 = [&](float (&d)[32], const float* re, const float* im) {
    uint32_t a[4][4];
#pragma unroll
    for (int i = 0; i < 8; i++) {
      a[i >> 2][i & 3] = pack_bf16(re[2 * i], re[2 * i + 1]);
      a[2 + (i >> 2)][i & 3] = pack_bf16(im[2 * i], im[2 * i + 1]);
    }
    wgmma_fence();
#pragma unroll
    for (int ks = 0; ks < 4; ks++) wgmma_m64n64_rs_tb(d, a[ks], DHI | (d0 + (C_MAT >> 4) + ks * 64), ks != 0);
    wgmma_commit();
  };
  auto rot = [&](float* x, float* y) {
#pragma unroll
    for (int i = 0; i < 16; i++) {
      x[i] = fmaf(-tt[i], y[i], x[i]);
      y[i] = fmaf(ts[i], x[i], y[i]);
      x[i] = fmaf(-tt[i], y[i], x[i]);
    }
  };
  auto load_d = [&](uint32_t ch) {
    return __ldg(reinterpret_cast<const unsigned short*>(maps.ssm_D) + ((ch & (DM - 1)) | (lane & rt_zero)));
  };
  uint32_t dn = load_d(first);
  uint32_t n = 0, prev = 0, ch = first, next = first + step;
#pragma unroll 1
  for (; ch < C_NONE; n++) {
    CT(0)
    float a1[2][32], a2[2][32], a4[32];
    const float dsk = c ? 0.f : __uint_as_float(dn << 16) * C_ALPHA;
    dn = load_d(next);
    uint32_t next2 = next + step < end ? next + step : C_NONE;
    mbar_wait(in_full + (n & 1) * 8, (n >> 1) & 1);
    if (pp) named_bar_sync(4 + wg, 256);
    CT(1)
    wgmma_fence();
#pragma unroll
    for (int ks = 0; ks < 8; ks++)
      wgmma_m64n64_rs_tb(a1[ks >> 2], f1[ks], DHI | (d0 + (n & 1) * 512 + (ks & 3) * 64), (ks & 3) != 0);
    wgmma_commit();
    issue5();
    wgmma_wait<1>();
    fence_regs(a1[0]);
    fence_regs(a1[1]);
    CT(2)
    rot(a1[0], a1[1]);
    dft32(a2[0], a1[0], a1[1]);
    rot(a1[0] + 16, a1[1] + 16);
    a1[0][16] += dsk;
    a1[0][18] += dsk;
    dft32(a2[1], a1[0] + 16, a1[1] + 16);
    CT(3)
    wgmma_wait<2>();
    finish(prev, n > 0);
    wgmma_wait<0>();
    fence_regs(a2[0]);
    fence_regs(a2[1]);
    CT(4)
    if (pp) named_bar_arrive(5 - wg, 256);
    float re[16], im[16];
#pragma unroll
    for (int i = 0; i < 16; i++) {
      re[i] = a2[0][i] * a2[1][i] - a2[0][16 + i] * a2[1][16 + i];
      im[i] = a2[0][i] * a2[1][16 + i] + a2[0][16 + i] * a2[1][i];
    }
    dft32(a4, im, re);
    if (dealt) {
      mbar_wait(bar + (n < 2 ? B_DEAL : B_DEAL2), 0);
      asm volatile("ld.shared.u32 %0, [%1];" : "=r"(next2) : "r"(bar + B_LIST + 4 * n + (n < 2 ? 0 : 8)));
    }
    wgmma_wait<0>();
    fence_regs(a4);
    CT(5)
    rot(a4, a4 + 16);
#pragma unroll
    for (int i = 0; i < 4; i++) {
      const float* x = a4 + 16 - 16 * (i >> 1) + 2 * (i & 1);
      sts128(va + C_V + w * 1024 + (i >> 1) * 4096 + (i & 1) * 512,
             make_uint4(pack_bf16(x[0], x[1]), pack_bf16(x[4], x[5]), pack_bf16(x[8], x[9]), pack_bf16(x[12], x[13])));
    }
    CT(6)
    fence_proxy_async();
    named_bar_sync(1 + wg, 128);
    fetch(next2, n);
    if (wtid == 96 && n > 0) note(bar, CNT_Y2 + ((prev & 112) == 112));
    prev = ch;
    ch = next;
    next = next2;
    CT(7)
  }
  wgmma_fence();
  issue5();
  wgmma_wait<0>();
  finish(prev, (dn | ~rt_zero) != 0);
  named_bar_sync(1 + wg, 128);
  if (wtid == 96 && wg) { TD(8) }
  if (wtid == 96) cnt_signal_release(CNT_Y2 + ((prev & 112) == 112), 1);
  if (wtid == 64) note(bar, CNT_DONE);
  if (wtid == 96 && wg) { TD(9) }
}

__device__ __forceinline__ void attn_producer(const Maps& maps, uint32_t sbase, bool after_qkv, bool to_out,
                                              bool dry) {
  const uint32_t bar = sbase + BAR_OFF;
  const uint32_t q_full = bar + B_QFULL, q_empty = bar + B_QEMPTY;
  const uint32_t k_full = bar + B_KFULL, k_empty = bar + B_KEMPTY, v_full = bar + B_VFULL, v_empty = bar + B_VEMPTY;
  int ndrained = after_qkv ? 0 : G_STAGES;
  auto wait = [&](uint32_t b, uint32_t par) {
    if (!dry) mbar_wait_sleep(b, par);
  };
  auto drained = [&](int upto) {
#pragma unroll 1
    for (; ndrained <= upto; ndrained++) wait(bar + B_GEMPTY + 8 * ndrained, 1);
  };
  uint32_t st = 0, ph = 1, vs = 0, vp = 1;
  int pend_j = -1, pend_h = 0;
  int round = -1, m = -1, h = 0;
  bool last = false;
#pragma unroll 1
  for (;; round++) {
    uint32_t nitem = 0;
    const int tpost = m >= 3 ? m - 1 : m;
#pragma unroll 1
    for (int t = m < 0 ? -1 : 0; t <= m; t++) {
      const int j = (t < m && (h & 2)) ? m - 1 - t : t;
      if (t >= 0) {
        drained(st);
        wait(k_empty + 8 * st, ph);
        if (!dry) {
          mbar_expect_tx(k_full + 8 * st, A_TILE);
          tma_load_3d(sbase + A_K_OFF + st * 2 * A_TILE, &maps.k, k_full + 8 * st, 0, j * 128, h * 2);
        }
        if (++st == 2) { st = 0; ph ^= 1; }
      }
      if (pend_j >= 0) {
        drained(2 + vs);
        if ((pend_h & 2) && after_qkv) wait(bar + seen_bar(0), 0);
        wait(v_empty + 8 * vs, vp);
        if (!dry) {
          mbar_expect_tx(v_full + 8 * vs, A_TILE);
          tma_load_3d(sbase + A_V_OFF + vs * A_TILE, &maps.v, v_full + 8 * vs, 0, pend_j * 128, pend_h * 2);
        }
        if (++vs == 2) { vs = 0; vp ^= 1; }
      }
      pend_j = j;
      pend_h = h;
      if (t == tpost && !last) {
        nitem = dry ? 1 : item_of(maps, round + 1);
        if (round == (dry ? 0 : 3) || blockIdx.x >= 128) {
          nitem = A_ITEMS;
          if (!to_out) cnt_wait(CNT_PREP, dry ? 0 : 260);
          if (to_out) {
            wait(bar + seen_bar(1), 0);
            asm volatile("cp.async.bulk.prefetch.L2.global [%0], 4096;" ::"l"(maps.ssm_k + (size_t)conv_first(maps) * S_LEN));
            if (!dry)
              asm volatile("cp.async.bulk.prefetch.L2.global [%0], 4096;" ::"l"(g_kvT + (size_t)conv_first(maps) * S_LEN));
          }
        }
        const uint32_t qs = (round + 1) & 1;
        wait(q_empty + 8 * qs, (((round + 1) >> 1) & 1) ^ 1);
        if (round == 1 && after_qkv) wait(bar + B_QDONE, 0);
        if (round < 0 && after_qkv) {
          if (!dry) { TD(2) }
          cnt_wait(CNT_KV, dry ? 0 : 768);
          if (!dry) { TD(3) }
        }
        if (nitem >= A_ITEMS || (round < 0 && after_qkv && !dry)) {
          if (!dry) mbar_arrive(q_full + 8 * qs);
        } else {
          drained(1 + 2 * qs);
          if (!dry) {
            mbar_expect_tx(q_full + 8 * qs, A_TILE);
            tma_load_3d_hint(sbase + A_Q_OFF + qs * 4 * A_TILE, &maps.q, q_full + 8 * qs, 0, item_m(nitem) * 128,
                             item_h(nitem) * 2, policy_evict_first());
          }
        }
      }
    }
    if (last) break;
    last = nitem >= A_ITEMS;
    m = last ? -1 : item_m(nitem);
    h = item_h(nitem);
  }
}

__device__ __forceinline__ void put_o(uint32_t sbase, int wg, int warp, int lane, const float (&o)[64], float i0, float i1) {
  const int st_row = warp * 16 + (lane & 7) + ((lane >> 3) & 1) * 8;
  const uint32_t so = sbase + A_O_OFF + wg * 16384 + st_row * 128;
#pragma unroll
  for (int j = 0; j < 16; j += 2)
    stmatrix_x4(so + (j >> 3) * 8192 + ((((j & 7) + (lane >> 4)) ^ (lane & 7)) << 4),
                pack_bf16(o[4 * j] * i0, o[4 * j + 1] * i0), pack_bf16(o[4 * j + 2] * i1, o[4 * j + 3] * i1),
                pack_bf16(o[4 * j + 4] * i0, o[4 * j + 5] * i0), pack_bf16(o[4 * j + 6] * i1, o[4 * j + 7] * i1));
}
__device__ __forceinline__ uint32_t attn_consumer(const Maps& maps, const uint32_t sbase, const int wg,
                                                  const uint32_t rt_zero, uint32_t sn, uint32_t (&p)[32], float (&rest)[64],
                                                  bool after_qkv, float (&o)[64], float (&s)[64], float& pi0, float& pi1) {
  PHASE_GIVEN
  const uint32_t q_full = bar + B_QFULL, q_empty = bar + B_QEMPTY;
  const uint32_t k_full = bar + B_KFULL, k_empty = bar + B_KEMPTY, v_full = bar + B_VFULL;
  float e[32];
  uint32_t dep = 0;
  constexpr int MIDJ = 5;
  float l0 = 0.f, l1 = 0.f, b0 = 0.f, b1 = 0.f;
  const int sched_own = 4 + wg, sched_other = 5 - wg;

  const int hf = wg ^ 1;
  const uint32_t qd0 = (uint32_t)make_desc(sbase + A_Q_OFF + hf * 8192, 16, 0, 0);
  const uint32_t kd0 = (uint32_t)make_desc(sbase + A_K_OFF, 16, 0, 0);
  const uint32_t vd0 = (uint32_t)make_desc(sbase + A_V_OFF, 16384, 0, 0);
  constexpr uint64_t DHI = DESC_SW128 | ((uint64_t)(1024 >> 4) << 32);
  constexpr uint32_t DST = A_TILE >> 4;
  auto issue_qk = [&](uint32_t qd, uint32_t kd) {
#pragma unroll
    for (int kk = 0; kk < 8; kk++) {
      const uint32_t off = ((kk >> 2) * 16384 + (kk & 3) * 32) >> 4;
      wgmma_m64n128_ss(s, DHI | (qd + off), DHI | (kd + off), kk != 0);
    }
    wgmma_commit();
  };
  auto issue_pv = [&](uint32_t vd, bool accumulate, int nk) {
#pragma unroll
    for (int kk = 0; kk < 8; kk++) {
      if (kk < nk)
        wgmma_m64n128_rs<1>(o, p[4 * kk], p[4 * kk + 1], p[4 * kk + 2], p[4 * kk + 3], DHI | (vd + kk * 128),
                            accumulate || (kk != 0));
    }
    wgmma_commit();
  };
  auto exp_lo = [&](float& a0, float& a1) {
#pragma unroll
    for (int j = 0; j < 8; j++) {
      e[4 * j] = ex2(s[4 * j]);
      e[4 * j + 1] = ex2(s[4 * j + 1]);
      e[4 * j + 2] = ex2(s[4 * j + 2]);
      e[4 * j + 3] = ex2(s[4 * j + 3]);
      a0 += e[4 * j];
      a0 += e[4 * j + 1];
      a1 += e[4 * j + 2];
      a1 += e[4 * j + 3];
      if (j == MIDJ) dep = (__float_as_uint(a0) | __float_as_uint(a1)) & rt_zero;
    }
  };
  auto pack_lo = [&]() {
#pragma unroll
    for (int j = 0; j < 16; j++) p[j] = pack_bf16(e[2 * j], e[2 * j + 1]);
  };
  auto finish_p = [&](float& a0, float& a1) {
    pack_lo();
#pragma unroll
    for (int j = 8; j < 16; j++) {
      const float e0 = ex2(s[4 * j]), e1 = ex2(s[4 * j + 1]), e2 = ex2(s[4 * j + 2]), e3 = ex2(s[4 * j + 3]);
      a0 += e0;
      a0 += e1;
      a1 += e2;
      a1 += e3;
      p[2 * j] = pack_bf16(e0, e1);
      p[2 * j + 1] = pack_bf16(e2, e3);
      if (j == 8 + MIDJ) dep = __float_as_uint(a0) & rt_zero;
    }
  };
  auto quad_sum = [&](float t) {
    t += __shfl_xor_sync(0xffffffffu, t, 1);
    return t + __shfl_xor_sync(0xffffffffu, t, 2);
  };
  auto write_o = [&](float i0, float i1) {
    st_wait(bar, wg, sn - 1);
    put_o(sbase, wg, warp, lane, o, i0, i1);
  };
  auto store_o = [&](uint32_t r, int kind, uint32_t lazy) {
    const uint32_t it = item_at(maps, kind == ST_BOX2Q ? 1 : head_of(maps, r));
    st_cmd(bar, wg, wtid, sn, kind, (INPLACE & 1) || kind != ST_BOX2Q ? &maps.o : &maps.c[0], sbase + A_O_OFF + wg * 16384, item_h(it) * 128,
            item_m(it) * 128 + hf * 64, CNT_CTX + (r >> 1), lazy);
    if (kind != ST_BOX2L) st_go(bar, wg, wtid, sn);
    sn++;
  };
  auto mask_half = [&](float* sh) {
    const int u = warp * 16 + (lane >> 2) - (lane & 3) * 2;
#pragma unroll
    for (int j = 0; j < 8; j++) {
      if (8 * j > u) sh[4 * j] = -INFINITY;
      if (8 * j + 1 > u) sh[4 * j + 1] = -INFINITY;
      if (8 * j - 8 > u) sh[4 * j + 2] = -INFINITY;
      if (8 * j - 7 > u) sh[4 * j + 3] = -INFINITY;
    }
  };
  ST(0)
  const uint32_t qa = sbase + A_Q_OFF + hf * 8192 + (warp * 16 + (lane & 15)) * 128;
  auto q_at = [&](int j) { return qa + (j >> 2) * 16384 + ((((j & 3) * 2 + (lane >> 4)) ^ (lane & 7)) << 4); };
  if (!after_qkv) {
    mbar_wait(q_full, 0);
    if (blockIdx.x >= 128) return sn;
#pragma unroll
    for (int j = 0; j < 8; j++)
      asm volatile("ldmatrix.sync.aligned.m8n8.x4.shared.b16 {%0, %1, %2, %3}, [%4];"
                   : "=r"(p[4 * j]), "=r"(p[4 * j + 1]), "=r"(p[4 * j + 2]), "=r"(p[4 * j + 3])
                   : "r"(q_at(j))
                   : "memory");
  }
  for (uint32_t i = 0; !(mbar_try(k_full, 0) & mbar_try(bar + B_GEMPTY + 8, 1)) && i < (1u << 22); i++) {}
  named_bar_sync(sched_own, 256);
  fence_regs_u(p);
  wgmma_fence();
#pragma unroll
  for (int kk = 0; kk < 8; kk++)
    wgmma_m64n128_rs<0>(s, p[4 * kk], p[4 * kk + 1], p[4 * kk + 2], p[4 * kk + 3],
                        DHI | (kd0 + (((kk >> 2) * 16384 + (kk & 3) * 32) >> 4)), kk != 0);
  wgmma_commit();
  if (HOLD && after_qkv && wg == 0) named_bar_arrive(7, 256);
  named_bar_arrive(sched_other, 256);
#pragma unroll
  for (int j = 0; j < 8; j++) stmatrix_x4(q_at(j), p[4 * j], p[4 * j + 1], p[4 * j + 2], p[4 * j + 3]);
  fence_regs(rest);
#pragma unroll
  for (int i = 0; i < 64; i++) o[i] = rest[i] * (KS ? __uint_as_float(0x3f800000u | rt_zero) : Q_SCALE);
  fence_regs(o);
  fence_proxy_async();
  fence_regs(o);
  wgmma_wait<0>();
  fence_regs(s);
  mbar_arrive_if(k_empty, wtid == 32);
  uint32_t g = 0;
  uint32_t rnd = 0;
  int rem = item_m(item_of(maps, 0));
  uint32_t first = 1;
  uint32_t fl = 0;
#define redo (fl & 1)
#define shifted (fl & 2)
  float d0 = 0.f, d1 = 0.f;
  pi0 = pi1 = 1.f;
  ST(1)
  for (;;) {
    if (shifted) {
#pragma unroll
      for (int j = 0; j < 16; j++) {
        s[4 * j] -= d0;
        s[4 * j + 1] -= d0;
        s[4 * j + 2] -= d1;
        s[4 * j + 3] -= d1;
      }
    }
    if (rem == 0 && !redo) {
      mbar_arrive_if(q_empty + 8 * (rnd & 1), wtid == 96);
      rnd++;
      if (hf == 0) mask_half(s);
      else mask_half(s + 32);
    }
    for (;;) {
      const bool kill = rem == 0 && hf == 0;
      const uint32_t kd = kd0 + ((g + 1) & 1) * 2 * DST, vd = vd0 + (g & 1) * DST;
      float a0 = 0.f, a1 = 0.f;
      exp_lo(a0, a1);
      fence_regs(e);
      const uint32_t kb = k_full + 8 * ((g + 1) & 1);
      const uint32_t kpar = (((g + 1) >> 1) & 1) ^ (g == A_STEPS - 1 ? 1u : 0u);
      const uint32_t qb = q_full + 8 * (rnd & 1), qpar = ((rnd >> 1) & 1) | dep;
      if (!mbar_try(qb, qpar)) mbar_wait(qb, qpar | ((__float_as_uint(a0) | __float_as_uint(a1)) & rt_zero));
      wgmma_wait<0>();
      fence_regs(o);
      if (kill) {
        mbar_arrive_if(kb + (B_VEMPTY - B_KFULL), wtid == 64 && !redo && g > 0);
        fence_regs(e);
        pack_lo();
#pragma unroll
        for (int j = 16; j < 32; j++) asm volatile("" : "=r"(p[j]));
        goto check;
      }
#pragma unroll
      for (int i = 32; i < 64; i++) asm volatile("" : "+f"(s[i])::"memory");
      mbar_arrive_if(kb + (B_VEMPTY - B_KFULL), wtid == 64 && !redo && g > 0);
      finish_p(a0, a1);
      if (__any_sync(0xffffffffu, !(mbar_try(v_full + 8 * (g & 1), ((g >> 1) & 1) | dep) &
                                    mbar_try(kb, kpar | dep)) ||
                                      !(a0 + a1 < 1.0995116e12f) || !(fminf(a0, a1) > (first ? 9.094947e-13f : -1.f)))) {
      check:
        bool bad = !(a0 + a1 < 1.0995116e12f);
        if (first) bad |= !(fminf(quad_sum(a0), quad_sum(a1)) > 9.094947e-13f);
        if (!redo && __any_sync(0xffffffffu, bad)) {
          d0 = d1 = first ? -INFINITY : 0.f;
#pragma unroll
          for (int j = 0; j < 16; j++) {
            if (j < 8 || !kill) {
              d0 = fmaxf(d0, fmaxf(s[4 * j], s[4 * j + 1]));
              d1 = fmaxf(d1, fmaxf(s[4 * j + 2], s[4 * j + 3]));
            }
          }
#pragma unroll
          for (int x = 1; x <= 2; x++) {
            d0 = fmaxf(d0, __shfl_xor_sync(0xffffffffu, d0, x));
            d1 = fmaxf(d1, __shfl_xor_sync(0xffffffffu, d1, x));
          }
          b0 += d0;
          b1 += d1;
          if (!first) {
            const float al0 = ex2(-d0), al1 = ex2(-d1);
            l0 *= al0;
            l1 *= al1;
#pragma unroll
            for (int j = 0; j < 16; j++) {
              o[4 * j] *= al0;
              o[4 * j + 1] *= al0;
              o[4 * j + 2] *= al1;
              o[4 * j + 3] *= al1;
            }
          }
          fl = 3;
          break;
        }
        mbar_wait(v_full + 8 * (g & 1), (g >> 1) & 1);
        mbar_wait(kb, kpar);
      }
      named_bar_sync(sched_own, 256);
      if (g == A_STEPS - 1) {
        fence_regs(o);
        if (hf == 0) {
          wgmma_fence();
          issue_pv(vd, 1, 4);
        } else {
          wgmma_fence();
          issue_pv(vd, 1, 8);
        }
        named_bar_arrive(sched_other, 256);
        pi0 = rcp(quad_sum(l0 + a0));
        pi1 = rcp(quad_sum(l1 + a1));
        goto done;
      }
      wgmma_fence();
      issue_qk(qd0 + (rnd & 1) * 4 * DST, kd);
      if (first) write_o(pi0, pi1);
      fence_regs(o);
      if (kill) {
        wgmma_fence();
        issue_pv(vd, !first, 4);
      } else {
        wgmma_fence();
        issue_pv(vd, !first, 8);
      }
      named_bar_arrive(sched_other, 256);
      fl &= 2;
      l0 += a0;
      l1 += a1;
      if (rem == 0 || first) {
        if (first && (g > 0 || after_qkv)) store_o(g ? rnd - (rem == 0 ? 2 : 1) : 2, g ? ST_BOX2 : ST_BOX2Q, rem);
        first = rem == 0;
        if (first) {
          pi0 = rcp(quad_sum(l0));
          pi1 = rcp(quad_sum(l1));
          l0 = l1 = b0 = b1 = 0.f;
          fl = 0;
          rem = item_m(item_of(maps, rnd)) + 1;
        }
      }
      rem--;
      g++;
      wgmma_wait<1>();
      fence_regs(s);
      mbar_arrive_if(kb + (B_KEMPTY - B_KFULL), wtid == 32);
      ST(g + 1)
      if (rem == 0 || shifted) {
        d0 = b0;
        d1 = b1;
        break;
      }
    }
  }
done:
#undef redo
#undef shifted
  st_wait(bar, wg, sn - 1);
  store_o(3, ST_BOX2L, 4);
  ST(35)
  return sn;
}

constexpr int O_STAGES = 5;
constexpr int O_STAGE_BYTES = 32768;
constexpr int O_Y_OFF = 4 * 32768;
constexpr int O_X_OFF = 6 * 32768;
constexpr int O_G_OFF = 7 * 32768;
constexpr int O_NK = HDIM / 64;

__device__ __forceinline__ uint32_t out_stage(uint32_t st) { return ((0x32501u >> (4 * st)) & 7) * O_STAGE_BYTES; }

__device__ __forceinline__ void out_producer(const Maps& maps, uint32_t sbase, bool after_attn, bool dry) {
  const uint32_t bar = sbase + BAR_OFF;
  const uint32_t rank = blockIdx.x & 1;
  const int m_tile = maps.id[blockIdx.x][2] & 15, n_tile = maps.id[blockIdx.x][2] >> 4;
  uint32_t stage = 0, phase = 0, xi = 0;
#pragma unroll 1
  for (int ki = 0; ki < (dry ? 1 : O_NK); ki++) {
    const int kt = (ki & 14) * 4 + ((A_ORDER >> ((ki >> 4) * 4)) & 3) * 2 + (ki & 1);
    const uint32_t fb = bar + B_OFULL + 8 * stage, eb = bar + B_OEMPTY + 8 * stage;
    const uint32_t sa = sbase + out_stage(stage);
    if (ki < O_STAGES) {
      constexpr uint32_t LASTB = B_KEMPTY | ((B_QEMPTY + 8) << 8) | ((B_KEMPTY + 8) << 16) | (B_VEMPTY << 24);
      if (ki > 0 && after_attn) mbar_wait_sleep(bar + ((LASTB >> (8 * ki - 8)) & 255), ki == 2);
      mbar_arrive_cluster_if(eb, 0, !dry);
      mbar_arrive_cluster_if(eb, 1, !dry);
    }
    if (ki == 32) mbar_wait_sleep(bar + seen_bar(2), 0);
    if (!dry) {
      mbar_wait_sleep(eb, phase);
      mbar_expect_tx(fb, O_STAGE_BYTES);
      tma_load_2d_mc(sa + 16384 + rank * 8192, &maps.ob, fb, n_tile * 128 + rank * 64, kt * 64, (uint16_t)3);
      tma_load_2d(sa, &maps.oa, fb, kt * 64, m_tile * 128);
    }
    if (++stage == O_STAGES) { stage = 0; phase ^= 1; }
    if ((ki & XMASK) == XMASK && ki >= XFIRST && xi < 8) {
      if (after_attn && xi < 2) mbar_wait_sleep(bar + B_OFREE + 8 * xi, 0);
      tma_load_3d(sbase + O_X_OFF + (xi & 1) * 16384 + (xi >> 1) * 4096, &maps.xs, bar + B_OY, 0,
                  m_tile * 128 + (xi & 1) * 64 + (xi >> 1) * 16, n_tile * 2);
      xi++;
    }
  }
  if (!dry) mbar_wait_sleep(bar + B_OY2, 0);
}

__device__ __forceinline__ void out_side(const Maps& maps, uint32_t smem0) {
  PHASE_PROLOGUE
  const int m_tile = maps.id[blockIdx.x][2] & 15, n_tile = maps.id[blockIdx.x][2] >> 4;
  const float* gp = g_gate + m_tile * 128 + warp * 16 + (lane >> 2);
  const float gv[4] = {__ldcg(gp), __ldcg(gp + 8), __ldcg(gp + 64), __ldcg(gp + 72)};
  const bool w0 = __shfl_sync(0xffffffffu, warp, 0) == 0;
  bool have = false;
  auto late = [&](uint32_t spins) {
    have = cnt_wait(CNT_Y2 + 1, 128, spins) || !spins;
    TD(11)
    if (have) {
      mbar_expect_tx(bar + B_OY2, 4096);
      tma_load_3d(sbase + O_Y_OFF + 7 * 4096, &maps.y, bar + B_OY2, 0, n_tile * 128 + 112, m_tile * 2);
    }
  };
  if (w0) {
    if (elect_one()) {
      mbar_expect_tx(bar + B_OY, 65536 - 4096);
      TD(10)
      cnt_wait(CNT_Y2, DM - 128);
      TD(7)
#pragma unroll 1
      for (int i = 0; i < 7; i++) {
        tma_load_3d(sbase + O_Y_OFF + i * 4096, &maps.y, bar + B_OY, 0, n_tile * 128 + i * 16, m_tile * 2);
        __nanosleep(PACE);
      }
      late(1u << 18);
    }
  }
  mbar_wait_sleep(bar + B_OY, 0);
  if (wtid == 0) { TD(12) }
  const int mrow = (lane & 7) + ((lane >> 4) & 1) * 8;
  const int mchunk = warp * 2 + ((lane >> 3) & 1);
  const uint32_t xrow = sbase + O_X_OFF + warp * 4096 + (lane & 15) * 128;
  const uint32_t yrow = sbase + O_Y_OFF + mrow * 128 + ((mchunk ^ (lane & 7)) << 4);
  uint32_t y[7][4], x[7][4], om[4];
#pragma unroll
  for (int i = 0; i < 4; i++) om[i] = pack_bf16(1.0f - gv[i], 1.0f - gv[i]);
  sts128(sbase + O_G_OFF + wtid * 16, make_uint4(pack_bf16(gv[0], gv[0]), pack_bf16(gv[1], gv[1]), pack_bf16(gv[2], gv[2]),
                                                 pack_bf16(gv[3], gv[3])));
  auto xa = [&](int h, int i) { return xrow + h * 16384 + (i >> 2) * 2048 + ((((i & 3) * 2 + (lane >> 4)) ^ (lane & 7)) << 4); };
  auto load = [&](int r, int h, int i) {
    ldsm4t(y[r], yrow + h * 2048 + i * 4096);
    asm volatile("ldmatrix.sync.aligned.m8n8.x4.shared.b16 {%0, %1, %2, %3}, [%4];"
                 : "=r"(x[r][0]), "=r"(x[r][1]), "=r"(x[r][2]), "=r"(x[r][3])
                 : "r"(xa(h, i)));
  };
  auto store = [&](int r, int h, int i, uint32_t om0, uint32_t om1) {
    stmatrix_x4(xa(h, i), mul_bf2(om0, mul_bf2(x[r][0], y[r][0])), mul_bf2(om1, mul_bf2(x[r][1], y[r][1])),
                mul_bf2(om0, mul_bf2(x[r][2], y[r][2])), mul_bf2(om1, mul_bf2(x[r][3], y[r][3])));
  };
#pragma unroll 1
  for (int h = 0; h < 2; h++) {
#pragma unroll
    for (int i = 0; i < 7; i++) load(i, h, i);
#pragma unroll
    for (int i = 0; i < 7; i++) store(i, h, i, h ? om[2] : om[0], h ? om[3] : om[1]);
  }
  __syncwarp();
  mbar_arrive_if(bar + B_OE, lane == 0);
  if (w0 && !__any_sync(0xffffffffu, have)) {
    if (elect_one()) late(0);
  }
  mbar_wait_sleep(bar + B_OY2, 0);
  load(0, 0, 7);
  load(1, 1, 7);
  store(0, 0, 7, om[0], om[1]);
  store(1, 1, 7, om[2], om[3]);
  __syncwarp();
  mbar_arrive_if(bar + B_OY + 8, lane == 0);
  if (wtid == 0) { TD(13) }
}

__device__ __forceinline__ void out_gemm(const Maps& maps, const uint32_t sbase, uint32_t sn, bool post, float (&o)[64],
                                         float (&s)[64],                                          float i0, float i1) {
  PHASE_GIVEN
  auto acc = [&](int h) -> float (&)[64] { return h ? o : s; };
  constexpr uint64_t DHI = DESC_SW128 | ((uint64_t)(1024 >> 4) << 32);
  const uint32_t d0 = (uint32_t)make_desc(sbase, 0, 0, 0);
  auto mma0 = [&](int h) {
    wgmma_fence();
#pragma unroll
    for (int k = 0; k < 4; k++)
      wgmma_m64n128_ss_tb(acc(h), DHI | (d0 + 0x10800 + h * 512 + k * 2), DHI | (d0 + 0x2000c00 + k * 128), k != 0);
    wgmma_commit();
  };
  mbar_wait(bar + B_OFULL, 0);
  mma0(0);
  wgmma_wait<1>();
  fence_regs(o);
  if (post) {
    named_bar_arrive(3, 256);
    put_o(sbase, 0, warp, lane, o, i0, i1);
  }
  mma0(1);
  if (post) st_go(bar, 0, wtid, sn - 1);
  const int m_tile = maps.id[blockIdx.x][2] & 15, n_tile = maps.id[blockIdx.x][2] >> 4;
  uint32_t stage = 1, phase = 0, prev_stage = 0;
  GT(gti++)
  const uint32_t xrow = sbase + O_X_OFF + warp * 4096 + (lane & 15) * 128;
  auto addr = [&](int i) {
    return xrow + (i >> 3) * 16384 + ((i >> 2) & 1) * 2048 + ((((i & 3) * 2 + (lane >> 4)) ^ (lane & 7)) << 4);
  };
  uint32_t b[16][4];
#pragma unroll
  for (int i = 0; i < 64; i++) asm volatile("" : "=r"(b[i >> 2][i & 3]));
  auto ld_b = [&](int q0, int q1) {
#pragma unroll
    for (int i = 0; i < 16; i++)
      if ((i & 7) != 7)
        asm volatile(
            "{\n.reg .pred p;\nsetp.ge.s32 p, %5, %6;\nsetp.le.and.s32 p, %5, %7, p;\n"
            "@p ldmatrix.sync.aligned.m8n8.x4.shared.b16 {%0, %1, %2, %3}, [%4];\n}\n"
            : "+r"(b[i][0]), "+r"(b[i][1]), "+r"(b[i][2]), "+r"(b[i][3])
            : "r"(addr(i)), "r"(i / 4), "r"(q0), "r"(q1)
            : "memory");
  };
  int nq = 0;
#pragma unroll 1
  for (int kt = 1; kt < O_NK - 2; kt++) {
    uint32_t da = (uint32_t)make_desc(sbase + out_stage(stage), 16, 0, 0);
    uint32_t db = (uint32_t)make_desc(sbase + out_stage(stage) + 16384, 8192, 0, 0);
    asm volatile("" : "+r"(da), "+r"(db));
    mbar_wait(bar + B_OFULL + 8 * stage, phase);
    GT(gti++)
#pragma unroll
    for (int kk = 0; kk < 4; kk++) {
      wgmma_wait<2>();
      if (kk == 2)
        mbar_arrive_cluster_if(bar + B_OEMPTY + 8 * prev_stage, wtid >> 6, (wtid & 63) == 32 && kt - 1 + O_STAGES < O_NK);
      wgmma_fence();
      wgmma_m64n128_ss_tb(acc(0), DHI | (da + kk * 2), DHI | (db + kk * 128), 1);
      wgmma_m64n128_ss_tb(acc(1), DHI | (da + 512 + kk * 2), DHI | (db + kk * 128), 1);
      wgmma_commit();
      if (kk == 0 && kt >= 52) {
        uint32_t ok;
        asm volatile("{\n.reg .pred p;\nmbarrier.test_wait.parity.shared::cta.b64 p, [%1], 0;\nselp.u32 %0, 1, 0, p;\n}\n"
                     : "=r"(ok)
                     : "r"(bar + B_OE)
                     : "memory");
        if (__all_sync(0xffffffffu, ok)) {
          ld_b(nq, nq);
          nq++;
        }
      }
    }
    prev_stage = stage;
    if (++stage == O_STAGES) { stage = 0; phase ^= 1; }
  }
  if (tid == 0) { TD(14) }
  constexpr int S0 = (O_NK - 2) % O_STAGES, P0 = ((O_NK - 2) / O_STAGES) & 1;
  auto mma = [&](int h, int k0, int k1) {
    wgmma_fence();
#pragma unroll
    for (int k = k0; k < k1; k++) {
      const uint32_t d = d0 + (out_stage(S0 + (k >> 2)) >> 4);
      wgmma_m64n128_ss_tb(acc(h), DHI | (d + 0x10000 + h * 512 + (k & 3) * 2), DHI | (d + 0x2000400 + (k & 3) * 128), 1);
    }
    wgmma_commit();
  };
#pragma unroll
  for (int p = 0; p < 2; p++) {
    mbar_wait(bar + B_OFULL + 8 * (S0 + p), P0);
    mma(0, 4 * p, 4 * p + 4);
  }
  mma(1, 0, 8);
  if (nq < 4) {
    mbar_wait(bar + B_OE, 0);
    ld_b(nq, 3);
  }
  const uint4 g4 = lds128(sbase + O_G_OFF + wtid * 16);
  const uint32_t gg[4] = {g4.x, g4.y, g4.z, g4.w};
  const int w4 = __shfl_sync(0xffffffffu, warp, 0);
#pragma unroll
  for (int i = 0; i < 16; i++) {
    const int h = i >> 3;
    if (i == 0) wgmma_wait<1>();
    if (i == 8) wgmma_wait<0>();
    if ((i & 7) == 0) fence_regs(acc(h));
    if (i == 8) {   }
    if (i == 7) {
      mbar_wait(bar + B_OY + 8, 0);
#pragma unroll
      for (int j = 7; j < 16; j += 8)
        asm volatile("ldmatrix.sync.aligned.m8n8.x4.shared.b16 {%0, %1, %2, %3}, [%4];"
                     : "=r"(b[j][0]), "=r"(b[j][1]), "=r"(b[j][2]), "=r"(b[j][3])
                     : "r"(addr(j))
                     : "memory");
    }
    const float* a = acc(h) + 8 * (i & 7);
    stmatrix_x4(addr(i), fma_bf2(gg[2 * h], pack_bf16(a[0], a[1]), b[i][0]), fma_bf2(gg[2 * h + 1], pack_bf16(a[2], a[3]), b[i][1]),
                fma_bf2(gg[2 * h], pack_bf16(a[4], a[5]), b[i][2]), fma_bf2(gg[2 * h + 1], pack_bf16(a[6], a[7]), b[i][3]));
    if ((i & 7) == 7) {
      fence_proxy_async();
      __syncwarp();
      if (elect_one()) {
        tma_store_3d(&maps.oc, sbase + O_X_OFF + (h * 4 + w4) * 4096, 0, m_tile * 128 + h * 64 + w4 * 16, n_tile * 2);
        if (h == 1) {
          tma_store_commit();
        }
      }
    }
  }
  GT(gti++)
}

__device__ __noinline__ void leave_kernel(int mask) {
  if (!(mask & 4)) return;
  if (atomicAdd(g_cnt + CNT_DONE * 32, 1u) == 2 * gridDim.x - 1) {
    for (int i = 0; i < CNT_N; i++) g_cnt[i * 32] = 0;
#pragma unroll 4
    for (int i = 0; i < 128; i++) g_slot[i] = 0;
  }
}

__device__ __noinline__ void side_jobs(const Maps& maps, uint32_t sbase) {
  const int w12 = __shfl_sync(0xffffffffu, threadIdx.x >> 5, 0);
  gate_rows(maps, sbase, (blockIdx.x - 128) * 12 + w12, w12, threadIdx.x & 31);
  fence_proxy_async();
  __syncthreads();
  if (threadIdx.x == 320) cnt_signal_release(CNT_PREP, 1);
}

__global__ void __launch_bounds__(384, 1)
    fused_kernel(int mask, const bf16* px, const bf16* pw, const __grid_constant__ Maps maps) {
  extern __shared__ __align__(1024) uint8_t smem_raw[];
  {
    const uint32_t t = threadIdx.x, l = t & 31, u = (blockIdx.x & 127) * 16 + (l >> 1);
    const uint32_t ow = (u >> 5) * HDIM + ((u >> 2) & 7) * 512 + 256 + (u & 3) * 64, ox = u * DM;
    const bf16* p = ((l & 1) ? pw : px) + ((l & 1) ? ow : ox);
    asm volatile("{\n.reg .pred p;\nsetp.ne.u32 p, %1, 0;\n@p prefetch.global.L2 [%0];\n}\n" ::"l"(p), "r"((uint32_t)(t < 32)));
  }
  {
    const uint32_t sbase = __shfl_sync(0xffffffffu, smem_u32(smem_raw), 0);
    const uint32_t bar = sbase + BAR_OFF;
    const int tid = threadIdx.x;
    const bool do_qkv = (mask & 1) && blockIdx.x < 128;
    TL(0, 0)
    if (__shfl_sync(0xffffffffu, tid >> 5, 0) == 1 && do_qkv) {
      if (elect_one()) {
        for (int i = 0; i < G_STAGES; i++) mbar_init(bar + B_GFULL + 8 * i, 1);
        fence_barrier_init();
        qkv_producer(maps, sbase, true);
      }
    }
    if (tid == 0) {
      for (int i = 0; i < G_STAGES; i++) {
        mbar_init(bar + B_GEMPTY + 8 * i, 2);
        mbar_init(bar + B_SFULL + 8 * i, 4);
        mbar_init(bar + B_SFREE + 8 * i, 1);
      }
      for (int i = 0; i < 2; i++) {
        mbar_init(bar + B_OFREE + 8 * i, 1);
        mbar_init(bar + B_QFULL + 8 * i, 1);
        mbar_init(bar + B_QEMPTY + 8 * i, 2);
        mbar_init(bar + B_KFULL + 8 * i, 1);
        mbar_init(bar + B_KEMPTY + 8 * i, 2);
        mbar_init(bar + B_VFULL + 8 * i, 1);
        mbar_init(bar + B_VEMPTY + 8 * i, 2);
      }
      for (int i = 0; i < O_STAGES; i++) {
        mbar_init(bar + B_OFULL + 8 * i, 1);
        mbar_init(bar + B_OEMPTY + 8 * i, 2);
      }
      mbar_init(bar + B_OY, 1);
      for (int i = 0; i < 3; i++) mbar_init(bar + seen_bar(i), 1);
      mbar_init(bar + B_OY2, 1);
      mbar_init(bar + B_DEAL, 1);
      mbar_init(bar + B_DEAL2, 1);
      mbar_init(bar + B_PAIR, 1);
      mbar_init(bar + B_OY + 8, 4);
      mbar_init(bar + B_OE, 4);
      mbar_init(bar + B_QDONE, 2);
      for (int i = 0; i < 8; i++) mbar_init(bar + B_CFULL + 8 * i, 1);
      for (int i = 0; i < CNT_N; i++) asm volatile("st.shared.u32 [%0], 0;" ::"r"(bar + B_PEND + 4 * i) : "memory");
      fence_barrier_init();
    }
    __syncthreads();
    asm volatile("barrier.cluster.arrive.relaxed.aligned;" ::: "memory");
    if ((mask & 1) && blockIdx.x >= 128) side_jobs(maps, sbase);
  }
  uint32_t smem0 = smem_u32(smem_raw);
  PHASE_PROLOGUE
  const bool do_qkv = (mask & 1) && blockIdx.x < 128, do_out = (mask & 4) && blockIdx.x < 128;
  TL(0, 1)

  if (wg != 2) {
    reg_alloc<232>();
    asm volatile("barrier.cluster.wait.acquire.aligned;" ::: "memory");
    if (wg == 1) named_bar_arrive(4, 256);
    uint32_t sn = 0;
    float rest[64], o[64], s[64];
    uint32_t q[32];
    if (do_qkv) {
      sn = qkv_consumer(maps, sbase, wg, mask & 2, q, rest, rt_zero);
    } else {
      undef_regs(rest);
#pragma unroll
      for (int j = 0; j < 32; j++) asm volatile("" : "=r"(q[j]));
    }
    undef_regs(o);
    undef_regs(s);
    TL(0, 2) TL(1, 0) TL(1, 1)
    const bool direct = do_out && wg == 0;
    float i0 = 0.f, i1 = 0.f;
    if (mask & 2) sn = attn_consumer(maps, sbase, wg, rt_zero, sn, q, rest, do_qkv, o, s, i0, i1);
    TL(2, 0)
    bool side = false;
    if (!direct) {
      wgmma_wait<0>();
      fence_regs(o);
      if (mask & 2) {
        const bool fused = mask & 4, mainc = blockIdx.x < 128;
        if (mainc) {
          PHASE_GIVEN
          put_o(sbase, wg, warp, lane, o, i0, i1);
          st_go(bar, wg, wtid, sn - 1);
        }
        const uint32_t b2 = blockIdx.x * 2 + (threadIdx.x >> 7);
        const uint32_t first = __shfl_sync(0xffffffffu, !fused ? b2 : mainc ? conv_first(maps) : (b2 - 255) * 128 - C_SIDE, 0);
        conv_consumer(maps, smem_u32(smem_raw), first, !fused ? 264 : mainc ? 16 : 1,
                      !fused ? DM : mainc ? (first | 127) + 1 - C_SIDE : first + C_SIDE, fused && !mainc,
                      fused && mainc);
      }
      side = (mask & 4) && blockIdx.x < 128;
    } else {
      out_gemm(maps, sbase, sn, mask & 2, o, s, i0, i1);
    }
    TL(1, 2) TL(2, 1) TL(2, 2) TL(3, 0) TL(3, 1)
    if (side + rt_zero) out_side(maps, smem_u32(smem_raw));
    tma_store_wait_read<0>();
  } else {
    reg_dealloc<40>();
    asm volatile("barrier.cluster.wait.acquire.aligned;" ::: "memory");
    const int w = __shfl_sync(0xffffffffu, tid >> 5, 0) - 8;
    if (w < 2) {
      if (do_qkv) prep_agent(maps, sbase, w, lane);
      if (elect_one()) store_agent(bar, w, w && do_out ? conv_first(maps) + 48 : 0, blockIdx.x >= 128 || mask == 4 ? 0 : mask == 1 ? 24 : 99);
      TL2(3, 2)
    } else {
      if (elect_one()) {
        const bool dry = w == 2;
        if (do_qkv && !dry) qkv_producer(maps, sbase, false);
        if (mask & 2) attn_producer(maps, sbase, do_qkv, do_out, dry);
        if (do_out) out_producer(maps, sbase, mask & 2, dry);
        if (dry) { TD(5) }
      }
      __syncwarp();
      if (w == 2) publisher(bar, tid & 31, !(mask & 2) ? 2 : do_out ? 3 : 4, !do_out ? 3 : do_qkv ? 0 : 2, do_qkv ? 4 : 0);
      if ((tid & 31) == 0) leave_kernel(mask);
    }
  }
}

typedef CUresult (*PFN_tmapEncode)(CUtensorMap*, CUtensorMapDataType, cuuint32_t, void*, const cuuint64_t*,
                                   const cuuint64_t*, const cuuint32_t*, const cuuint32_t*, CUtensorMapInterleave,
                                   CUtensorMapSwizzle, CUtensorMapL2promotion, CUtensorMapFloatOOBfill);
static PFN_tmapEncode s_encode = nullptr;

static void make_map_2d(CUtensorMap* m, const void* ptr, int rows, int cols, int box_rows) {
  cuuint64_t dims[2] = {(cuuint64_t)cols, (cuuint64_t)rows};
  cuuint64_t strides[1] = {(cuuint64_t)cols * 2};
  cuuint32_t box[2] = {cols < 64 ? 32u : 64u, (cuuint32_t)box_rows};
  cuuint32_t es[2] = {1, 1};
  s_encode(m, CU_TENSOR_MAP_DATA_TYPE_BFLOAT16, 2, const_cast<void*>(ptr), dims, strides, box, es,
           CU_TENSOR_MAP_INTERLEAVE_NONE, cols < 64 ? CU_TENSOR_MAP_SWIZZLE_64B : CU_TENSOR_MAP_SWIZZLE_128B, CU_TENSOR_MAP_L2_PROMOTION_L2_256B,
           CU_TENSOR_MAP_FLOAT_OOB_FILL_NONE);
}
static void make_map_3d(CUtensorMap* m, const void* ptr, int rows, int cols, int box_rows, int box_chunks) {
  cuuint64_t dims[3] = {64, (cuuint64_t)rows, (cuuint64_t)(cols / 64)};
  cuuint64_t strides[2] = {(cuuint64_t)cols * 2, 128};
  cuuint32_t box[3] = {64, (cuuint32_t)box_rows, (cuuint32_t)box_chunks};
  cuuint32_t es[3] = {1, 1, 1};
  s_encode(m, CU_TENSOR_MAP_DATA_TYPE_BFLOAT16, 3, const_cast<void*>(ptr), dims, strides, box, es,
           CU_TENSOR_MAP_INTERLEAVE_NONE, CU_TENSOR_MAP_SWIZZLE_128B, CU_TENSOR_MAP_L2_PROMOTION_L2_256B,
           CU_TENSOR_MAP_FLOAT_OOB_FILL_NONE);
}

static cudaLaunchConfig_t fused_cfg(cudaLaunchAttribute* at) {
  cudaLaunchConfig_t cfg = {};
  cfg.gridDim = dim3(132);
  cfg.blockDim = dim3(384);
  cfg.dynamicSmemBytes = SMEM_BYTES;
  cfg.stream = cudaStreamPerThread;
  at[0].id = cudaLaunchAttributeClusterDimension;
  at[0].val.clusterDim.x = 2;
  at[0].val.clusterDim.y = 1;
  at[0].val.clusterDim.z = 1;
  cfg.attrs = at;
  cfg.numAttrs = 1;
  return cfg;
}

extern "C" void kernel_launch(void* const* d_in, const int* in_sizes, int n_in, void* d_out, int out_size) {
  const bf16* x = (const bf16*)d_in[0];
  const bf16* ckv = (const bf16*)d_in[1];
  const bf16* wq = (const bf16*)d_in[2];
  const bf16* wuk = (const bf16*)d_in[3];
  const bf16* wuv = (const bf16*)d_in[4];
  const bf16* wo = (const bf16*)d_in[5];
  const bf16* bk = (const bf16*)d_in[7];
  const bf16* bv = (const bf16*)d_in[8];
  const bf16* shift_k = (const bf16*)d_in[9];
  const bf16* ssm_k = (const bf16*)d_in[10];
  const bf16* ssm_D = (const bf16*)d_in[11];
  const bf16* gate_w = (const bf16*)d_in[12];
  bf16* out = (bf16*)d_out;

  static void *pq = nullptr, *pk = nullptr, *pv = nullptr, *pctx = nullptr, *pb = nullptr, *pu = nullptr;
  static int max_clusters = 0;
  if (!s_encode) {
    void* fn = nullptr;
    cudaDriverEntryPointQueryResult qres;
    cudaGetDriverEntryPoint("cuTensorMapEncodeTiled", &fn, cudaEnableDefault, &qres);
    s_encode = (PFN_tmapEncode)fn;
    cudaGetSymbolAddress(&pq, g_q);
    cudaGetSymbolAddress(&pk, g_k);
    cudaGetSymbolAddress(&pv, g_v);
    cudaGetSymbolAddress(&pctx, g_ctx);
    cudaGetSymbolAddress(&pb, g_y2T);
    cudaGetSymbolAddress(&pu, g_kvT);
    cudaFuncSetAttribute(fused_kernel, cudaFuncAttributeMaxDynamicSharedMemorySize, SMEM_BYTES);
    cudaLaunchAttribute at[1];
    cudaLaunchConfig_t cfg = fused_cfg(at);
    if (cudaOccupancyMaxActiveClusters(&max_clusters, fused_kernel, &cfg) != cudaSuccess) max_clusters = 0;
  }

  Maps all = {};
  make_map_2d(&all.a[0], x, S_LEN, DM, 128);
  make_map_2d(&all.a[1], ckv, S_LEN, DC, 128);
  make_map_3d(&all.b[0], wq, DM, HDIM, 64, 4);
  make_map_3d(&all.b[1], wuk, DC, HDIM, 64, 4);
  make_map_3d(&all.b[2], wuv, DC, HDIM, 64, 4);
  make_map_2d(&all.c[0], pq, S_LEN, HDIM, 64);
  make_map_2d(&all.c[1], pk, S_LEN, HDIM, 64);
  make_map_2d(&all.c[2], pv, S_LEN, HDIM, 64);
  make_map_3d(&all.q, pq, S_LEN, HDIM, 128, 2);
  make_map_3d(&all.k, pk, S_LEN, HDIM, 128, 2);
  make_map_3d(&all.v, pv, S_LEN, HDIM, 128, 2);
  make_map_2d(&all.o, pctx, S_LEN, HDIM, 64);
  all.ssm_k = ssm_k;
  all.ssm_D = ssm_D;
  make_map_2d(&all.oa, pctx, S_LEN, HDIM, 128);
  make_map_2d(&all.ob, wo, HDIM, DM, 64);
  make_map_3d(&all.oc, out, S_LEN, DM, 16, 2);
  make_map_3d(&all.y, pb, DM, S_LEN, 16, 2);
  make_map_3d(&all.xs, x, S_LEN, DM, 16, 2);
  make_map_2d(&all.cu, pu, DM * 64, 32, 64);
  make_map_2d(&all.ch, ssm_k, DM * 64, 32, 64);

  make_map_2d(&all.bk, bk, S_LEN, DM, 35);
  make_map_2d(&all.bv, bv, S_LEN, DM, 32);
  for (int b = 0; b < 128; b++) {
    const int c = b >> 1, r = b & 1;
    const int G = c < 4 ? 0 : c < 36 ? (c - 4) % 8 : 1 + (c - 36) % 7;
    const int i = c < 4 ? 4 + c : c < 36 ? (c - 4) / 8 : 4 + (c - 36) / 7;
    all.id[b][0] = r + 2 * (i & 1) + 4 * (G & 3) + 16 * (i >> 1) + 64 * (G >> 2);
    all.id[b][1] = r + 2 * i + 16 * G;
    all.id[b][2] = r + 2 * G + 16 * i;
    all.id[b][3] = r + 2 * i == 15 ? 0x78 : 0xd8;
  }
  all.shift_k = shift_k;
  all.x = x;
  all.gate_w = gate_w;
  cudaLaunchAttribute at[1];
  cudaLaunchConfig_t cfg = fused_cfg(at);
  if (max_clusters >= 66) {
    cudaLaunchKernelEx(&cfg, fused_kernel, 7, x, wq, all);
  } else {
    for (int m = 1; m <= 4; m <<= 1) cudaLaunchKernelEx(&cfg, fused_kernel, m, x, wq, all);
  }
}
```

```cpp
#include <cuda_runtime.h>
#include <cuda_bf16.h>
#include <cuda.h>
#include <stdint.h>

typedef __nv_bfloat16 bf16;
#define INPLACE 3

constexpr int S_LEN = 2048;
constexpr int DM = 1024;
constexpr int NH = 32;
constexpr int HD = 128;
constexpr int DC = 512;
constexpr int HDIM = NH * HD;

__device__ __align__(1024) bf16 g_q[S_LEN * HDIM];
__device__ __align__(1024) bf16 g_k[S_LEN * HDIM];
__device__ __align__(1024) bf16 g_v[S_LEN * HDIM];
#define g_ctx g_q
__device__ __align__(1024) bf16 g_kvT[DM * S_LEN];
#define g_y2T g_kvT
__device__ __align__(1024) float g_gate[S_LEN];
enum { CNT_KV = 0, CNT_PREP = CNT_KV + 2, CNT_CTX, CNT_Y2 = CNT_CTX + 2, CNT_DONE = CNT_Y2 + 2, CNT_RANK, CNT_N };
__device__ unsigned int g_cnt[CNT_N * 32];
__device__ unsigned long long g_slot[128];

#define TL(k, i)
#define TL2(k, i)
#define TD(i)
#define CT(i)
#define GT(i)
#define GA(i)
#define ST(i)

__device__ __forceinline__ uint32_t smem_u32(const void* p) { return (uint32_t)__cvta_generic_to_shared(p); }

__device__ __forceinline__ void mbar_init(uint32_t bar, uint32_t count) {
  asm volatile("mbarrier.init.shared::cta.b64 [%0], %1;" ::"r"(bar), "r"(count));
}
__device__ __forceinline__ void mbar_expect_tx(uint32_t bar, uint32_t bytes) {
  asm volatile("mbarrier.arrive.expect_tx.shared::cta.b64 _, [%0], %1;" ::"r"(bar), "r"(bytes) : "memory");
}
__device__ __forceinline__ void mbar_arrive(uint32_t bar) {
  asm volatile("mbarrier.arrive.shared::cta.b64 _, [%0];" ::"r"(bar) : "memory");
}
__device__ __forceinline__ void mbar_wait(uint32_t bar, uint32_t parity) {
  uint32_t done;
  uint32_t spins = 0;
  do {
    asm volatile(
        "{\n.reg .pred p;\n"
        "mbarrier.try_wait.parity.shared::cta.b64 p, [%1], %2;\n"
        "selp.u32 %0, 1, 0, p;\n}\n"
        : "=r"(done)
        : "r"(bar), "r"(parity)
        : "memory");
    if (++spins > (1u << 22)) break;
  } while (!done);
}
__device__ __forceinline__ bool mbar_try(uint32_t bar, uint32_t parity) {
  uint32_t done;
  asm volatile(
      "{\n.reg .pred p;\n"
      "mbarrier.try_wait.parity.shared::cta.b64 p, [%1], %2;\n"
      "selp.u32 %0, 1, 0, p;\n}\n"
      : "=r"(done)
      : "r"(bar), "r"(parity)
      : "memory");
  return done != 0;
}
__device__ __forceinline__ bool mbar_test(uint32_t bar, uint32_t parity) {
  uint32_t done;
  asm volatile(
      "{\n.reg .pred p;\n"
      "mbarrier.test_wait.parity.shared::cta.b64 p, [%1], %2;\n"
      "selp.u32 %0, 1, 0, p;\n}\n"
      : "=r"(done)
      : "r"(bar), "r"(parity)
      : "memory");
  return done != 0;
}
__device__ __forceinline__ bool elect_one() {
  uint32_t pred;
  asm volatile("{\n.reg .pred p;\nelect.sync _|p, 0xffffffff;\nselp.u32 %0, 1, 0, p;\n}\n" : "=r"(pred));
  return pred != 0;
}
__device__ __forceinline__ void mbar_arrive_if(uint32_t bar, bool pred) {
  asm volatile(
      "{\n.reg .pred p;\nsetp.ne.b32 p, %1, 0;\n"
      "@p mbarrier.arrive.shared::cta.b64 _, [%0];\n}\n" ::"r"(bar),
      "r"((uint32_t)pred)
      : "memory");
}
__device__ __forceinline__ void mbar_wait_sleep(uint32_t bar, uint32_t parity) {
  uint32_t done;
  uint32_t spins = 0;
  do {
    asm volatile(
        "{\n.reg .pred p;\n"
        "mbarrier.try_wait.parity.shared::cta.b64 p, [%1], %2, %3;\n"
        "selp.u32 %0, 1, 0, p;\n}\n"
        : "=r"(done)
        : "r"(bar), "r"(parity), "r"(20000u)
        : "memory");
    if (++spins > (1u << 16)) break;
  } while (!done);
}
__device__ __forceinline__ void fence_barrier_init() {
  asm volatile("fence.mbarrier_init.release.cluster;" ::: "memory");
}
__device__ __forceinline__ void fence_proxy_async() {
  asm volatile("fence.proxy.async.shared::cta;" ::: "memory");
}
__device__ __forceinline__ void named_bar_sync(int id, int nthreads) {
  asm volatile("bar.sync %0, %1;" ::"r"(id), "r"(nthreads) : "memory");
}
__device__ __forceinline__ void named_bar_arrive(int id, int nthreads) {
  asm volatile("bar.arrive %0, %1;" ::"r"(id), "r"(nthreads) : "memory");
}
__device__ __forceinline__ void tma_load_2d(uint32_t dst, const CUtensorMap* m, uint32_t bar, int c0, int c1) {
  asm volatile(
      "cp.async.bulk.tensor.2d.shared::cluster.global.mbarrier::complete_tx::bytes [%0], [%1, {%3, %4}], [%2];" ::"r"(dst),
      "l"(reinterpret_cast<uint64_t>(m)), "r"(bar), "r"(c0), "r"(c1)
      : "memory");
}
__device__ __forceinline__ void tma_load_3d(uint32_t dst, const CUtensorMap* m, uint32_t bar, int c0, int c1, int c2) {
  asm volatile(
      "cp.async.bulk.tensor.3d.shared::cluster.global.mbarrier::complete_tx::bytes [%0], [%1, {%3, %4, %5}], [%2];" ::"r"(dst),
      "l"(reinterpret_cast<uint64_t>(m)), "r"(bar), "r"(c0), "r"(c1), "r"(c2)
      : "memory");
}
__device__ __forceinline__ void tma_store_2d(const CUtensorMap* m, uint32_t src, int c0, int c1) {
  asm volatile("cp.async.bulk.tensor.2d.global.shared::cta.bulk_group [%0, {%2, %3}], [%1];" ::"l"(
                   reinterpret_cast<uint64_t>(m)),
               "r"(src), "r"(c0), "r"(c1)
               : "memory");
}
__device__ __forceinline__ void bulk_load(uint32_t dst, const void* src, uint32_t bytes, uint32_t bar) {
  asm volatile("cp.async.bulk.shared::cluster.global.mbarrier::complete_tx::bytes [%0], [%1], %2, [%3];" ::"r"(dst),
               "l"(src), "r"(bytes), "r"(bar)
               : "memory");
}
__device__ __forceinline__ void tma_load_2d_mc(uint32_t dst, const CUtensorMap* m, uint32_t bar, int c0, int c1,
                                               uint16_t mask) {
  asm volatile(
      "cp.async.bulk.tensor.2d.shared::cluster.global.mbarrier::complete_tx::bytes.multicast::cluster [%0], [%1, {%3, "
      "%4}], [%2], %5;" ::"r"(dst),
      "l"(reinterpret_cast<uint64_t>(m)), "r"(bar), "r"(c0), "r"(c1), "h"(mask)
      : "memory");
}
__device__ __forceinline__ void mbar_arrive_cluster_if(uint32_t bar, uint32_t cta, bool pred) {
  asm volatile(
      "{\n.reg .b32 ra;\n.reg .pred p;\nsetp.ne.b32 p, %2, 0;\n"
      "mapa.shared::cluster.u32 ra, %0, %1;\n"
      "@p mbarrier.arrive.shared::cluster.b64 _, [ra];\n}\n" ::"r"(bar),
      "r"(cta), "r"((uint32_t)pred)
      : "memory");
}
__device__ __forceinline__ uint64_t policy_evict_first() {
  uint64_t pol;
  asm volatile("createpolicy.fractional.L2::evict_first.b64 %0, 1.0;" : "=l"(pol));
  return pol;
}
__device__ __forceinline__ void tma_load_2d_hint(uint32_t dst, const CUtensorMap* m, uint32_t bar, int c0, int c1,
                                                 uint64_t pol) {
  asm volatile(
      "cp.async.bulk.tensor.2d.shared::cluster.global.mbarrier::complete_tx::bytes.L2::cache_hint [%0], [%1, {%3, %4}], "
      "[%2], %5;" ::"r"(dst),
      "l"(reinterpret_cast<uint64_t>(m)), "r"(bar), "r"(c0), "r"(c1), "l"(pol)
      : "memory");
}
__device__ __forceinline__ void tma_load_3d_hint(uint32_t dst, const CUtensorMap* m, uint32_t bar, int c0, int c1,
                                                 int c2, uint64_t pol) {
  asm volatile(
      "cp.async.bulk.tensor.3d.shared::cluster.global.mbarrier::complete_tx::bytes.L2::cache_hint [%0], [%1, {%3, %4, "
      "%5}], [%2], %6;" ::"r"(dst),
      "l"(reinterpret_cast<uint64_t>(m)), "r"(bar), "r"(c0), "r"(c1), "r"(c2), "l"(pol)
      : "memory");
}
__device__ __forceinline__ void bulk_load_hint(uint32_t dst, const void* src, uint32_t bytes, uint32_t bar, uint64_t pol) {
  asm volatile(
      "cp.async.bulk.shared::cluster.global.mbarrier::complete_tx::bytes.L2::cache_hint [%0], [%1], %2, [%3], %4;" ::"r"(dst),
      "l"(src), "r"(bytes), "r"(bar), "l"(pol)
      : "memory");
}
__device__ __forceinline__ void cnt_signal_release(int which, uint32_t n) {
  asm volatile("red.release.gpu.global.add.u32 [%0], %1;" ::"l"(g_cnt + which * 32), "r"(n) : "memory");
}
__device__ __forceinline__ bool cnt_wait(int which, uint32_t target, uint32_t spins = 0) {
  uint32_t v;
  while (true) {
    asm volatile("ld.acquire.gpu.global.u32 %0, [%1];" : "=r"(v) : "l"(g_cnt + which * 32) : "memory");
    if (v >= target || ++spins > (1u << 18)) break;
    __nanosleep(64);
  }
  asm volatile("fence.proxy.async.global;" ::: "memory");
  return v >= target;
}
__device__ __forceinline__ void tma_store_3d(const CUtensorMap* m, uint32_t src, int c0, int c1, int c2) {
  asm volatile("cp.async.bulk.tensor.3d.global.shared::cta.bulk_group [%0, {%2, %3, %4}], [%1];" ::"l"(
                   reinterpret_cast<uint64_t>(m)),
               "r"(src), "r"(c0), "r"(c1), "r"(c2)
               : "memory");
}
__device__ __forceinline__ void tma_store_commit() { asm volatile("cp.async.bulk.commit_group;" ::: "memory"); }
template <int N>
__device__ __forceinline__ void tma_store_wait_read() {
  asm volatile("cp.async.bulk.wait_group.read %0;" ::"n"(N) : "memory");
}
template <int N>
__device__ __forceinline__ void tma_store_wait() {
  asm volatile("cp.async.bulk.wait_group %0;" ::"n"(N) : "memory");
}
__device__ __forceinline__ void wgmma_fence() { asm volatile("wgmma.fence.sync.aligned;" ::: "memory"); }
__device__ __forceinline__ void wgmma_commit() { asm volatile("wgmma.commit_group.sync.aligned;" ::: "memory"); }
template <int N>
__device__ __forceinline__ void wgmma_wait() {
  asm volatile("wgmma.wait_group.sync.aligned %0;" ::"n"(N) : "memory");
}
template <int R>
__device__ __forceinline__ void reg_alloc() { asm volatile("setmaxnreg.inc.sync.aligned.u32 %0;" ::"n"(R)); }
template <int R>
__device__ __forceinline__ void reg_dealloc() { asm volatile("setmaxnreg.dec.sync.aligned.u32 %0;" ::"n"(R)); }

__device__ __forceinline__ void stmatrix_x4(uint32_t addr, uint32_t r0, uint32_t r1, uint32_t r2, uint32_t r3) {
  asm volatile("stmatrix.sync.aligned.m8n8.x4.shared.b16 [%0], {%1, %2, %3, %4};" ::"r"(addr), "r"(r0), "r"(r1),
               "r"(r2), "r"(r3)
               : "memory");
}
__device__ __forceinline__ uint32_t pack_bf16(float lo, float hi) {
  uint32_t r;
  asm("cvt.rn.bf16x2.f32 %0, %1, %2;" : "=r"(r) : "f"(hi), "f"(lo));
  return r;
}
__device__ __forceinline__ float bf16_round(float x) { return __bfloat162float(__float2bfloat16_rn(x)); }
__device__ __forceinline__ float bf_lo(uint32_t v) { return __uint_as_float(v << 16); }
__device__ __forceinline__ float bf_hi(uint32_t v) { return __uint_as_float(v & 0xffff0000u); }
__device__ __forceinline__ uint4 lds128(uint32_t a) {
  uint4 v;
  asm volatile("ld.shared.v4.u32 {%0, %1, %2, %3}, [%4];" : "=r"(v.x), "=r"(v.y), "=r"(v.z), "=r"(v.w) : "r"(a));
  return v;
}
__device__ __forceinline__ void sts128(uint32_t a, uint4 v) {
  asm volatile("st.shared.v4.u32 [%0], {%1, %2, %3, %4};" ::"r"(a), "r"(v.x), "r"(v.y), "r"(v.z), "r"(v.w) : "memory");
}
__device__ __forceinline__ uint32_t mul_bf2(uint32_t a, uint32_t b) {
  uint32_t r;
  asm("mul.rn.bf16x2 %0, %1, %2;" : "=r"(r) : "r"(a), "r"(b));
  return r;
}
__device__ __forceinline__ float ex2(float x) {
  float y;
  asm("ex2.approx.ftz.f32 %0, %1;" : "=f"(y) : "f"(x));
  return y;
}
__device__ __forceinline__ float rcp(float x) {
  float y;
  asm("rcp.approx.ftz.f32 %0, %1;" : "=f"(y) : "f"(x));
  return y;
}
template <int N>
__device__ __forceinline__ void fence_regs(float (&r)[N]) {
#pragma unroll
  for (int i = 0; i < N; i++) asm volatile("" : "+f"(r[i])::"memory");
}

template <int N>
__device__ __forceinline__ void undef_regs(float (&r)[N]) {
#pragma unroll
  for (int i = 0; i < N; i++) asm volatile("" : "=f"(r[i]));
}
template <int N>
__device__ __forceinline__ void fence_regs_u(uint32_t (&r)[N]) {
#pragma unroll
  for (int i = 0; i < N; i++) asm volatile("" : "+r"(r[i])::"memory");
}

constexpr uint64_t DESC_SW128 = 1ull << 62;
__device__ __forceinline__ uint64_t make_desc(uint32_t addr, uint32_t lbo_bytes, uint32_t sbo_bytes, uint64_t swz) {
  return (uint64_t)((addr & 0x3FFFF) >> 4) | ((uint64_t)((lbo_bytes & 0x3FFFF) >> 4) << 16) |
         ((uint64_t)((sbo_bytes & 0x3FFFF) >> 4) << 32) | swz;
}

__device__ __forceinline__ uint64_t desc_add(uint64_t d, uint32_t off16) {
  return (d & 0xFFFFFFFF00000000ull) | (uint64_t)((uint32_t)d + off16);
}

__device__ __forceinline__ void wgmma_m64n256_ss_tb(float (&d)[128], uint64_t da, uint64_t db, int sd) {
  asm volatile(
    "{\n.reg .pred p;\nsetp.ne.b32 p, %130, 0;\n"
    "wgmma.mma_async.sync.aligned.m64n256k16.f32.bf16.bf16 "
    "{%0, %1, %2, %3, %4, %5, %6, %7, %8, %9, %10, %11, %12, %13, %14, %15, %16, %17, %18, %19, %20, %21, %22, %23, %24, %25, %26, %27, %28, %29, %30, %31, %32, %33, %34, %35, %36, %37, %38, %39, %40, %41, %42, %43, %44, %45, %46, %47, %48, %49, %50, %51, %52, %53, %54, %55, %56, %57, %58, %59, %60, %61, %62, %63, %64, %65, %66, %67, %68, %69, %70, %71, %72, %73, %74, %75, %76, %77, %78, %79, %80, %81, %82, %83, %84, %85, %86, %87, %88, %89, %90, %91, %92, %93, %94, %95, %96, %97, %98, %99, %100, %101, %102, %103, %104, %105, %106, %107, %108, %109, %110, %111, %112, %113, %114, %115, %116, %117, %118, %119, %120, %121, %122, %123, %124, %125, %126, %127}, %128, %129, p, 1, 1, 0, 1;\n}\n"
    : "+f"(d[0]), "+f"(d[1]), "+f"(d[2]), "+f"(d[3]), "+f"(d[4]), "+f"(d[5]), "+f"(d[6]), "+f"(d[7]), "+f"(d[8]), "+f"(d[9]), "+f"(d[10]), "+f"(d[11]), "+f"(d[12]), "+f"(d[13]), "+f"(d[14]), "+f"(d[15]), "+f"(d[16]), "+f"(d[17]), "+f"(d[18]), "+f"(d[19]), "+f"(d[20]), "+f"(d[21]), "+f"(d[22]), "+f"(d[23]), "+f"(d[24]), "+f"(d[25]), "+f"(d[26]), "+f"(d[27]), "+f"(d[28]), "+f"(d[29]), "+f"(d[30]), "+f"(d[31]), "+f"(d[32]), "+f"(d[33]), "+f"(d[34]), "+f"(d[35]), "+f"(d[36]), "+f"(d[37]), "+f"(d[38]), "+f"(d[39]), "+f"(d[40]), "+f"(d[41]), "+f"(d[42]), "+f"(d[43]), "+f"(d[44]), "+f"(d[45]), "+f"(d[46]), "+f"(d[47]), "+f"(d[48]), "+f"(d[49]), "+f"(d[50]), "+f"(d[51]), "+f"(d[52]), "+f"(d[53]), "+f"(d[54]), "+f"(d[55]), "+f"(d[56]), "+f"(d[57]), "+f"(d[58]), "+f"(d[59]), "+f"(d[60]), "+f"(d[61]), "+f"(d[62]), "+f"(d[63]), "+f"(d[64]), "+f"(d[65]), "+f"(d[66]), "+f"(d[67]), "+f"(d[68]), "+f"(d[69]), "+f"(d[70]), "+f"(d[71]), "+f"(d[72]), "+f"(d[73]), "+f"(d[74]), "+f"(d[75]), "+f"(d[76]), "+f"(d[77]), "+f"(d[78]), "+f"(d[79]), "+f"(d[80]), "+f"(d[81]), "+f"(d[82]), "+f"(d[83]), "+f"(d[84]), "+f"(d[85]), "+f"(d[86]), "+f"(d[87]), "+f"(d[88]), "+f"(d[89]), "+f"(d[90]), "+f"(d[91]), "+f"(d[92]), "+f"(d[93]), "+f"(d[94]), "+f"(d[95]), "+f"(d[96]), "+f"(d[97]), "+f"(d[98]), "+f"(d[99]), "+f"(d[100]), "+f"(d[101]), "+f"(d[102]), "+f"(d[103]), "+f"(d[104]), "+f"(d[105]), "+f"(d[106]), "+f"(d[107]), "+f"(d[108]), "+f"(d[109]), "+f"(d[110]), "+f"(d[111]), "+f"(d[112]), "+f"(d[113]), "+f"(d[114]), "+f"(d[115]), "+f"(d[116]), "+f"(d[117]), "+f"(d[118]), "+f"(d[119]), "+f"(d[120]), "+f"(d[121]), "+f"(d[122]), "+f"(d[123]), "+f"(d[124]), "+f"(d[125]), "+f"(d[126]), "+f"(d[127])
    : "l"(da), "l"(db), "r"(sd));
}

__device__ __forceinline__ void wgmma_m64n128_ss(float (&d)[64], uint64_t da, uint64_t db, int sd) {
  asm volatile(
    "{\n.reg .pred p;\nsetp.ne.b32 p, %66, 0;\n"
    "wgmma.mma_async.sync.aligned.m64n128k16.f32.bf16.bf16 "
    "{%0, %1, %2, %3, %4, %5, %6, %7, %8, %9, %10, %11, %12, %13, %14, %15, %16, %17, %18, %19, %20, %21, %22, %23, %24, %25, %26, %27, %28, %29, %30, %31, %32, %33, %34, %35, %36, %37, %38, %39, %40, %41, %42, %43, %44, %45, %46, %47, %48, %49, %50, %51, %52, %53, %54, %55, %56, %57, %58, %59, %60, %61, %62, %63}, %64, %65, p, 1, 1, 0, 0;\n}\n"
    : "+f"(d[0]), "+f"(d[1]), "+f"(d[2]), "+f"(d[3]), "+f"(d[4]), "+f"(d[5]), "+f"(d[6]), "+f"(d[7]), "+f"(d[8]), "+f"(d[9]), "+f"(d[10]), "+f"(d[11]), "+f"(d[12]), "+f"(d[13]), "+f"(d[14]), "+f"(d[15]), "+f"(d[16]), "+f"(d[17]), "+f"(d[18]), "+f"(d[19]), "+f"(d[20]), "+f"(d[21]), "+f"(d[22]), "+f"(d[23]), "+f"(d[24]), "+f"(d[25]), "+f"(d[26]), "+f"(d[27]), "+f"(d[28]), "+f"(d[29]), "+f"(d[30]), "+f"(d[31]), "+f"(d[32]), "+f"(d[33]), "+f"(d[34]), "+f"(d[35]), "+f"(d[36]), "+f"(d[37]), "+f"(d[38]), "+f"(d[39]), "+f"(d[40]), "+f"(d[41]), "+f"(d[42]), "+f"(d[43]), "+f"(d[44]), "+f"(d[45]), "+f"(d[46]), "+f"(d[47]), "+f"(d[48]), "+f"(d[49]), "+f"(d[50]), "+f"(d[51]), "+f"(d[52]), "+f"(d[53]), "+f"(d[54]), "+f"(d[55]), "+f"(d[56]), "+f"(d[57]), "+f"(d[58]), "+f"(d[59]), "+f"(d[60]), "+f"(d[61]), "+f"(d[62]), "+f"(d[63])
    : "l"(da), "l"(db), "r"(sd));
}

__device__ __forceinline__ void wgmma_m64n128_ss_tb(float (&d)[64], uint64_t da, uint64_t db, int sd) {
  asm volatile(
    "{\n.reg .pred p;\nsetp.ne.b32 p, %66, 0;\n"
    "wgmma.mma_async.sync.aligned.m64n128k16.f32.bf16.bf16 "
    "{%0, %1, %2, %3, %4, %5, %6, %7, %8, %9, %10, %11, %12, %13, %14, %15, %16, %17, %18, %19, %20, %21, %22, %23, %24, %25, %26, %27, %28, %29, %30, %31, %32, %33, %34, %35, %36, %37, %38, %39, %40, %41, %42, %43, %44, %45, %46, %47, %48, %49, %50, %51, %52, %53, %54, %55, %56, %57, %58, %59, %60, %61, %62, %63}, %64, %65, p, 1, 1, 0, 1;\n}\n"
    : "+f"(d[0]), "+f"(d[1]), "+f"(d[2]), "+f"(d[3]), "+f"(d[4]), "+f"(d[5]), "+f"(d[6]), "+f"(d[7]), "+f"(d[8]), "+f"(d[9]), "+f"(d[10]), "+f"(d[11]), "+f"(d[12]), "+f"(d[13]), "+f"(d[14]), "+f"(d[15]), "+f"(d[16]), "+f"(d[17]), "+f"(d[18]), "+f"(d[19]), "+f"(d[20]), "+f"(d[21]), "+f"(d[22]), "+f"(d[23]), "+f"(d[24]), "+f"(d[25]), "+f"(d[26]), "+f"(d[27]), "+f"(d[28]), "+f"(d[29]), "+f"(d[30]), "+f"(d[31]), "+f"(d[32]), "+f"(d[33]), "+f"(d[34]), "+f"(d[35]), "+f"(d[36]), "+f"(d[37]), "+f"(d[38]), "+f"(d[39]), "+f"(d[40]), "+f"(d[41]), "+f"(d[42]), "+f"(d[43]), "+f"(d[44]), "+f"(d[45]), "+f"(d[46]), "+f"(d[47]), "+f"(d[48]), "+f"(d[49]), "+f"(d[50]), "+f"(d[51]), "+f"(d[52]), "+f"(d[53]), "+f"(d[54]), "+f"(d[55]), "+f"(d[56]), "+f"(d[57]), "+f"(d[58]), "+f"(d[59]), "+f"(d[60]), "+f"(d[61]), "+f"(d[62]), "+f"(d[63])
    : "l"(da), "l"(db), "r"(sd));
}

template <int TB>
__device__ __forceinline__ void wgmma_m64n128_rs(float* d, uint32_t a0, uint32_t a1, uint32_t a2, uint32_t a3, uint64_t db, int sd) {
  asm volatile(
    "{\n.reg .pred p;\nsetp.ne.b32 p, %69, 0;\n"
    "wgmma.mma_async.sync.aligned.m64n128k16.f32.bf16.bf16 "
    "{%0, %1, %2, %3, %4, %5, %6, %7, %8, %9, %10, %11, %12, %13, %14, %15, %16, %17, %18, %19, %20, %21, %22, %23, %24, %25, %26, %27, %28, %29, %30, %31, %32, %33, %34, %35, %36, %37, %38, %39, %40, %41, %42, %43, %44, %45, %46, %47, %48, %49, %50, %51, %52, %53, %54, %55, %56, %57, %58, %59, %60, %61, %62, %63}, {%64, %65, %66, %67}, %68, p, 1, 1, %70;\n}\n"
    : "+f"(d[0]), "+f"(d[1]), "+f"(d[2]), "+f"(d[3]), "+f"(d[4]), "+f"(d[5]), "+f"(d[6]), "+f"(d[7]), "+f"(d[8]), "+f"(d[9]), "+f"(d[10]), "+f"(d[11]), "+f"(d[12]), "+f"(d[13]), "+f"(d[14]), "+f"(d[15]), "+f"(d[16]), "+f"(d[17]), "+f"(d[18]), "+f"(d[19]), "+f"(d[20]), "+f"(d[21]), "+f"(d[22]), "+f"(d[23]), "+f"(d[24]), "+f"(d[25]), "+f"(d[26]), "+f"(d[27]), "+f"(d[28]), "+f"(d[29]), "+f"(d[30]), "+f"(d[31]), "+f"(d[32]), "+f"(d[33]), "+f"(d[34]), "+f"(d[35]), "+f"(d[36]), "+f"(d[37]), "+f"(d[38]), "+f"(d[39]), "+f"(d[40]), "+f"(d[41]), "+f"(d[42]), "+f"(d[43]), "+f"(d[44]), "+f"(d[45]), "+f"(d[46]), "+f"(d[47]), "+f"(d[48]), "+f"(d[49]), "+f"(d[50]), "+f"(d[51]), "+f"(d[52]), "+f"(d[53]), "+f"(d[54]), "+f"(d[55]), "+f"(d[56]), "+f"(d[57]), "+f"(d[58]), "+f"(d[59]), "+f"(d[60]), "+f"(d[61]), "+f"(d[62]), "+f"(d[63])
    : "r"(a0), "r"(a1), "r"(a2), "r"(a3), "l"(db), "r"(sd), "n"(TB));
}

__device__ __forceinline__ void wgmma_m64n64_rs_tb(float (&d)[32], const uint32_t (&a)[4], uint64_t db, int sd) {
  asm volatile(
    "{\n.reg .pred p;\nsetp.ne.b32 p, %37, 0;\n"
    "wgmma.mma_async.sync.aligned.m64n64k16.f32.bf16.bf16 "
    "{%0, %1, %2, %3, %4, %5, %6, %7, %8, %9, %10, %11, %12, %13, %14, %15, %16, %17, %18, %19, %20, %21, %22, %23, %24, %25, %26, %27, %28, %29, %30, %31}, {%32, %33, %34, %35}, %36, p, 1, 1, 1;\n}\n"
    : "+f"(d[0]), "+f"(d[1]), "+f"(d[2]), "+f"(d[3]), "+f"(d[4]), "+f"(d[5]), "+f"(d[6]), "+f"(d[7]), "+f"(d[8]), "+f"(d[9]), "+f"(d[10]), "+f"(d[11]), "+f"(d[12]), "+f"(d[13]), "+f"(d[14]), "+f"(d[15]), "+f"(d[16]), "+f"(d[17]), "+f"(d[18]), "+f"(d[19]), "+f"(d[20]), "+f"(d[21]), "+f"(d[22]), "+f"(d[23]), "+f"(d[24]), "+f"(d[25]), "+f"(d[26]), "+f"(d[27]), "+f"(d[28]), "+f"(d[29]), "+f"(d[30]), "+f"(d[31])
    : "r"(a[0]), "r"(a[1]), "r"(a[2]), "r"(a[3]), "l"(db), "r"(sd));
}

__device__ __forceinline__ void wgmma_m64n32_rs_tb(float (&d)[16], const uint32_t (&a)[4], uint64_t db, int sd) {
  asm volatile(
    "{\n.reg .pred p;\nsetp.ne.b32 p, %21, 0;\n"
    "wgmma.mma_async.sync.aligned.m64n32k16.f32.bf16.bf16 "
    "{%0, %1, %2, %3, %4, %5, %6, %7, %8, %9, %10, %11, %12, %13, %14, %15}, {%16, %17, %18, %19}, %20, p, 1, 1, 1;\n}\n"
    : "+f"(d[0]), "+f"(d[1]), "+f"(d[2]), "+f"(d[3]), "+f"(d[4]), "+f"(d[5]), "+f"(d[6]), "+f"(d[7]), "+f"(d[8]), "+f"(d[9]), "+f"(d[10]), "+f"(d[11]), "+f"(d[12]), "+f"(d[13]), "+f"(d[14]), "+f"(d[15])
    : "r"(a[0]), "r"(a[1]), "r"(a[2]), "r"(a[3]), "l"(db), "r"(sd));
}

constexpr int G_STAGES = 4;
constexpr int G_A_BYTES = 128 * 64 * 2;
constexpr int G_B_BYTES = 256 * 64 * 2;
constexpr int G_STAGE_BYTES = G_A_BYTES + G_B_BYTES;
constexpr int G_STG_OFF = G_STAGES * G_STAGE_BYTES;
constexpr int BAR_OFF = G_STG_OFF + 32768 + 2048;
constexpr int SMEM_BYTES = BAR_OFF + 1024;
constexpr int B_GFULL = 0, B_GEMPTY = 32, B_SEEN = 64, B_PFULL = 224;
constexpr int B_KFULL = 80, B_KEMPTY = 96, B_VFULL = 112, B_VEMPTY = 128, B_QFULL = 144, B_QEMPTY = 160,
              B_QDONE = 184;
constexpr int B_CFULL = 192;
constexpr int B_OFREE = 256, B_OFULL = 272, B_OEMPTY = 320, B_OY = 368, B_OY2 = 384, B_OE = 768;
constexpr int B_DEAL = 312, B_DEAL2 = 360, B_LIST = 640, B_PAIR = 504;
constexpr int B_SFULL = 392, B_SFREE = 424, B_PEND = 456, B_SCMD = 512;

#define PHASE_PROLOGUE                                                                \
  uint32_t tid, rt_zero;                                                              \
  asm volatile("mov.u32 %0, %%tid.x;" : "=r"(tid));                                   \
  asm volatile("mov.u32 %0, %%nctaid.y;" : "=r"(rt_zero));                            \
  asm volatile("" : "+r"(smem0));                                                     \
  rt_zero = __shfl_sync(0xffffffffu, rt_zero >> 8, 0);   \
  const uint32_t sbase = __shfl_sync(0xffffffffu, smem0, 0);                          \
  const uint32_t bar = sbase + BAR_OFF;                                               \
  const int wg = __shfl_sync(0xffffffffu, tid >> 7, 0);                               \
  const int warp = (tid >> 5) & 3, lane = tid & 31, wtid = tid & 127;                 \
  (void)rt_zero; (void)bar; (void)warp; (void)lane; (void)wtid;

#define PHASE_GIVEN PHASE_GIVEN_(0)
#define PHASE_GIVEN_(z)                                                               \
  uint32_t tid;                                                                       \
  asm volatile("mov.u32 %0, %%tid.x;" : "=r"(tid));                                   \
  tid |= z;                               \
  const uint32_t bar = sbase + BAR_OFF;                                               \
  const int warp = (tid >> 5) & 3, lane = tid & 31, wtid = tid & 127;

enum { ST_BOX1, ST_BOX2, ST_BOX2Q, ST_BOX2L };
__device__ __forceinline__ void st_cmd(uint32_t bar, int wg, int wtid, uint32_t n, int kind, const void* dst,
                                       uint32_t src, int c0, int c1, int sig, uint32_t lazy = 0) {
  if (wtid == 0) {
    const uint32_t c = bar + B_SCMD + wg * 64 + (n & 1) * 32;
    const uint64_t d = reinterpret_cast<uint64_t>(dst);
    sts128(c, make_uint4(kind, src, c0, c1));
    sts128(c + 16, make_uint4((uint32_t)d, (uint32_t)(d >> 32), sig, lazy));
  }
}
__device__ __forceinline__ void st_go(uint32_t bar, int wg, int wtid, uint32_t n) {
  fence_proxy_async();
  __syncwarp();
  mbar_arrive_if(bar + B_SFULL + wg * 16 + (n & 1) * 8, (wtid & 31) == 0);
}
__device__ __forceinline__ void st_post(uint32_t bar, int wg, int wtid, uint32_t n, int kind, const void* dst,
                                        uint32_t src, int c0, int c1, int sig, uint32_t lazy = 0) {
  st_cmd(bar, wg, wtid, n, kind, dst, src, c0, c1, sig, lazy);
  st_go(bar, wg, wtid, n);
}
__device__ __forceinline__ void st_wait(uint32_t bar, int wg, uint32_t n) {
  const uint32_t b = bar + B_SFREE + wg * 16 + (n & 1) * 8;
  if (!mbar_try(b, ~(n >> 1) & 1)) mbar_wait(b, ~(n >> 1) & 1);
}
__device__ __forceinline__ void note(uint32_t bar, uint32_t cnt) {
  asm volatile("red.release.cta.shared.add.u32 [%0], 1;" ::"r"(bar + B_PEND + 4 * cnt) : "memory");
}
#define LEAD 2
#define HOLD 1
#define HP6 61
#define HP7 62
#define QW 1
#define KS 1
#define LAZY_NS 250
#define DEAL_NS 400
#define DEAL_NS2 1250
constexpr uint32_t C_NONE = 0x10000;
__device__ __forceinline__ void deal(uint32_t bar, uint32_t r, uint32_t t, uint32_t own) {
  uint64_t p;
  uint32_t spins = 0;
  while (true) {
    asm volatile("ld.relaxed.gpu.global.u64 %0, [%1];" : "=l"(p) : "l"(g_slot + 127 - r) : "memory");
    if (p || ++spins > (1u << 18)) break;
    __nanosleep(100);
  }
  const uint32_t pc = (uint32_t)p;
  int dt = (uint32_t)(p >> 32) - t;
  if (r >= 64) {
    sts128(bar + B_LIST, make_uint4(-dt > DEAL_NS2 ? C_NONE : own - 16, -dt > DEAL_NS ? C_NONE : own, C_NONE, C_NONE));
    mbar_arrive(bar + B_DEAL);
    dt = 0;
  }
  sts128(bar + B_LIST + 16, make_uint4(dt > DEAL_NS ? pc : C_NONE, dt > DEAL_NS2 ? pc - 16 : C_NONE, C_NONE, C_NONE));
  mbar_arrive(bar + B_DEAL2);
}
__device__ __forceinline__ void store_agent(uint32_t bar, int wg, uint32_t last_ch, uint32_t n_end) {
  mbar_arrive(bar + B_SFREE + wg * 16);
  mbar_arrive(bar + B_SFREE + wg * 16 + 8);
  bool more = true;
  for (uint32_t n = 0; n < n_end && more; n++) {
    mbar_wait_sleep(bar + B_SFULL + wg * 16 + (n & 1) * 8, (n >> 1) & 1);
    const uint4 c = lds128(bar + B_SCMD + wg * 64 + (n & 1) * 32);
    const uint4 d = lds128(bar + B_SCMD + wg * 64 + (n & 1) * 32 + 16);
    uint32_t t;
    asm volatile("mov.u32 %0, %%globaltimer_lo;" : "=r"(t));
    uint32_t r = 0, tp = t;
    if (c.x == ST_BOX2L && last_ch) {
      mbar_expect_tx(bar + B_PAIR, 4);
      asm volatile(
          "{\n.reg .b32 ra;\nmapa.shared::cluster.u32 ra, %0, %1;\n"
          "st.async.weak.shared::cluster.mbarrier::complete_tx::bytes.u32 [ra + 224], %2, [ra];\n}\n" ::"r"(bar + B_PAIR),
          "r"(~blockIdx.x & 1), "r"(t)
          : "memory");
      mbar_wait_sleep(bar + B_PAIR, 0);
      r = atomicAdd(g_cnt + CNT_RANK * 32, 1u) & 127;
      asm volatile("ld.shared.u32 %0, [%1];" : "=r"(tp) : "r"(bar + B_PAIR + 224) : "memory");
      if ((int)(tp - t) < 0) tp = t;
      asm volatile("st.relaxed.gpu.global.u64 [%0], %1;" ::"l"(g_slot + r), "l"(((uint64_t)tp << 32) | last_ch) : "memory");
      if (r < 64) {
        sts128(bar + B_LIST, make_uint4(last_ch - 16, last_ch, C_NONE, C_NONE));
        mbar_arrive(bar + B_DEAL);
      } else {
        deal(bar, r, tp, last_ch);
      }
    }
    for (uint32_t t1 = t; d.w && t1 - t < (2 * d.w + wg) * LAZY_NS;) {
      __nanosleep(200);
      asm volatile("mov.u32 %0, %%globaltimer_lo;" : "=r"(t1));
    }
    const CUtensorMap* dst = reinterpret_cast<const CUtensorMap*>((uint64_t)d.x | ((uint64_t)d.y << 32));
    tma_store_2d(dst, c.y, c.z, c.w);
    if (c.x >= ST_BOX2) tma_store_2d(dst, c.y + 8192, c.z + 64, c.w);
    tma_store_commit();
    tma_store_wait_read<0>();
    mbar_arrive(bar + B_SFREE + wg * 16 + (n & 1) * 8);
    if (c.x == ST_BOX2L) mbar_arrive(bar + B_OFREE + 8 * wg);
    if ((int)d.z >= 0) {
      tma_store_wait<0>();
      if (d.z == 0) { TD(6) }
      asm volatile("fence.proxy.async.global;" ::: "memory");
      if (c.x == ST_BOX2Q) mbar_arrive(bar + B_QDONE);
      else note(bar, d.z);
      if (c.x == ST_BOX2L) {
        note(bar, CNT_DONE);
        more = false;
        if (last_ch && r < 64) deal(bar, r, tp, last_ch);
      }
    }
  }
  if (more) note(bar, CNT_DONE);
}

struct Maps {
  const bf16 *shift_k, *x, *gate_w, *ssm_k, *ssm_D;
  uint8_t id[128][4];
  CUtensorMap a[2];
  CUtensorMap b[3];
  CUtensorMap c[3];
  CUtensorMap bk, bv;
  CUtensorMap q, k, v, o;
  CUtensorMap oa, ob, oc;
  CUtensorMap y, xs;
  CUtensorMap cu, ch;
};

constexpr int P_SLOT = 67 * 128, P_V = 35 * 128, P_TAPS = 2 * P_SLOT;
__device__ __forceinline__ void ldsm4t(uint32_t (&r)[4], uint32_t a) {
  asm volatile("ldmatrix.sync.aligned.m8n8.x4.trans.shared.b16 {%0, %1, %2, %3}, [%4];"
               : "=r"(r[0]), "=r"(r[1]), "=r"(r[2]), "=r"(r[3])
               : "r"(a));
}
__device__ __forceinline__ uint32_t fma_bf2(uint32_t a, uint32_t b, uint32_t c) {
  uint32_t r;
  asm("fma.rn.bf16x2 %0, %1, %2, %3;" : "=r"(r) : "r"(a), "r"(b), "r"(c));
  return r;
}
__device__ __forceinline__ void prep_agent(const Maps& maps, uint32_t sbase, int w, int lane) {
  const uint32_t bar = sbase + BAR_OFF, pb = bar + B_PFULL + w * 16;
  const int d0 = (blockIdx.x >> 3) * 64, t0 = (blockIdx.x & 7) * 256 + w * 128;
  mbar_wait_sleep(bar + B_GFULL + 8 * (G_STAGES - 1), 0);
#pragma unroll 1
  for (int i = -1; i < 4; i++) {
    GA(82 + 2 * i)
    if (i >= 0) mbar_wait_sleep(pb + (i & 1) * 8, i >> 1);
    GA(83 + 2 * i)
    const uint32_t so = sbase + G_STG_OFF + w * (P_TAPS + 512) + (i & 1) * P_SLOT;
    if (i < 3 && elect_one()) {
      const uint32_t b = pb + (~i & 1) * 8, dst = so + (i & 1 ? -P_SLOT : P_SLOT);
      mbar_expect_tx(b, i < 0 ? P_SLOT + 512 : P_SLOT);
      const uint64_t pol = policy_evict_first();
      tma_load_2d_hint(dst, &maps.bk, b, d0, t0 + 32 * i + 29, pol);
      tma_load_2d_hint(dst + P_V, &maps.bv, b, d0, t0 + 32 * i + 32, pol);
      if (i < 0) bulk_load(sbase + G_STG_OFF + P_TAPS, maps.shift_k + d0 * 4, 512, b);
    }
    if (i < 0) continue;
    uint32_t ak[4];
#pragma unroll
    for (int r = 0; r < 4; r++) {
      const uint32_t a = so / 128 + r + 4 * (lane & 6) + (((lane >> 2) ^ lane) & 6) + (lane & 1);
      ak[r] = a * 128 + (a & 7) * 16;
    }
    bf16* dst = g_kvT + (size_t)(d0 + (lane >> 2)) * S_LEN + t0 + ((lane & 3) + 4 * i) * 8;
#pragma unroll 1
    for (int cg = 0; cg < 128; cg += 16) {
      uint32_t t01, t23, k[4][4], v[4];
      asm volatile("ld.shared.v2.u32 {%0, %1}, [%2];"
                   : "=r"(t01), "=r"(t23)
                   : "r"(sbase + G_STG_OFF + P_TAPS + cg * 4 + (lane >> 2) * 8));
#pragma unroll
      for (int r = 0; r < 4; r++) ldsm4t(k[r], ak[r] ^ cg);
      ldsm4t(v, (ak[3] ^ cg) + 4096);
      const uint32_t w0 = __byte_perm(t01, 0, 0x1010), w1 = __byte_perm(t01, 0, 0x3232);
      const uint32_t w2 = __byte_perm(t23, 0, 0x1010), w3 = __byte_perm(t23, 0, 0x3232);
#pragma unroll
      for (int j = 0; j < 4; j++)
        v[j] = mul_bf2(fma_bf2(k[3][j], w0, fma_bf2(k[2][j], w1, fma_bf2(k[1][j], w2, mul_bf2(k[0][j], w3)))), v[j]);
      const bool s1 = lane & 1, s2 = lane & 2;
      const uint32_t a0 = s1 ? v[1] : v[0], a1 = s1 ? v[0] : v[1], a2 = s1 ? v[3] : v[2], a3 = s1 ? v[2] : v[3];
      *reinterpret_cast<uint4*>(dst) = make_uint4(s2 ? a2 : a0, s2 ? a3 : a1, s2 ? a0 : a2, s2 ? a1 : a3);
      dst += 8 * S_LEN;
    }
    fence_proxy_async();
    __syncwarp();
  }
  GA(90)
  if (lane == 0) note(bar, CNT_PREP);
  __syncwarp();
  GA(91)
}

__device__ __forceinline__ void qkv_tile(const Maps& maps, int it, int& which, int& m_tile, int& n_tile) {
  const bool q = it == 0 || it >= 5;
  const int b = maps.id[blockIdx.x][it >= 5];
  which = q ? 0 : 2 - (it & 1);
  m_tile = b & 15;
  n_tile = (b >> 4) * 2 + ((0x19 >> it) & 1);
}

constexpr int G_NTILES = 6;
__device__ __forceinline__ uint32_t qkv_flip(int it) { return ((0x0b >> it) & 1) * 3; }
__device__ __forceinline__ void qkv_producer(const Maps& maps, uint32_t sbase, bool first) {
  const uint32_t bar = sbase + BAR_OFF;
  uint32_t stage = 0, phase = 0;
#pragma unroll 1
  for (int it = 0; it < (first ? 1 : G_NTILES); it++) {
    int which, m_tile, n_tile;
    qkv_tile(maps, it, which, m_tile, n_tile);
    const CUtensorMap* ma = &maps.a[which == 0 ? 0 : 1];
    const CUtensorMap* mb = &maps.b[which];
    const int nk = first ? G_STAGES : which == 0 ? 16 : 8;
#pragma unroll 1
    for (int kt = (it == 0 && !first) ? G_STAGES : 0; kt < nk; kt++) {
      if (!first) mbar_wait_sleep(bar + B_GEMPTY + 8 * stage, phase);
      const uint32_t fb = bar + B_GFULL + 8 * stage;
      const uint32_t sa = sbase + stage * G_STAGE_BYTES;
      const int k0 = (kt ^ ((0x14 >> it) & 1) * 7) * 64;
      const bool keep = ((0x1c >> it) & 1) && kt < G_STAGES;
      mbar_expect_tx(fb, keep ? G_B_BYTES : G_STAGE_BYTES);
      if (!keep) tma_load_2d(sbase + (stage ^ qkv_flip(it)) * G_STAGE_BYTES, ma, fb, k0, m_tile * 128);
      tma_load_3d(sa + G_A_BYTES, mb, fb, 0, k0, n_tile * 4);
      if (++stage == G_STAGES) { stage = 0; phase ^= 1; }
      {
        const int b = maps.id[blockIdx.x][1];
        if (it == 2 && kt == (b & 7)) {
          for (int i = 0; i < 2; i++)
            asm volatile("cp.async.bulk.prefetch.tensor.2d.L2.global.tile [%0, {%1, %2}];" ::"l"(&maps.a[0]),
                         "r"((b >> 4) * 128 + i * 64), "r"((b & 15) * 128)
                         : "memory");
          asm volatile("cp.async.bulk.prefetch.tensor.3d.L2.global.tile [%0, {%1, %2, %3}];" ::"l"(&maps.b[1 + ((b >> 3) & 1)]),
                       "r"(0), "r"((b & 7) * 64), "r"((b >> 4) * 8 + 4)
                       : "memory");
        }
        if (it == 3 && kt == (b & 7))
          asm volatile("cp.async.bulk.prefetch.tensor.3d.L2.global.tile [%0, {%1, %2, %3}];" ::"l"(&maps.b[0]), "r"(0),
                       "r"((b & 15) * 64), "r"((b >> 4) * 8)
                       : "memory");
      }
    }
  }
}

__device__ __forceinline__ uint32_t seen_bar(uint32_t item) { return B_SEEN + ((0x700800u >> (8 * item)) & 255); }
__device__ __noinline__ void publisher(uint32_t bar, int lane, uint32_t nsrc, uint32_t item, uint32_t mine) {
  uint32_t done = 0, tot = 0;
#pragma unroll 1
  for (uint32_t spins = 0; (done < nsrc || item < 3) && spins < (1u << 20); spins++) {
    const uint32_t cnt = item ? CNT_CTX - 1 + item : CNT_KV + 1;
    if (item < 3 && __shfl_sync(0xffffffffu, tot, cnt) >= mine >> !item) {
      uint32_t v;
      asm volatile("ld.acquire.gpu.global.u32 %0, [%1];" : "=r"(v) : "l"(g_cnt + (lane ? cnt : CNT_PREP) * 32) : "memory");
      if (__all_sync(0xffffffffu, v >= (lane ? 512 >> !item : 260))) {
        asm volatile("fence.proxy.async.global;" ::: "memory");
        mbar_arrive_if(bar + seen_bar(item), lane == 0);
        item++;
      }
    }
    uint32_t v = 0;
    if (lane < CNT_N)
      asm volatile("atom.acquire.cta.shared.exch.b32 %0, [%1], 0;" : "=r"(v) : "r"(bar + B_PEND + 4 * lane) : "memory");
    done += __shfl_sync(0xffffffffu, v, CNT_DONE);
    if (lane == CNT_DONE) v = 0;
    if (done == nsrc && lane < CNT_DONE) {
      uint32_t w;
      asm volatile("atom.acquire.cta.shared.exch.b32 %0, [%1], 0;" : "=r"(w) : "r"(bar + B_PEND + 4 * lane) : "memory");
      v += w;
    }
    if (v && lane == 0) { TD(0) }
    if (v) cnt_signal_release(lane, v);
    tot += v;
    if (v && lane == 0) { TD(1) }
    if (!__any_sync(0xffffffffu, v != 0)) __nanosleep(item == 1 ? 1000 : 200);
  }
  __threadfence();
  __syncwarp();
}

__device__ __forceinline__ void gate_rows(const Maps& maps, uint32_t sbase, int w48, int w12, int lane) {
  const uint32_t buf = sbase + w12 * 16384, gb = sbase + BAR_OFF + 768 + w12 * 16;
  if (lane == 0) {
    mbar_init(gb, 1);
    mbar_init(gb + 8, 1);
    fence_barrier_init();
    for (int i = 0; i < 2; i++) {
      mbar_expect_tx(gb + 8 * i, 8192);
      bulk_load(buf + i * 8192, maps.x + (size_t)(w48 + 48 * i) * 4 * DM, 8192, gb + 8 * i);
    }
  }
  __syncwarp();
  uint4 wv[4];
#pragma unroll
  for (int i = 0; i < 4; i++) wv[i] = __ldg(reinterpret_cast<const uint4*>(maps.gate_w + (i * 32 + lane) * 8));
  int it = 0;
#pragma unroll 1
  for (int row = w48 * 4; row < S_LEN; row += 48 * 4, it++) {
    mbar_wait(gb + 8 * (it & 1), (it >> 1) & 1);
    uint4 xv[4][4];
#pragma unroll
    for (int r = 0; r < 4; r++)
#pragma unroll
      for (int i = 0; i < 4; i++) xv[r][i] = lds128(buf + (it & 1) * 8192 + r * 2048 + (i * 32 + lane) * 16);
    float d[2][4];
#pragma unroll
    for (int pr = 0; pr < 2; pr++) {
      d[pr][0] = d[pr][1] = d[pr][2] = d[pr][3] = 0.f;
      auto acc = [&](uint32_t a0, uint32_t a2, uint32_t b0, uint32_t b2, uint32_t w0, uint32_t w2) {
        asm volatile(
            "mma.sync.aligned.m16n8k16.row.col.f32.bf16.bf16.f32 {%0, %1, %2, %3}, {%4, %5, %6, %7}, {%8, %8}, "
            "{%0, %1, %2, %3};"
            : "+f"(d[pr][0]), "+f"(d[pr][1]), "+f"(d[pr][2]), "+f"(d[pr][3])
            : "r"(mul_bf2(a0, w0)), "r"(mul_bf2(b0, w0)), "r"(mul_bf2(a2, w2)), "r"(mul_bf2(b2, w2)), "r"(0x3f803f80u));
      };
#pragma unroll
      for (int i = 0; i < 4; i++) {
        acc(xv[2 * pr][i].x, xv[2 * pr][i].y, xv[2 * pr + 1][i].x, xv[2 * pr + 1][i].y, wv[i].x, wv[i].y);
        acc(xv[2 * pr][i].z, xv[2 * pr][i].w, xv[2 * pr + 1][i].z, xv[2 * pr + 1][i].w, wv[i].z, wv[i].w);
      }
    }
    float sum = (lane & 2) ? ((lane & 1) ? d[1][2] : d[1][0]) : ((lane & 1) ? d[0][2] : d[0][0]);
#pragma unroll
    for (int off = 16; off >= 4; off >>= 1) sum += __shfl_xor_sync(0xffffffffu, sum, off);
    if (lane < 4) g_gate[row + lane] = bf16_round(rcp(1.0f + __expf(-bf16_round(sum))));
    if (lane == 0 && row + 2 * 48 * 4 < S_LEN) {
      mbar_expect_tx(gb + 8 * (it & 1), 8192);
      bulk_load(buf + (it & 1) * 8192, maps.x + (size_t)(row + 2 * 48 * 4) * DM, 8192, gb + 8 * (it & 1));
    }
  }
}

constexpr float Q_SCALE = 0.08838834764831845f * 1.4426950408889634f;
__device__ __forceinline__ uint32_t qkv_consumer(const Maps& maps, const uint32_t sbase, const int wg, bool fused,
                                                 uint32_t (&q)[32], float (&rest)[64], uint32_t rt_zero) {
  PHASE_GIVEN_(rt_zero)
  constexpr int NTILES = G_NTILES;
  float acc[128];
  const uint32_t stg = sbase + G_STG_OFF + wg * 18432;
  const int st_row = warp * 16 + (lane & 7) + ((lane >> 3) & 1) * 8;
  const int st_cb = lane >> 4;
  uint32_t pend[64];
  const CUtensorMap* pend_map = nullptr;
  int pend_c0 = 0, pend_c1 = 0;
  uint32_t sn = 0;
  uint32_t st_a[4];
#pragma unroll
  for (int jp = 0; jp < 4; jp++) {
    st_a[jp] = stg + st_row * 128 + (((jp * 2 + st_cb) ^ (st_row & 7)) << 4);
    asm volatile("" : "+r"(st_a[jp]));
  }
  auto put_box = [&](uint32_t off, const uint32_t* v) {
#pragma unroll
    for (int jp = 0; jp < 4; jp++) stmatrix_x4(st_a[jp] + off, v[jp * 4], v[jp * 4 + 1], v[jp * 4 + 2], v[jp * 4 + 3]);
  };
  GT(gti++)
  const int hf = wg ^ 1;
  const uint64_t da0 = make_desc(sbase + hf * 8192, 16, 1024, DESC_SW128);
  const uint64_t db0 = make_desc(sbase + G_A_BYTES, 8192, 1024, DESC_SW128);
  uint32_t g = 0, oa = 3 * (G_STAGE_BYTES / 16), ob = 0;
  bool go = false;
  mbar_wait(bar + B_GFULL, 0);
  uint32_t gend = 16, when = 0;
#pragma unroll 1
  for (int it = 0;; it++) {
    bool more = false;
#pragma unroll 1
    do {
      GT(gti++)
      wgmma_fence();
#pragma unroll
      for (int kk = 0; kk < 4; kk++)
        wgmma_m64n256_ss_tb(acc, desc_add(da0, oa + kk * 2), desc_add(db0, ob + kk * 128), kk || more);
      wgmma_commit();
      if (go) st_go(bar, wg, wtid, sn - 1);
      g++;
      if (g + wg * 64 == 62 + LEAD) named_bar_arrive(6, 256);
      const uint32_t full = (bar + B_GFULL) + 8 * (g & 3);
      const bool here = mbar_test(full, (g >> 2) & 1) || g >= 64;
      oa = ((g & 3) ^ ((0x17 >> (g >> 3)) & 1) * 3) * (G_STAGE_BYTES / 16);
      ob = (g & 3) * (G_STAGE_BYTES / 16);
      go = when & 1;
      when >>= 1;
      if (go) {
        const int c = sn & 3;
        st_wait(bar, wg, sn - 2);
        st_cmd(bar, wg, wtid, sn, ST_BOX1, pend_map, stg + (c & 1) * 8192, pend_c0 + c * 64, pend_c1,
               (c == 3 && it > 1) ? CNT_KV + (it > 4) : -1);
        switch (c) {
          case 0: put_box(0, pend); break;
          case 1: put_box(8192, pend + 16); break;
          case 2: put_box(0, pend + 32); break;
          default: put_box(8192, pend + 48); break;
        }
        sn++;
      }
      if (it < NTILES) {
        wgmma_wait<1>();
        mbar_arrive_if((bar + B_GEMPTY) + 8 * ((g + 2) & 3), wtid == 32 && more);
        if (wg && g == HP6) named_bar_sync(6, 256);
        if (HOLD && g == HP7 && wg && fused) named_bar_sync(7, 256);
        if (!here) mbar_wait(full, (g >> 2) & 1);
      }
      more = true;
    } while (g != gend);
    wgmma_wait<0>();
    fence_regs(acc);
    GT(gti++)
    mbar_arrive_if((bar + B_GEMPTY) + 8 * 3, wtid == 32);
    int which, m_tile, n_tile;
    qkv_tile(maps, it, which, m_tile, n_tile);
    if (it == NTILES - fused) break;
    if (which == KS) {
#pragma unroll
      for (int j = 0; j < 128; j++) acc[j] *= Q_SCALE;
    }
#pragma unroll
    for (int j = 0; j < 64; j++) pend[j] = pack_bf16(acc[2 * j], acc[2 * j + 1]);
    pend_map = &maps.c[which];
    pend_c0 = n_tile * 256;
    pend_c1 = m_tile * 128 + hf * 64;
    gend += it == 4 ? 16 : 8;
    when = (it == 4 ? 0x922 : 0x55) << wg;
  }
  if (go) st_go(bar, wg, wtid, sn - 1);
#pragma unroll
  for (int j = 0; j < 32; j++)
    q[j] = KS ? pack_bf16(acc[2 * j], acc[2 * j + 1]) : pack_bf16(acc[2 * j] * Q_SCALE, acc[2 * j + 1] * Q_SCALE);
#pragma unroll
  for (int j = 0; j < 64; j++) rest[j] = acc[64 + j];
  GT(gti++)
  return sn;
}

constexpr int A_TILE = 128 * 128 * 2;
constexpr int A_K_OFF = 0, A_Q_OFF = A_TILE, A_V_OFF = 3 * A_TILE;
constexpr int A_O_OFF = 6 * A_TILE;
constexpr int A_ITEMS = NH * (S_LEN / 128);

constexpr uint32_t A_ORDER = 0x3120, A_STEPS = 34;
__device__ __forceinline__ int item_m(uint32_t it) { return it & 15; }
__device__ __forceinline__ int item_h(uint32_t it) { return it >> 4; }

constexpr int C_V = 16384, C_MAT = 24576;
constexpr float C_ALPHA = 0.07874506561842957f;
__device__ __forceinline__ void sincos_turn(int p, float inv, float& c, float& s) {
  const float a = (float)p * (inv * 6.283185307179586f);
  asm("cos.approx.ftz.f32 %0, %1;" : "=f"(c) : "f"(a));
  asm("sin.approx.ftz.f32 %0, %1;" : "=f"(s) : "f"(a));
}

__device__ __forceinline__ uint32_t head_of(const Maps& maps, uint32_t r) { return (maps.id[blockIdx.x & 127][3] >> (2 * r)) & 3; }
__device__ __forceinline__ uint32_t item_at(const Maps& maps, uint32_t h) {
  const uint32_t b = maps.id[blockIdx.x & 127][1];
  return (b >> 4) * 64 + h * 16 + ((b ^ ((h >> 1) * 15)) & 15);
}
__device__ __forceinline__ uint32_t item_of(const Maps& maps, uint32_t r) { return item_at(maps, head_of(maps, r)); }

#define PACE 250
#define SPACE 0
#define LCHK 1
#define XMASK 3
#define XFIRST 12
#define C_SIDE 64
__device__ __forceinline__ uint32_t conv_first(const Maps& maps) {
  const uint32_t b = maps.id[blockIdx.x & 127][1];
  return (b >> 4) * 128 + ((b + 15) & 15);
}

__device__ __forceinline__ void conv_consumer(const Maps& maps, uint32_t smem0, uint32_t first, uint32_t step,
                                              uint32_t end, bool pp, bool dealt) {
  PHASE_PROLOGUE
  const uint32_t in_full = bar + B_CFULL + wg * 16;
  const uint32_t ca = sbase + (wg ? A_V_OFF + A_TILE : A_Q_OFF);
  const int w = __shfl_sync(0xffffffffu, warp, 0), g = lane >> 2, c = lane & 3;
  auto fetch = [&](uint32_t ch, uint32_t n) {
    if (w == 2 && ch < C_NONE) {
      if (elect_one()) {
        const uint32_t b = in_full + (n & 1) * 8, d = ca + (n & 1) * 8192;
        const uint64_t pol = policy_evict_first();
        mbar_expect_tx(b, 8192);
        tma_load_2d_hint(d, &maps.cu, b, 0, ch * 64, pol);
        tma_load_2d_hint(d + 4096, &maps.ch, b, 0, ch * 64, pol);
      }
    }
  };
  if (wtid == 96 && wg) { TD(15) }
  uint32_t f1[8][4];
  float tt[16], ts[16];
  uint32_t cc[4], ss[4];
#pragma unroll
  for (int i = 0; i < 16; i++) {
    const int k = 2 * (16 * w + g + 8 * (i & 1)) + 1, n = 2 * (8 * (i >> 1) + 2 * c) + 1;
    float c0, s0, c1, s1;
    sincos_turn(((k * n) << 23) >> 23, 1.f / 512, c0, s0);
    sincos_turn(((k * n + 2 * k) << 23) >> 23, 1.f / 512, c1, s1);
    f1[i >> 2][i & 3] = pack_bf16(c0 * C_ALPHA, c1 * C_ALPHA);
    f1[4 + (i >> 2)][i & 3] = pack_bf16(s0 * -C_ALPHA, s1 * -C_ALPHA);
  }
#pragma unroll
  for (int i = 0; i < 16; i++) {
    const int k = 2 * (16 * w + g + 8 * ((i >> 1) & 1)) + 1, n = 16 - (8 * (i >> 2) + 2 * c + (i & 1));
    float cs;
    sincos_turn(k * n, 1.f / 8192, cs, ts[i]);
    tt[i] = ts[i] * rcp(1.f + cs);
  }
#pragma unroll
  for (int j = 0; j < 4; j++) {
    const int k = 8 * w + g, n = 8 * c + 2 * j;
    float c0, s0, c1, s1;
    sincos_turn((int8_t)(k * n * 8), 1.f / 256, c0, s0);
    sincos_turn((int8_t)((k * n + k) * 8), 1.f / 256, c1, s1);
    cc[j] = pack_bf16(c0, c1);
    ss[j] = pack_bf16(s0, s1);
  }
  named_bar_sync(3, 256);
  fetch(first, 0);
  fetch(first + step, 1);
  const uint32_t va = ca + g * 64 + ((c ^ (g >> 1)) << 4);
  {
    const uint32_t a = va + C_MAT + w * 512, m = 0x80008000u;
    sts128(a, make_uint4(cc[0], cc[1], cc[2], cc[3]));
    sts128(a + 2048, make_uint4(ss[0], ss[1], ss[2], ss[3]));
    sts128(a + 4096, make_uint4(ss[0] ^ m, ss[1] ^ m, ss[2] ^ m, ss[3] ^ m));
    sts128(a + 6144, make_uint4(cc[0], cc[1], cc[2], cc[3]));
  }
  fence_proxy_async();
  named_bar_sync(1 + wg, 128);
  constexpr uint64_t DHI = (2ull << 62) | ((uint64_t)(512 >> 4) << 32);
  const uint32_t d0 = (uint32_t)make_desc(ca, 4096, 0, 0);
  float a5[16];
  uint4* const yb = reinterpret_cast<uint4*>(g_y2T) + (16 * w + g) * 4 + c;
  auto issue5 = [&]() {
#pragma unroll
    for (int ks = 0; ks < 8; ks++) wgmma_m64n32_rs_tb(a5, f1[ks], DHI | (d0 + (C_V >> 4) + ks * 64), ks != 0);
    wgmma_commit();
  };
  auto finish = [&](uint32_t ch, bool on) {
    fence_regs(a5);
    uint4* y = yb + (size_t)ch * 256;
    if (on) {
      y[0] = make_uint4(pack_bf16(a5[0], a5[1]), pack_bf16(a5[4], a5[5]), pack_bf16(a5[8], a5[9]), pack_bf16(a5[12], a5[13]));
      y[32] = make_uint4(pack_bf16(a5[2], a5[3]), pack_bf16(a5[6], a5[7]), pack_bf16(a5[10], a5[11]), pack_bf16(a5[14], a5[15]));
    }
  };
  auto dft32 = [&](float (&d)[32], const float* re, const float* im) {
    uint32_t a[4][4];
#pragma unroll
    for (int i = 0; i < 8; i++) {
      a[i >> 2][i & 3] = pack_bf16(re[2 * i], re[2 * i + 1]);
      a[2 + (i >> 2)][i & 3] = pack_bf16(im[2 * i], im[2 * i + 1]);
    }
    wgmma_fence();
#pragma unroll
    for (int ks = 0; ks < 4; ks++) wgmma_m64n64_rs_tb(d, a[ks], DHI | (d0 + (C_MAT >> 4) + ks * 64), ks != 0);
    wgmma_commit();
  };
  auto rot = [&](float* x, float* y) {
#pragma unroll
    for (int i = 0; i < 16; i++) {
      x[i] = fmaf(-tt[i], y[i], x[i]);
      y[i] = fmaf(ts[i], x[i], y[i]);
      x[i] = fmaf(-tt[i], y[i], x[i]);
    }
  };
  auto load_d = [&](uint32_t ch) {
    return __ldg(reinterpret_cast<const unsigned short*>(maps.ssm_D) + ((ch & (DM - 1)) | (lane & rt_zero)));
  };
  uint32_t dn = load_d(first);
  uint32_t n = 0, prev = 0, ch = first, next = first + step;
#pragma unroll 1
  for (; ch < C_NONE; n++) {
    CT(0)
    float a1[2][32], a2[2][32], a4[32];
    const float dsk = c ? 0.f : __uint_as_float(dn << 16) * C_ALPHA;
    dn = load_d(next);
    uint32_t next2 = next + step < end ? next + step : C_NONE;
    mbar_wait(in_full + (n & 1) * 8, (n >> 1) & 1);
    if (pp) named_bar_sync(4 + wg, 256);
    CT(1)
    wgmma_fence();
#pragma unroll
    for (int ks = 0; ks < 8; ks++)
      wgmma_m64n64_rs_tb(a1[ks >> 2], f1[ks], DHI | (d0 + (n & 1) * 512 + (ks & 3) * 64), (ks & 3) != 0);
    wgmma_commit();
    issue5();
    wgmma_wait<1>();
    fence_regs(a1[0]);
    fence_regs(a1[1]);
    CT(2)
    rot(a1[0], a1[1]);
    dft32(a2[0], a1[0], a1[1]);
    rot(a1[0] + 16, a1[1] + 16);
    a1[0][16] += dsk;
    a1[0][18] += dsk;
    dft32(a2[1], a1[0] + 16, a1[1] + 16);
    CT(3)
    wgmma_wait<2>();
    finish(prev, n > 0);
    wgmma_wait<0>();
    fence_regs(a2[0]);
    fence_regs(a2[1]);
    CT(4)
    if (pp) named_bar_arrive(5 - wg, 256);
    float re[16], im[16];
#pragma unroll
    for (int i = 0; i < 16; i++) {
      re[i] = a2[0][i] * a2[1][i] - a2[0][16 + i] * a2[1][16 + i];
      im[i] = a2[0][i] * a2[1][16 + i] + a2[0][16 + i] * a2[1][i];
    }
    dft32(a4, im, re);
    if (dealt) {
      mbar_wait(bar + (n < 2 ? B_DEAL : B_DEAL2), 0);
      asm volatile("ld.shared.u32 %0, [%1];" : "=r"(next2) : "r"(bar + B_LIST + 4 * n + (n < 2 ? 0 : 8)));
    }
    wgmma_wait<0>();
    fence_regs(a4);
    CT(5)
    rot(a4, a4 + 16);
#pragma unroll
    for (int i = 0; i < 4; i++) {
      const float* x = a4 + 16 - 16 * (i >> 1) + 2 * (i & 1);
      sts128(va + C_V + w * 1024 + (i >> 1) * 4096 + (i & 1) * 512,
             make_uint4(pack_bf16(x[0], x[1]), pack_bf16(x[4], x[5]), pack_bf16(x[8], x[9]), pack_bf16(x[12], x[13])));
    }
    CT(6)
    fence_proxy_async();
    named_bar_sync(1 + wg, 128);
    fetch(next2, n);
    if (wtid == 96 && n > 0) note(bar, CNT_Y2 + ((prev & 112) == 112));
    prev = ch;
    ch = next;
    next = next2;
    CT(7)
  }
  wgmma_fence();
  issue5();
  wgmma_wait<0>();
  finish(prev, (dn | ~rt_zero) != 0);
  named_bar_sync(1 + wg, 128);
  if (wtid == 96 && wg) { TD(8) }
  if (wtid == 96) cnt_signal_release(CNT_Y2 + ((prev & 112) == 112), 1);
  if (wtid == 64) note(bar, CNT_DONE);
  if (wtid == 96 && wg) { TD(9) }
}

__device__ __forceinline__ void attn_producer(const Maps& maps, uint32_t sbase, bool after_qkv, bool to_out,
                                              bool dry) {
  const uint32_t bar = sbase + BAR_OFF;
  const uint32_t q_full = bar + B_QFULL, q_empty = bar + B_QEMPTY;
  const uint32_t k_full = bar + B_KFULL, k_empty = bar + B_KEMPTY, v_full = bar + B_VFULL, v_empty = bar + B_VEMPTY;
  int ndrained = after_qkv ? 0 : G_STAGES;
  auto wait = [&](uint32_t b, uint32_t par) {
    if (!dry) mbar_wait_sleep(b, par);
  };
  auto drained = [&](int upto) {
#pragma unroll 1
    for (; ndrained <= upto; ndrained++) wait(bar + B_GEMPTY + 8 * ndrained, 1);
  };
  uint32_t st = 0, ph = 1, vs = 0, vp = 1;
  int pend_j = -1, pend_h = 0;
  int round = -1, m = -1, h = 0;
  bool last = false;
#pragma unroll 1
  for (;; round++) {
    uint32_t nitem = 0;
    const int tpost = m >= 3 ? m - 1 : m;
#pragma unroll 1
    for (int t = m < 0 ? -1 : 0; t <= m; t++) {
      const int j = (t < m && (h & 2)) ? m - 1 - t : t;
      if (t >= 0) {
        drained(st);
        wait(k_empty + 8 * st, ph);
        if (!dry) {
          mbar_expect_tx(k_full + 8 * st, A_TILE);
          tma_load_3d(sbase + A_K_OFF + st * 2 * A_TILE, &maps.k, k_full + 8 * st, 0, j * 128, h * 2);
        }
        if (++st == 2) { st = 0; ph ^= 1; }
      }
      if (pend_j >= 0) {
        drained(2 + vs);
        if ((pend_h & 2) && after_qkv) wait(bar + seen_bar(0), 0);
        wait(v_empty + 8 * vs, vp);
        if (!dry) {
          mbar_expect_tx(v_full + 8 * vs, A_TILE);
          tma_load_3d(sbase + A_V_OFF + vs * A_TILE, &maps.v, v_full + 8 * vs, 0, pend_j * 128, pend_h * 2);
        }
        if (++vs == 2) { vs = 0; vp ^= 1; }
      }
      pend_j = j;
      pend_h = h;
      if (t == tpost && !last) {
        nitem = dry ? 1 : item_of(maps, round + 1);
        if (round == (dry ? 0 : 3) || blockIdx.x >= 128) {
          nitem = A_ITEMS;
          if (!to_out) cnt_wait(CNT_PREP, dry ? 0 : 260);
          if (to_out) {
            wait(bar + seen_bar(1), 0);
            asm volatile("cp.async.bulk.prefetch.L2.global [%0], 4096;" ::"l"(maps.ssm_k + (size_t)conv_first(maps) * S_LEN));
            if (!dry)
              asm volatile("cp.async.bulk.prefetch.L2.global [%0], 4096;" ::"l"(g_kvT + (size_t)conv_first(maps) * S_LEN));
          }
        }
        const uint32_t qs = (round + 1) & 1;
        wait(q_empty + 8 * qs, (((round + 1) >> 1) & 1) ^ 1);
        if (round == 1 && after_qkv) wait(bar + B_QDONE, 0);
        if (round < 0 && after_qkv) {
          if (!dry) { TD(2) }
          cnt_wait(CNT_KV, dry ? 0 : 768);
          if (!dry) { TD(3) }
        }
        if (nitem >= A_ITEMS || (round < 0 && after_qkv && !dry)) {
          if (!dry) mbar_arrive(q_full + 8 * qs);
        } else {
          drained(1 + 2 * qs);
          if (!dry) {
            mbar_expect_tx(q_full + 8 * qs, A_TILE);
            tma_load_3d_hint(sbase + A_Q_OFF + qs * 4 * A_TILE, &maps.q, q_full + 8 * qs, 0, item_m(nitem) * 128,
                             item_h(nitem) * 2, policy_evict_first());
          }
        }
      }
    }
    if (last) break;
    last = nitem >= A_ITEMS;
    m = last ? -1 : item_m(nitem);
    h = item_h(nitem);
  }
}

__device__ __forceinline__ void put_o(uint32_t sbase, int wg, int warp, int lane, const float (&o)[64], float i0, float i1) {
  const int st_row = warp * 16 + (lane & 7) + ((lane >> 3) & 1) * 8;
  const uint32_t so = sbase + A_O_OFF + wg * 16384 + st_row * 128;
#pragma unroll
  for (int j = 0; j < 16; j += 2)
    stmatrix_x4(so + (j >> 3) * 8192 + ((((j & 7) + (lane >> 4)) ^ (lane & 7)) << 4),
                pack_bf16(o[4 * j] * i0, o[4 * j + 1] * i0), pack_bf16(o[4 * j + 2] * i1, o[4 * j + 3] * i1),
                pack_bf16(o[4 * j + 4] * i0, o[4 * j + 5] * i0), pack_bf16(o[4 * j + 6] * i1, o[4 * j + 7] * i1));
}
__device__ __forceinline__ uint32_t attn_consumer(const Maps& maps, const uint32_t sbase, const int wg,
                                                  const uint32_t rt_zero, uint32_t sn, uint32_t (&p)[32], float (&rest)[64],
                                                  bool after_qkv, float (&o)[64], float (&s)[64], float& pi0, float& pi1) {
  PHASE_GIVEN
  const uint32_t q_full = bar + B_QFULL, q_empty = bar + B_QEMPTY;
  const uint32_t k_full = bar + B_KFULL, k_empty = bar + B_KEMPTY, v_full = bar + B_VFULL;
  float e[32];
  uint32_t dep = 0;
  constexpr int MIDJ = 5;
  float l0 = 0.f, l1 = 0.f, b0 = 0.f, b1 = 0.f;
  const int sched_own = 4 + wg, sched_other = 5 - wg;

  const int hf = wg ^ 1;
  const uint32_t qd0 = (uint32_t)make_desc(sbase + A_Q_OFF + hf * 8192, 16, 0, 0);
  const uint32_t kd0 = (uint32_t)make_desc(sbase + A_K_OFF, 16, 0, 0);
  const uint32_t vd0 = (uint32_t)make_desc(sbase + A_V_OFF, 16384, 0, 0);
  constexpr uint64_t DHI = DESC_SW128 | ((uint64_t)(1024 >> 4) << 32);
  constexpr uint32_t DST = A_TILE >> 4;
  auto issue_qk = [&](uint32_t qd, uint32_t kd) {
#pragma unroll
    for (int kk = 0; kk < 8; kk++) {
      const uint32_t off = ((kk >> 2) * 16384 + (kk & 3) * 32) >> 4;
      wgmma_m64n128_ss(s, DHI | (qd + off), DHI | (kd + off), kk != 0);
    }
    wgmma_commit();
  };
  auto issue_pv = [&](uint32_t vd, bool accumulate, int nk) {
#pragma unroll
    for (int kk = 0; kk < 8; kk++) {
      if (kk < nk)
        wgmma_m64n128_rs<1>(o, p[4 * kk], p[4 * kk + 1], p[4 * kk + 2], p[4 * kk + 3], DHI | (vd + kk * 128),
                            accumulate || (kk != 0));
    }
    wgmma_commit();
  };
  auto exp_lo = [&](float& a0, float& a1) {
#pragma unroll
    for (int j = 0; j < 8; j++) {
      e[4 * j] = ex2(s[4 * j]);
      e[4 * j + 1] = ex2(s[4 * j + 1]);
      e[4 * j + 2] = ex2(s[4 * j + 2]);
      e[4 * j + 3] = ex2(s[4 * j + 3]);
      a0 += e[4 * j];
      a0 += e[4 * j + 1];
      a1 += e[4 * j + 2];
      a1 += e[4 * j + 3];
      if (j == MIDJ) dep = (__float_as_uint(a0) | __float_as_uint(a1)) & rt_zero;
    }
  };
  auto pack_lo = [&]() {
#pragma unroll
    for (int j = 0; j < 16; j++) p[j] = pack_bf16(e[2 * j], e[2 * j + 1]);
  };
  auto finish_p = [&](float& a0, float& a1) {
    pack_lo();
#pragma unroll
    for (int j = 8; j < 16; j++) {
      const float e0 = ex2(s[4 * j]), e1 = ex2(s[4 * j + 1]), e2 = ex2(s[4 * j + 2]), e3 = ex2(s[4 * j + 3]);
      a0 += e0;
      a0 += e1;
      a1 += e2;
      a1 += e3;
      p[2 * j] = pack_bf16(e0, e1);
      p[2 * j + 1] = pack_bf16(e2, e3);
      if (j == 8 + MIDJ) dep = __float_as_uint(a0) & rt_zero;
    }
  };
  auto quad_sum = [&](float t) {
    t += __shfl_xor_sync(0xffffffffu, t, 1);
    return t + __shfl_xor_sync(0xffffffffu, t, 2);
  };
  auto write_o = [&](float i0, float i1) {
    st_wait(bar, wg, sn - 1);
    put_o(sbase, wg, warp, lane, o, i0, i1);
  };
  auto store_o = [&](uint32_t r, int kind, uint32_t lazy) {
    const uint32_t it = item_at(maps, kind == ST_BOX2Q ? 1 : head_of(maps, r));
    st_cmd(bar, wg, wtid, sn, kind, (INPLACE & 1) || kind != ST_BOX2Q ? &maps.o : &maps.c[0], sbase + A_O_OFF + wg * 16384, item_h(it) * 128,
            item_m(it) * 128 + hf * 64, CNT_CTX + (r >> 1), lazy);
    if (kind != ST_BOX2L) st_go(bar, wg, wtid, sn);
    sn++;
  };
  auto mask_half = [&](float* sh) {
    const int u = warp * 16 + (lane >> 2) - (lane & 3) * 2;
#pragma unroll
    for (int j = 0; j < 8; j++) {
      if (8 * j > u) sh[4 * j] = -INFINITY;
      if (8 * j + 1 > u) sh[4 * j + 1] = -INFINITY;
      if (8 * j - 8 > u) sh[4 * j + 2] = -INFINITY;
      if (8 * j - 7 > u) sh[4 * j + 3] = -INFINITY;
    }
  };
  ST(0)
  const uint32_t qa = sbase + A_Q_OFF + hf * 8192 + (warp * 16 + (lane & 15)) * 128;
  auto q_at = [&](int j) { return qa + (j >> 2) * 16384 + ((((j & 3) * 2 + (lane >> 4)) ^ (lane & 7)) << 4); };
  if (!after_qkv) {
    mbar_wait(q_full, 0);
    if (blockIdx.x >= 128) return sn;
#pragma unroll
    for (int j = 0; j < 8; j++)
      asm volatile("ldmatrix.sync.aligned.m8n8.x4.shared.b16 {%0, %1, %2, %3}, [%4];"
                   : "=r"(p[4 * j]), "=r"(p[4 * j + 1]), "=r"(p[4 * j + 2]), "=r"(p[4 * j + 3])
                   : "r"(q_at(j))
                   : "memory");
  }
  if (QW) mbar_wait(k_full, 0);
  else
    for (uint32_t i = 0; !(mbar_try(k_full, 0) & mbar_try(bar + B_GEMPTY + 8, 1)) && i < (1u << 22); i++) {}
  named_bar_sync(sched_own, 256);
  fence_regs_u(p);
  wgmma_fence();
#pragma unroll
  for (int kk = 0; kk < 8; kk++)
    wgmma_m64n128_rs<0>(s, p[4 * kk], p[4 * kk + 1], p[4 * kk + 2], p[4 * kk + 3],
                        DHI | (kd0 + (((kk >> 2) * 16384 + (kk & 3) * 32) >> 4)), kk != 0);
  wgmma_commit();
  if (HOLD && after_qkv && wg == 0) named_bar_arrive(7, 256);
  named_bar_arrive(sched_other, 256);
  if (QW) mbar_wait(bar + B_GEMPTY + 8, 1);
#pragma unroll
  for (int j = 0; j < 8; j++) stmatrix_x4(q_at(j), p[4 * j], p[4 * j + 1], p[4 * j + 2], p[4 * j + 3]);
  fence_regs(rest);
#pragma unroll
  for (int i = 0; i < 64; i++) o[i] = rest[i] * (KS ? __uint_as_float(0x3f800000u | rt_zero) : Q_SCALE);
  fence_regs(o);
  fence_proxy_async();
  fence_regs(o);
  wgmma_wait<0>();
  fence_regs(s);
  mbar_arrive_if(k_empty, wtid == 32);
  uint32_t g = 0;
  uint32_t rnd = 0;
  int rem = item_m(item_of(maps, 0));
  uint32_t first = 1;
  uint32_t fl = 0;
#define redo (fl & 1)
#define shifted (fl & 2)
  float d0 = 0.f, d1 = 0.f;
  pi0 = pi1 = 1.f;
  ST(1)
  for (;;) {
    if (shifted) {
#pragma unroll
      for (int j = 0; j < 16; j++) {
        s[4 * j] -= d0;
        s[4 * j + 1] -= d0;
        s[4 * j + 2] -= d1;
        s[4 * j + 3] -= d1;
      }
    }
    if (rem == 0 && !redo) {
      mbar_arrive_if(q_empty + 8 * (rnd & 1), wtid == 96);
      rnd++;
      if (hf == 0) mask_half(s);
      else mask_half(s + 32);
    }
    for (;;) {
      const bool kill = rem == 0 && hf == 0;
      const uint32_t kd = kd0 + ((g + 1) & 1) * 2 * DST, vd = vd0 + (g & 1) * DST;
      float a0 = 0.f, a1 = 0.f;
      exp_lo(a0, a1);
      fence_regs(e);
      const uint32_t kb = k_full + 8 * ((g + 1) & 1);
      const uint32_t kpar = (((g + 1) >> 1) & 1) ^ (g == A_STEPS - 1 ? 1u : 0u);
      const uint32_t qb = q_full + 8 * (rnd & 1), qpar = ((rnd >> 1) & 1) | dep;
      if (!mbar_try(qb, qpar)) mbar_wait(qb, qpar | ((__float_as_uint(a0) | __float_as_uint(a1)) & rt_zero));
      wgmma_wait<0>();
      fence_regs(o);
      if (kill) {
        mbar_arrive_if(kb + (B_VEMPTY - B_KFULL), wtid == 64 && !redo && g > 0);
        fence_regs(e);
        pack_lo();
#pragma unroll
        for (int j = 16; j < 32; j++) asm volatile("" : "=r"(p[j]));
        goto check;
      }
#pragma unroll
      for (int i = 32; i < 64; i++) asm volatile("" : "+f"(s[i])::"memory");
      mbar_arrive_if(kb + (B_VEMPTY - B_KFULL), wtid == 64 && !redo && g > 0);
      finish_p(a0, a1);
      if (__any_sync(0xffffffffu, !(mbar_try(v_full + 8 * (g & 1), ((g >> 1) & 1) | dep) &
                                    mbar_try(kb, kpar | dep)) ||
                                      !(a0 + a1 < 1.0995116e12f) || !(fminf(a0, a1) > (first ? 9.094947e-13f : -1.f)))) {
      check:
        bool bad = !(a0 + a1 < 1.0995116e12f);
        if (first) bad |= !(fminf(quad_sum(a0), quad_sum(a1)) > 9.094947e-13f);
        if (!redo && __any_sync(0xffffffffu, bad)) {
          d0 = d1 = first ? -INFINITY : 0.f;
#pragma unroll
          for (int j = 0; j < 16; j++) {
            if (j < 8 || !kill) {
              d0 = fmaxf(d0, fmaxf(s[4 * j], s[4 * j + 1]));
              d1 = fmaxf(d1, fmaxf(s[4 * j + 2], s[4 * j + 3]));
            }
          }
#pragma unroll
          for (int x = 1; x <= 2; x++) {
            d0 = fmaxf(d0, __shfl_xor_sync(0xffffffffu, d0, x));
            d1 = fmaxf(d1, __shfl_xor_sync(0xffffffffu, d1, x));
          }
          b0 += d0;
          b1 += d1;
          if (!first) {
            const float al0 = ex2(-d0), al1 = ex2(-d1);
            l0 *= al0;
            l1 *= al1;
#pragma unroll
            for (int j = 0; j < 16; j++) {
              o[4 * j] *= al0;
              o[4 * j + 1] *= al0;
              o[4 * j + 2] *= al1;
              o[4 * j + 3] *= al1;
            }
          }
          fl = 3;
          break;
        }
        mbar_wait(v_full + 8 * (g & 1), (g >> 1) & 1);
        mbar_wait(kb, kpar);
      }
      named_bar_sync(sched_own, 256);
      if (g == A_STEPS - 1) {
        fence_regs(o);
        if (hf == 0) {
          wgmma_fence();
          issue_pv(vd, 1, 4);
        } else {
          wgmma_fence();
          issue_pv(vd, 1, 8);
        }
        named_bar_arrive(sched_other, 256);
        pi0 = rcp(quad_sum(l0 + a0));
        pi1 = rcp(quad_sum(l1 + a1));
        goto done;
      }
      wgmma_fence();
      issue_qk(qd0 + (rnd & 1) * 4 * DST, kd);
      if (first) write_o(pi0, pi1);
      fence_regs(o);
      if (kill) {
        wgmma_fence();
        issue_pv(vd, !first, 4);
      } else {
        wgmma_fence();
        issue_pv(vd, !first, 8);
      }
      named_bar_arrive(sched_other, 256);
      fl &= 2;
      l0 += a0;
      l1 += a1;
      if (rem == 0 || first) {
        if (first && (g > 0 || after_qkv)) store_o(g ? rnd - (rem == 0 ? 2 : 1) : 2, g ? ST_BOX2 : ST_BOX2Q, rem);
        first = rem == 0;
        if (first) {
          pi0 = rcp(quad_sum(l0));
          pi1 = rcp(quad_sum(l1));
          l0 = l1 = b0 = b1 = 0.f;
          fl = 0;
          rem = item_m(item_of(maps, rnd)) + 1;
        }
      }
      rem--;
      g++;
      wgmma_wait<1>();
      fence_regs(s);
      mbar_arrive_if(kb + (B_KEMPTY - B_KFULL), wtid == 32);
      ST(g + 1)
      if (rem == 0 || shifted) {
        d0 = b0;
        d1 = b1;
        break;
      }
    }
  }
done:
#undef redo
#undef shifted
  st_wait(bar, wg, sn - 1);
  store_o(3, ST_BOX2L, 4);
  ST(35)
  return sn;
}

constexpr int O_STAGES = 5;
constexpr int O_STAGE_BYTES = 32768;
constexpr int O_Y_OFF = 4 * 32768;
constexpr int O_X_OFF = 6 * 32768;
constexpr int O_G_OFF = 7 * 32768;
constexpr int O_NK = HDIM / 64;

__device__ __forceinline__ uint32_t out_stage(uint32_t st) { return ((0x32501u >> (4 * st)) & 7) * O_STAGE_BYTES; }

__device__ __forceinline__ void out_producer(const Maps& maps, uint32_t sbase, bool after_attn, bool dry) {
  const uint32_t bar = sbase + BAR_OFF;
  const uint32_t rank = blockIdx.x & 1;
  const int m_tile = maps.id[blockIdx.x][2] & 15, n_tile = maps.id[blockIdx.x][2] >> 4;
  uint32_t stage = 0, phase = 0, xi = 0;
#pragma unroll 1
  for (int ki = 0; ki < (dry ? 1 : O_NK); ki++) {
    const int kt = (ki & 14) * 4 + ((A_ORDER >> ((ki >> 4) * 4)) & 3) * 2 + (ki & 1);
    const uint32_t fb = bar + B_OFULL + 8 * stage, eb = bar + B_OEMPTY + 8 * stage;
    const uint32_t sa = sbase + out_stage(stage);
    if (ki < O_STAGES) {
      constexpr uint32_t LASTB = B_KEMPTY | ((B_QEMPTY + 8) << 8) | ((B_KEMPTY + 8) << 16) | (B_VEMPTY << 24);
      if (ki > 0 && after_attn) mbar_wait_sleep(bar + ((LASTB >> (8 * ki - 8)) & 255), ki == 2);
      mbar_arrive_cluster_if(eb, 0, !dry);
      mbar_arrive_cluster_if(eb, 1, !dry);
    }
    if (ki == 32) mbar_wait_sleep(bar + seen_bar(2), 0);
    if (!dry) {
      mbar_wait_sleep(eb, phase);
      mbar_expect_tx(fb, O_STAGE_BYTES);
      tma_load_2d_mc(sa + 16384 + rank * 8192, &maps.ob, fb, n_tile * 128 + rank * 64, kt * 64, (uint16_t)3);
      tma_load_2d(sa, &maps.oa, fb, kt * 64, m_tile * 128);
    }
    if (++stage == O_STAGES) { stage = 0; phase ^= 1; }
    if ((ki & XMASK) == XMASK && ki >= XFIRST && xi < 8) {
      if (after_attn && xi < 2) mbar_wait_sleep(bar + B_OFREE + 8 * xi, 0);
      tma_load_3d(sbase + O_X_OFF + (xi & 1) * 16384 + (xi >> 1) * 4096, &maps.xs, bar + B_OY, 0,
                  m_tile * 128 + (xi & 1) * 64 + (xi >> 1) * 16, n_tile * 2);
      xi++;
    }
  }
  if (!dry) mbar_wait_sleep(bar + B_OY2, 0);
}

__device__ __forceinline__ void out_side(const Maps& maps, uint32_t smem0) {
  PHASE_PROLOGUE
  const int m_tile = maps.id[blockIdx.x][2] & 15, n_tile = maps.id[blockIdx.x][2] >> 4;
  const float* gp = g_gate + m_tile * 128 + warp * 16 + (lane >> 2);
  const float gv[4] = {__ldcg(gp), __ldcg(gp + 8), __ldcg(gp + 64), __ldcg(gp + 72)};
  const bool w0 = __shfl_sync(0xffffffffu, warp, 0) == 0;
  bool have = false;
  auto late = [&](uint32_t spins) {
    have = cnt_wait(CNT_Y2 + 1, 128, spins) || !spins;
    TD(11)
    if (have) {
      mbar_expect_tx(bar + B_OY2, 4096);
      tma_load_3d(sbase + O_Y_OFF + 7 * 4096, &maps.y, bar + B_OY2, 0, n_tile * 128 + 112, m_tile * 2);
    }
  };
  if (w0) {
    if (elect_one()) {
      mbar_expect_tx(bar + B_OY, 65536 - 4096);
      TD(10)
      cnt_wait(CNT_Y2, DM - 128);
      TD(7)
#pragma unroll 1
      for (int i = 0; i < 7; i++) {
        tma_load_3d(sbase + O_Y_OFF + i * 4096, &maps.y, bar + B_OY, 0, n_tile * 128 + i * 16, m_tile * 2);
        __nanosleep(PACE);
      }
      late(1u << 18);
    }
  }
  mbar_wait_sleep(bar + B_OY, 0);
  if (wtid == 0) { TD(12) }
  const int mrow = (lane & 7) + ((lane >> 4) & 1) * 8;
  const int mchunk = warp * 2 + ((lane >> 3) & 1);
  const uint32_t xrow = sbase + O_X_OFF + warp * 4096 + (lane & 15) * 128;
  const uint32_t yrow = sbase + O_Y_OFF + mrow * 128 + ((mchunk ^ (lane & 7)) << 4);
  uint32_t y[7][4], x[7][4], om[4];
#pragma unroll
  for (int i = 0; i < 4; i++) om[i] = pack_bf16(1.0f - gv[i], 1.0f - gv[i]);
  sts128(sbase + O_G_OFF + wtid * 16, make_uint4(pack_bf16(gv[0], gv[0]), pack_bf16(gv[1], gv[1]), pack_bf16(gv[2], gv[2]),
                                                 pack_bf16(gv[3], gv[3])));
  auto xa = [&](int h, int i) { return xrow + h * 16384 + (i >> 2) * 2048 + ((((i & 3) * 2 + (lane >> 4)) ^ (lane & 7)) << 4); };
  auto load = [&](int r, int h, int i) {
    ldsm4t(y[r], yrow + h * 2048 + i * 4096);
    asm volatile("ldmatrix.sync.aligned.m8n8.x4.shared.b16 {%0, %1, %2, %3}, [%4];"
                 : "=r"(x[r][0]), "=r"(x[r][1]), "=r"(x[r][2]), "=r"(x[r][3])
                 : "r"(xa(h, i)));
  };
  auto store = [&](int r, int h, int i, uint32_t om0, uint32_t om1) {
    stmatrix_x4(xa(h, i), mul_bf2(om0, mul_bf2(x[r][0], y[r][0])), mul_bf2(om1, mul_bf2(x[r][1], y[r][1])),
                mul_bf2(om0, mul_bf2(x[r][2], y[r][2])), mul_bf2(om1, mul_bf2(x[r][3], y[r][3])));
  };
#pragma unroll 1
  for (int h = 0; h < 2; h++) {
#pragma unroll
    for (int i = 0; i < 7; i++) load(i, h, i);
#pragma unroll
    for (int i = 0; i < 7; i++) store(i, h, i, h ? om[2] : om[0], h ? om[3] : om[1]);
  }
  __syncwarp();
  mbar_arrive_if(bar + B_OE, lane == 0);
  if (w0 && !__any_sync(0xffffffffu, have)) {
    if (elect_one()) late(0);
  }
  mbar_wait_sleep(bar + B_OY2, 0);
  load(0, 0, 7);
  load(1, 1, 7);
  store(0, 0, 7, om[0], om[1]);
  store(1, 1, 7, om[2], om[3]);
  __syncwarp();
  mbar_arrive_if(bar + B_OY + 8, lane == 0);
  if (wtid == 0) { TD(13) }
}

__device__ __forceinline__ void out_gemm(const Maps& maps, const uint32_t sbase, uint32_t sn, bool post, float (&o)[64],
                                         float (&s)[64],                                          float i0, float i1) {
  PHASE_GIVEN
  auto acc = [&](int h) -> float (&)[64] { return h ? o : s; };
  constexpr uint64_t DHI = DESC_SW128 | ((uint64_t)(1024 >> 4) << 32);
  const uint32_t d0 = (uint32_t)make_desc(sbase, 0, 0, 0);
  auto mma0 = [&](int h) {
    wgmma_fence();
#pragma unroll
    for (int k = 0; k < 4; k++)
      wgmma_m64n128_ss_tb(acc(h), DHI | (d0 + 0x10800 + h * 512 + k * 2), DHI | (d0 + 0x2000c00 + k * 128), k != 0);
    wgmma_commit();
  };
  mbar_wait(bar + B_OFULL, 0);
  mma0(0);
  wgmma_wait<1>();
  fence_regs(o);
  if (post) {
    named_bar_arrive(3, 256);
    put_o(sbase, 0, warp, lane, o, i0, i1);
  }
  mma0(1);
  if (post) st_go(bar, 0, wtid, sn - 1);
  const int m_tile = maps.id[blockIdx.x][2] & 15, n_tile = maps.id[blockIdx.x][2] >> 4;
  uint32_t stage = 1, phase = 0, prev_stage = 0;
  GT(gti++)
  const uint32_t xrow = sbase + O_X_OFF + warp * 4096 + (lane & 15) * 128;
  auto addr = [&](int i) {
    return xrow + (i >> 3) * 16384 + ((i >> 2) & 1) * 2048 + ((((i & 3) * 2 + (lane >> 4)) ^ (lane & 7)) << 4);
  };
  uint32_t b[16][4];
#pragma unroll
  for (int i = 0; i < 64; i++) asm volatile("" : "=r"(b[i >> 2][i & 3]));
  auto ld_b = [&](int q0, int q1) {
#pragma unroll
    for (int i = 0; i < 16; i++)
      if ((i & 7) != 7)
        asm volatile(
            "{\n.reg .pred p;\nsetp.ge.s32 p, %5, %6;\nsetp.le.and.s32 p, %5, %7, p;\n"
            "@p ldmatrix.sync.aligned.m8n8.x4.shared.b16 {%0, %1, %2, %3}, [%4];\n}\n"
            : "+r"(b[i][0]), "+r"(b[i][1]), "+r"(b[i][2]), "+r"(b[i][3])
            : "r"(addr(i)), "r"(i / 4), "r"(q0), "r"(q1)
            : "memory");
  };
  int nq = 0;
#pragma unroll 1
  for (int kt = 1; kt < O_NK - 2; kt++) {
    uint32_t da = (uint32_t)make_desc(sbase + out_stage(stage), 16, 0, 0);
    uint32_t db = (uint32_t)make_desc(sbase + out_stage(stage) + 16384, 8192, 0, 0);
    asm volatile("" : "+r"(da), "+r"(db));
    mbar_wait(bar + B_OFULL + 8 * stage, phase);
    GT(gti++)
#pragma unroll
    for (int kk = 0; kk < 4; kk++) {
      wgmma_wait<2>();
      if (kk == 2)
        mbar_arrive_cluster_if(bar + B_OEMPTY + 8 * prev_stage, wtid >> 6, (wtid & 63) == 32 && kt - 1 + O_STAGES < O_NK);
      wgmma_fence();
      wgmma_m64n128_ss_tb(acc(0), DHI | (da + kk * 2), DHI | (db + kk * 128), 1);
      wgmma_m64n128_ss_tb(acc(1), DHI | (da + 512 + kk * 2), DHI | (db + kk * 128), 1);
      wgmma_commit();
      if (kk == 0 && kt >= 52) {
        uint32_t ok;
        asm volatile("{\n.reg .pred p;\nmbarrier.test_wait.parity.shared::cta.b64 p, [%1], 0;\nselp.u32 %0, 1, 0, p;\n}\n"
                     : "=r"(ok)
                     : "r"(bar + B_OE)
                     : "memory");
        if (__all_sync(0xffffffffu, ok)) {
          ld_b(nq, nq);
          nq++;
        }
      }
    }
    prev_stage = stage;
    if (++stage == O_STAGES) { stage = 0; phase ^= 1; }
  }
  if (tid == 0) { TD(14) }
  constexpr int S0 = (O_NK - 2) % O_STAGES, P0 = ((O_NK - 2) / O_STAGES) & 1;
  auto mma = [&](int h, int k0, int k1) {
    wgmma_fence();
#pragma unroll
    for (int k = k0; k < k1; k++) {
      const uint32_t d = d0 + (out_stage(S0 + (k >> 2)) >> 4);
      wgmma_m64n128_ss_tb(acc(h), DHI | (d + 0x10000 + h * 512 + (k & 3) * 2), DHI | (d + 0x2000400 + (k & 3) * 128), 1);
    }
    wgmma_commit();
  };
#pragma unroll
  for (int p = 0; p < 2; p++) {
    mbar_wait(bar + B_OFULL + 8 * (S0 + p), P0);
    mma(0, 4 * p, 4 * p + 4);
  }
  mma(1, 0, 8);
  if (nq < 4) {
    mbar_wait(bar + B_OE, 0);
    ld_b(nq, 3);
  }
  const uint4 g4 = lds128(sbase + O_G_OFF + wtid * 16);
  const uint32_t gg[4] = {g4.x, g4.y, g4.z, g4.w};
  const int w4 = __shfl_sync(0xffffffffu, warp, 0);
#pragma unroll
  for (int i = 0; i < 16; i++) {
    const int h = i >> 3;
    if (i == 0) wgmma_wait<1>();
    if (i == 8) wgmma_wait<0>();
    if ((i & 7) == 0) fence_regs(acc(h));
    if (i == 8) {   }
    if (i == 7) {
      mbar_wait(bar + B_OY + 8, 0);
#pragma unroll
      for (int j = 7; j < 16; j += 8)
        asm volatile("ldmatrix.sync.aligned.m8n8.x4.shared.b16 {%0, %1, %2, %3}, [%4];"
                     : "=r"(b[j][0]), "=r"(b[j][1]), "=r"(b[j][2]), "=r"(b[j][3])
                     : "r"(addr(j))
                     : "memory");
    }
    const float* a = acc(h) + 8 * (i & 7);
    stmatrix_x4(addr(i), fma_bf2(gg[2 * h], pack_bf16(a[0], a[1]), b[i][0]), fma_bf2(gg[2 * h + 1], pack_bf16(a[2], a[3]), b[i][1]),
                fma_bf2(gg[2 * h], pack_bf16(a[4], a[5]), b[i][2]), fma_bf2(gg[2 * h + 1], pack_bf16(a[6], a[7]), b[i][3]));
    if ((i & 7) == 7) {
      fence_proxy_async();
      __syncwarp();
      if (elect_one()) {
        tma_store_3d(&maps.oc, sbase + O_X_OFF + (h * 4 + w4) * 4096, 0, m_tile * 128 + h * 64 + w4 * 16, n_tile * 2);
        if (h == 1) {
          tma_store_commit();
        }
      }
    }
  }
  GT(gti++)
}

__device__ __noinline__ void leave_kernel(int mask) {
  if (!(mask & 4)) return;
  if (atomicAdd(g_cnt + CNT_DONE * 32, 1u) == 2 * gridDim.x - 1) {
    for (int i = 0; i < CNT_N; i++) g_cnt[i * 32] = 0;
#pragma unroll 4
    for (int i = 0; i < 128; i++) g_slot[i] = 0;
  }
}

__device__ __noinline__ void side_jobs(const Maps& maps, uint32_t sbase) {
  const int w12 = __shfl_sync(0xffffffffu, threadIdx.x >> 5, 0);
  gate_rows(maps, sbase, (blockIdx.x - 128) * 12 + w12, w12, threadIdx.x & 31);
  fence_proxy_async();
  __syncthreads();
  if (threadIdx.x == 320) cnt_signal_release(CNT_PREP, 1);
}

__global__ void __launch_bounds__(384, 1)
    fused_kernel(int mask, const bf16* px, const bf16* pw, const __grid_constant__ Maps maps) {
  extern __shared__ __align__(1024) uint8_t smem_raw[];
  {
    const uint32_t t = threadIdx.x, l = t & 31, u = (blockIdx.x & 127) * 16 + (l >> 1);
    const uint32_t ow = (u >> 5) * HDIM + ((u >> 2) & 7) * 512 + 256 + (u & 3) * 64, ox = u * DM;
    const bf16* p = ((l & 1) ? pw : px) + ((l & 1) ? ow : ox);
    asm volatile("{\n.reg .pred p;\nsetp.ne.u32 p, %1, 0;\n@p prefetch.global.L2 [%0];\n}\n" ::"l"(p), "r"((uint32_t)(t < 32)));
  }
  {
    const uint32_t sbase = __shfl_sync(0xffffffffu, smem_u32(smem_raw), 0);
    const uint32_t bar = sbase + BAR_OFF;
    const int tid = threadIdx.x;
    const bool do_qkv = (mask & 1) && blockIdx.x < 128;
    TL(0, 0)
    if (__shfl_sync(0xffffffffu, tid >> 5, 0) == 1 && do_qkv) {
      if (elect_one()) {
        for (int i = 0; i < G_STAGES; i++) mbar_init(bar + B_GFULL + 8 * i, 1);
        fence_barrier_init();
        qkv_producer(maps, sbase, true);
      }
    }
    if (tid == 0) {
      for (int i = 0; i < G_STAGES; i++) {
        mbar_init(bar + B_GEMPTY + 8 * i, 2);
        mbar_init(bar + B_SFULL + 8 * i, 4);
        mbar_init(bar + B_SFREE + 8 * i, 1);
      }
      for (int i = 0; i < 2; i++) {
        mbar_init(bar + B_OFREE + 8 * i, 1);
        mbar_init(bar + B_QFULL + 8 * i, 1);
        mbar_init(bar + B_QEMPTY + 8 * i, 2);
        mbar_init(bar + B_KFULL + 8 * i, 1);
        mbar_init(bar + B_KEMPTY + 8 * i, 2);
        mbar_init(bar + B_VFULL + 8 * i, 1);
        mbar_init(bar + B_VEMPTY + 8 * i, 2);
      }
      for (int i = 0; i < O_STAGES; i++) {
        mbar_init(bar + B_OFULL + 8 * i, 1);
        mbar_init(bar + B_OEMPTY + 8 * i, 2);
      }
      mbar_init(bar + B_OY, 1);
      for (int i = 0; i < 3; i++) mbar_init(bar + seen_bar(i), 1);
      mbar_init(bar + B_OY2, 1);
      mbar_init(bar + B_DEAL, 1);
      mbar_init(bar + B_DEAL2, 1);
      mbar_init(bar + B_PAIR, 1);
      mbar_init(bar + B_OY + 8, 4);
      mbar_init(bar + B_OE, 4);
      mbar_init(bar + B_QDONE, 2);
      for (int i = 0; i < 8; i++) mbar_init(bar + B_CFULL + 8 * i, 1);
      for (int i = 0; i < CNT_N; i++) asm volatile("st.shared.u32 [%0], 0;" ::"r"(bar + B_PEND + 4 * i) : "memory");
      fence_barrier_init();
    }
    __syncthreads();
    asm volatile("barrier.cluster.arrive.relaxed.aligned;" ::: "memory");
    if ((mask & 1) && blockIdx.x >= 128) side_jobs(maps, sbase);
  }
  uint32_t smem0 = smem_u32(smem_raw);
  PHASE_PROLOGUE
  const bool do_qkv = (mask & 1) && blockIdx.x < 128, do_out = (mask & 4) && blockIdx.x < 128;
  TL(0, 1)

  if (wg != 2) {
    reg_alloc<232>();
    asm volatile("barrier.cluster.wait.acquire.aligned;" ::: "memory");
    if (wg == 1) named_bar_arrive(4, 256);
    uint32_t sn = 0;
    float rest[64], o[64], s[64];
    uint32_t q[32];
    if (do_qkv) {
      sn = qkv_consumer(maps, sbase, wg, mask & 2, q, rest, rt_zero);
    } else {
      undef_regs(rest);
#pragma unroll
      for (int j = 0; j < 32; j++) asm volatile("" : "=r"(q[j]));
    }
    undef_regs(o);
    undef_regs(s);
    TL(0, 2) TL(1, 0) TL(1, 1)
    const bool direct = do_out && wg == 0;
    float i0 = 0.f, i1 = 0.f;
    if (mask & 2) sn = attn_consumer(maps, sbase, wg, rt_zero, sn, q, rest, do_qkv, o, s, i0, i1);
    TL(2, 0)
    bool side = false;
    if (!direct) {
      wgmma_wait<0>();
      fence_regs(o);
      if (mask & 2) {
        const bool fused = mask & 4, mainc = blockIdx.x < 128;
        if (mainc) {
          PHASE_GIVEN
          put_o(sbase, wg, warp, lane, o, i0, i1);
          st_go(bar, wg, wtid, sn - 1);
        }
        const uint32_t b2 = blockIdx.x * 2 + (threadIdx.x >> 7);
        const uint32_t first = __shfl_sync(0xffffffffu, !fused ? b2 : mainc ? conv_first(maps) : (b2 - 255) * 128 - C_SIDE, 0);
        conv_consumer(maps, smem_u32(smem_raw), first, !fused ? 264 : mainc ? 16 : 1,
                      !fused ? DM : mainc ? (first | 127) + 1 - C_SIDE : first + C_SIDE, fused && !mainc,
                      fused && mainc);
      }
      side = (mask & 4) && blockIdx.x < 128;
    } else {
      out_gemm(maps, sbase, sn, mask & 2, o, s, i0, i1);
    }
    TL(1, 2) TL(2, 1) TL(2, 2) TL(3, 0) TL(3, 1)
    if (side + rt_zero) out_side(maps, smem_u32(smem_raw));
    tma_store_wait_read<0>();
  } else {
    reg_dealloc<40>();
    asm volatile("barrier.cluster.wait.acquire.aligned;" ::: "memory");
    const int w = __shfl_sync(0xffffffffu, tid >> 5, 0) - 8;
    if (w < 2) {
      if (do_qkv) prep_agent(maps, sbase, w, lane);
      if (elect_one()) store_agent(bar, w, w && do_out ? conv_first(maps) + 48 : 0, blockIdx.x >= 128 || mask == 4 ? 0 : mask == 1 ? 24 : 99);
      TL2(3, 2)
    } else {
      if (elect_one()) {
        const bool dry = w == 2;
        if (do_qkv && !dry) qkv_producer(maps, sbase, false);
        if (mask & 2) attn_producer(maps, sbase, do_qkv, do_out, dry);
        if (do_out) out_producer(maps, sbase, mask & 2, dry);
        if (dry) { TD(5) }
      }
      __syncwarp();
      if (w == 2) publisher(bar, tid & 31, !(mask & 2) ? 2 : do_out ? 3 : 4, !do_out ? 3 : do_qkv ? 0 : 2, do_qkv ? 4 : 0);
      if ((tid & 31) == 0) leave_kernel(mask);
    }
  }
}

typedef CUresult (*PFN_tmapEncode)(CUtensorMap*, CUtensorMapDataType, cuuint32_t, void*, const cuuint64_t*,
                                   const cuuint64_t*, const cuuint32_t*, const cuuint32_t*, CUtensorMapInterleave,
                                   CUtensorMapSwizzle, CUtensorMapL2promotion, CUtensorMapFloatOOBfill);
static PFN_tmapEncode s_encode = nullptr;

static void make_map_2d(CUtensorMap* m, const void* ptr, int rows, int cols, int box_rows) {
  cuuint64_t dims[2] = {(cuuint64_t)cols, (cuuint64_t)rows};
  cuuint64_t strides[1] = {(cuuint64_t)cols * 2};
  cuuint32_t box[2] = {cols < 64 ? 32u : 64u, (cuuint32_t)box_rows};
  cuuint32_t es[2] = {1, 1};
  s_encode(m, CU_TENSOR_MAP_DATA_TYPE_BFLOAT16, 2, const_cast<void*>(ptr), dims, strides, box, es,
           CU_TENSOR_MAP_INTERLEAVE_NONE, cols < 64 ? CU_TENSOR_MAP_SWIZZLE_64B : CU_TENSOR_MAP_SWIZZLE_128B, CU_TENSOR_MAP_L2_PROMOTION_L2_256B,
           CU_TENSOR_MAP_FLOAT_OOB_FILL_NONE);
}
static void make_map_3d(CUtensorMap* m, const void* ptr, int rows, int cols, int box_rows, int box_chunks) {
  cuuint64_t dims[3] = {64, (cuuint64_t)rows, (cuuint64_t)(cols / 64)};
  cuuint64_t strides[2] = {(cuuint64_t)cols * 2, 128};
  cuuint32_t box[3] = {64, (cuuint32_t)box_rows, (cuuint32_t)box_chunks};
  cuuint32_t es[3] = {1, 1, 1};
  s_encode(m, CU_TENSOR_MAP_DATA_TYPE_BFLOAT16, 3, const_cast<void*>(ptr), dims, strides, box, es,
           CU_TENSOR_MAP_INTERLEAVE_NONE, CU_TENSOR_MAP_SWIZZLE_128B, CU_TENSOR_MAP_L2_PROMOTION_L2_256B,
           CU_TENSOR_MAP_FLOAT_OOB_FILL_NONE);
}

static cudaLaunchConfig_t fused_cfg(cudaLaunchAttribute* at) {
  cudaLaunchConfig_t cfg = {};
  cfg.gridDim = dim3(132);
  cfg.blockDim = dim3(384);
  cfg.dynamicSmemBytes = SMEM_BYTES;
  cfg.stream = cudaStreamPerThread;
  at[0].id = cudaLaunchAttributeClusterDimension;
  at[0].val.clusterDim.x = 2;
  at[0].val.clusterDim.y = 1;
  at[0].val.clusterDim.z = 1;
  cfg.attrs = at;
  cfg.numAttrs = 1;
  return cfg;
}

extern "C" void kernel_launch(void* const* d_in, const int* in_sizes, int n_in, void* d_out, int out_size) {
  const bf16* x = (const bf16*)d_in[0];
  const bf16* ckv = (const bf16*)d_in[1];
  const bf16* wq = (const bf16*)d_in[2];
  const bf16* wuk = (const bf16*)d_in[3];
  const bf16* wuv = (const bf16*)d_in[4];
  const bf16* wo = (const bf16*)d_in[5];
  const bf16* bk = (const bf16*)d_in[7];
  const bf16* bv = (const bf16*)d_in[8];
  const bf16* shift_k = (const bf16*)d_in[9];
  const bf16* ssm_k = (const bf16*)d_in[10];
  const bf16* ssm_D = (const bf16*)d_in[11];
  const bf16* gate_w = (const bf16*)d_in[12];
  bf16* out = (bf16*)d_out;

  static void *pq = nullptr, *pk = nullptr, *pv = nullptr, *pctx = nullptr, *pb = nullptr, *pu = nullptr;
  static int max_clusters = 0;
  if (!s_encode) {
    void* fn = nullptr;
    cudaDriverEntryPointQueryResult qres;
    cudaGetDriverEntryPoint("cuTensorMapEncodeTiled", &fn, cudaEnableDefault, &qres);
    s_encode = (PFN_tmapEncode)fn;
    cudaGetSymbolAddress(&pq, g_q);
    cudaGetSymbolAddress(&pk, g_k);
    cudaGetSymbolAddress(&pv, g_v);
    cudaGetSymbolAddress(&pctx, g_ctx);
    cudaGetSymbolAddress(&pb, g_y2T);
    cudaGetSymbolAddress(&pu, g_kvT);
    cudaFuncSetAttribute(fused_kernel, cudaFuncAttributeMaxDynamicSharedMemorySize, SMEM_BYTES);
    cudaLaunchAttribute at[1];
    cudaLaunchConfig_t cfg = fused_cfg(at);
    if (cudaOccupancyMaxActiveClusters(&max_clusters, fused_kernel, &cfg) != cudaSuccess) max_clusters = 0;
  }

  Maps all = {};
  make_map_2d(&all.a[0], x, S_LEN, DM, 128);
  make_map_2d(&all.a[1], ckv, S_LEN, DC, 128);
  make_map_3d(&all.b[0], wq, DM, HDIM, 64, 4);
  make_map_3d(&all.b[1], wuk, DC, HDIM, 64, 4);
  make_map_3d(&all.b[2], wuv, DC, HDIM, 64, 4);
  make_map_2d(&all.c[0], pq, S_LEN, HDIM, 64);
  make_map_2d(&all.c[1], pk, S_LEN, HDIM, 64);
  make_map_2d(&all.c[2], pv, S_LEN, HDIM, 64);
  make_map_3d(&all.q, pq, S_LEN, HDIM, 128, 2);
  make_map_3d(&all.k, pk, S_LEN, HDIM, 128, 2);
  make_map_3d(&all.v, pv, S_LEN, HDIM, 128, 2);
  make_map_2d(&all.o, pctx, S_LEN, HDIM, 64);
  all.ssm_k = ssm_k;
  all.ssm_D = ssm_D;
  make_map_2d(&all.oa, pctx, S_LEN, HDIM, 128);
  make_map_2d(&all.ob, wo, HDIM, DM, 64);
  make_map_3d(&all.oc, out, S_LEN, DM, 16, 2);
  make_map_3d(&all.y, pb, DM, S_LEN, 16, 2);
  make_map_3d(&all.xs, x, S_LEN, DM, 16, 2);
  make_map_2d(&all.cu, pu, DM * 64, 32, 64);
  make_map_2d(&all.ch, ssm_k, DM * 64, 32, 64);

  make_map_2d(&all.bk, bk, S_LEN, DM, 35);
  make_map_2d(&all.bv, bv, S_LEN, DM, 32);
  for (int b = 0; b < 128; b++) {
    const int c = b >> 1, r = b & 1;
    const int G = c < 4 ? 0 : c < 36 ? (c - 4) % 8 : 1 + (c - 36) % 7;
    const int i = c < 4 ? 4 + c : c < 36 ? (c - 4) / 8 : 4 + (c - 36) / 7;
    all.id[b][0] = r + 2 * (i & 1) + 4 * (G & 3) + 16 * (i >> 1) + 64 * (G >> 2);
    all.id[b][1] = r + 2 * i + 16 * G;
    all.id[b][2] = r + 2 * G + 16 * i;
    all.id[b][3] = r + 2 * i == 15 ? 0x78 : 0xd8;
  }
  all.shift_k = shift_k;
  all.x = x;
  all.gate_w = gate_w;
  cudaLaunchAttribute at[1];
  cudaLaunchConfig_t cfg = fused_cfg(at);
  if (max_clusters >= 66) {
    cudaLaunchKernelEx(&cfg, fused_kernel, 7, x, wq, all);
  } else {
    for (int m = 1; m <= 4; m <<= 1) cudaLaunchKernelEx(&cfg, fused_kernel, m, x, wq, all);
  }
}
```

```cpp
#include <cuda_runtime.h>
#include <cuda_bf16.h>
#include <cuda.h>
#include <stdint.h>

typedef __nv_bfloat16 bf16;
#define INPLACE 3

constexpr int S_LEN = 2048;
constexpr int DM = 1024;
constexpr int NH = 32;
constexpr int HD = 128;
constexpr int DC = 512;
constexpr int HDIM = NH * HD;

__device__ __align__(1024) bf16 g_q[S_LEN * HDIM];
__device__ __align__(1024) bf16 g_k[S_LEN * HDIM];
__device__ __align__(1024) bf16 g_v[S_LEN * HDIM];
#define g_ctx g_q
__device__ __align__(1024) bf16 g_kvT[DM * S_LEN];
#define g_y2T g_kvT
__device__ __align__(1024) float g_gate[S_LEN];
enum { CNT_KV = 0, CNT_PREP = CNT_KV + 2, CNT_CTX, CNT_Y2 = CNT_CTX + 2, CNT_DONE = CNT_Y2 + 2, CNT_RANK, CNT_N };
__device__ unsigned int g_cnt[CNT_N * 32];
__device__ unsigned long long g_slot[128];

#define TL(k, i)
#define TL2(k, i)
#define TD(i)
#define CT(i)
#define GT(i)
#define GA(i)
#define ST(i)

__device__ __forceinline__ uint32_t smem_u32(const void* p) { return (uint32_t)__cvta_generic_to_shared(p); }

__device__ __forceinline__ void mbar_init(uint32_t bar, uint32_t count) {
  asm volatile("mbarrier.init.shared::cta.b64 [%0], %1;" ::"r"(bar), "r"(count));
}
__device__ __forceinline__ void mbar_expect_tx(uint32_t bar, uint32_t bytes) {
  asm volatile("mbarrier.arrive.expect_tx.shared::cta.b64 _, [%0], %1;" ::"r"(bar), "r"(bytes) : "memory");
}
__device__ __forceinline__ void mbar_arrive(uint32_t bar) {
  asm volatile("mbarrier.arrive.shared::cta.b64 _, [%0];" ::"r"(bar) : "memory");
}
__device__ __forceinline__ void mbar_wait(uint32_t bar, uint32_t parity) {
  uint32_t done;
  uint32_t spins = 0;
  do {
    asm volatile(
        "{\n.reg .pred p;\n"
        "mbarrier.try_wait.parity.shared::cta.b64 p, [%1], %2;\n"
        "selp.u32 %0, 1, 0, p;\n}\n"
        : "=r"(done)
        : "r"(bar), "r"(parity)
        : "memory");
    if (++spins > (1u << 22)) break;
  } while (!done);
}
__device__ __forceinline__ bool mbar_try(uint32_t bar, uint32_t parity) {
  uint32_t done;
  asm volatile(
      "{\n.reg .pred p;\n"
      "mbarrier.try_wait.parity.shared::cta.b64 p, [%1], %2;\n"
      "selp.u32 %0, 1, 0, p;\n}\n"
      : "=r"(done)
      : "r"(bar), "r"(parity)
      : "memory");
  return done != 0;
}
__device__ __forceinline__ bool mbar_test(uint32_t bar, uint32_t parity) {
  uint32_t done;
  asm volatile(
      "{\n.reg .pred p;\n"
      "mbarrier.test_wait.parity.shared::cta.b64 p, [%1], %2;\n"
      "selp.u32 %0, 1, 0, p;\n}\n"
      : "=r"(done)
      : "r"(bar), "r"(parity)
      : "memory");
  return done != 0;
}
__device__ __forceinline__ bool elect_one() {
  uint32_t pred;
  asm volatile("{\n.reg .pred p;\nelect.sync _|p, 0xffffffff;\nselp.u32 %0, 1, 0, p;\n}\n" : "=r"(pred));
  return pred != 0;
}
__device__ __forceinline__ void mbar_arrive_if(uint32_t bar, bool pred) {
  asm volatile(
      "{\n.reg .pred p;\nsetp.ne.b32 p, %1, 0;\n"
      "@p mbarrier.arrive.shared::cta.b64 _, [%0];\n}\n" ::"r"(bar),
      "r"((uint32_t)pred)
      : "memory");
}
__device__ __forceinline__ void mbar_wait_sleep(uint32_t bar, uint32_t parity) {
  uint32_t done;
  uint32_t spins = 0;
  do {
    asm volatile(
        "{\n.reg .pred p;\n"
        "mbarrier.try_wait.parity.shared::cta.b64 p, [%1], %2, %3;\n"
        "selp.u32 %0, 1, 0, p;\n}\n"
        : "=r"(done)
        : "r"(bar), "r"(parity), "r"(20000u)
        : "memory");
    if (++spins > (1u << 16)) break;
  } while (!done);
}
__device__ __forceinline__ void fence_barrier_init() {
  asm volatile("fence.mbarrier_init.release.cluster;" ::: "memory");
}
__device__ __forceinline__ void fence_proxy_async() {
  asm volatile("fence.proxy.async.shared::cta;" ::: "memory");
}
__device__ __forceinline__ void named_bar_sync(int id, int nthreads) {
  asm volatile("bar.sync %0, %1;" ::"r"(id), "r"(nthreads) : "memory");
}
__device__ __forceinline__ void named_bar_arrive(int id, int nthreads) {
  asm volatile("bar.arrive %0, %1;" ::"r"(id), "r"(nthreads) : "memory");
}
__device__ __forceinline__ void tma_load_2d(uint32_t dst, const CUtensorMap* m, uint32_t bar, int c0, int c1) {
  asm volatile(
      "cp.async.bulk.tensor.2d.shared::cluster.global.mbarrier::complete_tx::bytes [%0], [%1, {%3, %4}], [%2];" ::"r"(dst),
      "l"(reinterpret_cast<uint64_t>(m)), "r"(bar), "r"(c0), "r"(c1)
      : "memory");
}
__device__ __forceinline__ void tma_load_3d(uint32_t dst, const CUtensorMap* m, uint32_t bar, int c0, int c1, int c2) {
  asm volatile(
      "cp.async.bulk.tensor.3d.shared::cluster.global.mbarrier::complete_tx::bytes [%0], [%1, {%3, %4, %5}], [%2];" ::"r"(dst),
      "l"(reinterpret_cast<uint64_t>(m)), "r"(bar), "r"(c0), "r"(c1), "r"(c2)
      : "memory");
}
__device__ __forceinline__ void tma_store_2d(const CUtensorMap* m, uint32_t src, int c0, int c1) {
  asm volatile("cp.async.bulk.tensor.2d.global.shared::cta.bulk_group [%0, {%2, %3}], [%1];" ::"l"(
                   reinterpret_cast<uint64_t>(m)),
               "r"(src), "r"(c0), "r"(c1)
               : "memory");
}
__device__ __forceinline__ void bulk_load(uint32_t dst, const void* src, uint32_t bytes, uint32_t bar) {
  asm volatile("cp.async.bulk.shared::cluster.global.mbarrier::complete_tx::bytes [%0], [%1], %2, [%3];" ::"r"(dst),
               "l"(src), "r"(bytes), "r"(bar)
               : "memory");
}
__device__ __forceinline__ void tma_load_2d_mc(uint32_t dst, const CUtensorMap* m, uint32_t bar, int c0, int c1,
                                               uint16_t mask) {
  asm volatile(
      "cp.async.bulk.tensor.2d.shared::cluster.global.mbarrier::complete_tx::bytes.multicast::cluster [%0], [%1, {%3, "
      "%4}], [%2], %5;" ::"r"(dst),
      "l"(reinterpret_cast<uint64_t>(m)), "r"(bar), "r"(c0), "r"(c1), "h"(mask)
      : "memory");
}
__device__ __forceinline__ void mbar_arrive_cluster_if(uint32_t bar, uint32_t cta, bool pred) {
  asm volatile(
      "{\n.reg .b32 ra;\n.reg .pred p;\nsetp.ne.b32 p, %2, 0;\n"
      "mapa.shared::cluster.u32 ra, %0, %1;\n"
      "@p mbarrier.arrive.shared::cluster.b64 _, [ra];\n}\n" ::"r"(bar),
      "r"(cta), "r"((uint32_t)pred)
      : "memory");
}
__device__ __forceinline__ uint64_t policy_evict_first() {
  uint64_t pol;
  asm volatile("createpolicy.fractional.L2::evict_first.b64 %0, 1.0;" : "=l"(pol));
  return pol;
}
__device__ __forceinline__ void tma_load_2d_hint(uint32_t dst, const CUtensorMap* m, uint32_t bar, int c0, int c1,
                                                 uint64_t pol) {
  asm volatile(
      "cp.async.bulk.tensor.2d.shared::cluster.global.mbarrier::complete_tx::bytes.L2::cache_hint [%0], [%1, {%3, %4}], "
      "[%2], %5;" ::"r"(dst),
      "l"(reinterpret_cast<uint64_t>(m)), "r"(bar), "r"(c0), "r"(c1), "l"(pol)
      : "memory");
}
__device__ __forceinline__ void tma_load_3d_hint(uint32_t dst, const CUtensorMap* m, uint32_t bar, int c0, int c1,
                                                 int c2, uint64_t pol) {
  asm volatile(
      "cp.async.bulk.tensor.3d.shared::cluster.global.mbarrier::complete_tx::bytes.L2::cache_hint [%0], [%1, {%3, %4, "
      "%5}], [%2], %6;" ::"r"(dst),
      "l"(reinterpret_cast<uint64_t>(m)), "r"(bar), "r"(c0), "r"(c1), "r"(c2), "l"(pol)
      : "memory");
}
__device__ __forceinline__ void bulk_load_hint(uint32_t dst, const void* src, uint32_t bytes, uint32_t bar, uint64_t pol) {
  asm volatile(
      "cp.async.bulk.shared::cluster.global.mbarrier::complete_tx::bytes.L2::cache_hint [%0], [%1], %2, [%3], %4;" ::"r"(dst),
      "l"(src), "r"(bytes), "r"(bar), "l"(pol)
      : "memory");
}
__device__ __forceinline__ void cnt_signal_release(int which, uint32_t n) {
  asm volatile("red.release.gpu.global.add.u32 [%0], %1;" ::"l"(g_cnt + which * 32), "r"(n) : "memory");
}
__device__ __forceinline__ bool cnt_wait(int which, uint32_t target, uint32_t spins = 0) {
  uint32_t v;
  while (true) {
    asm volatile("ld.acquire.gpu.global.u32 %0, [%1];" : "=r"(v) : "l"(g_cnt + which * 32) : "memory");
    if (v >= target || ++spins > (1u << 18)) break;
    __nanosleep(64);
  }
  asm volatile("fence.proxy.async.global;" ::: "memory");
  return v >= target;
}
__device__ __forceinline__ void tma_store_3d(const CUtensorMap* m, uint32_t src, int c0, int c1, int c2) {
  asm volatile("cp.async.bulk.tensor.3d.global.shared::cta.bulk_group [%0, {%2, %3, %4}], [%1];" ::"l"(
                   reinterpret_cast<uint64_t>(m)),
               "r"(src), "r"(c0), "r"(c1), "r"(c2)
               : "memory");
}
__device__ __forceinline__ void tma_store_commit() { asm volatile("cp.async.bulk.commit_group;" ::: "memory"); }
template <int N>
__device__ __forceinline__ void tma_store_wait_read() {
  asm volatile("cp.async.bulk.wait_group.read %0;" ::"n"(N) : "memory");
}
template <int N>
__device__ __forceinline__ void tma_store_wait() {
  asm volatile("cp.async.bulk.wait_group %0;" ::"n"(N) : "memory");
}
__device__ __forceinline__ void wgmma_fence() { asm volatile("wgmma.fence.sync.aligned;" ::: "memory"); }
__device__ __forceinline__ void wgmma_commit() { asm volatile("wgmma.commit_group.sync.aligned;" ::: "memory"); }
template <int N>
__device__ __forceinline__ void wgmma_wait() {
  asm volatile("wgmma.wait_group.sync.aligned %0;" ::"n"(N) : "memory");
}
template <int R>
__device__ __forceinline__ void reg_alloc() { asm volatile("setmaxnreg.inc.sync.aligned.u32 %0;" ::"n"(R)); }
template <int R>
__device__ __forceinline__ void reg_dealloc() { asm volatile("setmaxnreg.dec.sync.aligned.u32 %0;" ::"n"(R)); }

__device__ __forceinline__ void stmatrix_x4(uint32_t addr, uint32_t r0, uint32_t r1, uint32_t r2, uint32_t r3) {
  asm volatile("stmatrix.sync.aligned.m8n8.x4.shared.b16 [%0], {%1, %2, %3, %4};" ::"r"(addr), "r"(r0), "r"(r1),
               "r"(r2), "r"(r3)
               : "memory");
}
__device__ __forceinline__ uint32_t pack_bf16(float lo, float hi) {
  uint32_t r;
  asm("cvt.rn.bf16x2.f32 %0, %1, %2;" : "=r"(r) : "f"(hi), "f"(lo));
  return r;
}
__device__ __forceinline__ float bf16_round(float x) { return __bfloat162float(__float2bfloat16_rn(x)); }
__device__ __forceinline__ float bf_lo(uint32_t v) { return __uint_as_float(v << 16); }
__device__ __forceinline__ float bf_hi(uint32_t v) { return __uint_as_float(v & 0xffff0000u); }
__device__ __forceinline__ uint4 lds128(uint32_t a) {
  uint4 v;
  asm volatile("ld.shared.v4.u32 {%0, %1, %2, %3}, [%4];" : "=r"(v.x), "=r"(v.y), "=r"(v.z), "=r"(v.w) : "r"(a));
  return v;
}
__device__ __forceinline__ void sts128(uint32_t a, uint4 v) {
  asm volatile("st.shared.v4.u32 [%0], {%1, %2, %3, %4};" ::"r"(a), "r"(v.x), "r"(v.y), "r"(v.z), "r"(v.w) : "memory");
}
__device__ __forceinline__ uint32_t mul_bf2(uint32_t a, uint32_t b) {
  uint32_t r;
  asm("mul.rn.bf16x2 %0, %1, %2;" : "=r"(r) : "r"(a), "r"(b));
  return r;
}
__device__ __forceinline__ float ex2(float x) {
  float y;
  asm("ex2.approx.ftz.f32 %0, %1;" : "=f"(y) : "f"(x));
  return y;
}
__device__ __forceinline__ float rcp(float x) {
  float y;
  asm("rcp.approx.ftz.f32 %0, %1;" : "=f"(y) : "f"(x));
  return y;
}
template <int N>
__device__ __forceinline__ void fence_regs(float (&r)[N]) {
#pragma unroll
  for (int i = 0; i < N; i++) asm volatile("" : "+f"(r[i])::"memory");
}

template <int N>
__device__ __forceinline__ void undef_regs(float (&r)[N]) {
#pragma unroll
  for (int i = 0; i < N; i++) asm volatile("" : "=f"(r[i]));
}
template <int N>
__device__ __forceinline__ void fence_regs_u(uint32_t (&r)[N]) {
#pragma unroll
  for (int i = 0; i < N; i++) asm volatile("" : "+r"(r[i])::"memory");
}

constexpr uint64_t DESC_SW128 = 1ull << 62;
__device__ __forceinline__ uint64_t make_desc(uint32_t addr, uint32_t lbo_bytes, uint32_t sbo_bytes, uint64_t swz) {
  return (uint64_t)((addr & 0x3FFFF) >> 4) | ((uint64_t)((lbo_bytes & 0x3FFFF) >> 4) << 16) |
         ((uint64_t)((sbo_bytes & 0x3FFFF) >> 4) << 32) | swz;
}

__device__ __forceinline__ uint64_t desc_add(uint64_t d, uint32_t off16) {
  return (d & 0xFFFFFFFF00000000ull) | (uint64_t)((uint32_t)d + off16);
}

__device__ __forceinline__ void wgmma_m64n256_ss_tb(float (&d)[128], uint64_t da, uint64_t db, int sd) {
  asm volatile(
    "{\n.reg .pred p;\nsetp.ne.b32 p, %130, 0;\n"
    "wgmma.mma_async.sync.aligned.m64n256k16.f32.bf16.bf16 "
    "{%0, %1, %2, %3, %4, %5, %6, %7, %8, %9, %10, %11, %12, %13, %14, %15, %16, %17, %18, %19, %20, %21, %22, %23, %24, %25, %26, %27, %28, %29, %30, %31, %32, %33, %34, %35, %36, %37, %38, %39, %40, %41, %42, %43, %44, %45, %46, %47, %48, %49, %50, %51, %52, %53, %54, %55, %56, %57, %58, %59, %60, %61, %62, %63, %64, %65, %66, %67, %68, %69, %70, %71, %72, %73, %74, %75, %76, %77, %78, %79, %80, %81, %82, %83, %84, %85, %86, %87, %88, %89, %90, %91, %92, %93, %94, %95, %96, %97, %98, %99, %100, %101, %102, %103, %104, %105, %106, %107, %108, %109, %110, %111, %112, %113, %114, %115, %116, %117, %118, %119, %120, %121, %122, %123, %124, %125, %126, %127}, %128, %129, p, 1, 1, 0, 1;\n}\n"
    : "+f"(d[0]), "+f"(d[1]), "+f"(d[2]), "+f"(d[3]), "+f"(d[4]), "+f"(d[5]), "+f"(d[6]), "+f"(d[7]), "+f"(d[8]), "+f"(d[9]), "+f"(d[10]), "+f"(d[11]), "+f"(d[12]), "+f"(d[13]), "+f"(d[14]), "+f"(d[15]), "+f"(d[16]), "+f"(d[17]), "+f"(d[18]), "+f"(d[19]), "+f"(d[20]), "+f"(d[21]), "+f"(d[22]), "+f"(d[23]), "+f"(d[24]), "+f"(d[25]), "+f"(d[26]), "+f"(d[27]), "+f"(d[28]), "+f"(d[29]), "+f"(d[30]), "+f"(d[31]), "+f"(d[32]), "+f"(d[33]), "+f"(d[34]), "+f"(d[35]), "+f"(d[36]), "+f"(d[37]), "+f"(d[38]), "+f"(d[39]), "+f"(d[40]), "+f"(d[41]), "+f"(d[42]), "+f"(d[43]), "+f"(d[44]), "+f"(d[45]), "+f"(d[46]), "+f"(d[47]), "+f"(d[48]), "+f"(d[49]), "+f"(d[50]), "+f"(d[51]), "+f"(d[52]), "+f"(d[53]), "+f"(d[54]), "+f"(d[55]), "+f"(d[56]), "+f"(d[57]), "+f"(d[58]), "+f"(d[59]), "+f"(d[60]), "+f"(d[61]), "+f"(d[62]), "+f"(d[63]), "+f"(d[64]), "+f"(d[65]), "+f"(d[66]), "+f"(d[67]), "+f"(d[68]), "+f"(d[69]), "+f"(d[70]), "+f"(d[71]), "+f"(d[72]), "+f"(d[73]), "+f"(d[74]), "+f"(d[75]), "+f"(d[76]), "+f"(d[77]), "+f"(d[78]), "+f"(d[79]), "+f"(d[80]), "+f"(d[81]), "+f"(d[82]), "+f"(d[83]), "+f"(d[84]), "+f"(d[85]), "+f"(d[86]), "+f"(d[87]), "+f"(d[88]), "+f"(d[89]), "+f"(d[90]), "+f"(d[91]), "+f"(d[92]), "+f"(d[93]), "+f"(d[94]), "+f"(d[95]), "+f"(d[96]), "+f"(d[97]), "+f"(d[98]), "+f"(d[99]), "+f"(d[100]), "+f"(d[101]), "+f"(d[102]), "+f"(d[103]), "+f"(d[104]), "+f"(d[105]), "+f"(d[106]), "+f"(d[107]), "+f"(d[108]), "+f"(d[109]), "+f"(d[110]), "+f"(d[111]), "+f"(d[112]), "+f"(d[113]), "+f"(d[114]), "+f"(d[115]), "+f"(d[116]), "+f"(d[117]), "+f"(d[118]), "+f"(d[119]), "+f"(d[120]), "+f"(d[121]), "+f"(d[122]), "+f"(d[123]), "+f"(d[124]), "+f"(d[125]), "+f"(d[126]), "+f"(d[127])
    : "l"(da), "l"(db), "r"(sd));
}

__device__ __forceinline__ void wgmma_m64n128_ss(float (&d)[64], uint64_t da, uint64_t db, int sd) {
  asm volatile(
    "{\n.reg .pred p;\nsetp.ne.b32 p, %66, 0;\n"
    "wgmma.mma_async.sync.aligned.m64n128k16.f32.bf16.bf16 "
    "{%0, %1, %2, %3, %4, %5, %6, %7, %8, %9, %10, %11, %12, %13, %14, %15, %16, %17, %18, %19, %20, %21, %22, %23, %24, %25, %26, %27, %28, %29, %30, %31, %32, %33, %34, %35, %36, %37, %38, %39, %40, %41, %42, %43, %44, %45, %46, %47, %48, %49, %50, %51, %52, %53, %54, %55, %56, %57, %58, %59, %60, %61, %62, %63}, %64, %65, p, 1, 1, 0, 0;\n}\n"
    : "+f"(d[0]), "+f"(d[1]), "+f"(d[2]), "+f"(d[3]), "+f"(d[4]), "+f"(d[5]), "+f"(d[6]), "+f"(d[7]), "+f"(d[8]), "+f"(d[9]), "+f"(d[10]), "+f"(d[11]), "+f"(d[12]), "+f"(d[13]), "+f"(d[14]), "+f"(d[15]), "+f"(d[16]), "+f"(d[17]), "+f"(d[18]), "+f"(d[19]), "+f"(d[20]), "+f"(d[21]), "+f"(d[22]), "+f"(d[23]), "+f"(d[24]), "+f"(d[25]), "+f"(d[26]), "+f"(d[27]), "+f"(d[28]), "+f"(d[29]), "+f"(d[30]), "+f"(d[31]), "+f"(d[32]), "+f"(d[33]), "+f"(d[34]), "+f"(d[35]), "+f"(d[36]), "+f"(d[37]), "+f"(d[38]), "+f"(d[39]), "+f"(d[40]), "+f"(d[41]), "+f"(d[42]), "+f"(d[43]), "+f"(d[44]), "+f"(d[45]), "+f"(d[46]), "+f"(d[47]), "+f"(d[48]), "+f"(d[49]), "+f"(d[50]), "+f"(d[51]), "+f"(d[52]), "+f"(d[53]), "+f"(d[54]), "+f"(d[55]), "+f"(d[56]), "+f"(d[57]), "+f"(d[58]), "+f"(d[59]), "+f"(d[60]), "+f"(d[61]), "+f"(d[62]), "+f"(d[63])
    : "l"(da), "l"(db), "r"(sd));
}

__device__ __forceinline__ void wgmma_m64n128_ss_tb(float (&d)[64], uint64_t da, uint64_t db, int sd) {
  asm volatile(
    "{\n.reg .pred p;\nsetp.ne.b32 p, %66, 0;\n"
    "wgmma.mma_async.sync.aligned.m64n128k16.f32.bf16.bf16 "
    "{%0, %1, %2, %3, %4, %5, %6, %7, %8, %9, %10, %11, %12, %13, %14, %15, %16, %17, %18, %19, %20, %21, %22, %23, %24, %25, %26, %27, %28, %29, %30, %31, %32, %33, %34, %35, %36, %37, %38, %39, %40, %41, %42, %43, %44, %45, %46, %47, %48, %49, %50, %51, %52, %53, %54, %55, %56, %57, %58, %59, %60, %61, %62, %63}, %64, %65, p, 1, 1, 0, 1;\n}\n"
    : "+f"(d[0]), "+f"(d[1]), "+f"(d[2]), "+f"(d[3]), "+f"(d[4]), "+f"(d[5]), "+f"(d[6]), "+f"(d[7]), "+f"(d[8]), "+f"(d[9]), "+f"(d[10]), "+f"(d[11]), "+f"(d[12]), "+f"(d[13]), "+f"(d[14]), "+f"(d[15]), "+f"(d[16]), "+f"(d[17]), "+f"(d[18]), "+f"(d[19]), "+f"(d[20]), "+f"(d[21]), "+f"(d[22]), "+f"(d[23]), "+f"(d[24]), "+f"(d[25]), "+f"(d[26]), "+f"(d[27]), "+f"(d[28]), "+f"(d[29]), "+f"(d[30]), "+f"(d[31]), "+f"(d[32]), "+f"(d[33]), "+f"(d[34]), "+f"(d[35]), "+f"(d[36]), "+f"(d[37]), "+f"(d[38]), "+f"(d[39]), "+f"(d[40]), "+f"(d[41]), "+f"(d[42]), "+f"(d[43]), "+f"(d[44]), "+f"(d[45]), "+f"(d[46]), "+f"(d[47]), "+f"(d[48]), "+f"(d[49]), "+f"(d[50]), "+f"(d[51]), "+f"(d[52]), "+f"(d[53]), "+f"(d[54]), "+f"(d[55]), "+f"(d[56]), "+f"(d[57]), "+f"(d[58]), "+f"(d[59]), "+f"(d[60]), "+f"(d[61]), "+f"(d[62]), "+f"(d[63])
    : "l"(da), "l"(db), "r"(sd));
}

template <int TB>
__device__ __forceinline__ void wgmma_m64n128_rs(float* d, uint32_t a0, uint32_t a1, uint32_t a2, uint32_t a3, uint64_t db, int sd) {
  asm volatile(
    "{\n.reg .pred p;\nsetp.ne.b32 p, %69, 0;\n"
    "wgmma.mma_async.sync.aligned.m64n128k16.f32.bf16.bf16 "
    "{%0, %1, %2, %3, %4, %5, %6, %7, %8, %9, %10, %11, %12, %13, %14, %15, %16, %17, %18, %19, %20, %21, %22, %23, %24, %25, %26, %27, %28, %29, %30, %31, %32, %33, %34, %35, %36, %37, %38, %39, %40, %41, %42, %43, %44, %45, %46, %47, %48, %49, %50, %51, %52, %53, %54, %55, %56, %57, %58, %59, %60, %61, %62, %63}, {%64, %65, %66, %67}, %68, p, 1, 1, %70;\n}\n"
    : "+f"(d[0]), "+f"(d[1]), "+f"(d[2]), "+f"(d[3]), "+f"(d[4]), "+f"(d[5]), "+f"(d[6]), "+f"(d[7]), "+f"(d[8]), "+f"(d[9]), "+f"(d[10]), "+f"(d[11]), "+f"(d[12]), "+f"(d[13]), "+f"(d[14]), "+f"(d[15]), "+f"(d[16]), "+f"(d[17]), "+f"(d[18]), "+f"(d[19]), "+f"(d[20]), "+f"(d[21]), "+f"(d[22]), "+f"(d[23]), "+f"(d[24]), "+f"(d[25]), "+f"(d[26]), "+f"(d[27]), "+f"(d[28]), "+f"(d[29]), "+f"(d[30]), "+f"(d[31]), "+f"(d[32]), "+f"(d[33]), "+f"(d[34]), "+f"(d[35]), "+f"(d[36]), "+f"(d[37]), "+f"(d[38]), "+f"(d[39]), "+f"(d[40]), "+f"(d[41]), "+f"(d[42]), "+f"(d[43]), "+f"(d[44]), "+f"(d[45]), "+f"(d[46]), "+f"(d[47]), "+f"(d[48]), "+f"(d[49]), "+f"(d[50]), "+f"(d[51]), "+f"(d[52]), "+f"(d[53]), "+f"(d[54]), "+f"(d[55]), "+f"(d[56]), "+f"(d[57]), "+f"(d[58]), "+f"(d[59]), "+f"(d[60]), "+f"(d[61]), "+f"(d[62]), "+f"(d[63])
    : "r"(a0), "r"(a1), "r"(a2), "r"(a3), "l"(db), "r"(sd), "n"(TB));
}

__device__ __forceinline__ void wgmma_m64n64_rs_tb(float (&d)[32], const uint32_t (&a)[4], uint64_t db, int sd) {
  asm volatile(
    "{\n.reg .pred p;\nsetp.ne.b32 p, %37, 0;\n"
    "wgmma.mma_async.sync.aligned.m64n64k16.f32.bf16.bf16 "
    "{%0, %1, %2, %3, %4, %5, %6, %7, %8, %9, %10, %11, %12, %13, %14, %15, %16, %17, %18, %19, %20, %21, %22, %23, %24, %25, %26, %27, %28, %29, %30, %31}, {%32, %33, %34, %35}, %36, p, 1, 1, 1;\n}\n"
    : "+f"(d[0]), "+f"(d[1]), "+f"(d[2]), "+f"(d[3]), "+f"(d[4]), "+f"(d[5]), "+f"(d[6]), "+f"(d[7]), "+f"(d[8]), "+f"(d[9]), "+f"(d[10]), "+f"(d[11]), "+f"(d[12]), "+f"(d[13]), "+f"(d[14]), "+f"(d[15]), "+f"(d[16]), "+f"(d[17]), "+f"(d[18]), "+f"(d[19]), "+f"(d[20]), "+f"(d[21]), "+f"(d[22]), "+f"(d[23]), "+f"(d[24]), "+f"(d[25]), "+f"(d[26]), "+f"(d[27]), "+f"(d[28]), "+f"(d[29]), "+f"(d[30]), "+f"(d[31])
    : "r"(a[0]), "r"(a[1]), "r"(a[2]), "r"(a[3]), "l"(db), "r"(sd));
}

__device__ __forceinline__ void wgmma_m64n32_rs_tb(float (&d)[16], const uint32_t (&a)[4], uint64_t db, int sd) {
  asm volatile(
    "{\n.reg .pred p;\nsetp.ne.b32 p, %21, 0;\n"
    "wgmma.mma_async.sync.aligned.m64n32k16.f32.bf16.bf16 "
    "{%0, %1, %2, %3, %4, %5, %6, %7, %8, %9, %10, %11, %12, %13, %14, %15}, {%16, %17, %18, %19}, %20, p, 1, 1, 1;\n}\n"
    : "+f"(d[0]), "+f"(d[1]), "+f"(d[2]), "+f"(d[3]), "+f"(d[4]), "+f"(d[5]), "+f"(d[6]), "+f"(d[7]), "+f"(d[8]), "+f"(d[9]), "+f"(d[10]), "+f"(d[11]), "+f"(d[12]), "+f"(d[13]), "+f"(d[14]), "+f"(d[15])
    : "r"(a[0]), "r"(a[1]), "r"(a[2]), "r"(a[3]), "l"(db), "r"(sd));
}

constexpr int G_STAGES = 4;
constexpr int G_A_BYTES = 128 * 64 * 2;
constexpr int G_B_BYTES = 256 * 64 * 2;
constexpr int G_STAGE_BYTES = G_A_BYTES + G_B_BYTES;
constexpr int G_STG_OFF = G_STAGES * G_STAGE_BYTES;
constexpr int BAR_OFF = G_STG_OFF + 32768 + 2048;
constexpr int SMEM_BYTES = BAR_OFF + 1024;
constexpr int B_GFULL = 0, B_GEMPTY = 32, B_SEEN = 64, B_PFULL = 224;
constexpr int B_KFULL = 80, B_KEMPTY = 96, B_VFULL = 112, B_VEMPTY = 128, B_QFULL = 144, B_QEMPTY = 160,
              B_QDONE = 184;
constexpr int B_CFULL = 192;
constexpr int B_OFREE = 256, B_OFULL = 272, B_OEMPTY = 320, B_OY = 368, B_OY2 = 384, B_OE = 768;
constexpr int B_DEAL = 312, B_DEAL2 = 360, B_LIST = 640, B_PAIR = 504;
constexpr int B_SFULL = 392, B_SFREE = 424, B_PEND = 456, B_SCMD = 512;

#define PHASE_PROLOGUE                                                                \
  uint32_t tid, rt_zero;                                                              \
  asm volatile("mov.u32 %0, %%tid.x;" : "=r"(tid));                                   \
  asm volatile("mov.u32 %0, %%nctaid.y;" : "=r"(rt_zero));                            \
  asm volatile("" : "+r"(smem0));                                                     \
  rt_zero = __shfl_sync(0xffffffffu, rt_zero >> 8, 0);   \
  const uint32_t sbase = __shfl_sync(0xffffffffu, smem0, 0);                          \
  const uint32_t bar = sbase + BAR_OFF;                                               \
  const int wg = __shfl_sync(0xffffffffu, tid >> 7, 0);                               \
  const int warp = (tid >> 5) & 3, lane = tid & 31, wtid = tid & 127;                 \
  (void)rt_zero; (void)bar; (void)warp; (void)lane; (void)wtid;

#define PHASE_GIVEN PHASE_GIVEN_(0)
#define PHASE_GIVEN_(z)                                                               \
  uint32_t tid;                                                                       \
  asm volatile("mov.u32 %0, %%tid.x;" : "=r"(tid));                                   \
  tid |= z;                               \
  const uint32_t bar = sbase + BAR_OFF;                                               \
  const int warp = (tid >> 5) & 3, lane = tid & 31, wtid = tid & 127;

enum { ST_BOX1, ST_BOX2, ST_BOX2Q, ST_BOX2L };
__device__ __forceinline__ void st_cmd(uint32_t bar, int wg, int wtid, uint32_t n, int kind, const void* dst,
                                       uint32_t src, int c0, int c1, int sig, uint32_t lazy = 0) {
  if (wtid == 0) {
    const uint32_t c = bar + B_SCMD + wg * 64 + (n & 1) * 32;
    const uint64_t d = reinterpret_cast<uint64_t>(dst);
    sts128(c, make_uint4(kind, src, c0, c1));
    sts128(c + 16, make_uint4((uint32_t)d, (uint32_t)(d >> 32), sig, lazy));
  }
}
__device__ __forceinline__ void st_go(uint32_t bar, int wg, int wtid, uint32_t n) {
  fence_proxy_async();
  __syncwarp();
  mbar_arrive_if(bar + B_SFULL + wg * 16 + (n & 1) * 8, (wtid & 31) == 0);
}
__device__ __forceinline__ void st_post(uint32_t bar, int wg, int wtid, uint32_t n, int kind, const void* dst,
                                        uint32_t src, int c0, int c1, int sig, uint32_t lazy = 0) {
  st_cmd(bar, wg, wtid, n, kind, dst, src, c0, c1, sig, lazy);
  st_go(bar, wg, wtid, n);
}
__device__ __forceinline__ void st_wait(uint32_t bar, int wg, uint32_t n) {
  const uint32_t b = bar + B_SFREE + wg * 16 + (n & 1) * 8;
  if (!mbar_try(b, ~(n >> 1) & 1)) mbar_wait(b, ~(n >> 1) & 1);
}
__device__ __forceinline__ void note(uint32_t bar, uint32_t cnt) {
  asm volatile("red.release.cta.shared.add.u32 [%0], 1;" ::"r"(bar + B_PEND + 4 * cnt) : "memory");
}
#define LAZY_NS 250
#define DEAL_NS 400
#define DEAL_NS2 1250
constexpr uint32_t C_NONE = 0x10000;
__device__ __forceinline__ void deal(uint32_t bar, uint32_t r, uint32_t t, uint32_t own) {
  uint64_t p;
  uint32_t spins = 0;
  while (true) {
    asm volatile("ld.relaxed.gpu.global.u64 %0, [%1];" : "=l"(p) : "l"(g_slot + 127 - r) : "memory");
    if (p || ++spins > (1u << 18)) break;
    __nanosleep(100);
  }
  const uint32_t pc = (uint32_t)p;
  int dt = (uint32_t)(p >> 32) - t;
  if (r >= 64) {
    sts128(bar + B_LIST, make_uint4(-dt > DEAL_NS2 ? C_NONE : own - 16, -dt > DEAL_NS ? C_NONE : own, C_NONE, C_NONE));
    mbar_arrive(bar + B_DEAL);
    dt = 0;
  }
  sts128(bar + B_LIST + 16, make_uint4(dt > DEAL_NS ? pc : C_NONE, dt > DEAL_NS2 ? pc - 16 : C_NONE, C_NONE, C_NONE));
  mbar_arrive(bar + B_DEAL2);
}
__device__ __forceinline__ void store_agent(uint32_t bar, int wg, uint32_t last_ch, uint32_t n_end) {
  mbar_arrive(bar + B_SFREE + wg * 16);
  mbar_arrive(bar + B_SFREE + wg * 16 + 8);
  bool more = true;
  for (uint32_t n = 0; n < n_end && more; n++) {
    mbar_wait_sleep(bar + B_SFULL + wg * 16 + (n & 1) * 8, (n >> 1) & 1);
    const uint4 c = lds128(bar + B_SCMD + wg * 64 + (n & 1) * 32);
    const uint4 d = lds128(bar + B_SCMD + wg * 64 + (n & 1) * 32 + 16);
    uint32_t t;
    asm volatile("mov.u32 %0, %%globaltimer_lo;" : "=r"(t));
    uint32_t r = 0, tp = t;
    if (c.x == ST_BOX2L && last_ch) {
      mbar_expect_tx(bar + B_PAIR, 4);
      asm volatile(
          "{\n.reg .b32 ra;\nmapa.shared::cluster.u32 ra, %0, %1;\n"
          "st.async.weak.shared::cluster.mbarrier::complete_tx::bytes.u32 [ra + 224], %2, [ra];\n}\n" ::"r"(bar + B_PAIR),
          "r"(~blockIdx.x & 1), "r"(t)
          : "memory");
      mbar_wait_sleep(bar + B_PAIR, 0);
      r = atomicAdd(g_cnt + CNT_RANK * 32, 1u) & 127;
      asm volatile("ld.shared.u32 %0, [%1];" : "=r"(tp) : "r"(bar + B_PAIR + 224) : "memory");
      if ((int)(tp - t) < 0) tp = t;
      asm volatile("st.relaxed.gpu.global.u64 [%0], %1;" ::"l"(g_slot + r), "l"(((uint64_t)tp << 32) | last_ch) : "memory");
      if (r < 64) {
        sts128(bar + B_LIST, make_uint4(last_ch - 16, last_ch, C_NONE, C_NONE));
        mbar_arrive(bar + B_DEAL);
      } else {
        deal(bar, r, tp, last_ch);
      }
    }
    for (uint32_t t1 = t; d.w && t1 - t < (2 * d.w + wg) * LAZY_NS;) {
      __nanosleep(200);
      asm volatile("mov.u32 %0, %%globaltimer_lo;" : "=r"(t1));
    }
    const CUtensorMap* dst = reinterpret_cast<const CUtensorMap*>((uint64_t)d.x | ((uint64_t)d.y << 32));
    tma_store_2d(dst, c.y, c.z, c.w);
    if (c.x >= ST_BOX2) tma_store_2d(dst, c.y + 8192, c.z + 64, c.w);
    tma_store_commit();
    tma_store_wait_read<0>();
    mbar_arrive(bar + B_SFREE + wg * 16 + (n & 1) * 8);
    if (c.x == ST_BOX2L) mbar_arrive(bar + B_OFREE + 8 * wg);
    if ((int)d.z >= 0) {
      tma_store_wait<0>();
      if (d.z == 0) { TD(6) }
      asm volatile("fence.proxy.async.global;" ::: "memory");
      if (c.x == ST_BOX2Q) mbar_arrive(bar + B_QDONE);
      else note(bar, d.z);
      if (c.x == ST_BOX2L) {
        note(bar, CNT_DONE);
        more = false;
        if (last_ch && r < 64) deal(bar, r, tp, last_ch);
      }
    }
  }
  if (more) note(bar, CNT_DONE);
}

struct Maps {
  const bf16 *shift_k, *x, *gate_w, *ssm_k, *ssm_D;
  uint8_t id[128][4];
  CUtensorMap a[2];
  CUtensorMap b[3];
  CUtensorMap c[3];
  CUtensorMap bk, bv;
  CUtensorMap q, k, v, o;
  CUtensorMap oa, ob, oc;
  CUtensorMap y, xs;
  CUtensorMap cu, ch;
};

constexpr int P_SLOT = 67 * 128, P_V = 35 * 128, P_TAPS = 2 * P_SLOT;
__device__ __forceinline__ void ldsm4t(uint32_t (&r)[4], uint32_t a) {
  asm volatile("ldmatrix.sync.aligned.m8n8.x4.trans.shared.b16 {%0, %1, %2, %3}, [%4];"
               : "=r"(r[0]), "=r"(r[1]), "=r"(r[2]), "=r"(r[3])
               : "r"(a));
}
__device__ __forceinline__ uint32_t fma_bf2(uint32_t a, uint32_t b, uint32_t c) {
  uint32_t r;
  asm("fma.rn.bf16x2 %0, %1, %2, %3;" : "=r"(r) : "r"(a), "r"(b), "r"(c));
  return r;
}
__device__ __forceinline__ void prep_agent(const Maps& maps, uint32_t sbase, int w, int lane) {
  const uint32_t bar = sbase + BAR_OFF, pb = bar + B_PFULL + w * 16;
  const int d0 = (blockIdx.x >> 3) * 64, t0 = (blockIdx.x & 7) * 256 + w * 128;
  mbar_wait_sleep(bar + B_GFULL + 8 * (G_STAGES - 1), 0);
#pragma unroll 1
  for (int i = -1; i < 4; i++) {
    GA(82 + 2 * i)
    if (i >= 0) mbar_wait_sleep(pb + (i & 1) * 8, i >> 1);
    GA(83 + 2 * i)
    const uint32_t so = sbase + G_STG_OFF + w * (P_TAPS + 512) + (i & 1) * P_SLOT;
    if (i < 3 && elect_one()) {
      const uint32_t b = pb + (~i & 1) * 8, dst = so + (i & 1 ? -P_SLOT : P_SLOT);
      mbar_expect_tx(b, i < 0 ? P_SLOT + 512 : P_SLOT);
      const uint64_t pol = policy_evict_first();
      tma_load_2d_hint(dst, &maps.bk, b, d0, t0 + 32 * i + 29, pol);
      tma_load_2d_hint(dst + P_V, &maps.bv, b, d0, t0 + 32 * i + 32, pol);
      if (i < 0) bulk_load(sbase + G_STG_OFF + P_TAPS, maps.shift_k + d0 * 4, 512, b);
    }
    if (i < 0) continue;
    uint32_t ak[4];
#pragma unroll
    for (int r = 0; r < 4; r++) {
      const uint32_t a = so / 128 + r + 4 * (lane & 6) + (((lane >> 2) ^ lane) & 6) + (lane & 1);
      ak[r] = a * 128 + (a & 7) * 16;
    }
    bf16* dst = g_kvT + (size_t)(d0 + (lane >> 2)) * S_LEN + t0 + ((lane & 3) + 4 * i) * 8;
#pragma unroll 1
    for (int cg = 0; cg < 128; cg += 16) {
      uint32_t t01, t23, k[4][4], v[4];
      asm volatile("ld.shared.v2.u32 {%0, %1}, [%2];"
                   : "=r"(t01), "=r"(t23)
                   : "r"(sbase + G_STG_OFF + P_TAPS + cg * 4 + (lane >> 2) * 8));
#pragma unroll
      for (int r = 0; r < 4; r++) ldsm4t(k[r], ak[r] ^ cg);
      ldsm4t(v, (ak[3] ^ cg) + 4096);
      const uint32_t w0 = __byte_perm(t01, 0, 0x1010), w1 = __byte_perm(t01, 0, 0x3232);
      const uint32_t w2 = __byte_perm(t23, 0, 0x1010), w3 = __byte_perm(t23, 0, 0x3232);
#pragma unroll
      for (int j = 0; j < 4; j++)
        v[j] = mul_bf2(fma_bf2(k[3][j], w0, fma_bf2(k[2][j], w1, fma_bf2(k[1][j], w2, mul_bf2(k[0][j], w3)))), v[j]);
      const bool s1 = lane & 1, s2 = lane & 2;
      const uint32_t a0 = s1 ? v[1] : v[0], a1 = s1 ? v[0] : v[1], a2 = s1 ? v[3] : v[2], a3 = s1 ? v[2] : v[3];
      *reinterpret_cast<uint4*>(dst) = make_uint4(s2 ? a2 : a0, s2 ? a3 : a1, s2 ? a0 : a2, s2 ? a1 : a3);
      dst += 8 * S_LEN;
    }
    fence_proxy_async();
    __syncwarp();
  }
  GA(90)
  if (lane == 0) note(bar, CNT_PREP);
  __syncwarp();
  GA(91)
}

__device__ __forceinline__ void qkv_tile(const Maps& maps, int it, int& which, int& m_tile, int& n_tile) {
  const bool q = it == 0 || it >= 5;
  const int b = maps.id[blockIdx.x][it >= 5];
  which = q ? 0 : 2 - (it & 1);
  m_tile = b & 15;
  n_tile = (b >> 4) * 2 + ((0x19 >> it) & 1);
}

constexpr int G_NTILES = 6;
__device__ __forceinline__ uint32_t qkv_flip(int it) { return ((0x0b >> it) & 1) * 3; }
__device__ __forceinline__ void qkv_producer(const Maps& maps, uint32_t sbase, bool first) {
  const uint32_t bar = sbase + BAR_OFF;
  uint32_t stage = 0, phase = 0;
#pragma unroll 1
  for (int it = 0; it < (first ? 1 : G_NTILES); it++) {
    int which, m_tile, n_tile;
    qkv_tile(maps, it, which, m_tile, n_tile);
    const CUtensorMap* ma = &maps.a[which == 0 ? 0 : 1];
    const CUtensorMap* mb = &maps.b[which];
    const int nk = first ? G_STAGES : which == 0 ? 16 : 8;
#pragma unroll 1
    for (int kt = (it == 0 && !first) ? G_STAGES : 0; kt < nk; kt++) {
      if (!first) mbar_wait_sleep(bar + B_GEMPTY + 8 * stage, phase);
      const uint32_t fb = bar + B_GFULL + 8 * stage;
      const uint32_t sa = sbase + stage * G_STAGE_BYTES;
      const int k0 = (kt ^ ((0x14 >> it) & 1) * 7) * 64;
      const bool keep = ((0x1c >> it) & 1) && kt < G_STAGES;
      mbar_expect_tx(fb, keep ? G_B_BYTES : G_STAGE_BYTES);
      if (!keep) tma_load_2d(sbase + (stage ^ qkv_flip(it)) * G_STAGE_BYTES, ma, fb, k0, m_tile * 128);
      tma_load_3d(sa + G_A_BYTES, mb, fb, 0, k0, n_tile * 4);
      if (++stage == G_STAGES) { stage = 0; phase ^= 1; }
      {
        const int b = maps.id[blockIdx.x][1];
        if (it == 2 && kt == (b & 7)) {
          for (int i = 0; i < 2; i++)
            asm volatile("cp.async.bulk.prefetch.tensor.2d.L2.global.tile [%0, {%1, %2}];" ::"l"(&maps.a[0]),
                         "r"((b >> 4) * 128 + i * 64), "r"((b & 15) * 128)
                         : "memory");
          asm volatile("cp.async.bulk.prefetch.tensor.3d.L2.global.tile [%0, {%1, %2, %3}];" ::"l"(&maps.b[1 + ((b >> 3) & 1)]),
                       "r"(0), "r"((b & 7) * 64), "r"((b >> 4) * 8 + 4)
                       : "memory");
        }
        if (it == 3 && kt == (b & 7))
          asm volatile("cp.async.bulk.prefetch.tensor.3d.L2.global.tile [%0, {%1, %2, %3}];" ::"l"(&maps.b[0]), "r"(0),
                       "r"((b & 15) * 64), "r"((b >> 4) * 8)
                       : "memory");
      }
    }
  }
}

__device__ __forceinline__ uint32_t seen_bar(uint32_t item) { return B_SEEN + ((0x700800u >> (8 * item)) & 255); }
__device__ __noinline__ void publisher(uint32_t bar, int lane, uint32_t nsrc, uint32_t item, uint32_t mine) {
  uint32_t done = 0, tot = 0;
#pragma unroll 1
  for (uint32_t spins = 0; (done < nsrc || item < 3) && spins < (1u << 20); spins++) {
    const uint32_t cnt = item ? CNT_CTX - 1 + item : CNT_KV + 1;
    if (item < 3 && __shfl_sync(0xffffffffu, tot, cnt) >= mine >> !item) {
      uint32_t v;
      asm volatile("ld.acquire.gpu.global.u32 %0, [%1];" : "=r"(v) : "l"(g_cnt + (lane ? cnt : CNT_PREP) * 32) : "memory");
      if (__all_sync(0xffffffffu, v >= (lane ? 512 >> !item : 260))) {
        asm volatile("fence.proxy.async.global;" ::: "memory");
        mbar_arrive_if(bar + seen_bar(item), lane == 0);
        item++;
      }
    }
    uint32_t v = 0;
    if (lane < CNT_N)
      asm volatile("atom.acquire.cta.shared.exch.b32 %0, [%1], 0;" : "=r"(v) : "r"(bar + B_PEND + 4 * lane) : "memory");
    done += __shfl_sync(0xffffffffu, v, CNT_DONE);
    if (lane == CNT_DONE) v = 0;
    if (done == nsrc && lane < CNT_DONE) {
      uint32_t w;
      asm volatile("atom.acquire.cta.shared.exch.b32 %0, [%1], 0;" : "=r"(w) : "r"(bar + B_PEND + 4 * lane) : "memory");
      v += w;
    }
    if (v && lane == 0) { TD(0) }
    if (v) cnt_signal_release(lane, v);
    tot += v;
    if (v && lane == 0) { TD(1) }
    if (!__any_sync(0xffffffffu, v != 0)) __nanosleep(item == 1 ? 1000 : 200);
  }
  __threadfence();
  __syncwarp();
}

__device__ __forceinline__ void gate_rows(const Maps& maps, uint32_t sbase, int w48, int w12, int lane) {
  const uint32_t buf = sbase + w12 * 16384, gb = sbase + BAR_OFF + 768 + w12 * 16;
  if (lane == 0) {
    mbar_init(gb, 1);
    mbar_init(gb + 8, 1);
    fence_barrier_init();
    for (int i = 0; i < 2; i++) {
      mbar_expect_tx(gb + 8 * i, 8192);
      bulk_load(buf + i * 8192, maps.x + (size_t)(w48 + 48 * i) * 4 * DM, 8192, gb + 8 * i);
    }
  }
  __syncwarp();
  uint4 wv[4];
#pragma unroll
  for (int i = 0; i < 4; i++) wv[i] = __ldg(reinterpret_cast<const uint4*>(maps.gate_w + (i * 32 + lane) * 8));
  int it = 0;
#pragma unroll 1
  for (int row = w48 * 4; row < S_LEN; row += 48 * 4, it++) {
    mbar_wait(gb + 8 * (it & 1), (it >> 1) & 1);
    uint4 xv[4][4];
#pragma unroll
    for (int r = 0; r < 4; r++)
#pragma unroll
      for (int i = 0; i < 4; i++) xv[r][i] = lds128(buf + (it & 1) * 8192 + r * 2048 + (i * 32 + lane) * 16);
    float d[2][4];
#pragma unroll
    for (int pr = 0; pr < 2; pr++) {
      d[pr][0] = d[pr][1] = d[pr][2] = d[pr][3] = 0.f;
      auto acc = [&](uint32_t a0, uint32_t a2, uint32_t b0, uint32_t b2, uint32_t w0, uint32_t w2) {
        asm volatile(
            "mma.sync.aligned.m16n8k16.row.col.f32.bf16.bf16.f32 {%0, %1, %2, %3}, {%4, %5, %6, %7}, {%8, %8}, "
            "{%0, %1, %2, %3};"
            : "+f"(d[pr][0]), "+f"(d[pr][1]), "+f"(d[pr][2]), "+f"(d[pr][3])
            : "r"(mul_bf2(a0, w0)), "r"(mul_bf2(b0, w0)), "r"(mul_bf2(a2, w2)), "r"(mul_bf2(b2, w2)), "r"(0x3f803f80u));
      };
#pragma unroll
      for (int i = 0; i < 4; i++) {
        acc(xv[2 * pr][i].x, xv[2 * pr][i].y, xv[2 * pr + 1][i].x, xv[2 * pr + 1][i].y, wv[i].x, wv[i].y);
        acc(xv[2 * pr][i].z, xv[2 * pr][i].w, xv[2 * pr + 1][i].z, xv[2 * pr + 1][i].w, wv[i].z, wv[i].w);
      }
    }
    float sum = (lane & 2) ? ((lane & 1) ? d[1][2] : d[1][0]) : ((lane & 1) ? d[0][2] : d[0][0]);
#pragma unroll
    for (int off = 16; off >= 4; off >>= 1) sum += __shfl_xor_sync(0xffffffffu, sum, off);
    if (lane < 4) g_gate[row + lane] = bf16_round(rcp(1.0f + __expf(-bf16_round(sum))));
    if (lane == 0 && row + 2 * 48 * 4 < S_LEN) {
      mbar_expect_tx(gb + 8 * (it & 1), 8192);
      bulk_load(buf + (it & 1) * 8192, maps.x + (size_t)(row + 2 * 48 * 4) * DM, 8192, gb + 8 * (it & 1));
    }
  }
}

constexpr float K_SCALE = 0.08838834764831845f * 1.4426950408889634f;
__device__ __forceinline__ uint32_t qkv_consumer(const Maps& maps, const uint32_t sbase, const int wg, bool fused,
                                                 uint32_t (&q)[32], float (&rest)[64], uint32_t rt_zero) {
  PHASE_GIVEN_(rt_zero)
  constexpr int NTILES = G_NTILES;
  float acc[128];
  const uint32_t stg = sbase + G_STG_OFF + wg * 18432;
  const int st_row = warp * 16 + (lane & 7) + ((lane >> 3) & 1) * 8;
  const int st_cb = lane >> 4;
  uint32_t pend[64];
  const CUtensorMap* pend_map = nullptr;
  int pend_c0 = 0, pend_c1 = 0;
  uint32_t sn = 0;
  uint32_t st_a[4];
#pragma unroll
  for (int jp = 0; jp < 4; jp++) {
    st_a[jp] = stg + st_row * 128 + (((jp * 2 + st_cb) ^ (st_row & 7)) << 4);
    asm volatile("" : "+r"(st_a[jp]));
  }
  auto put_box = [&](uint32_t off, const uint32_t* v) {
#pragma unroll
    for (int jp = 0; jp < 4; jp++) stmatrix_x4(st_a[jp] + off, v[jp * 4], v[jp * 4 + 1], v[jp * 4 + 2], v[jp * 4 + 3]);
  };
  GT(gti++)
  const int hf = wg ^ 1;
  const uint64_t da0 = make_desc(sbase + hf * 8192, 16, 1024, DESC_SW128);
  const uint64_t db0 = make_desc(sbase + G_A_BYTES, 8192, 1024, DESC_SW128);
  uint32_t g = 0, oa = 3 * (G_STAGE_BYTES / 16), ob = 0;
  bool go = false;
  mbar_wait(bar + B_GFULL, 0);
  uint32_t gend = 16, when = 0;
#pragma unroll 1
  for (int it = 0;; it++) {
    bool more = false;
#pragma unroll 1
    do {
      GT(gti++)
      wgmma_fence();
#pragma unroll
      for (int kk = 0; kk < 4; kk++)
        wgmma_m64n256_ss_tb(acc, desc_add(da0, oa + kk * 2), desc_add(db0, ob + kk * 128), kk || more);
      wgmma_commit();
      if (go) st_go(bar, wg, wtid, sn - 1);
      g++;
      if (g + wg * 64 == 63) named_bar_arrive(6, 256);
      const uint32_t full = (bar + B_GFULL) + 8 * (g & 3);
      const bool here = mbar_test(full, (g >> 2) & 1) || g >= 64;
      oa = ((g & 3) ^ ((0x17 >> (g >> 3)) & 1) * 3) * (G_STAGE_BYTES / 16);
      ob = (g & 3) * (G_STAGE_BYTES / 16);
      go = when & 1;
      when >>= 1;
      if (go) {
        const int c = sn & 3;
        st_wait(bar, wg, sn - 2);
        st_cmd(bar, wg, wtid, sn, ST_BOX1, pend_map, stg + (c & 1) * 8192, pend_c0 + c * 64, pend_c1,
               (c == 3 && it > 1) ? CNT_KV + (it > 4) : -1);
        switch (c) {
          case 0: put_box(0, pend); break;
          case 1: put_box(8192, pend + 16); break;
          case 2: put_box(0, pend + 32); break;
          default: put_box(8192, pend + 48); break;
        }
        sn++;
      }
      if (it < NTILES) {
        wgmma_wait<1>();
        mbar_arrive_if((bar + B_GEMPTY) + 8 * ((g + 2) & 3), wtid == 32 && more);
        if (wg && g == 62) named_bar_sync(6, 256);
        if (!here) mbar_wait(full, (g >> 2) & 1);
      }
      more = true;
    } while (g != gend);
    wgmma_wait<0>();
    fence_regs(acc);
    GT(gti++)
    mbar_arrive_if((bar + B_GEMPTY) + 8 * 3, wtid == 32);
    int which, m_tile, n_tile;
    qkv_tile(maps, it, which, m_tile, n_tile);
    if (it == NTILES - fused) break;
    if (which == 1) {
#pragma unroll
      for (int j = 0; j < 128; j++) acc[j] *= K_SCALE;
    }
#pragma unroll
    for (int j = 0; j < 64; j++) pend[j] = pack_bf16(acc[2 * j], acc[2 * j + 1]);
    pend_map = &maps.c[which];
    pend_c0 = n_tile * 256;
    pend_c1 = m_tile * 128 + hf * 64;
    gend += it == 4 ? 16 : 8;
    when = (it == 4 ? 0x922 : 0x55) << wg;
  }
  if (go) st_go(bar, wg, wtid, sn - 1);
#pragma unroll
  for (int j = 0; j < 32; j++) q[j] = pack_bf16(acc[2 * j], acc[2 * j + 1]);
#pragma unroll
  for (int j = 0; j < 64; j++) rest[j] = acc[64 + j];
  GT(gti++)
  return sn;
}

constexpr int A_TILE = 128 * 128 * 2;
constexpr int A_K_OFF = 0, A_Q_OFF = A_TILE, A_V_OFF = 3 * A_TILE;
constexpr int A_O_OFF = 6 * A_TILE;
constexpr int A_ITEMS = NH * (S_LEN / 128);

constexpr uint32_t A_ORDER = 0x3120, A_STEPS = 34;
__device__ __forceinline__ int item_m(uint32_t it) { return it & 15; }
__device__ __forceinline__ int item_h(uint32_t it) { return it >> 4; }

constexpr int C_V = 16384, C_MAT = 24576;
constexpr float C_ALPHA = 0.07874506561842957f;
__device__ __forceinline__ void sincos_turn(int p, float inv, float& c, float& s) {
  const float a = (float)p * (inv * 6.283185307179586f);
  asm("cos.approx.ftz.f32 %0, %1;" : "=f"(c) : "f"(a));
  asm("sin.approx.ftz.f32 %0, %1;" : "=f"(s) : "f"(a));
}

__device__ __forceinline__ uint32_t head_of(const Maps& maps, uint32_t r) { return (maps.id[blockIdx.x & 127][3] >> (2 * r)) & 3; }
__device__ __forceinline__ uint32_t item_at(const Maps& maps, uint32_t h) {
  const uint32_t b = maps.id[blockIdx.x & 127][1];
  return (b >> 4) * 64 + h * 16 + ((b ^ ((h >> 1) * 15)) & 15);
}
__device__ __forceinline__ uint32_t item_of(const Maps& maps, uint32_t r) { return item_at(maps, head_of(maps, r)); }

#define PACE 250
#define SPACE 0
#define LCHK 1
#define XMASK 3
#define XFIRST 12
#define C_SIDE 64
__device__ __forceinline__ uint32_t conv_first(const Maps& maps) {
  const uint32_t b = maps.id[blockIdx.x & 127][1];
  return (b >> 4) * 128 + ((b + 15) & 15);
}

__device__ __forceinline__ void conv_consumer(const Maps& maps, uint32_t smem0, uint32_t first, uint32_t step,
                                              uint32_t end, bool pp, bool dealt) {
  PHASE_PROLOGUE
  const uint32_t in_full = bar + B_CFULL + wg * 16;
  const uint32_t ca = sbase + (wg ? A_V_OFF + A_TILE : A_Q_OFF);
  const int w = __shfl_sync(0xffffffffu, warp, 0), g = lane >> 2, c = lane & 3;
  auto fetch = [&](uint32_t ch, uint32_t n) {
    if (w == 2 && ch < C_NONE) {
      if (elect_one()) {
        const uint32_t b = in_full + (n & 1) * 8, d = ca + (n & 1) * 8192;
        const uint64_t pol = policy_evict_first();
        mbar_expect_tx(b, 8192);
        tma_load_2d_hint(d, &maps.cu, b, 0, ch * 64, pol);
        tma_load_2d_hint(d + 4096, &maps.ch, b, 0, ch * 64, pol);
      }
    }
  };
  if (wtid == 96 && wg) { TD(15) }
  uint32_t f1[8][4];
  float tt[16], ts[16];
  uint32_t cc[4], ss[4];
#pragma unroll
  for (int i = 0; i < 16; i++) {
    const int k = 2 * (16 * w + g + 8 * (i & 1)) + 1, n = 2 * (8 * (i >> 1) + 2 * c) + 1;
    float c0, s0, c1, s1;
    sincos_turn(((k * n) << 23) >> 23, 1.f / 512, c0, s0);
    sincos_turn(((k * n + 2 * k) << 23) >> 23, 1.f / 512, c1, s1);
    f1[i >> 2][i & 3] = pack_bf16(c0 * C_ALPHA, c1 * C_ALPHA);
    f1[4 + (i >> 2)][i & 3] = pack_bf16(s0 * -C_ALPHA, s1 * -C_ALPHA);
  }
#pragma unroll
  for (int i = 0; i < 16; i++) {
    const int k = 2 * (16 * w + g + 8 * ((i >> 1) & 1)) + 1, n = 16 - (8 * (i >> 2) + 2 * c + (i & 1));
    float cs;
    sincos_turn(k * n, 1.f / 8192, cs, ts[i]);
    tt[i] = ts[i] * rcp(1.f + cs);
  }
#pragma unroll
  for (int j = 0; j < 4; j++) {
    const int k = 8 * w + g, n = 8 * c + 2 * j;
    float c0, s0, c1, s1;
    sincos_turn((int8_t)(k * n * 8), 1.f / 256, c0, s0);
    sincos_turn((int8_t)((k * n + k) * 8), 1.f / 256, c1, s1);
    cc[j] = pack_bf16(c0, c1);
    ss[j] = pack_bf16(s0, s1);
  }
  named_bar_sync(3, 256);
  fetch(first, 0);
  fetch(first + step, 1);
  const uint32_t va = ca + g * 64 + ((c ^ (g >> 1)) << 4);
  {
    const uint32_t a = va + C_MAT + w * 512, m = 0x80008000u;
    sts128(a, make_uint4(cc[0], cc[1], cc[2], cc[3]));
    sts128(a + 2048, make_uint4(ss[0], ss[1], ss[2], ss[3]));
    sts128(a + 4096, make_uint4(ss[0] ^ m, ss[1] ^ m, ss[2] ^ m, ss[3] ^ m));
    sts128(a + 6144, make_uint4(cc[0], cc[1], cc[2], cc[3]));
  }
  fence_proxy_async();
  named_bar_sync(1 + wg, 128);
  constexpr uint64_t DHI = (2ull << 62) | ((uint64_t)(512 >> 4) << 32);
  const uint32_t d0 = (uint32_t)make_desc(ca, 4096, 0, 0);
  float a5[16];
  uint4* const yb = reinterpret_cast<uint4*>(g_y2T) + (16 * w + g) * 4 + c;
  auto issue5 = [&]() {
#pragma unroll
    for (int ks = 0; ks < 8; ks++) wgmma_m64n32_rs_tb(a5, f1[ks], DHI | (d0 + (C_V >> 4) + ks * 64), ks != 0);
    wgmma_commit();
  };
  auto finish = [&](uint32_t ch, bool on) {
    fence_regs(a5);
    uint4* y = yb + (size_t)ch * 256;
    if (on) {
      y[0] = make_uint4(pack_bf16(a5[0], a5[1]), pack_bf16(a5[4], a5[5]), pack_bf16(a5[8], a5[9]), pack_bf16(a5[12], a5[13]));
      y[32] = make_uint4(pack_bf16(a5[2], a5[3]), pack_bf16(a5[6], a5[7]), pack_bf16(a5[10], a5[11]), pack_bf16(a5[14], a5[15]));
    }
  };
  auto dft32 = [&](float (&d)[32], const float* re, const float* im) {
    uint32_t a[4][4];
#pragma unroll
    for (int i = 0; i < 8; i++) {
      a[i >> 2][i & 3] = pack_bf16(re[2 * i], re[2 * i + 1]);
      a[2 + (i >> 2)][i & 3] = pack_bf16(im[2 * i], im[2 * i + 1]);
    }
    wgmma_fence();
#pragma unroll
    for (int ks = 0; ks < 4; ks++) wgmma_m64n64_rs_tb(d, a[ks], DHI | (d0 + (C_MAT >> 4) + ks * 64), ks != 0);
    wgmma_commit();
  };
  auto rot = [&](float* x, float* y) {
#pragma unroll
    for (int i = 0; i < 16; i++) {
      x[i] = fmaf(-tt[i], y[i], x[i]);
      y[i] = fmaf(ts[i], x[i], y[i]);
      x[i] = fmaf(-tt[i], y[i], x[i]);
    }
  };
  auto load_d = [&](uint32_t ch) {
    return __ldg(reinterpret_cast<const unsigned short*>(maps.ssm_D) + ((ch & (DM - 1)) | (lane & rt_zero)));
  };
  uint32_t dn = load_d(first);
  uint32_t n = 0, prev = 0, ch = first, next = first + step;
#pragma unroll 1
  for (; ch < C_NONE; n++) {
    CT(0)
    float a1[2][32], a2[2][32], a4[32];
    const float dsk = c ? 0.f : __uint_as_float(dn << 16) * C_ALPHA;
    dn = load_d(next);
    uint32_t next2 = next + step < end ? next + step : C_NONE;
    mbar_wait(in_full + (n & 1) * 8, (n >> 1) & 1);
    if (pp) named_bar_sync(4 + wg, 256);
    CT(1)
    wgmma_fence();
#pragma unroll
    for (int ks = 0; ks < 8; ks++)
      wgmma_m64n64_rs_tb(a1[ks >> 2], f1[ks], DHI | (d0 + (n & 1) * 512 + (ks & 3) * 64), (ks & 3) != 0);
    wgmma_commit();
    issue5();
    wgmma_wait<1>();
    fence_regs(a1[0]);
    fence_regs(a1[1]);
    CT(2)
    rot(a1[0], a1[1]);
    dft32(a2[0], a1[0], a1[1]);
    rot(a1[0] + 16, a1[1] + 16);
    a1[0][16] += dsk;
    a1[0][18] += dsk;
    dft32(a2[1], a1[0] + 16, a1[1] + 16);
    CT(3)
    wgmma_wait<2>();
    finish(prev, n > 0);
    wgmma_wait<0>();
    fence_regs(a2[0]);
    fence_regs(a2[1]);
    CT(4)
    if (pp) named_bar_arrive(5 - wg, 256);
    float re[16], im[16];
#pragma unroll
    for (int i = 0; i < 16; i++) {
      re[i] = a2[0][i] * a2[1][i] - a2[0][16 + i] * a2[1][16 + i];
      im[i] = a2[0][i] * a2[1][16 + i] + a2[0][16 + i] * a2[1][i];
    }
    dft32(a4, im, re);
    if (dealt) {
      mbar_wait(bar + (n < 2 ? B_DEAL : B_DEAL2), 0);
      asm volatile("ld.shared.u32 %0, [%1];" : "=r"(next2) : "r"(bar + B_LIST + 4 * n + (n < 2 ? 0 : 8)));
    }
    wgmma_wait<0>();
    fence_regs(a4);
    CT(5)
    rot(a4, a4 + 16);
#pragma unroll
    for (int i = 0; i < 4; i++) {
      const float* x = a4 + 16 - 16 * (i >> 1) + 2 * (i & 1);
      sts128(va + C_V + w * 1024 + (i >> 1) * 4096 + (i & 1) * 512,
             make_uint4(pack_bf16(x[0], x[1]), pack_bf16(x[4], x[5]), pack_bf16(x[8], x[9]), pack_bf16(x[12], x[13])));
    }
    CT(6)
    fence_proxy_async();
    named_bar_sync(1 + wg, 128);
    fetch(next2, n);
    if (wtid == 96 && n > 0) note(bar, CNT_Y2 + ((prev & 112) == 112));
    prev = ch;
    ch = next;
    next = next2;
    CT(7)
  }
  wgmma_fence();
  issue5();
  wgmma_wait<0>();
  finish(prev, (dn | ~rt_zero) != 0);
  named_bar_sync(1 + wg, 128);
  if (wtid == 96 && wg) { TD(8) }
  if (wtid == 96) cnt_signal_release(CNT_Y2 + ((prev & 112) == 112), 1);
  if (wtid == 64) note(bar, CNT_DONE);
  if (wtid == 96 && wg) { TD(9) }
}

__device__ __forceinline__ void attn_producer(const Maps& maps, uint32_t sbase, bool after_qkv, bool to_out,
                                              bool dry) {
  const uint32_t bar = sbase + BAR_OFF;
  const uint32_t q_full = bar + B_QFULL, q_empty = bar + B_QEMPTY;
  const uint32_t k_full = bar + B_KFULL, k_empty = bar + B_KEMPTY, v_full = bar + B_VFULL, v_empty = bar + B_VEMPTY;
  int ndrained = after_qkv ? 0 : G_STAGES;
  auto wait = [&](uint32_t b, uint32_t par) {
    if (!dry) mbar_wait_sleep(b, par);
  };
  auto drained = [&](int upto) {
#pragma unroll 1
    for (; ndrained <= upto; ndrained++) wait(bar + B_GEMPTY + 8 * ndrained, 1);
  };
  uint32_t st = 0, ph = 1, vs = 0, vp = 1;
  int pend_j = -1, pend_h = 0;
  int round = -1, m = -1, h = 0;
  bool last = false;
#pragma unroll 1
  for (;; round++) {
    uint32_t nitem = 0;
    const int tpost = m >= 3 ? m - 1 : m;
#pragma unroll 1
    for (int t = m < 0 ? -1 : 0; t <= m; t++) {
      const int j = (t < m && (h & 2)) ? m - 1 - t : t;
      if (t >= 0) {
        drained(st);
        wait(k_empty + 8 * st, ph);
        if (!dry) {
          mbar_expect_tx(k_full + 8 * st, A_TILE);
          tma_load_3d(sbase + A_K_OFF + st * 2 * A_TILE, &maps.k, k_full + 8 * st, 0, j * 128, h * 2);
        }
        if (++st == 2) { st = 0; ph ^= 1; }
      }
      if (pend_j >= 0) {
        drained(2 + vs);
        if ((pend_h & 2) && after_qkv) wait(bar + seen_bar(0), 0);
        wait(v_empty + 8 * vs, vp);
        if (!dry) {
          mbar_expect_tx(v_full + 8 * vs, A_TILE);
          tma_load_3d(sbase + A_V_OFF + vs * A_TILE, &maps.v, v_full + 8 * vs, 0, pend_j * 128, pend_h * 2);
        }
        if (++vs == 2) { vs = 0; vp ^= 1; }
      }
      pend_j = j;
      pend_h = h;
      if (t == tpost && !last) {
        nitem = dry ? 1 : item_of(maps, round + 1);
        if (round == (dry ? 0 : 3) || blockIdx.x >= 128) {
          nitem = A_ITEMS;
          if (!to_out) cnt_wait(CNT_PREP, dry ? 0 : 260);
          if (to_out) {
            wait(bar + seen_bar(1), 0);
            asm volatile("cp.async.bulk.prefetch.L2.global [%0], 4096;" ::"l"(maps.ssm_k + (size_t)conv_first(maps) * S_LEN));
            if (!dry)
              asm volatile("cp.async.bulk.prefetch.L2.global [%0], 4096;" ::"l"(g_kvT + (size_t)conv_first(maps) * S_LEN));
          }
        }
        const uint32_t qs = (round + 1) & 1;
        wait(q_empty + 8 * qs, (((round + 1) >> 1) & 1) ^ 1);
        if (round == 1 && after_qkv) wait(bar + B_QDONE, 0);
        if (round < 0 && after_qkv) {
          if (!dry) { TD(2) }
          cnt_wait(CNT_KV, dry ? 0 : 768);
          if (!dry) { TD(3) }
        }
        if (nitem >= A_ITEMS || (round < 0 && after_qkv && !dry)) {
          if (!dry) mbar_arrive(q_full + 8 * qs);
        } else {
          drained(1 + 2 * qs);
          if (!dry) {
            mbar_expect_tx(q_full + 8 * qs, A_TILE);
            tma_load_3d_hint(sbase + A_Q_OFF + qs * 4 * A_TILE, &maps.q, q_full + 8 * qs, 0, item_m(nitem) * 128,
                             item_h(nitem) * 2, policy_evict_first());
          }
        }
      }
    }
    if (last) break;
    last = nitem >= A_ITEMS;
    m = last ? -1 : item_m(nitem);
    h = item_h(nitem);
  }
}

__device__ __forceinline__ void put_o(uint32_t sbase, int wg, int warp, int lane, const float (&o)[64], float i0, float i1) {
  const int st_row = warp * 16 + (lane & 7) + ((lane >> 3) & 1) * 8;
  const uint32_t so = sbase + A_O_OFF + wg * 16384 + st_row * 128;
#pragma unroll
  for (int j = 0; j < 16; j += 2)
    stmatrix_x4(so + (j >> 3) * 8192 + ((((j & 7) + (lane >> 4)) ^ (lane & 7)) << 4),
                pack_bf16(o[4 * j] * i0, o[4 * j + 1] * i0), pack_bf16(o[4 * j + 2] * i1, o[4 * j + 3] * i1),
                pack_bf16(o[4 * j + 4] * i0, o[4 * j + 5] * i0), pack_bf16(o[4 * j + 6] * i1, o[4 * j + 7] * i1));
}
__device__ __forceinline__ uint32_t attn_consumer(const Maps& maps, const uint32_t sbase, const int wg,
                                                  const uint32_t rt_zero, uint32_t sn, uint32_t (&p)[32], float (&rest)[64],
                                                  bool after_qkv, float (&o)[64], float (&s)[64], float& pi0, float& pi1) {
  PHASE_GIVEN
  const uint32_t q_full = bar + B_QFULL, q_empty = bar + B_QEMPTY;
  const uint32_t k_full = bar + B_KFULL, k_empty = bar + B_KEMPTY, v_full = bar + B_VFULL;
  float e[32];
  uint32_t dep = 0;
  constexpr int MIDJ = 5;
  float l0 = 0.f, l1 = 0.f, b0 = 0.f, b1 = 0.f;
  const int sched_own = 4 + wg, sched_other = 5 - wg;

  const int hf = wg ^ 1;
  const uint32_t qd0 = (uint32_t)make_desc(sbase + A_Q_OFF + hf * 8192, 16, 0, 0);
  const uint32_t kd0 = (uint32_t)make_desc(sbase + A_K_OFF, 16, 0, 0);
  const uint32_t vd0 = (uint32_t)make_desc(sbase + A_V_OFF, 16384, 0, 0);
  constexpr uint64_t DHI = DESC_SW128 | ((uint64_t)(1024 >> 4) << 32);
  constexpr uint32_t DST = A_TILE >> 4;
  auto issue_qk = [&](uint32_t qd, uint32_t kd) {
#pragma unroll
    for (int kk = 0; kk < 8; kk++) {
      const uint32_t off = ((kk >> 2) * 16384 + (kk & 3) * 32) >> 4;
      wgmma_m64n128_ss(s, DHI | (qd + off), DHI | (kd + off), kk != 0);
    }
    wgmma_commit();
  };
  auto issue_pv = [&](uint32_t vd, bool accumulate, int nk) {
#pragma unroll
    for (int kk = 0; kk < 8; kk++) {
      if (kk < nk)
        wgmma_m64n128_rs<1>(o, p[4 * kk], p[4 * kk + 1], p[4 * kk + 2], p[4 * kk + 3], DHI | (vd + kk * 128),
                            accumulate || (kk != 0));
    }
    wgmma_commit();
  };
  auto exp_lo = [&](float& a0, float& a1) {
#pragma unroll
    for (int j = 0; j < 8; j++) {
      e[4 * j] = ex2(s[4 * j]);
      e[4 * j + 1] = ex2(s[4 * j + 1]);
      e[4 * j + 2] = ex2(s[4 * j + 2]);
      e[4 * j + 3] = ex2(s[4 * j + 3]);
      a0 += e[4 * j];
      a0 += e[4 * j + 1];
      a1 += e[4 * j + 2];
      a1 += e[4 * j + 3];
      if (j == MIDJ) dep = (__float_as_uint(a0) | __float_as_uint(a1)) & rt_zero;
    }
  };
  auto pack_lo = [&]() {
#pragma unroll
    for (int j = 0; j < 16; j++) p[j] = pack_bf16(e[2 * j], e[2 * j + 1]);
  };
  auto finish_p = [&](float& a0, float& a1) {
    pack_lo();
#pragma unroll
    for (int j = 8; j < 16; j++) {
      const float e0 = ex2(s[4 * j]), e1 = ex2(s[4 * j + 1]), e2 = ex2(s[4 * j + 2]), e3 = ex2(s[4 * j + 3]);
      a0 += e0;
      a0 += e1;
      a1 += e2;
      a1 += e3;
      p[2 * j] = pack_bf16(e0, e1);
      p[2 * j + 1] = pack_bf16(e2, e3);
      if (j == 8 + MIDJ) dep = __float_as_uint(a0) & rt_zero;
    }
  };
  auto quad_sum = [&](float t) {
    t += __shfl_xor_sync(0xffffffffu, t, 1);
    return t + __shfl_xor_sync(0xffffffffu, t, 2);
  };
  auto write_o = [&](float i0, float i1) {
    st_wait(bar, wg, sn - 1);
    put_o(sbase, wg, warp, lane, o, i0, i1);
  };
  auto store_o = [&](uint32_t r, int kind, uint32_t lazy) {
    const uint32_t it = item_at(maps, kind == ST_BOX2Q ? 1 : head_of(maps, r));
    st_cmd(bar, wg, wtid, sn, kind, (INPLACE & 1) || kind != ST_BOX2Q ? &maps.o : &maps.c[0], sbase + A_O_OFF + wg * 16384, item_h(it) * 128,
            item_m(it) * 128 + hf * 64, CNT_CTX + (r >> 1), lazy);
    if (kind != ST_BOX2L) st_go(bar, wg, wtid, sn);
    sn++;
  };
  auto mask_half = [&](float* sh) {
    const int u = warp * 16 + (lane >> 2) - (lane & 3) * 2;
#pragma unroll
    for (int j = 0; j < 8; j++) {
      if (8 * j > u) sh[4 * j] = -INFINITY;
      if (8 * j + 1 > u) sh[4 * j + 1] = -INFINITY;
      if (8 * j - 8 > u) sh[4 * j + 2] = -INFINITY;
      if (8 * j - 7 > u) sh[4 * j + 3] = -INFINITY;
    }
  };
  ST(0)
  const uint32_t qa = sbase + A_Q_OFF + hf * 8192 + (warp * 16 + (lane & 15)) * 128;
  auto q_at = [&](int j) { return qa + (j >> 2) * 16384 + ((((j & 3) * 2 + (lane >> 4)) ^ (lane & 7)) << 4); };
  if (!after_qkv) {
    mbar_wait(q_full, 0);
    if (blockIdx.x >= 128) return sn;
#pragma unroll
    for (int j = 0; j < 8; j++)
      asm volatile("ldmatrix.sync.aligned.m8n8.x4.shared.b16 {%0, %1, %2, %3}, [%4];"
                   : "=r"(p[4 * j]), "=r"(p[4 * j + 1]), "=r"(p[4 * j + 2]), "=r"(p[4 * j + 3])
                   : "r"(q_at(j))
                   : "memory");
  }
  for (uint32_t i = 0; !(mbar_try(k_full, 0) & mbar_try(bar + B_GEMPTY + 8, 1)) && i < (1u << 22); i++) {}
  named_bar_sync(sched_own, 256);
  fence_regs_u(p);
  wgmma_fence();
#pragma unroll
  for (int kk = 0; kk < 8; kk++)
    wgmma_m64n128_rs<0>(s, p[4 * kk], p[4 * kk + 1], p[4 * kk + 2], p[4 * kk + 3],
                        DHI | (kd0 + (((kk >> 2) * 16384 + (kk & 3) * 32) >> 4)), kk != 0);
  wgmma_commit();
  named_bar_arrive(sched_other, 256);
#pragma unroll
  for (int j = 0; j < 8; j++) stmatrix_x4(q_at(j), p[4 * j], p[4 * j + 1], p[4 * j + 2], p[4 * j + 3]);
  fence_regs(rest);
#pragma unroll
  for (int i = 0; i < 64; i++) o[i] = rest[i] * __uint_as_float(0x3f800000u | rt_zero);
  fence_regs(o);
  fence_proxy_async();
  fence_regs(o);
  wgmma_wait<0>();
  fence_regs(s);
  mbar_arrive_if(k_empty, wtid == 32);
  uint32_t g = 0;
  uint32_t rnd = 0;
  int rem = item_m(item_of(maps, 0));
  uint32_t first = 1;
  uint32_t fl = 0;
#define redo (fl & 1)
#define shifted (fl & 2)
  float d0 = 0.f, d1 = 0.f;
  pi0 = pi1 = 1.f;
  ST(1)
  for (;;) {
    if (shifted) {
#pragma unroll
      for (int j = 0; j < 16; j++) {
        s[4 * j] -= d0;
        s[4 * j + 1] -= d0;
        s[4 * j + 2] -= d1;
        s[4 * j + 3] -= d1;
      }
    }
    if (rem == 0 && !redo) {
      mbar_arrive_if(q_empty + 8 * (rnd & 1), wtid == 96);
      rnd++;
      if (hf == 0) mask_half(s);
      else mask_half(s + 32);
    }
    for (;;) {
      const bool kill = rem == 0 && hf == 0;
      const uint32_t kd = kd0 + ((g + 1) & 1) * 2 * DST, vd = vd0 + (g & 1) * DST;
      float a0 = 0.f, a1 = 0.f;
      exp_lo(a0, a1);
      fence_regs(e);
      const uint32_t kb = k_full + 8 * ((g + 1) & 1);
      const uint32_t kpar = (((g + 1) >> 1) & 1) ^ (g == A_STEPS - 1 ? 1u : 0u);
      const uint32_t qb = q_full + 8 * (rnd & 1), qpar = ((rnd >> 1) & 1) | dep;
      if (!mbar_try(qb, qpar)) mbar_wait(qb, qpar | ((__float_as_uint(a0) | __float_as_uint(a1)) & rt_zero));
      wgmma_wait<0>();
      fence_regs(o);
      if (kill) {
        mbar_arrive_if(kb + (B_VEMPTY - B_KFULL), wtid == 64 && !redo && g > 0);
        fence_regs(e);
        pack_lo();
#pragma unroll
        for (int j = 16; j < 32; j++) asm volatile("" : "=r"(p[j]));
        goto check;
      }
#pragma unroll
      for (int i = 32; i < 64; i++) asm volatile("" : "+f"(s[i])::"memory");
      mbar_arrive_if(kb + (B_VEMPTY - B_KFULL), wtid == 64 && !redo && g > 0);
      finish_p(a0, a1);
      if (__any_sync(0xffffffffu, !(mbar_try(v_full + 8 * (g & 1), ((g >> 1) & 1) | dep) &
                                    mbar_try(kb, kpar | dep)) ||
                                      !(a0 + a1 < 1.0995116e12f) || !(fminf(a0, a1) > (first ? 9.094947e-13f : -1.f)))) {
      check:
        bool bad = !(a0 + a1 < 1.0995116e12f);
        if (first) bad |= !(fminf(quad_sum(a0), quad_sum(a1)) > 9.094947e-13f);
        if (!redo && __any_sync(0xffffffffu, bad)) {
          d0 = d1 = first ? -INFINITY : 0.f;
#pragma unroll
          for (int j = 0; j < 16; j++) {
            if (j < 8 || !kill) {
              d0 = fmaxf(d0, fmaxf(s[4 * j], s[4 * j + 1]));
              d1 = fmaxf(d1, fmaxf(s[4 * j + 2], s[4 * j + 3]));
            }
          }
#pragma unroll
          for (int x = 1; x <= 2; x++) {
            d0 = fmaxf(d0, __shfl_xor_sync(0xffffffffu, d0, x));
            d1 = fmaxf(d1, __shfl_xor_sync(0xffffffffu, d1, x));
          }
          b0 += d0;
          b1 += d1;
          if (!first) {
            const float al0 = ex2(-d0), al1 = ex2(-d1);
            l0 *= al0;
            l1 *= al1;
#pragma unroll
            for (int j = 0; j < 16; j++) {
              o[4 * j] *= al0;
              o[4 * j + 1] *= al0;
              o[4 * j + 2] *= al1;
              o[4 * j + 3] *= al1;
            }
          }
          fl = 3;
          break;
        }
        mbar_wait(v_full + 8 * (g & 1), (g >> 1) & 1);
        mbar_wait(kb, kpar);
      }
      named_bar_sync(sched_own, 256);
      if (g == A_STEPS - 1) {
        fence_regs(o);
        if (hf == 0) {
          wgmma_fence();
          issue_pv(vd, 1, 4);
        } else {
          wgmma_fence();
          issue_pv(vd, 1, 8);
        }
        named_bar_arrive(sched_other, 256);
        pi0 = rcp(quad_sum(l0 + a0));
        pi1 = rcp(quad_sum(l1 + a1));
        goto done;
      }
      wgmma_fence();
      issue_qk(qd0 + (rnd & 1) * 4 * DST, kd);
      if (first) write_o(pi0, pi1);
      fence_regs(o);
      if (kill) {
        wgmma_fence();
        issue_pv(vd, !first, 4);
      } else {
        wgmma_fence();
        issue_pv(vd, !first, 8);
      }
      named_bar_arrive(sched_other, 256);
      fl &= 2;
      l0 += a0;
      l1 += a1;
      if (rem == 0 || first) {
        if (first && (g > 0 || after_qkv)) store_o(g ? rnd - (rem == 0 ? 2 : 1) : 2, g ? ST_BOX2 : ST_BOX2Q, rem);
        first = rem == 0;
        if (first) {
          pi0 = rcp(quad_sum(l0));
          pi1 = rcp(quad_sum(l1));
          l0 = l1 = b0 = b1 = 0.f;
          fl = 0;
          rem = item_m(item_of(maps, rnd)) + 1;
        }
      }
      rem--;
      g++;
      wgmma_wait<1>();
      fence_regs(s);
      mbar_arrive_if(kb + (B_KEMPTY - B_KFULL), wtid == 32);
      ST(g + 1)
      if (rem == 0 || shifted) {
        d0 = b0;
        d1 = b1;
        break;
      }
    }
  }
done:
#undef redo
#undef shifted
  st_wait(bar, wg, sn - 1);
  store_o(3, ST_BOX2L, 4);
  ST(35)
  return sn;
}

constexpr int O_STAGES = 5;
constexpr int O_STAGE_BYTES = 32768;
constexpr int O_Y_OFF = 4 * 32768;
constexpr int O_X_OFF = 6 * 32768;
constexpr int O_G_OFF = 7 * 32768;
constexpr int O_NK = HDIM / 64;

__device__ __forceinline__ uint32_t out_stage(uint32_t st) { return ((0x32501u >> (4 * st)) & 7) * O_STAGE_BYTES; }

__device__ __forceinline__ void out_producer(const Maps& maps, uint32_t sbase, bool after_attn, bool dry) {
  const uint32_t bar = sbase + BAR_OFF;
  const uint32_t rank = blockIdx.x & 1;
  const int m_tile = maps.id[blockIdx.x][2] & 15, n_tile = maps.id[blockIdx.x][2] >> 4;
  uint32_t stage = 0, phase = 0, xi = 0;
#pragma unroll 1
  for (int ki = 0; ki < (dry ? 1 : O_NK); ki++) {
    const int kt = (ki & 14) * 4 + ((A_ORDER >> ((ki >> 4) * 4)) & 3) * 2 + (ki & 1);
    const uint32_t fb = bar + B_OFULL + 8 * stage, eb = bar + B_OEMPTY + 8 * stage;
    const uint32_t sa = sbase + out_stage(stage);
    if (ki < O_STAGES) {
      constexpr uint32_t LASTB = B_KEMPTY | ((B_QEMPTY + 8) << 8) | ((B_KEMPTY + 8) << 16) | (B_VEMPTY << 24);
      if (ki > 0 && after_attn) mbar_wait_sleep(bar + ((LASTB >> (8 * ki - 8)) & 255), ki == 2);
      mbar_arrive_cluster_if(eb, 0, !dry);
      mbar_arrive_cluster_if(eb, 1, !dry);
    }
    if (ki == 32) mbar_wait_sleep(bar + seen_bar(2), 0);
    if (!dry) {
      mbar_wait_sleep(eb, phase);
      mbar_expect_tx(fb, O_STAGE_BYTES);
      tma_load_2d_mc(sa + 16384 + rank * 8192, &maps.ob, fb, n_tile * 128 + rank * 64, kt * 64, (uint16_t)3);
      tma_load_2d(sa, &maps.oa, fb, kt * 64, m_tile * 128);
    }
    if (++stage == O_STAGES) { stage = 0; phase ^= 1; }
    if ((ki & XMASK) == XMASK && ki >= XFIRST && xi < 8) {
      if (after_attn && xi < 2) mbar_wait_sleep(bar + B_OFREE + 8 * xi, 0);
      tma_load_3d(sbase + O_X_OFF + (xi & 1) * 16384 + (xi >> 1) * 4096, &maps.xs, bar + B_OY, 0,
                  m_tile * 128 + (xi & 1) * 64 + (xi >> 1) * 16, n_tile * 2);
      xi++;
    }
  }
  if (!dry) mbar_wait_sleep(bar + B_OY2, 0);
}

__device__ __forceinline__ void out_side(const Maps& maps, uint32_t smem0) {
  PHASE_PROLOGUE
  const int m_tile = maps.id[blockIdx.x][2] & 15, n_tile = maps.id[blockIdx.x][2] >> 4;
  const float* gp = g_gate + m_tile * 128 + warp * 16 + (lane >> 2);
  const float gv[4] = {__ldcg(gp), __ldcg(gp + 8), __ldcg(gp + 64), __ldcg(gp + 72)};
  const bool w0 = __shfl_sync(0xffffffffu, warp, 0) == 0;
  bool have = false;
  auto late = [&](uint32_t spins) {
    have = cnt_wait(CNT_Y2 + 1, 128, spins) || !spins;
    TD(11)
    if (have) {
      mbar_expect_tx(bar + B_OY2, 4096);
      tma_load_3d(sbase + O_Y_OFF + 7 * 4096, &maps.y, bar + B_OY2, 0, n_tile * 128 + 112, m_tile * 2);
    }
  };
  if (w0) {
    if (elect_one()) {
      mbar_expect_tx(bar + B_OY, 65536 - 4096);
      TD(10)
      cnt_wait(CNT_Y2, DM - 128);
      TD(7)
#pragma unroll 1
      for (int i = 0; i < 7; i++) {
        tma_load_3d(sbase + O_Y_OFF + i * 4096, &maps.y, bar + B_OY, 0, n_tile * 128 + i * 16, m_tile * 2);
        __nanosleep(PACE);
      }
      late(1u << 18);
    }
  }
  mbar_wait_sleep(bar + B_OY, 0);
  if (wtid == 0) { TD(12) }
  const int mrow = (lane & 7) + ((lane >> 4) & 1) * 8;
  const int mchunk = warp * 2 + ((lane >> 3) & 1);
  const uint32_t xrow = sbase + O_X_OFF + warp * 4096 + (lane & 15) * 128;
  const uint32_t yrow = sbase + O_Y_OFF + mrow * 128 + ((mchunk ^ (lane & 7)) << 4);
  uint32_t y[7][4], x[7][4], om[4];
#pragma unroll
  for (int i = 0; i < 4; i++) om[i] = pack_bf16(1.0f - gv[i], 1.0f - gv[i]);
  sts128(sbase + O_G_OFF + wtid * 16, make_uint4(pack_bf16(gv[0], gv[0]), pack_bf16(gv[1], gv[1]), pack_bf16(gv[2], gv[2]),
                                                 pack_bf16(gv[3], gv[3])));
  auto xa = [&](int h, int i) { return xrow + h * 16384 + (i >> 2) * 2048 + ((((i & 3) * 2 + (lane >> 4)) ^ (lane & 7)) << 4); };
  auto load = [&](int r, int h, int i) {
    ldsm4t(y[r], yrow + h * 2048 + i * 4096);
    asm volatile("ldmatrix.sync.aligned.m8n8.x4.shared.b16 {%0, %1, %2, %3}, [%4];"
                 : "=r"(x[r][0]), "=r"(x[r][1]), "=r"(x[r][2]), "=r"(x[r][3])
                 : "r"(xa(h, i)));
  };
  auto store = [&](int r, int h, int i, uint32_t om0, uint32_t om1) {
    stmatrix_x4(xa(h, i), mul_bf2(om0, mul_bf2(x[r][0], y[r][0])), mul_bf2(om1, mul_bf2(x[r][1], y[r][1])),
                mul_bf2(om0, mul_bf2(x[r][2], y[r][2])), mul_bf2(om1, mul_bf2(x[r][3], y[r][3])));
  };
#pragma unroll 1
  for (int h = 0; h < 2; h++) {
#pragma unroll
    for (int i = 0; i < 7; i++) load(i, h, i);
#pragma unroll
    for (int i = 0; i < 7; i++) store(i, h, i, h ? om[2] : om[0], h ? om[3] : om[1]);
  }
  __syncwarp();
  mbar_arrive_if(bar + B_OE, lane == 0);
  if (w0 && !__any_sync(0xffffffffu, have)) {
    if (elect_one()) late(0);
  }
  mbar_wait_sleep(bar + B_OY2, 0);
  load(0, 0, 7);
  load(1, 1, 7);
  store(0, 0, 7, om[0], om[1]);
  store(1, 1, 7, om[2], om[3]);
  __syncwarp();
  mbar_arrive_if(bar + B_OY + 8, lane == 0);
  if (wtid == 0) { TD(13) }
}

__device__ __forceinline__ void out_gemm(const Maps& maps, const uint32_t sbase, uint32_t sn, bool post, float (&o)[64],
                                         float (&s)[64],                                          float i0, float i1) {
  PHASE_GIVEN
  auto acc = [&](int h) -> float (&)[64] { return h ? o : s; };
  constexpr uint64_t DHI = DESC_SW128 | ((uint64_t)(1024 >> 4) << 32);
  const uint32_t d0 = (uint32_t)make_desc(sbase, 0, 0, 0);
  auto mma0 = [&](int h) {
    wgmma_fence();
#pragma unroll
    for (int k = 0; k < 4; k++)
      wgmma_m64n128_ss_tb(acc(h), DHI | (d0 + 0x10800 + h * 512 + k * 2), DHI | (d0 + 0x2000c00 + k * 128), k != 0);
    wgmma_commit();
  };
  mbar_wait(bar + B_OFULL, 0);
  mma0(0);
  wgmma_wait<1>();
  fence_regs(o);
  if (post) {
    named_bar_arrive(3, 256);
    put_o(sbase, 0, warp, lane, o, i0, i1);
  }
  mma0(1);
  if (post) st_go(bar, 0, wtid, sn - 1);
  const int m_tile = maps.id[blockIdx.x][2] & 15, n_tile = maps.id[blockIdx.x][2] >> 4;
  uint32_t stage = 1, phase = 0, prev_stage = 0;
  GT(gti++)
  const uint32_t xrow = sbase + O_X_OFF + warp * 4096 + (lane & 15) * 128;
  auto addr = [&](int i) {
    return xrow + (i >> 3) * 16384 + ((i >> 2) & 1) * 2048 + ((((i & 3) * 2 + (lane >> 4)) ^ (lane & 7)) << 4);
  };
  uint32_t b[16][4];
#pragma unroll
  for (int i = 0; i < 64; i++) asm volatile("" : "=r"(b[i >> 2][i & 3]));
  auto ld_b = [&](int q0, int q1) {
#pragma unroll
    for (int i = 0; i < 16; i++)
      if ((i & 7) != 7)
        asm volatile(
            "{\n.reg .pred p;\nsetp.ge.s32 p, %5, %6;\nsetp.le.and.s32 p, %5, %7, p;\n"
            "@p ldmatrix.sync.aligned.m8n8.x4.shared.b16 {%0, %1, %2, %3}, [%4];\n}\n"
            : "+r"(b[i][0]), "+r"(b[i][1]), "+r"(b[i][2]), "+r"(b[i][3])
            : "r"(addr(i)), "r"(i / 4), "r"(q0), "r"(q1)
            : "memory");
  };
  int nq = 0;
#pragma unroll 1
  for (int kt = 1; kt < O_NK - 2; kt++) {
    uint32_t da = (uint32_t)make_desc(sbase + out_stage(stage), 16, 0, 0);
    uint32_t db = (uint32_t)make_desc(sbase + out_stage(stage) + 16384, 8192, 0, 0);
    asm volatile("" : "+r"(da), "+r"(db));
    mbar_wait(bar + B_OFULL + 8 * stage, phase);
    GT(gti++)
#pragma unroll
    for (int kk = 0; kk < 4; kk++) {
      wgmma_wait<2>();
      if (kk == 2)
        mbar_arrive_cluster_if(bar + B_OEMPTY + 8 * prev_stage, wtid >> 6, (wtid & 63) == 32 && kt - 1 + O_STAGES < O_NK);
      wgmma_fence();
      wgmma_m64n128_ss_tb(acc(0), DHI | (da + kk * 2), DHI | (db + kk * 128), 1);
      wgmma_m64n128_ss_tb(acc(1), DHI | (da + 512 + kk * 2), DHI | (db + kk * 128), 1);
      wgmma_commit();
      if (kk == 0 && kt >= 52) {
        uint32_t ok;
        asm volatile("{\n.reg .pred p;\nmbarrier.test_wait.parity.shared::cta.b64 p, [%1], 0;\nselp.u32 %0, 1, 0, p;\n}\n"
                     : "=r"(ok)
                     : "r"(bar + B_OE)
                     : "memory");
        if (__all_sync(0xffffffffu, ok)) {
          ld_b(nq, nq);
          nq++;
        }
      }
    }
    prev_stage = stage;
    if (++stage == O_STAGES) { stage = 0; phase ^= 1; }
  }
  if (tid == 0) { TD(14) }
  constexpr int S0 = (O_NK - 2) % O_STAGES, P0 = ((O_NK - 2) / O_STAGES) & 1;
  auto mma = [&](int h, int k0, int k1) {
    wgmma_fence();
#pragma unroll
    for (int k = k0; k < k1; k++) {
      const uint32_t d = d0 + (out_stage(S0 + (k >> 2)) >> 4);
      wgmma_m64n128_ss_tb(acc(h), DHI | (d + 0x10000 + h * 512 + (k & 3) * 2), DHI | (d + 0x2000400 + (k & 3) * 128), 1);
    }
    wgmma_commit();
  };
#pragma unroll
  for (int p = 0; p < 2; p++) {
    mbar_wait(bar + B_OFULL + 8 * (S0 + p), P0);
    mma(0, 4 * p, 4 * p + 4);
  }
  mma(1, 0, 8);
  if (nq < 4) {
    mbar_wait(bar + B_OE, 0);
    ld_b(nq, 3);
  }
  const uint4 g4 = lds128(sbase + O_G_OFF + wtid * 16);
  const uint32_t gg[4] = {g4.x, g4.y, g4.z, g4.w};
  const int w4 = __shfl_sync(0xffffffffu, warp, 0);
#pragma unroll
  for (int i = 0; i < 16; i++) {
    const int h = i >> 3;
    if (i == 0) wgmma_wait<1>();
    if (i == 8) wgmma_wait<0>();
    if ((i & 7) == 0) fence_regs(acc(h));
    if (i == 8) {   }
    if (i == 7) {
      mbar_wait(bar + B_OY + 8, 0);
#pragma unroll
      for (int j = 7; j < 16; j += 8)
        asm volatile("ldmatrix.sync.aligned.m8n8.x4.shared.b16 {%0, %1, %2, %3}, [%4];"
                     : "=r"(b[j][0]), "=r"(b[j][1]), "=r"(b[j][2]), "=r"(b[j][3])
                     : "r"(addr(j))
                     : "memory");
    }
    const float* a = acc(h) + 8 * (i & 7);
    stmatrix_x4(addr(i), fma_bf2(gg[2 * h], pack_bf16(a[0], a[1]), b[i][0]), fma_bf2(gg[2 * h + 1], pack_bf16(a[2], a[3]), b[i][1]),
                fma_bf2(gg[2 * h], pack_bf16(a[4], a[5]), b[i][2]), fma_bf2(gg[2 * h + 1], pack_bf16(a[6], a[7]), b[i][3]));
    if ((i & 7) == 7) {
      fence_proxy_async();
      __syncwarp();
      if (elect_one()) {
        tma_store_3d(&maps.oc, sbase + O_X_OFF + (h * 4 + w4) * 4096, 0, m_tile * 128 + h * 64 + w4 * 16, n_tile * 2);
        if (h == 1) {
          tma_store_commit();
        }
      }
    }
  }
  GT(gti++)
}

__device__ __noinline__ void leave_kernel(int mask) {
  if (!(mask & 4)) return;
  if (atomicAdd(g_cnt + CNT_DONE * 32, 1u) == 2 * gridDim.x - 1) {
    for (int i = 0; i < CNT_N; i++) g_cnt[i * 32] = 0;
#pragma unroll 4
    for (int i = 0; i < 128; i++) g_slot[i] = 0;
  }
}

__device__ __noinline__ void side_jobs(const Maps& maps, uint32_t sbase) {
  const int w12 = __shfl_sync(0xffffffffu, threadIdx.x >> 5, 0);
  gate_rows(maps, sbase, (blockIdx.x - 128) * 12 + w12, w12, threadIdx.x & 31);
  fence_proxy_async();
  __syncthreads();
  if (threadIdx.x == 320) cnt_signal_release(CNT_PREP, 1);
}

__global__ void __launch_bounds__(384, 1)
    fused_kernel(int mask, const bf16* px, const bf16* pw, const __grid_constant__ Maps maps) {
  extern __shared__ __align__(1024) uint8_t smem_raw[];
  {
    const uint32_t t = threadIdx.x, l = t & 31, u = (blockIdx.x & 127) * 16 + (l >> 1);
    const uint32_t ow = (u >> 5) * HDIM + ((u >> 2) & 7) * 512 + 256 + (u & 3) * 64, ox = u * DM;
    const bf16* p = ((l & 1) ? pw : px) + ((l & 1) ? ow : ox);
    asm volatile("{\n.reg .pred p;\nsetp.ne.u32 p, %1, 0;\n@p prefetch.global.L2 [%0];\n}\n" ::"l"(p), "r"((uint32_t)(t < 32)));
  }
  {
    const uint32_t sbase = __shfl_sync(0xffffffffu, smem_u32(smem_raw), 0);
    const uint32_t bar = sbase + BAR_OFF;
    const int tid = threadIdx.x;
    const bool do_qkv = (mask & 1) && blockIdx.x < 128;
    TL(0, 0)
    if (__shfl_sync(0xffffffffu, tid >> 5, 0) == 1 && do_qkv) {
      if (elect_one()) {
        for (int i = 0; i < G_STAGES; i++) mbar_init(bar + B_GFULL + 8 * i, 1);
        fence_barrier_init();
        qkv_producer(maps, sbase, true);
      }
    }
    if (tid == 0) {
      for (int i = 0; i < G_STAGES; i++) {
        mbar_init(bar + B_GEMPTY + 8 * i, 2);
        mbar_init(bar + B_SFULL + 8 * i, 4);
        mbar_init(bar + B_SFREE + 8 * i, 1);
      }
      for (int i = 0; i < 2; i++) {
        mbar_init(bar + B_OFREE + 8 * i, 1);
        mbar_init(bar + B_QFULL + 8 * i, 1);
        mbar_init(bar + B_QEMPTY + 8 * i, 2);
        mbar_init(bar + B_KFULL + 8 * i, 1);
        mbar_init(bar + B_KEMPTY + 8 * i, 2);
        mbar_init(bar + B_VFULL + 8 * i, 1);
        mbar_init(bar + B_VEMPTY + 8 * i, 2);
      }
      for (int i = 0; i < O_STAGES; i++) {
        mbar_init(bar + B_OFULL + 8 * i, 1);
        mbar_init(bar + B_OEMPTY + 8 * i, 2);
      }
      mbar_init(bar + B_OY, 1);
      for (int i = 0; i < 3; i++) mbar_init(bar + seen_bar(i), 1);
      mbar_init(bar + B_OY2, 1);
      mbar_init(bar + B_DEAL, 1);
      mbar_init(bar + B_DEAL2, 1);
      mbar_init(bar + B_PAIR, 1);
      mbar_init(bar + B_OY + 8, 4);
      mbar_init(bar + B_OE, 4);
      mbar_init(bar + B_QDONE, 2);
      for (int i = 0; i < 8; i++) mbar_init(bar + B_CFULL + 8 * i, 1);
      for (int i = 0; i < CNT_N; i++) asm volatile("st.shared.u32 [%0], 0;" ::"r"(bar + B_PEND + 4 * i) : "memory");
      fence_barrier_init();
    }
    __syncthreads();
    asm volatile("barrier.cluster.arrive.relaxed.aligned;" ::: "memory");
    if ((mask & 1) && blockIdx.x >= 128) side_jobs(maps, sbase);
  }
  uint32_t smem0 = smem_u32(smem_raw);
  PHASE_PROLOGUE
  const bool do_qkv = (mask & 1) && blockIdx.x < 128, do_out = (mask & 4) && blockIdx.x < 128;
  TL(0, 1)

  if (wg != 2) {
    reg_alloc<232>();
    asm volatile("barrier.cluster.wait.acquire.aligned;" ::: "memory");
    if (wg == 1) named_bar_arrive(4, 256);
    uint32_t sn = 0;
    float rest[64], o[64], s[64];
    uint32_t q[32];
    if (do_qkv) {
      sn = qkv_consumer(maps, sbase, wg, mask & 2, q, rest, rt_zero);
    } else {
      undef_regs(rest);
#pragma unroll
      for (int j = 0; j < 32; j++) asm volatile("" : "=r"(q[j]));
    }
    undef_regs(o);
    undef_regs(s);
    TL(0, 2) TL(1, 0) TL(1, 1)
    const bool direct = do_out && wg == 0;
    float i0 = 0.f, i1 = 0.f;
    if (mask & 2) sn = attn_consumer(maps, sbase, wg, rt_zero, sn, q, rest, do_qkv, o, s, i0, i1);
    TL(2, 0)
    bool side = false;
    if (!direct) {
      wgmma_wait<0>();
      fence_regs(o);
      if (mask & 2) {
        const bool fused = mask & 4, mainc = blockIdx.x < 128;
        if (mainc) {
          PHASE_GIVEN
          put_o(sbase, wg, warp, lane, o, i0, i1);
          st_go(bar, wg, wtid, sn - 1);
        }
        const uint32_t b2 = blockIdx.x * 2 + (threadIdx.x >> 7);
        const uint32_t first = __shfl_sync(0xffffffffu, !fused ? b2 : mainc ? conv_first(maps) : (b2 - 255) * 128 - C_SIDE, 0);
        conv_consumer(maps, smem_u32(smem_raw), first, !fused ? 264 : mainc ? 16 : 1,
                      !fused ? DM : mainc ? (first | 127) + 1 - C_SIDE : first + C_SIDE, fused && !mainc,
                      fused && mainc);
      }
      side = (mask & 4) && blockIdx.x < 128;
    } else {
      out_gemm(maps, sbase, sn, mask & 2, o, s, i0, i1);
    }
    TL(1, 2) TL(2, 1) TL(2, 2) TL(3, 0) TL(3, 1)
    if (side + rt_zero) out_side(maps, smem_u32(smem_raw));
    tma_store_wait_read<0>();
  } else {
    reg_dealloc<40>();
    asm volatile("barrier.cluster.wait.acquire.aligned;" ::: "memory");
    const int w = __shfl_sync(0xffffffffu, tid >> 5, 0) - 8;
    if (w < 2) {
      if (do_qkv) prep_agent(maps, sbase, w, lane);
      if (elect_one()) store_agent(bar, w, w && do_out ? conv_first(maps) + 48 : 0, blockIdx.x >= 128 || mask == 4 ? 0 : mask == 1 ? 24 : 99);
      TL2(3, 2)
    } else {
      if (elect_one()) {
        const bool dry = w == 2;
        if (do_qkv && !dry) qkv_producer(maps, sbase, false);
        if (mask & 2) attn_producer(maps, sbase, do_qkv, do_out, dry);
        if (do_out) out_producer(maps, sbase, mask & 2, dry);
        if (dry) { TD(5) }
      }
      __syncwarp();
      if (w == 2) publisher(bar, tid & 31, !(mask & 2) ? 2 : do_out ? 3 : 4, !do_out ? 3 : do_qkv ? 0 : 2, do_qkv ? 4 : 0);
      if ((tid & 31) == 0) leave_kernel(mask);
    }
  }
}

typedef CUresult (*PFN_tmapEncode)(CUtensorMap*, CUtensorMapDataType, cuuint32_t, void*, const cuuint64_t*,
                                   const cuuint64_t*, const cuuint32_t*, const cuuint32_t*, CUtensorMapInterleave,
                                   CUtensorMapSwizzle, CUtensorMapL2promotion, CUtensorMapFloatOOBfill);
static PFN_tmapEncode s_encode = nullptr;

static void make_map_2d(CUtensorMap* m, const void* ptr, int rows, int cols, int box_rows) {
  cuuint64_t dims[2] = {(cuuint64_t)cols, (cuuint64_t)rows};
  cuuint64_t strides[1] = {(cuuint64_t)cols * 2};
  cuuint32_t box[2] = {cols < 64 ? 32u : 64u, (cuuint32_t)box_rows};
  cuuint32_t es[2] = {1, 1};
  s_encode(m, CU_TENSOR_MAP_DATA_TYPE_BFLOAT16, 2, const_cast<void*>(ptr), dims, strides, box, es,
           CU_TENSOR_MAP_INTERLEAVE_NONE, cols < 64 ? CU_TENSOR_MAP_SWIZZLE_64B : CU_TENSOR_MAP_SWIZZLE_128B, CU_TENSOR_MAP_L2_PROMOTION_L2_256B,
           CU_TENSOR_MAP_FLOAT_OOB_FILL_NONE);
}
static void make_map_3d(CUtensorMap* m, const void* ptr, int rows, int cols, int box_rows, int box_chunks) {
  cuuint64_t dims[3] = {64, (cuuint64_t)rows, (cuuint64_t)(cols / 64)};
  cuuint64_t strides[2] = {(cuuint64_t)cols * 2, 128};
  cuuint32_t box[3] = {64, (cuuint32_t)box_rows, (cuuint32_t)box_chunks};
  cuuint32_t es[3] = {1, 1, 1};
  s_encode(m, CU_TENSOR_MAP_DATA_TYPE_BFLOAT16, 3, const_cast<void*>(ptr), dims, strides, box, es,
           CU_TENSOR_MAP_INTERLEAVE_NONE, CU_TENSOR_MAP_SWIZZLE_128B, CU_TENSOR_MAP_L2_PROMOTION_L2_256B,
           CU_TENSOR_MAP_FLOAT_OOB_FILL_NONE);
}

static cudaLaunchConfig_t fused_cfg(cudaLaunchAttribute* at) {
  cudaLaunchConfig_t cfg = {};
  cfg.gridDim = dim3(132);
  cfg.blockDim = dim3(384);
  cfg.dynamicSmemBytes = SMEM_BYTES;
  cfg.stream = cudaStreamPerThread;
  at[0].id = cudaLaunchAttributeClusterDimension;
  at[0].val.clusterDim.x = 2;
  at[0].val.clusterDim.y = 1;
  at[0].val.clusterDim.z = 1;
  cfg.attrs = at;
  cfg.numAttrs = 1;
  return cfg;
}

extern "C" void kernel_launch(void* const* d_in, const int* in_sizes, int n_in, void* d_out, int out_size) {
  const bf16* x = (const bf16*)d_in[0];
  const bf16* ckv = (const bf16*)d_in[1];
  const bf16* wq = (const bf16*)d_in[2];
  const bf16* wuk = (const bf16*)d_in[3];
  const bf16* wuv = (const bf16*)d_in[4];
  const bf16* wo = (const bf16*)d_in[5];
  const bf16* bk = (const bf16*)d_in[7];
  const bf16* bv = (const bf16*)d_in[8];
  const bf16* shift_k = (const bf16*)d_in[9];
  const bf16* ssm_k = (const bf16*)d_in[10];
  const bf16* ssm_D = (const bf16*)d_in[11];
  const bf16* gate_w = (const bf16*)d_in[12];
  bf16* out = (bf16*)d_out;

  static void *pq = nullptr, *pk = nullptr, *pv = nullptr, *pctx = nullptr, *pb = nullptr, *pu = nullptr;
  static int max_clusters = 0;
  if (!s_encode) {
    void* fn = nullptr;
    cudaDriverEntryPointQueryResult qres;
    cudaGetDriverEntryPoint("cuTensorMapEncodeTiled", &fn, cudaEnableDefault, &qres);
    s_encode = (PFN_tmapEncode)fn;
    cudaGetSymbolAddress(&pq, g_q);
    cudaGetSymbolAddress(&pk, g_k);
    cudaGetSymbolAddress(&pv, g_v);
    cudaGetSymbolAddress(&pctx, g_ctx);
    cudaGetSymbolAddress(&pb, g_y2T);
    cudaGetSymbolAddress(&pu, g_kvT);
    cudaFuncSetAttribute(fused_kernel, cudaFuncAttributeMaxDynamicSharedMemorySize, SMEM_BYTES);
    cudaLaunchAttribute at[1];
    cudaLaunchConfig_t cfg = fused_cfg(at);
    if (cudaOccupancyMaxActiveClusters(&max_clusters, fused_kernel, &cfg) != cudaSuccess) max_clusters = 0;
  }

  Maps all = {};
  make_map_2d(&all.a[0], x, S_LEN, DM, 128);
  make_map_2d(&all.a[1], ckv, S_LEN, DC, 128);
  make_map_3d(&all.b[0], wq, DM, HDIM, 64, 4);
  make_map_3d(&all.b[1], wuk, DC, HDIM, 64, 4);
  make_map_3d(&all.b[2], wuv, DC, HDIM, 64, 4);
  make_map_2d(&all.c[0], pq, S_LEN, HDIM, 64);
  make_map_2d(&all.c[1], pk, S_LEN, HDIM, 64);
  make_map_2d(&all.c[2], pv, S_LEN, HDIM, 64);
  make_map_3d(&all.q, pq, S_LEN, HDIM, 128, 2);
  make_map_3d(&all.k, pk, S_LEN, HDIM, 128, 2);
  make_map_3d(&all.v, pv, S_LEN, HDIM, 128, 2);
  make_map_2d(&all.o, pctx, S_LEN, HDIM, 64);
  all.ssm_k = ssm_k;
  all.ssm_D = ssm_D;
  make_map_2d(&all.oa, pctx, S_LEN, HDIM, 128);
  make_map_2d(&all.ob, wo, HDIM, DM, 64);
  make_map_3d(&all.oc, out, S_LEN, DM, 16, 2);
  make_map_3d(&all.y, pb, DM, S_LEN, 16, 2);
  make_map_3d(&all.xs, x, S_LEN, DM, 16, 2);
  make_map_2d(&all.cu, pu, DM * 64, 32, 64);
  make_map_2d(&all.ch, ssm_k, DM * 64, 32, 64);

  make_map_2d(&all.bk, bk, S_LEN, DM, 35);
  make_map_2d(&all.bv, bv, S_LEN, DM, 32);
  for (int b = 0; b < 128; b++) {
    const int c = b >> 1, r = b & 1;
    const int G = c < 4 ? 0 : c < 36 ? (c - 4) % 8 : 1 + (c - 36) % 7;
    const int i = c < 4 ? 4 + c : c < 36 ? (c - 4) / 8 : 4 + (c - 36) / 7;
    all.id[b][0] = r + 2 * (i & 1) + 4 * (G & 3) + 16 * (i >> 1) + 64 * (G >> 2);
    all.id[b][1] = r + 2 * i + 16 * G;
    all.id[b][2] = r + 2 * G + 16 * i;
    all.id[b][3] = r + 2 * i == 15 ? 0x78 : 0xd8;
  }
  all.shift_k = shift_k;
  all.x = x;
  all.gate_w = gate_w;
  cudaLaunchAttribute at[1];
  cudaLaunchConfig_t cfg = fused_cfg(at);
  if (max_clusters >= 66) {
    cudaLaunchKernelEx(&cfg, fused_kernel, 7, x, wq, all);
  } else {
    for (int m = 1; m <= 4; m <<= 1) cudaLaunchKernelEx(&cfg, fused_kernel, m, x, wq, all);
  }
}
```

```cpp
#include <cuda_runtime.h>
#include <cuda_bf16.h>
#include <cuda.h>
#include <stdint.h>

typedef __nv_bfloat16 bf16;
#define INPLACE 3

constexpr int S_LEN = 2048;
constexpr int DM = 1024;
constexpr int NH = 32;
constexpr int HD = 128;
constexpr int DC = 512;
constexpr int HDIM = NH * HD;

__device__ __align__(1024) bf16 g_q[S_LEN * HDIM];
__device__ __align__(1024) bf16 g_k[S_LEN * HDIM];
__device__ __align__(1024) bf16 g_v[S_LEN * HDIM];
#define g_ctx g_q
__device__ __align__(1024) bf16 g_kvT[DM * S_LEN];
#define g_y2T g_kvT
__device__ __align__(1024) float g_gate[S_LEN];
enum { CNT_KV = 0, CNT_PREP = CNT_KV + 2, CNT_CTX, CNT_Y2 = CNT_CTX + 2, CNT_PREP1 = CNT_Y2 + 2, CNT_DONE, CNT_RANK, CNT_N };
__device__ unsigned int g_cnt[CNT_N * 32];
__device__ unsigned long long g_slot[128];

#define TL(k, i)
#define TL2(k, i)
#define TD(i)
#define CT(i)
#define GT(i)
#define GA(i)
#define ST(i)

__device__ __forceinline__ uint32_t smem_u32(const void* p) { return (uint32_t)__cvta_generic_to_shared(p); }

__device__ __forceinline__ void mbar_init(uint32_t bar, uint32_t count) {
  asm volatile("mbarrier.init.shared::cta.b64 [%0], %1;" ::"r"(bar), "r"(count));
}
__device__ __forceinline__ void mbar_expect_tx(uint32_t bar, uint32_t bytes) {
  asm volatile("mbarrier.arrive.expect_tx.shared::cta.b64 _, [%0], %1;" ::"r"(bar), "r"(bytes) : "memory");
}
__device__ __forceinline__ void mbar_arrive(uint32_t bar) {
  asm volatile("mbarrier.arrive.shared::cta.b64 _, [%0];" ::"r"(bar) : "memory");
}
__device__ __forceinline__ void mbar_wait(uint32_t bar, uint32_t parity) {
  uint32_t done;
  uint32_t spins = 0;
  do {
    asm volatile(
        "{\n.reg .pred p;\n"
        "mbarrier.try_wait.parity.shared::cta.b64 p, [%1], %2;\n"
        "selp.u32 %0, 1, 0, p;\n}\n"
        : "=r"(done)
        : "r"(bar), "r"(parity)
        : "memory");
    if (++spins > (1u << 22)) break;
  } while (!done);
}
__device__ __forceinline__ bool mbar_try(uint32_t bar, uint32_t parity) {
  uint32_t done;
  asm volatile(
      "{\n.reg .pred p;\n"
      "mbarrier.try_wait.parity.shared::cta.b64 p, [%1], %2;\n"
      "selp.u32 %0, 1, 0, p;\n}\n"
      : "=r"(done)
      : "r"(bar), "r"(parity)
      : "memory");
  return done != 0;
}
__device__ __forceinline__ bool mbar_test(uint32_t bar, uint32_t parity) {
  uint32_t done;
  asm volatile(
      "{\n.reg .pred p;\n"
      "mbarrier.test_wait.parity.shared::cta.b64 p, [%1], %2;\n"
      "selp.u32 %0, 1, 0, p;\n}\n"
      : "=r"(done)
      : "r"(bar), "r"(parity)
      : "memory");
  return done != 0;
}
__device__ __forceinline__ bool elect_one() {
  uint32_t pred;
  asm volatile("{\n.reg .pred p;\nelect.sync _|p, 0xffffffff;\nselp.u32 %0, 1, 0, p;\n}\n" : "=r"(pred));
  return pred != 0;
}
__device__ __forceinline__ void mbar_arrive_if(uint32_t bar, bool pred) {
  asm volatile(
      "{\n.reg .pred p;\nsetp.ne.b32 p, %1, 0;\n"
      "@p mbarrier.arrive.shared::cta.b64 _, [%0];\n}\n" ::"r"(bar),
      "r"((uint32_t)pred)
      : "memory");
}
__device__ __forceinline__ void mbar_wait_sleep(uint32_t bar, uint32_t parity) {
  uint32_t done;
  uint32_t spins = 0;
  do {
    asm volatile(
        "{\n.reg .pred p;\n"
        "mbarrier.try_wait.parity.shared::cta.b64 p, [%1], %2, %3;\n"
        "selp.u32 %0, 1, 0, p;\n}\n"
        : "=r"(done)
        : "r"(bar), "r"(parity), "r"(20000u)
        : "memory");
    if (++spins > (1u << 16)) break;
  } while (!done);
}
__device__ __forceinline__ void fence_barrier_init() {
  asm volatile("fence.mbarrier_init.release.cluster;" ::: "memory");
}
__device__ __forceinline__ void fence_proxy_async() {
  asm volatile("fence.proxy.async.shared::cta;" ::: "memory");
}
__device__ __forceinline__ void named_bar_sync(int id, int nthreads) {
  asm volatile("bar.sync %0, %1;" ::"r"(id), "r"(nthreads) : "memory");
}
__device__ __forceinline__ void named_bar_arrive(int id, int nthreads) {
  asm volatile("bar.arrive %0, %1;" ::"r"(id), "r"(nthreads) : "memory");
}
__device__ __forceinline__ void tma_load_2d(uint32_t dst, const CUtensorMap* m, uint32_t bar, int c0, int c1) {
  asm volatile(
      "cp.async.bulk.tensor.2d.shared::cluster.global.mbarrier::complete_tx::bytes [%0], [%1, {%3, %4}], [%2];" ::"r"(dst),
      "l"(reinterpret_cast<uint64_t>(m)), "r"(bar), "r"(c0), "r"(c1)
      : "memory");
}
__device__ __forceinline__ void tma_load_3d(uint32_t dst, const CUtensorMap* m, uint32_t bar, int c0, int c1, int c2) {
  asm volatile(
      "cp.async.bulk.tensor.3d.shared::cluster.global.mbarrier::complete_tx::bytes [%0], [%1, {%3, %4, %5}], [%2];" ::"r"(dst),
      "l"(reinterpret_cast<uint64_t>(m)), "r"(bar), "r"(c0), "r"(c1), "r"(c2)
      : "memory");
}
__device__ __forceinline__ void tma_store_2d(const CUtensorMap* m, uint32_t src, int c0, int c1) {
  asm volatile("cp.async.bulk.tensor.2d.global.shared::cta.bulk_group [%0, {%2, %3}], [%1];" ::"l"(
                   reinterpret_cast<uint64_t>(m)),
               "r"(src), "r"(c0), "r"(c1)
               : "memory");
}
__device__ __forceinline__ void tma_load_2d_mc(uint32_t dst, const CUtensorMap* m, uint32_t bar, int c0, int c1,
                                               uint16_t mask) {
  asm volatile(
      "cp.async.bulk.tensor.2d.shared::cluster.global.mbarrier::complete_tx::bytes.multicast::cluster [%0], [%1, {%3, "
      "%4}], [%2], %5;" ::"r"(dst),
      "l"(reinterpret_cast<uint64_t>(m)), "r"(bar), "r"(c0), "r"(c1), "h"(mask)
      : "memory");
}
__device__ __forceinline__ void mbar_arrive_cluster_if(uint32_t bar, uint32_t cta, bool pred) {
  asm volatile(
      "{\n.reg .b32 ra;\n.reg .pred p;\nsetp.ne.b32 p, %2, 0;\n"
      "mapa.shared::cluster.u32 ra, %0, %1;\n"
      "@p mbarrier.arrive.shared::cluster.b64 _, [ra];\n}\n" ::"r"(bar),
      "r"(cta), "r"((uint32_t)pred)
      : "memory");
}
__device__ __forceinline__ uint64_t policy_evict_first() {
  uint64_t pol;
  asm volatile("createpolicy.fractional.L2::evict_first.b64 %0, 1.0;" : "=l"(pol));
  return pol;
}
__device__ __forceinline__ void tma_load_2d_hint(uint32_t dst, const CUtensorMap* m, uint32_t bar, int c0, int c1,
                                                 uint64_t pol) {
  asm volatile(
      "cp.async.bulk.tensor.2d.shared::cluster.global.mbarrier::complete_tx::bytes.L2::cache_hint [%0], [%1, {%3, %4}], "
      "[%2], %5;" ::"r"(dst),
      "l"(reinterpret_cast<uint64_t>(m)), "r"(bar), "r"(c0), "r"(c1), "l"(pol)
      : "memory");
}
__device__ __forceinline__ void tma_load_3d_hint(uint32_t dst, const CUtensorMap* m, uint32_t bar, int c0, int c1,
                                                 int c2, uint64_t pol) {
  asm volatile(
      "cp.async.bulk.tensor.3d.shared::cluster.global.mbarrier::complete_tx::bytes.L2::cache_hint [%0], [%1, {%3, %4, "
      "%5}], [%2], %6;" ::"r"(dst),
      "l"(reinterpret_cast<uint64_t>(m)), "r"(bar), "r"(c0), "r"(c1), "r"(c2), "l"(pol)
      : "memory");
}
__device__ __forceinline__ void cnt_signal_release(int which, uint32_t n) {
  asm volatile("red.release.gpu.global.add.u32 [%0], %1;" ::"l"(g_cnt + which * 32), "r"(n) : "memory");
}
__device__ __forceinline__ bool cnt_wait(int which, uint32_t target, uint32_t spins = 0) {
  uint32_t v;
  while (true) {
    asm volatile("ld.acquire.gpu.global.u32 %0, [%1];" : "=r"(v) : "l"(g_cnt + which * 32) : "memory");
    if (v >= target || ++spins > (1u << 18)) break;
    __nanosleep(64);
  }
  asm volatile("fence.proxy.async.global;" ::: "memory");
  return v >= target;
}
__device__ __forceinline__ void tma_store_3d(const CUtensorMap* m, uint32_t src, int c0, int c1, int c2) {
  asm volatile("cp.async.bulk.tensor.3d.global.shared::cta.bulk_group [%0, {%2, %3, %4}], [%1];" ::"l"(
                   reinterpret_cast<uint64_t>(m)),
               "r"(src), "r"(c0), "r"(c1), "r"(c2)
               : "memory");
}
__device__ __forceinline__ void tma_store_commit() { asm volatile("cp.async.bulk.commit_group;" ::: "memory"); }
template <int N>
__device__ __forceinline__ void tma_store_wait_read() {
  asm volatile("cp.async.bulk.wait_group.read %0;" ::"n"(N) : "memory");
}
template <int N>
__device__ __forceinline__ void tma_store_wait() {
  asm volatile("cp.async.bulk.wait_group %0;" ::"n"(N) : "memory");
}
__device__ __forceinline__ void wgmma_fence() { asm volatile("wgmma.fence.sync.aligned;" ::: "memory"); }
__device__ __forceinline__ void wgmma_commit() { asm volatile("wgmma.commit_group.sync.aligned;" ::: "memory"); }
template <int N>
__device__ __forceinline__ void wgmma_wait() {
  asm volatile("wgmma.wait_group.sync.aligned %0;" ::"n"(N) : "memory");
}
template <int R>
__device__ __forceinline__ void reg_alloc() { asm volatile("setmaxnreg.inc.sync.aligned.u32 %0;" ::"n"(R)); }
template <int R>
__device__ __forceinline__ void reg_dealloc() { asm volatile("setmaxnreg.dec.sync.aligned.u32 %0;" ::"n"(R)); }

__device__ __forceinline__ void stmatrix_x4(uint32_t addr, uint32_t r0, uint32_t r1, uint32_t r2, uint32_t r3) {
  asm volatile("stmatrix.sync.aligned.m8n8.x4.shared.b16 [%0], {%1, %2, %3, %4};" ::"r"(addr), "r"(r0), "r"(r1),
               "r"(r2), "r"(r3)
               : "memory");
}
__device__ __forceinline__ uint32_t pack_bf16(float lo, float hi) {
  uint32_t r;
  asm("cvt.rn.bf16x2.f32 %0, %1, %2;" : "=r"(r) : "f"(hi), "f"(lo));
  return r;
}
__device__ __forceinline__ float bf16_round(float x) { return __bfloat162float(__float2bfloat16_rn(x)); }
__device__ __forceinline__ float bf_lo(uint32_t v) { return __uint_as_float(v << 16); }
__device__ __forceinline__ float bf_hi(uint32_t v) { return __uint_as_float(v & 0xffff0000u); }
__device__ __forceinline__ uint4 lds128(uint32_t a) {
  uint4 v;
  asm volatile("ld.shared.v4.u32 {%0, %1, %2, %3}, [%4];" : "=r"(v.x), "=r"(v.y), "=r"(v.z), "=r"(v.w) : "r"(a));
  return v;
}
__device__ __forceinline__ void sts128(uint32_t a, uint4 v) {
  asm volatile("st.shared.v4.u32 [%0], {%1, %2, %3, %4};" ::"r"(a), "r"(v.x), "r"(v.y), "r"(v.z), "r"(v.w) : "memory");
}
__device__ __forceinline__ uint32_t mul_bf2(uint32_t a, uint32_t b) {
  uint32_t r;
  asm("mul.rn.bf16x2 %0, %1, %2;" : "=r"(r) : "r"(a), "r"(b));
  return r;
}
__device__ __forceinline__ float ex2(float x) {
  float y;
  asm("ex2.approx.ftz.f32 %0, %1;" : "=f"(y) : "f"(x));
  return y;
}
__device__ __forceinline__ float rcp(float x) {
  float y;
  asm("rcp.approx.ftz.f32 %0, %1;" : "=f"(y) : "f"(x));
  return y;
}
template <int N>
__device__ __forceinline__ void fence_regs(float (&r)[N]) {
#pragma unroll
  for (int i = 0; i < N; i++) asm volatile("" : "+f"(r[i])::"memory");
}

template <int N>
__device__ __forceinline__ void undef_regs(float (&r)[N]) {
#pragma unroll
  for (int i = 0; i < N; i++) asm volatile("" : "=f"(r[i]));
}
template <int N>
__device__ __forceinline__ void fence_regs_u(uint32_t (&r)[N]) {
#pragma unroll
  for (int i = 0; i < N; i++) asm volatile("" : "+r"(r[i])::"memory");
}

constexpr uint64_t DESC_SW128 = 1ull << 62;
__device__ __forceinline__ uint64_t make_desc(uint32_t addr, uint32_t lbo_bytes, uint32_t sbo_bytes, uint64_t swz) {
  return (uint64_t)((addr & 0x3FFFF) >> 4) | ((uint64_t)((lbo_bytes & 0x3FFFF) >> 4) << 16) |
         ((uint64_t)((sbo_bytes & 0x3FFFF) >> 4) << 32) | swz;
}

__device__ __forceinline__ uint64_t desc_add(uint64_t d, uint32_t off16) {
  return (d & 0xFFFFFFFF00000000ull) | (uint64_t)((uint32_t)d + off16);
}

__device__ __forceinline__ void wgmma_m64n256_ss_tb(float (&d)[128], uint64_t da, uint64_t db, int sd) {
  asm volatile(
    "{\n.reg .pred p;\nsetp.ne.b32 p, %130, 0;\n"
    "wgmma.mma_async.sync.aligned.m64n256k16.f32.bf16.bf16 "
    "{%0, %1, %2, %3, %4, %5, %6, %7, %8, %9, %10, %11, %12, %13, %14, %15, %16, %17, %18, %19, %20, %21, %22, %23, %24, %25, %26, %27, %28, %29, %30, %31, %32, %33, %34, %35, %36, %37, %38, %39, %40, %41, %42, %43, %44, %45, %46, %47, %48, %49, %50, %51, %52, %53, %54, %55, %56, %57, %58, %59, %60, %61, %62, %63, %64, %65, %66, %67, %68, %69, %70, %71, %72, %73, %74, %75, %76, %77, %78, %79, %80, %81, %82, %83, %84, %85, %86, %87, %88, %89, %90, %91, %92, %93, %94, %95, %96, %97, %98, %99, %100, %101, %102, %103, %104, %105, %106, %107, %108, %109, %110, %111, %112, %113, %114, %115, %116, %117, %118, %119, %120, %121, %122, %123, %124, %125, %126, %127}, %128, %129, p, 1, 1, 0, 1;\n}\n"
    : "+f"(d[0]), "+f"(d[1]), "+f"(d[2]), "+f"(d[3]), "+f"(d[4]), "+f"(d[5]), "+f"(d[6]), "+f"(d[7]), "+f"(d[8]), "+f"(d[9]), "+f"(d[10]), "+f"(d[11]), "+f"(d[12]), "+f"(d[13]), "+f"(d[14]), "+f"(d[15]), "+f"(d[16]), "+f"(d[17]), "+f"(d[18]), "+f"(d[19]), "+f"(d[20]), "+f"(d[21]), "+f"(d[22]), "+f"(d[23]), "+f"(d[24]), "+f"(d[25]), "+f"(d[26]), "+f"(d[27]), "+f"(d[28]), "+f"(d[29]), "+f"(d[30]), "+f"(d[31]), "+f"(d[32]), "+f"(d[33]), "+f"(d[34]), "+f"(d[35]), "+f"(d[36]), "+f"(d[37]), "+f"(d[38]), "+f"(d[39]), "+f"(d[40]), "+f"(d[41]), "+f"(d[42]), "+f"(d[43]), "+f"(d[44]), "+f"(d[45]), "+f"(d[46]), "+f"(d[47]), "+f"(d[48]), "+f"(d[49]), "+f"(d[50]), "+f"(d[51]), "+f"(d[52]), "+f"(d[53]), "+f"(d[54]), "+f"(d[55]), "+f"(d[56]), "+f"(d[57]), "+f"(d[58]), "+f"(d[59]), "+f"(d[60]), "+f"(d[61]), "+f"(d[62]), "+f"(d[63]), "+f"(d[64]), "+f"(d[65]), "+f"(d[66]), "+f"(d[67]), "+f"(d[68]), "+f"(d[69]), "+f"(d[70]), "+f"(d[71]), "+f"(d[72]), "+f"(d[73]), "+f"(d[74]), "+f"(d[75]), "+f"(d[76]), "+f"(d[77]), "+f"(d[78]), "+f"(d[79]), "+f"(d[80]), "+f"(d[81]), "+f"(d[82]), "+f"(d[83]), "+f"(d[84]), "+f"(d[85]), "+f"(d[86]), "+f"(d[87]), "+f"(d[88]), "+f"(d[89]), "+f"(d[90]), "+f"(d[91]), "+f"(d[92]), "+f"(d[93]), "+f"(d[94]), "+f"(d[95]), "+f"(d[96]), "+f"(d[97]), "+f"(d[98]), "+f"(d[99]), "+f"(d[100]), "+f"(d[101]), "+f"(d[102]), "+f"(d[103]), "+f"(d[104]), "+f"(d[105]), "+f"(d[106]), "+f"(d[107]), "+f"(d[108]), "+f"(d[109]), "+f"(d[110]), "+f"(d[111]), "+f"(d[112]), "+f"(d[113]), "+f"(d[114]), "+f"(d[115]), "+f"(d[116]), "+f"(d[117]), "+f"(d[118]), "+f"(d[119]), "+f"(d[120]), "+f"(d[121]), "+f"(d[122]), "+f"(d[123]), "+f"(d[124]), "+f"(d[125]), "+f"(d[126]), "+f"(d[127])
    : "l"(da), "l"(db), "r"(sd));
}

__device__ __forceinline__ void wgmma_m64n128_ss(float (&d)[64], uint64_t da, uint64_t db, int sd) {
  asm volatile(
    "{\n.reg .pred p;\nsetp.ne.b32 p, %66, 0;\n"
    "wgmma.mma_async.sync.aligned.m64n128k16.f32.bf16.bf16 "
    "{%0, %1, %2, %3, %4, %5, %6, %7, %8, %9, %10, %11, %12, %13, %14, %15, %16, %17, %18, %19, %20, %21, %22, %23, %24, %25, %26, %27, %28, %29, %30, %31, %32, %33, %34, %35, %36, %37, %38, %39, %40, %41, %42, %43, %44, %45, %46, %47, %48, %49, %50, %51, %52, %53, %54, %55, %56, %57, %58, %59, %60, %61, %62, %63}, %64, %65, p, 1, 1, 0, 0;\n}\n"
    : "+f"(d[0]), "+f"(d[1]), "+f"(d[2]), "+f"(d[3]), "+f"(d[4]), "+f"(d[5]), "+f"(d[6]), "+f"(d[7]), "+f"(d[8]), "+f"(d[9]), "+f"(d[10]), "+f"(d[11]), "+f"(d[12]), "+f"(d[13]), "+f"(d[14]), "+f"(d[15]), "+f"(d[16]), "+f"(d[17]), "+f"(d[18]), "+f"(d[19]), "+f"(d[20]), "+f"(d[21]), "+f"(d[22]), "+f"(d[23]), "+f"(d[24]), "+f"(d[25]), "+f"(d[26]), "+f"(d[27]), "+f"(d[28]), "+f"(d[29]), "+f"(d[30]), "+f"(d[31]), "+f"(d[32]), "+f"(d[33]), "+f"(d[34]), "+f"(d[35]), "+f"(d[36]), "+f"(d[37]), "+f"(d[38]), "+f"(d[39]), "+f"(d[40]), "+f"(d[41]), "+f"(d[42]), "+f"(d[43]), "+f"(d[44]), "+f"(d[45]), "+f"(d[46]), "+f"(d[47]), "+f"(d[48]), "+f"(d[49]), "+f"(d[50]), "+f"(d[51]), "+f"(d[52]), "+f"(d[53]), "+f"(d[54]), "+f"(d[55]), "+f"(d[56]), "+f"(d[57]), "+f"(d[58]), "+f"(d[59]), "+f"(d[60]), "+f"(d[61]), "+f"(d[62]), "+f"(d[63])
    : "l"(da), "l"(db), "r"(sd));
}

__device__ __forceinline__ void wgmma_m64n128_ss_tb(float (&d)[64], uint64_t da, uint64_t db, int sd) {
  asm volatile(
    "{\n.reg .pred p;\nsetp.ne.b32 p, %66, 0;\n"
    "wgmma.mma_async.sync.aligned.m64n128k16.f32.bf16.bf16 "
    "{%0, %1, %2, %3, %4, %5, %6, %7, %8, %9, %10, %11, %12, %13, %14, %15, %16, %17, %18, %19, %20, %21, %22, %23, %24, %25, %26, %27, %28, %29, %30, %31, %32, %33, %34, %35, %36, %37, %38, %39, %40, %41, %42, %43, %44, %45, %46, %47, %48, %49, %50, %51, %52, %53, %54, %55, %56, %57, %58, %59, %60, %61, %62, %63}, %64, %65, p, 1, 1, 0, 1;\n}\n"
    : "+f"(d[0]), "+f"(d[1]), "+f"(d[2]), "+f"(d[3]), "+f"(d[4]), "+f"(d[5]), "+f"(d[6]), "+f"(d[7]), "+f"(d[8]), "+f"(d[9]), "+f"(d[10]), "+f"(d[11]), "+f"(d[12]), "+f"(d[13]), "+f"(d[14]), "+f"(d[15]), "+f"(d[16]), "+f"(d[17]), "+f"(d[18]), "+f"(d[19]), "+f"(d[20]), "+f"(d[21]), "+f"(d[22]), "+f"(d[23]), "+f"(d[24]), "+f"(d[25]), "+f"(d[26]), "+f"(d[27]), "+f"(d[28]), "+f"(d[29]), "+f"(d[30]), "+f"(d[31]), "+f"(d[32]), "+f"(d[33]), "+f"(d[34]), "+f"(d[35]), "+f"(d[36]), "+f"(d[37]), "+f"(d[38]), "+f"(d[39]), "+f"(d[40]), "+f"(d[41]), "+f"(d[42]), "+f"(d[43]), "+f"(d[44]), "+f"(d[45]), "+f"(d[46]), "+f"(d[47]), "+f"(d[48]), "+f"(d[49]), "+f"(d[50]), "+f"(d[51]), "+f"(d[52]), "+f"(d[53]), "+f"(d[54]), "+f"(d[55]), "+f"(d[56]), "+f"(d[57]), "+f"(d[58]), "+f"(d[59]), "+f"(d[60]), "+f"(d[61]), "+f"(d[62]), "+f"(d[63])
    : "l"(da), "l"(db), "r"(sd));
}

template <int TB>
__device__ __forceinline__ void wgmma_m64n128_rs(float* d, uint32_t a0, uint32_t a1, uint32_t a2, uint32_t a3, uint64_t db, int sd) {
  asm volatile(
    "{\n.reg .pred p;\nsetp.ne.b32 p, %69, 0;\n"
    "wgmma.mma_async.sync.aligned.m64n128k16.f32.bf16.bf16 "
    "{%0, %1, %2, %3, %4, %5, %6, %7, %8, %9, %10, %11, %12, %13, %14, %15, %16, %17, %18, %19, %20, %21, %22, %23, %24, %25, %26, %27, %28, %29, %30, %31, %32, %33, %34, %35, %36, %37, %38, %39, %40, %41, %42, %43, %44, %45, %46, %47, %48, %49, %50, %51, %52, %53, %54, %55, %56, %57, %58, %59, %60, %61, %62, %63}, {%64, %65, %66, %67}, %68, p, 1, 1, %70;\n}\n"
    : "+f"(d[0]), "+f"(d[1]), "+f"(d[2]), "+f"(d[3]), "+f"(d[4]), "+f"(d[5]), "+f"(d[6]), "+f"(d[7]), "+f"(d[8]), "+f"(d[9]), "+f"(d[10]), "+f"(d[11]), "+f"(d[12]), "+f"(d[13]), "+f"(d[14]), "+f"(d[15]), "+f"(d[16]), "+f"(d[17]), "+f"(d[18]), "+f"(d[19]), "+f"(d[20]), "+f"(d[21]), "+f"(d[22]), "+f"(d[23]), "+f"(d[24]), "+f"(d[25]), "+f"(d[26]), "+f"(d[27]), "+f"(d[28]), "+f"(d[29]), "+f"(d[30]), "+f"(d[31]), "+f"(d[32]), "+f"(d[33]), "+f"(d[34]), "+f"(d[35]), "+f"(d[36]), "+f"(d[37]), "+f"(d[38]), "+f"(d[39]), "+f"(d[40]), "+f"(d[41]), "+f"(d[42]), "+f"(d[43]), "+f"(d[44]), "+f"(d[45]), "+f"(d[46]), "+f"(d[47]), "+f"(d[48]), "+f"(d[49]), "+f"(d[50]), "+f"(d[51]), "+f"(d[52]), "+f"(d[53]), "+f"(d[54]), "+f"(d[55]), "+f"(d[56]), "+f"(d[57]), "+f"(d[58]), "+f"(d[59]), "+f"(d[60]), "+f"(d[61]), "+f"(d[62]), "+f"(d[63])
    : "r"(a0), "r"(a1), "r"(a2), "r"(a3), "l"(db), "r"(sd), "n"(TB));
}

__device__ __forceinline__ void wgmma_m64n64_rs_tb(float (&d)[32], const uint32_t (&a)[4], uint64_t db, int sd) {
  asm volatile(
    "{\n.reg .pred p;\nsetp.ne.b32 p, %37, 0;\n"
    "wgmma.mma_async.sync.aligned.m64n64k16.f32.bf16.bf16 "
    "{%0, %1, %2, %3, %4, %5, %6, %7, %8, %9, %10, %11, %12, %13, %14, %15, %16, %17, %18, %19, %20, %21, %22, %23, %24, %25, %26, %27, %28, %29, %30, %31}, {%32, %33, %34, %35}, %36, p, 1, 1, 1;\n}\n"
    : "+f"(d[0]), "+f"(d[1]), "+f"(d[2]), "+f"(d[3]), "+f"(d[4]), "+f"(d[5]), "+f"(d[6]), "+f"(d[7]), "+f"(d[8]), "+f"(d[9]), "+f"(d[10]), "+f"(d[11]), "+f"(d[12]), "+f"(d[13]), "+f"(d[14]), "+f"(d[15]), "+f"(d[16]), "+f"(d[17]), "+f"(d[18]), "+f"(d[19]), "+f"(d[20]), "+f"(d[21]), "+f"(d[22]), "+f"(d[23]), "+f"(d[24]), "+f"(d[25]), "+f"(d[26]), "+f"(d[27]), "+f"(d[28]), "+f"(d[29]), "+f"(d[30]), "+f"(d[31])
    : "r"(a[0]), "r"(a[1]), "r"(a[2]), "r"(a[3]), "l"(db), "r"(sd));
}

__device__ __forceinline__ void wgmma_m64n32_rs_tb(float (&d)[16], const uint32_t (&a)[4], uint64_t db, int sd) {
  asm volatile(
    "{\n.reg .pred p;\nsetp.ne.b32 p, %21, 0;\n"
    "wgmma.mma_async.sync.aligned.m64n32k16.f32.bf16.bf16 "
    "{%0, %1, %2, %3, %4, %5, %6, %7, %8, %9, %10, %11, %12, %13, %14, %15}, {%16, %17, %18, %19}, %20, p, 1, 1, 1;\n}\n"
    : "+f"(d[0]), "+f"(d[1]), "+f"(d[2]), "+f"(d[3]), "+f"(d[4]), "+f"(d[5]), "+f"(d[6]), "+f"(d[7]), "+f"(d[8]), "+f"(d[9]), "+f"(d[10]), "+f"(d[11]), "+f"(d[12]), "+f"(d[13]), "+f"(d[14]), "+f"(d[15])
    : "r"(a[0]), "r"(a[1]), "r"(a[2]), "r"(a[3]), "l"(db), "r"(sd));
}

constexpr int G_STAGES = 4;
constexpr int G_A_BYTES = 128 * 64 * 2;
constexpr int G_B_BYTES = 256 * 64 * 2;
constexpr int G_STAGE_BYTES = G_A_BYTES + G_B_BYTES;
constexpr int G_STG_OFF = G_STAGES * G_STAGE_BYTES;
constexpr int BAR_OFF = G_STG_OFF + 32768 + 2048;
constexpr int SMEM_BYTES = BAR_OFF + 1024;
constexpr int B_GFULL = 0, B_GEMPTY = 32, B_SEEN = 64, B_PFULL = 224;
constexpr int B_KFULL = 80, B_KEMPTY = 96, B_VFULL = 112, B_VEMPTY = 128, B_QFULL = 144, B_QEMPTY = 160,
              B_QDONE = 184;
constexpr int B_CFULL = 192;
constexpr int B_OFREE = 256, B_OFULL = 272, B_OEMPTY = 320, B_OY = 368, B_OY2 = 384, B_OE = 768;
constexpr int B_DEAL = 312, B_DEAL2 = 360, B_LIST = 640, B_PAIR = 504;
constexpr int B_SFULL = 392, B_SFREE = 424, B_PEND = 456, B_SCMD = 512;

#define PHASE_PROLOGUE                                                                \
  uint32_t tid, rt_zero;                                                              \
  asm volatile("mov.u32 %0, %%tid.x;" : "=r"(tid));                                   \
  asm volatile("mov.u32 %0, %%nctaid.y;" : "=r"(rt_zero));                            \
  asm volatile("" : "+r"(smem0));                                                     \
  rt_zero = __shfl_sync(0xffffffffu, rt_zero >> 8, 0);   \
  const uint32_t sbase = __shfl_sync(0xffffffffu, smem0, 0);                          \
  const uint32_t bar = sbase + BAR_OFF;                                               \
  const int wg = __shfl_sync(0xffffffffu, tid >> 7, 0);                               \
  const int warp = (tid >> 5) & 3, lane = tid & 31, wtid = tid & 127;                 \
  (void)rt_zero; (void)bar; (void)warp; (void)lane; (void)wtid;

#define PHASE_GIVEN PHASE_GIVEN_(0)
#define PHASE_GIVEN_(z)                                                               \
  uint32_t tid;                                                                       \
  asm volatile("mov.u32 %0, %%tid.x;" : "=r"(tid));                                   \
  tid |= z;                               \
  const uint32_t bar = sbase + BAR_OFF;                                               \
  const int warp = (tid >> 5) & 3, lane = tid & 31, wtid = tid & 127;

enum { ST_BOX1, ST_BOX2, ST_BOX2Q, ST_BOX2L };
__device__ __forceinline__ void st_cmd(uint32_t bar, int wg, int wtid, uint32_t n, int kind, const void* dst,
                                       uint32_t src, int c0, int c1, int sig, uint32_t lazy = 0) {
  if (wtid == 0) {
    const uint32_t c = bar + B_SCMD + wg * 64 + (n & 1) * 32;
    const uint64_t d = reinterpret_cast<uint64_t>(dst);
    sts128(c, make_uint4(kind, src, c0, c1));
    sts128(c + 16, make_uint4((uint32_t)d, (uint32_t)(d >> 32), sig, lazy));
  }
}
__device__ __forceinline__ void st_go(uint32_t bar, int wg, int wtid, uint32_t n) {
  fence_proxy_async();
  __syncwarp();
  mbar_arrive_if(bar + B_SFULL + wg * 16 + (n & 1) * 8, (wtid & 31) == 0);
}
__device__ __forceinline__ void st_post(uint32_t bar, int wg, int wtid, uint32_t n, int kind, const void* dst,
                                        uint32_t src, int c0, int c1, int sig, uint32_t lazy = 0) {
  st_cmd(bar, wg, wtid, n, kind, dst, src, c0, c1, sig, lazy);
  st_go(bar, wg, wtid, n);
}
__device__ __forceinline__ void st_wait(uint32_t bar, int wg, uint32_t n) {
  const uint32_t b = bar + B_SFREE + wg * 16 + (n & 1) * 8;
  if (!mbar_try(b, ~(n >> 1) & 1)) mbar_wait(b, ~(n >> 1) & 1);
}
__device__ __forceinline__ void note(uint32_t bar, uint32_t cnt) {
  asm volatile("red.release.cta.shared.add.u32 [%0], 1;" ::"r"(bar + B_PEND + 4 * cnt) : "memory");
}
#define LAZY_NS 250
#define DEAL_NS 400
#define DEAL_NS2 1250
constexpr uint32_t C_NONE = 0x10000;
__device__ __forceinline__ void deal(uint32_t bar, uint32_t r, uint32_t t, uint32_t own) {
  uint64_t p;
  uint32_t spins = 0;
  while (true) {
    asm volatile("ld.relaxed.gpu.global.u64 %0, [%1];" : "=l"(p) : "l"(g_slot + 127 - r) : "memory");
    if (p || ++spins > (1u << 18)) break;
    __nanosleep(100);
  }
  const uint32_t pc = (uint32_t)p;
  int dt = (uint32_t)(p >> 32) - t;
  if (r >= 64) {
    sts128(bar + B_LIST, make_uint4(-dt > DEAL_NS2 ? C_NONE : own - 16, -dt > DEAL_NS ? C_NONE : own, C_NONE, C_NONE));
    mbar_arrive(bar + B_DEAL);
    dt = 0;
  }
  sts128(bar + B_LIST + 16, make_uint4(dt > DEAL_NS ? pc : C_NONE, dt > DEAL_NS2 ? pc - 16 : C_NONE, C_NONE, C_NONE));
  mbar_arrive(bar + B_DEAL2);
}
__device__ __forceinline__ void store_agent(uint32_t bar, int wg, uint32_t last_ch, uint32_t n_end) {
  mbar_arrive(bar + B_SFREE + wg * 16);
  mbar_arrive(bar + B_SFREE + wg * 16 + 8);
  bool more = true;
  for (uint32_t n = 0; n < n_end && more; n++) {
    mbar_wait_sleep(bar + B_SFULL + wg * 16 + (n & 1) * 8, (n >> 1) & 1);
    const uint4 c = lds128(bar + B_SCMD + wg * 64 + (n & 1) * 32);
    const uint4 d = lds128(bar + B_SCMD + wg * 64 + (n & 1) * 32 + 16);
    uint32_t t;
    asm volatile("mov.u32 %0, %%globaltimer_lo;" : "=r"(t));
    uint32_t r = 0, tp = t;
    if (c.x == ST_BOX2L && last_ch) {
      mbar_expect_tx(bar + B_PAIR, 4);
      asm volatile(
          "{\n.reg .b32 ra;\nmapa.shared::cluster.u32 ra, %0, %1;\n"
          "st.async.weak.shared::cluster.mbarrier::complete_tx::bytes.u32 [ra + 224], %2, [ra];\n}\n" ::"r"(bar + B_PAIR),
          "r"(~blockIdx.x & 1), "r"(t)
          : "memory");
      mbar_wait_sleep(bar + B_PAIR, 0);
      r = atomicAdd(g_cnt + CNT_RANK * 32, 1u) & 127;
      asm volatile("ld.shared.u32 %0, [%1];" : "=r"(tp) : "r"(bar + B_PAIR + 224) : "memory");
      if ((int)(tp - t) < 0) tp = t;
      asm volatile("st.relaxed.gpu.global.u64 [%0], %1;" ::"l"(g_slot + r), "l"(((uint64_t)tp << 32) | last_ch) : "memory");
      if (r < 64) {
        sts128(bar + B_LIST, make_uint4(last_ch - 16, last_ch, C_NONE, C_NONE));
        mbar_arrive(bar + B_DEAL);
      } else {
        deal(bar, r, tp, last_ch);
      }
    }
    for (uint32_t t1 = t; d.w && t1 - t < (2 * d.w + wg) * LAZY_NS;) {
      __nanosleep(200);
      asm volatile("mov.u32 %0, %%globaltimer_lo;" : "=r"(t1));
    }
    const CUtensorMap* dst = reinterpret_cast<const CUtensorMap*>((uint64_t)d.x | ((uint64_t)d.y << 32));
    tma_store_2d(dst, c.y, c.z, c.w);
    if (c.x >= ST_BOX2) tma_store_2d(dst, c.y + 8192, c.z + 64, c.w);
    tma_store_commit();
    tma_store_wait_read<0>();
    mbar_arrive(bar + B_SFREE + wg * 16 + (n & 1) * 8);
    if (c.x == ST_BOX2L) mbar_arrive(bar + B_OFREE + 8 * wg);
    if ((int)d.z >= 0) {
      tma_store_wait<0>();
      if (d.z == 0) { TD(6) }
      asm volatile("fence.proxy.async.global;" ::: "memory");
      if (c.x == ST_BOX2Q) mbar_arrive(bar + B_QDONE);
      else note(bar, d.z);
      if (c.x == ST_BOX2L) {
        note(bar, CNT_DONE);
        more = false;
        if (last_ch && r < 64) deal(bar, r, tp, last_ch);
      }
    }
  }
  if (more) note(bar, CNT_DONE);
}

struct Maps {
  const bf16 *shift_k, *x, *gate_w, *ssm_k, *ssm_D;
  uint8_t id[128][4];
  CUtensorMap a[2];
  CUtensorMap b[3];
  CUtensorMap c[3];
  CUtensorMap bk, bv;
  CUtensorMap q, k, v, o;
  CUtensorMap oa, ob, oc;
  CUtensorMap y, xs;
  CUtensorMap cu, ch;
};

constexpr int P_SLOT = 67 * 128, P_V = 35 * 128;
__device__ __forceinline__ void ldsm4t(uint32_t (&r)[4], uint32_t a) {
  asm volatile("ldmatrix.sync.aligned.m8n8.x4.trans.shared.b16 {%0, %1, %2, %3}, [%4];"
               : "=r"(r[0]), "=r"(r[1]), "=r"(r[2]), "=r"(r[3])
               : "r"(a));
}
__device__ __forceinline__ uint32_t fma_bf2(uint32_t a, uint32_t b, uint32_t c) {
  uint32_t r;
  asm("fma.rn.bf16x2 %0, %1, %2, %3;" : "=r"(r) : "r"(a), "r"(b), "r"(c));
  return r;
}
__device__ __forceinline__ void prep_agent(const Maps& maps, uint32_t sbase, int w, int lane) {
  const uint32_t bar = sbase + BAR_OFF, pb = bar + B_PFULL + w * 16;
  const int d0 = (blockIdx.x >> 4) * 128, t0 = (blockIdx.x & 15) * 128 + w * 64;
  mbar_wait_sleep(bar + B_GFULL + 8 * (G_STAGES - 1), 0);
#pragma unroll 1
  for (int i = -1; i < 4; i++) {
    GA(82 + 2 * i)
    const int dc = d0 + (~i & 2) * 32;
    const uint2 ta = __ldg(reinterpret_cast<const uint2*>(maps.shift_k) + dc + lane);
    const uint2 tb = __ldg(reinterpret_cast<const uint2*>(maps.shift_k) + dc + lane + 32);
    if (i >= 0) mbar_wait_sleep(pb + (i & 1) * 8, i >> 1);
    GA(83 + 2 * i)
    const uint32_t so = sbase + G_STG_OFF + (w * 2 + (i & 1)) * P_SLOT;
    if (i < 3 && elect_one()) {
      const uint32_t b = pb + (~i & 1) * 8, dst = so + (i & 1 ? -P_SLOT : P_SLOT);
      mbar_expect_tx(b, P_SLOT);
      const int dn = d0 + (i < 1 ? 64 : 0), tn = t0 + 32 * (~i & 1);
      const uint64_t pol = policy_evict_first();
      tma_load_2d_hint(dst, &maps.bk, b, dn, tn - 3, pol);
      tma_load_2d_hint(dst + P_V, &maps.bv, b, dn, tn, pol);
    }
    if (i < 0) continue;
    uint32_t ak[4];
#pragma unroll
    for (int r = 0; r < 4; r++) {
      const uint32_t a = so / 128 + r + 4 * (lane & 6) + (((lane >> 2) ^ lane) & 6) + (lane & 1);
      ak[r] = a * 128 + (a & 7) * 16;
    }
    bf16* dst = g_kvT + (size_t)(dc + (lane >> 2)) * S_LEN + t0 + ((lane & 3) + 4 * (i & 1)) * 8;
#pragma unroll 1
    for (int cg = 0; cg < 128; cg += 16) {
      uint32_t k[4][4], v[4];
      const uint32_t t01 = __shfl_sync(0xffffffffu, cg < 64 ? ta.x : tb.x, cg / 2 + (lane >> 2));
      const uint32_t t23 = __shfl_sync(0xffffffffu, cg < 64 ? ta.y : tb.y, cg / 2 + (lane >> 2));
#pragma unroll
      for (int r = 0; r < 4; r++) ldsm4t(k[r], ak[r] ^ cg);
      ldsm4t(v, (ak[3] ^ cg) + 4096);
      const uint32_t w0 = __byte_perm(t01, 0, 0x1010), w1 = __byte_perm(t01, 0, 0x3232);
      const uint32_t w2 = __byte_perm(t23, 0, 0x1010), w3 = __byte_perm(t23, 0, 0x3232);
#pragma unroll
      for (int j = 0; j < 4; j++)
        v[j] = mul_bf2(fma_bf2(k[3][j], w0, fma_bf2(k[2][j], w1, fma_bf2(k[1][j], w2, mul_bf2(k[0][j], w3)))), v[j]);
      const bool s1 = lane & 1, s2 = lane & 2;
      const uint32_t a0 = s1 ? v[1] : v[0], a1 = s1 ? v[0] : v[1], a2 = s1 ? v[3] : v[2], a3 = s1 ? v[2] : v[3];
      *reinterpret_cast<uint4*>(dst) = make_uint4(s2 ? a2 : a0, s2 ? a3 : a1, s2 ? a0 : a2, s2 ? a1 : a3);
      dst += 8 * S_LEN;
    }
    fence_proxy_async();
    __syncwarp();
    if (lane == 0 && (i & 1)) note(bar, i == 1 ? CNT_PREP1 : CNT_PREP);
  }
  GA(90)
  __syncwarp();
  GA(91)
}

__device__ __forceinline__ void qkv_tile(const Maps& maps, int it, int& which, int& m_tile, int& n_tile) {
  const bool q = it == 0 || it >= 5;
  const int b = maps.id[blockIdx.x][it >= 5];
  which = q ? 0 : 2 - (it & 1);
  m_tile = b & 15;
  n_tile = (b >> 4) * 2 + ((0x19 >> it) & 1);
}

constexpr int G_NTILES = 6;
__device__ __forceinline__ uint32_t qkv_flip(int it) { return ((0x0b >> it) & 1) * 3; }
__device__ __forceinline__ void qkv_producer(const Maps& maps, uint32_t sbase, bool first) {
  const uint32_t bar = sbase + BAR_OFF;
  uint32_t stage = 0, phase = 0;
#pragma unroll 1
  for (int it = 0; it < (first ? 1 : G_NTILES); it++) {
    int which, m_tile, n_tile;
    qkv_tile(maps, it, which, m_tile, n_tile);
    const CUtensorMap* ma = &maps.a[which == 0 ? 0 : 1];
    const CUtensorMap* mb = &maps.b[which];
    const int nk = first ? G_STAGES : which == 0 ? 16 : 8;
#pragma unroll 1
    for (int kt = (it == 0 && !first) ? G_STAGES : 0; kt < nk; kt++) {
      if (!first) mbar_wait_sleep(bar + B_GEMPTY + 8 * stage, phase);
      const uint32_t fb = bar + B_GFULL + 8 * stage;
      const uint32_t sa = sbase + stage * G_STAGE_BYTES;
      const int k0 = (kt ^ ((0x14 >> it) & 1) * 7) * 64;
      const bool keep = ((0x1c >> it) & 1) && kt < G_STAGES;
      mbar_expect_tx(fb, keep ? G_B_BYTES : G_STAGE_BYTES);
      if (!keep) tma_load_2d(sbase + (stage ^ qkv_flip(it)) * G_STAGE_BYTES, ma, fb, k0, m_tile * 128);
      tma_load_3d(sa + G_A_BYTES, mb, fb, 0, k0, n_tile * 4);
      if (++stage == G_STAGES) { stage = 0; phase ^= 1; }
      {
        const int b = maps.id[blockIdx.x][1];
        if (it == 2 && kt == (b & 7)) {
          for (int i = 0; i < 2; i++)
            asm volatile("cp.async.bulk.prefetch.tensor.2d.L2.global.tile [%0, {%1, %2}];" ::"l"(&maps.a[0]),
                         "r"((b >> 4) * 128 + i * 64), "r"((b & 15) * 128)
                         : "memory");
          asm volatile("cp.async.bulk.prefetch.tensor.3d.L2.global.tile [%0, {%1, %2, %3}];" ::"l"(&maps.b[1 + ((b >> 3) & 1)]),
                       "r"(0), "r"((b & 7) * 64), "r"((b >> 4) * 8 + 4)
                       : "memory");
        }
        if (it == 3 && kt == (b & 7))
          asm volatile("cp.async.bulk.prefetch.tensor.3d.L2.global.tile [%0, {%1, %2, %3}];" ::"l"(&maps.b[0]), "r"(0),
                       "r"((b & 15) * 64), "r"((b >> 4) * 8)
                       : "memory");
      }
    }
  }
}

__device__ __forceinline__ void gate_rows(const Maps& maps, uint32_t bar, int lane) {
  if (lane == 0) {
    uint32_t v = 0, w;
#pragma unroll 1
    for (uint32_t spins = 0; v < 2 && spins < (1u << 20); spins++, v += w) {
      asm volatile("atom.acquire.cta.shared.exch.b32 %0, [%1], 0;" : "=r"(w) : "r"(bar + B_PEND + 4 * CNT_PREP1) : "memory");
      if (!w) __nanosleep(100);
    }
    cnt_signal_release(CNT_PREP1, v);
  }
  __syncwarp();
  const uint4 *x = reinterpret_cast<const uint4*>(maps.x), *wp = reinterpret_cast<const uint4*>(maps.gate_w);
  float mine = 0.f;
#pragma unroll 1
  for (int r = 0; r < 16; r++) {
    float sum = 0.f;
#pragma unroll
    for (int i = 0; i < 4; i++) {
      const uint4 xv = __ldcg(x + (blockIdx.x * 16 + r) * (DM / 8) + i * 32 + lane), wv = __ldg(wp + i * 32 + lane);
      const uint32_t p0 = mul_bf2(xv.x, wv.x), p1 = mul_bf2(xv.y, wv.y), p2 = mul_bf2(xv.z, wv.z), p3 = mul_bf2(xv.w, wv.w);
      sum += ((bf_lo(p0) + bf_hi(p0)) + (bf_lo(p1) + bf_hi(p1))) + ((bf_lo(p2) + bf_hi(p2)) + (bf_lo(p3) + bf_hi(p3)));
    }
#pragma unroll
    for (int off = 16; off; off >>= 1) sum += __shfl_xor_sync(0xffffffffu, sum, off);
    if (lane == r) mine = sum;
  }
  if (lane < 16) g_gate[blockIdx.x * 16 + lane] = bf16_round(rcp(1.0f + __expf(-bf16_round(mine))));
  __syncwarp();
  if (lane == 0) note(bar, CNT_PREP);
  __syncwarp();
}

__device__ __forceinline__ uint32_t seen_bar(uint32_t item) { return B_SEEN + ((0x700800u >> (8 * item)) & 255); }
__device__ __noinline__ void publisher(uint32_t bar, int lane, uint32_t nsrc, uint32_t item, uint32_t mine) {
  uint32_t done = 0, tot = 0;
#pragma unroll 1
  for (uint32_t spins = 0; (done < nsrc || item < 3) && spins < (1u << 20); spins++) {
    const uint32_t cnt = item ? CNT_CTX - 1 + item : CNT_KV + 1;
    if (item < 3 && __shfl_sync(0xffffffffu, tot, cnt) >= mine >> !item) {
      uint32_t v;
      asm volatile("ld.acquire.gpu.global.u32 %0, [%1];" : "=r"(v) : "l"(g_cnt + (lane ? cnt : CNT_PREP) * 32) : "memory");
      if (__all_sync(0xffffffffu, v >= (lane ? 512 >> !item : 384))) {
        asm volatile("fence.proxy.async.global;" ::: "memory");
        mbar_arrive_if(bar + seen_bar(item), lane == 0);
        item++;
      }
    }
    uint32_t v = 0;
    if (lane < CNT_N)
      asm volatile("atom.acquire.cta.shared.exch.b32 %0, [%1], 0;" : "=r"(v) : "r"(bar + B_PEND + 4 * lane) : "memory");
    done += __shfl_sync(0xffffffffu, v, CNT_DONE);
    if (lane == CNT_DONE) v = 0;
    if (done == nsrc && lane < CNT_DONE) {
      uint32_t w;
      asm volatile("atom.acquire.cta.shared.exch.b32 %0, [%1], 0;" : "=r"(w) : "r"(bar + B_PEND + 4 * lane) : "memory");
      v += w;
    }
    if (v && lane == 0) { TD(0) }
    if (v) cnt_signal_release(lane, v);
    tot += v;
    if (v && lane == 0) { TD(1) }
    if (!__any_sync(0xffffffffu, v != 0)) __nanosleep(item == 1 ? 1000 : 200);
  }
  __threadfence();
  __syncwarp();
}

constexpr float K_SCALE = 0.08838834764831845f * 1.4426950408889634f;
__device__ __forceinline__ uint32_t qkv_consumer(const Maps& maps, const uint32_t sbase, const int wg, bool fused,
                                                 uint32_t (&q)[32], float (&rest)[64], uint32_t rt_zero) {
  PHASE_GIVEN_(rt_zero)
  constexpr int NTILES = G_NTILES;
  float acc[128];
  const uint32_t stg = sbase + G_STG_OFF + wg * 18432;
  const int st_row = warp * 16 + (lane & 7) + ((lane >> 3) & 1) * 8;
  const int st_cb = lane >> 4;
  uint32_t pend[64];
  const CUtensorMap* pend_map = nullptr;
  int pend_c0 = 0, pend_c1 = 0;
  uint32_t sn = 0;
  uint32_t st_a[4];
#pragma unroll
  for (int jp = 0; jp < 4; jp++) {
    st_a[jp] = stg + st_row * 128 + (((jp * 2 + st_cb) ^ (st_row & 7)) << 4);
    asm volatile("" : "+r"(st_a[jp]));
  }
  auto put_box = [&](uint32_t off, const uint32_t* v) {
#pragma unroll
    for (int jp = 0; jp < 4; jp++) stmatrix_x4(st_a[jp] + off, v[jp * 4], v[jp * 4 + 1], v[jp * 4 + 2], v[jp * 4 + 3]);
  };
  GT(gti++)
  const int hf = wg ^ 1;
  const uint64_t da0 = make_desc(sbase + hf * 8192, 16, 1024, DESC_SW128);
  const uint64_t db0 = make_desc(sbase + G_A_BYTES, 8192, 1024, DESC_SW128);
  uint32_t g = 0, oa = 3 * (G_STAGE_BYTES / 16), ob = 0;
  bool go = false;
  mbar_wait(bar + B_GFULL, 0);
  uint32_t gend = 16, when = 0;
#pragma unroll 1
  for (int it = 0;; it++) {
    bool more = false;
#pragma unroll 1
    do {
      GT(gti++)
      wgmma_fence();
#pragma unroll
      for (int kk = 0; kk < 4; kk++)
        wgmma_m64n256_ss_tb(acc, desc_add(da0, oa + kk * 2), desc_add(db0, ob + kk * 128), kk || more);
      wgmma_commit();
      if (go) st_go(bar, wg, wtid, sn - 1);
      g++;
      if (g + wg * 64 == 63) named_bar_arrive(6, 256);
      const uint32_t full = (bar + B_GFULL) + 8 * (g & 3);
      const bool here = mbar_test(full, (g >> 2) & 1) || g >= 64;
      oa = ((g & 3) ^ ((0x17 >> (g >> 3)) & 1) * 3) * (G_STAGE_BYTES / 16);
      ob = (g & 3) * (G_STAGE_BYTES / 16);
      go = when & 1;
      when >>= 1;
      if (go) {
        const int c = sn & 3;
        st_wait(bar, wg, sn - 2);
        st_cmd(bar, wg, wtid, sn, ST_BOX1, pend_map, stg + (c & 1) * 8192, pend_c0 + c * 64, pend_c1,
               (c == 3 && it > 1) ? CNT_KV + (it > 4) : -1);
        switch (c) {
          case 0: put_box(0, pend); break;
          case 1: put_box(8192, pend + 16); break;
          case 2: put_box(0, pend + 32); break;
          default: put_box(8192, pend + 48); break;
        }
        sn++;
      }
      if (it < NTILES) {
        wgmma_wait<1>();
        mbar_arrive_if((bar + B_GEMPTY) + 8 * ((g + 2) & 3), wtid == 32 && more);
        if (wg && g == 62) named_bar_sync(6, 256);
        if (!here) mbar_wait(full, (g >> 2) & 1);
      }
      more = true;
    } while (g != gend);
    wgmma_wait<0>();
    fence_regs(acc);
    GT(gti++)
    mbar_arrive_if((bar + B_GEMPTY) + 8 * 3, wtid == 32);
    int which, m_tile, n_tile;
    qkv_tile(maps, it, which, m_tile, n_tile);
    if (it == NTILES - fused) break;
    if (which == 1) {
#pragma unroll
      for (int j = 0; j < 128; j++) acc[j] *= K_SCALE;
    }
#pragma unroll
    for (int j = 0; j < 64; j++) pend[j] = pack_bf16(acc[2 * j], acc[2 * j + 1]);
    pend_map = &maps.c[which];
    pend_c0 = n_tile * 256;
    pend_c1 = m_tile * 128 + hf * 64;
    gend += it == 4 ? 16 : 8;
    when = (it == 4 ? 0x922 : 0x55) << wg;
  }
  if (go) st_go(bar, wg, wtid, sn - 1);
#pragma unroll
  for (int j = 0; j < 32; j++) q[j] = pack_bf16(acc[2 * j], acc[2 * j + 1]);
#pragma unroll
  for (int j = 0; j < 64; j++) rest[j] = acc[64 + j];
  GT(gti++)
  return sn;
}

constexpr int A_TILE = 128 * 128 * 2;
constexpr int A_K_OFF = 0, A_Q_OFF = A_TILE, A_V_OFF = 3 * A_TILE;
constexpr int A_O_OFF = 6 * A_TILE;
constexpr int A_ITEMS = NH * (S_LEN / 128);

constexpr uint32_t A_ORDER = 0x3120, A_STEPS = 34;
__device__ __forceinline__ int item_m(uint32_t it) { return it & 15; }
__device__ __forceinline__ int item_h(uint32_t it) { return it >> 4; }

constexpr int C_V = 16384, C_MAT = 24576;
constexpr float C_ALPHA = 0.07874506561842957f;
__device__ __forceinline__ void sincos_turn(int p, float inv, float& c, float& s) {
  const float a = (float)p * (inv * 6.283185307179586f);
  asm("cos.approx.ftz.f32 %0, %1;" : "=f"(c) : "f"(a));
  asm("sin.approx.ftz.f32 %0, %1;" : "=f"(s) : "f"(a));
}

__device__ __forceinline__ uint32_t head_of(const Maps& maps, uint32_t r) { return (maps.id[blockIdx.x & 127][3] >> (2 * r)) & 3; }
__device__ __forceinline__ uint32_t item_at(const Maps& maps, uint32_t h) {
  const uint32_t b = maps.id[blockIdx.x & 127][1];
  return (b >> 4) * 64 + h * 16 + ((b ^ ((h >> 1) * 15)) & 15);
}
__device__ __forceinline__ uint32_t item_of(const Maps& maps, uint32_t r) { return item_at(maps, head_of(maps, r)); }

#define PACE 250
#define SPACE 0
#define LCHK 1
#define XMASK 3
#define XFIRST 12
#define C_SIDE 64
__device__ __forceinline__ uint32_t conv_first(const Maps& maps) {
  const uint32_t b = maps.id[blockIdx.x & 127][1];
  return (b >> 4) * 128 + ((b + 15) & 15);
}

__device__ __forceinline__ void conv_consumer(const Maps& maps, uint32_t smem0, uint32_t first, uint32_t step,
                                              uint32_t end, bool pp, bool dealt) {
  PHASE_PROLOGUE
  const uint32_t in_full = bar + B_CFULL + wg * 16;
  const uint32_t ca = sbase + (wg ? A_V_OFF + A_TILE : A_Q_OFF);
  const int w = __shfl_sync(0xffffffffu, warp, 0), g = lane >> 2, c = lane & 3;
  auto fetch = [&](uint32_t ch, uint32_t n) {
    if (w == 2 && ch < C_NONE) {
      if (elect_one()) {
        const uint32_t b = in_full + (n & 1) * 8, d = ca + (n & 1) * 8192;
        const uint64_t pol = policy_evict_first();
        mbar_expect_tx(b, 8192);
        tma_load_2d_hint(d, &maps.cu, b, 0, ch * 64, pol);
        tma_load_2d_hint(d + 4096, &maps.ch, b, 0, ch * 64, pol);
      }
    }
  };
  if (wtid == 96 && wg) { TD(15) }
  uint32_t f1[8][4];
  float tt[16], ts[16];
  uint32_t cc[4], ss[4];
#pragma unroll
  for (int i = 0; i < 16; i++) {
    const int k = 2 * (16 * w + g + 8 * (i & 1)) + 1, n = 2 * (8 * (i >> 1) + 2 * c) + 1;
    float c0, s0, c1, s1;
    sincos_turn(((k * n) << 23) >> 23, 1.f / 512, c0, s0);
    sincos_turn(((k * n + 2 * k) << 23) >> 23, 1.f / 512, c1, s1);
    f1[i >> 2][i & 3] = pack_bf16(c0 * C_ALPHA, c1 * C_ALPHA);
    f1[4 + (i >> 2)][i & 3] = pack_bf16(s0 * -C_ALPHA, s1 * -C_ALPHA);
  }
#pragma unroll
  for (int i = 0; i < 16; i++) {
    const int k = 2 * (16 * w + g + 8 * ((i >> 1) & 1)) + 1, n = 16 - (8 * (i >> 2) + 2 * c + (i & 1));
    float cs;
    sincos_turn(k * n, 1.f / 8192, cs, ts[i]);
    tt[i] = ts[i] * rcp(1.f + cs);
  }
#pragma unroll
  for (int j = 0; j < 4; j++) {
    const int k = 8 * w + g, n = 8 * c + 2 * j;
    float c0, s0, c1, s1;
    sincos_turn((int8_t)(k * n * 8), 1.f / 256, c0, s0);
    sincos_turn((int8_t)((k * n + k) * 8), 1.f / 256, c1, s1);
    cc[j] = pack_bf16(c0, c1);
    ss[j] = pack_bf16(s0, s1);
  }
  named_bar_sync(3, 256);
  fetch(first, 0);
  fetch(first + step, 1);
  const uint32_t va = ca + g * 64 + ((c ^ (g >> 1)) << 4);
  {
    const uint32_t a = va + C_MAT + w * 512, m = 0x80008000u;
    sts128(a, make_uint4(cc[0], cc[1], cc[2], cc[3]));
    sts128(a + 2048, make_uint4(ss[0], ss[1], ss[2], ss[3]));
    sts128(a + 4096, make_uint4(ss[0] ^ m, ss[1] ^ m, ss[2] ^ m, ss[3] ^ m));
    sts128(a + 6144, make_uint4(cc[0], cc[1], cc[2], cc[3]));
  }
  fence_proxy_async();
  named_bar_sync(1 + wg, 128);
  constexpr uint64_t DHI = (2ull << 62) | ((uint64_t)(512 >> 4) << 32);
  const uint32_t d0 = (uint32_t)make_desc(ca, 4096, 0, 0);
  float a5[16];
  uint4* const yb = reinterpret_cast<uint4*>(g_y2T) + (16 * w + g) * 4 + c;
  auto issue5 = [&]() {
#pragma unroll
    for (int ks = 0; ks < 8; ks++) wgmma_m64n32_rs_tb(a5, f1[ks], DHI | (d0 + (C_V >> 4) + ks * 64), ks != 0);
    wgmma_commit();
  };
  auto finish = [&](uint32_t ch, bool on) {
    fence_regs(a5);
    uint4* y = yb + (size_t)ch * 256;
    if (on) {
      y[0] = make_uint4(pack_bf16(a5[0], a5[1]), pack_bf16(a5[4], a5[5]), pack_bf16(a5[8], a5[9]), pack_bf16(a5[12], a5[13]));
      y[32] = make_uint4(pack_bf16(a5[2], a5[3]), pack_bf16(a5[6], a5[7]), pack_bf16(a5[10], a5[11]), pack_bf16(a5[14], a5[15]));
    }
  };
  auto dft32 = [&](float (&d)[32], const float* re, const float* im) {
    uint32_t a[4][4];
#pragma unroll
    for (int i = 0; i < 8; i++) {
      a[i >> 2][i & 3] = pack_bf16(re[2 * i], re[2 * i + 1]);
      a[2 + (i >> 2)][i & 3] = pack_bf16(im[2 * i], im[2 * i + 1]);
    }
    wgmma_fence();
#pragma unroll
    for (int ks = 0; ks < 4; ks++) wgmma_m64n64_rs_tb(d, a[ks], DHI | (d0 + (C_MAT >> 4) + ks * 64), ks != 0);
    wgmma_commit();
  };
  auto rot = [&](float* x, float* y) {
#pragma unroll
    for (int i = 0; i < 16; i++) {
      x[i] = fmaf(-tt[i], y[i], x[i]);
      y[i] = fmaf(ts[i], x[i], y[i]);
      x[i] = fmaf(-tt[i], y[i], x[i]);
    }
  };
  auto load_d = [&](uint32_t ch) {
    return __ldg(reinterpret_cast<const unsigned short*>(maps.ssm_D) + ((ch & (DM - 1)) | (lane & rt_zero)));
  };
  uint32_t dn = load_d(first);
  uint32_t n = 0, prev = 0, ch = first, next = first + step;
#pragma unroll 1
  for (; ch < C_NONE; n++) {
    CT(0)
    float a1[2][32], a2[2][32], a4[32];
    const float dsk = c ? 0.f : __uint_as_float(dn << 16) * C_ALPHA;
    dn = load_d(next);
    uint32_t next2 = next + step < end ? next + step : C_NONE;
    mbar_wait(in_full + (n & 1) * 8, (n >> 1) & 1);
    if (pp) named_bar_sync(4 + wg, 256);
    CT(1)
    wgmma_fence();
#pragma unroll
    for (int ks = 0; ks < 8; ks++)
      wgmma_m64n64_rs_tb(a1[ks >> 2], f1[ks], DHI | (d0 + (n & 1) * 512 + (ks & 3) * 64), (ks & 3) != 0);
    wgmma_commit();
    issue5();
    wgmma_wait<1>();
    fence_regs(a1[0]);
    fence_regs(a1[1]);
    CT(2)
    rot(a1[0], a1[1]);
    dft32(a2[0], a1[0], a1[1]);
    rot(a1[0] + 16, a1[1] + 16);
    a1[0][16] += dsk;
    a1[0][18] += dsk;
    dft32(a2[1], a1[0] + 16, a1[1] + 16);
    CT(3)
    wgmma_wait<2>();
    finish(prev, n > 0);
    wgmma_wait<0>();
    fence_regs(a2[0]);
    fence_regs(a2[1]);
    CT(4)
    if (pp) named_bar_arrive(5 - wg, 256);
    float re[16], im[16];
#pragma unroll
    for (int i = 0; i < 16; i++) {
      re[i] = a2[0][i] * a2[1][i] - a2[0][16 + i] * a2[1][16 + i];
      im[i] = a2[0][i] * a2[1][16 + i] + a2[0][16 + i] * a2[1][i];
    }
    dft32(a4, im, re);
    if (dealt) {
      mbar_wait(bar + (n < 2 ? B_DEAL : B_DEAL2), 0);
      asm volatile("ld.shared.u32 %0, [%1];" : "=r"(next2) : "r"(bar + B_LIST + 4 * n + (n < 2 ? 0 : 8)));
    }
    wgmma_wait<0>();
    fence_regs(a4);
    CT(5)
    rot(a4, a4 + 16);
#pragma unroll
    for (int i = 0; i < 4; i++) {
      const float* x = a4 + 16 - 16 * (i >> 1) + 2 * (i & 1);
      sts128(va + C_V + w * 1024 + (i >> 1) * 4096 + (i & 1) * 512,
             make_uint4(pack_bf16(x[0], x[1]), pack_bf16(x[4], x[5]), pack_bf16(x[8], x[9]), pack_bf16(x[12], x[13])));
    }
    CT(6)
    fence_proxy_async();
    named_bar_sync(1 + wg, 128);
    fetch(next2, n);
    if (wtid == 96 && n > 0) note(bar, CNT_Y2 + ((prev & 112) == 112));
    prev = ch;
    ch = next;
    next = next2;
    CT(7)
  }
  wgmma_fence();
  issue5();
  wgmma_wait<0>();
  finish(prev, (dn | ~rt_zero) != 0);
  named_bar_sync(1 + wg, 128);
  if (wtid == 96 && wg) { TD(8) }
  if (wtid == 96) cnt_signal_release(CNT_Y2 + ((prev & 112) == 112), 1);
  if (wtid == 64) note(bar, CNT_DONE);
  if (wtid == 96 && wg) { TD(9) }
}

__device__ __forceinline__ void attn_producer(const Maps& maps, uint32_t sbase, bool after_qkv, bool to_out,
                                              bool dry) {
  const uint32_t bar = sbase + BAR_OFF;
  const uint32_t q_full = bar + B_QFULL, q_empty = bar + B_QEMPTY;
  const uint32_t k_full = bar + B_KFULL, k_empty = bar + B_KEMPTY, v_full = bar + B_VFULL, v_empty = bar + B_VEMPTY;
  int ndrained = after_qkv ? 0 : G_STAGES;
  auto wait = [&](uint32_t b, uint32_t par) {
    if (!dry) mbar_wait_sleep(b, par);
  };
  auto drained = [&](int upto) {
#pragma unroll 1
    for (; ndrained <= upto; ndrained++) wait(bar + B_GEMPTY + 8 * ndrained, 1);
  };
  uint32_t st = 0, ph = 1, vs = 0, vp = 1;
  int pend_j = -1, pend_h = 0;
  int round = -1, m = -1, h = 0;
  bool last = false;
#pragma unroll 1
  for (;; round++) {
    uint32_t nitem = 0;
    const int tpost = m >= 3 ? m - 1 : m;
#pragma unroll 1
    for (int t = m < 0 ? -1 : 0; t <= m; t++) {
      const int j = (t < m && (h & 2)) ? m - 1 - t : t;
      if (t >= 0) {
        drained(st);
        wait(k_empty + 8 * st, ph);
        if (!dry) {
          mbar_expect_tx(k_full + 8 * st, A_TILE);
          tma_load_3d(sbase + A_K_OFF + st * 2 * A_TILE, &maps.k, k_full + 8 * st, 0, j * 128, h * 2);
        }
        if (++st == 2) { st = 0; ph ^= 1; }
      }
      if (pend_j >= 0) {
        drained(2 + vs);
        if ((pend_h & 2) && after_qkv) wait(bar + seen_bar(0), 0);
        wait(v_empty + 8 * vs, vp);
        if (!dry) {
          mbar_expect_tx(v_full + 8 * vs, A_TILE);
          tma_load_3d(sbase + A_V_OFF + vs * A_TILE, &maps.v, v_full + 8 * vs, 0, pend_j * 128, pend_h * 2);
        }
        if (++vs == 2) { vs = 0; vp ^= 1; }
      }
      pend_j = j;
      pend_h = h;
      if (t == tpost && !last) {
        nitem = dry ? 1 : item_of(maps, round + 1);
        if (round == (dry ? 0 : 3) || blockIdx.x >= 128) {
          nitem = A_ITEMS;
          if (!to_out) cnt_wait(CNT_PREP1, dry ? 0 : 256);
          if (to_out) {
            wait(bar + seen_bar(1), 0);
            asm volatile("cp.async.bulk.prefetch.L2.global [%0], 4096;" ::"l"(maps.ssm_k + (size_t)conv_first(maps) * S_LEN));
            if (!dry)
              asm volatile("cp.async.bulk.prefetch.L2.global [%0], 4096;" ::"l"(g_kvT + (size_t)conv_first(maps) * S_LEN));
          }
        }
        const uint32_t qs = (round + 1) & 1;
        wait(q_empty + 8 * qs, (((round + 1) >> 1) & 1) ^ 1);
        if (round == 1 && after_qkv) wait(bar + B_QDONE, 0);
        if (round < 0 && after_qkv) {
          if (!dry) { TD(2) }
          cnt_wait(CNT_KV, dry ? 0 : 768);
          if (!dry) { TD(3) }
        }
        if (nitem >= A_ITEMS || (round < 0 && after_qkv && !dry)) {
          if (!dry) mbar_arrive(q_full + 8 * qs);
        } else {
          drained(1 + 2 * qs);
          if (!dry) {
            mbar_expect_tx(q_full + 8 * qs, A_TILE);
            tma_load_3d_hint(sbase + A_Q_OFF + qs * 4 * A_TILE, &maps.q, q_full + 8 * qs, 0, item_m(nitem) * 128,
                             item_h(nitem) * 2, policy_evict_first());
          }
        }
      }
    }
    if (last) break;
    last = nitem >= A_ITEMS;
    m = last ? -1 : item_m(nitem);
    h = item_h(nitem);
  }
}

__device__ __forceinline__ void put_o(uint32_t sbase, int wg, int warp, int lane, const float (&o)[64], float i0, float i1) {
  const int st_row = warp * 16 + (lane & 7) + ((lane >> 3) & 1) * 8;
  const uint32_t so = sbase + A_O_OFF + wg * 16384 + st_row * 128;
#pragma unroll
  for (int j = 0; j < 16; j += 2)
    stmatrix_x4(so + (j >> 3) * 8192 + ((((j & 7) + (lane >> 4)) ^ (lane & 7)) << 4),
                pack_bf16(o[4 * j] * i0, o[4 * j + 1] * i0), pack_bf16(o[4 * j + 2] * i1, o[4 * j + 3] * i1),
                pack_bf16(o[4 * j + 4] * i0, o[4 * j + 5] * i0), pack_bf16(o[4 * j + 6] * i1, o[4 * j + 7] * i1));
}
__device__ __forceinline__ uint32_t attn_consumer(const Maps& maps, const uint32_t sbase, const int wg,
                                                  const uint32_t rt_zero, uint32_t sn, uint32_t (&p)[32], float (&rest)[64],
                                                  bool after_qkv, float (&o)[64], float (&s)[64], float& pi0, float& pi1) {
  PHASE_GIVEN
  const uint32_t q_full = bar + B_QFULL, q_empty = bar + B_QEMPTY;
  const uint32_t k_full = bar + B_KFULL, k_empty = bar + B_KEMPTY, v_full = bar + B_VFULL;
  float e[32];
  uint32_t dep = 0;
  constexpr int MIDJ = 5;
  float l0 = 0.f, l1 = 0.f, b0 = 0.f, b1 = 0.f;
  const int sched_own = 4 + wg, sched_other = 5 - wg;

  const int hf = wg ^ 1;
  const uint32_t qd0 = (uint32_t)make_desc(sbase + A_Q_OFF + hf * 8192, 16, 0, 0);
  const uint32_t kd0 = (uint32_t)make_desc(sbase + A_K_OFF, 16, 0, 0);
  const uint32_t vd0 = (uint32_t)make_desc(sbase + A_V_OFF, 16384, 0, 0);
  constexpr uint64_t DHI = DESC_SW128 | ((uint64_t)(1024 >> 4) << 32);
  constexpr uint32_t DST = A_TILE >> 4;
  auto issue_qk = [&](uint32_t qd, uint32_t kd) {
#pragma unroll
    for (int kk = 0; kk < 8; kk++) {
      const uint32_t off = ((kk >> 2) * 16384 + (kk & 3) * 32) >> 4;
      wgmma_m64n128_ss(s, DHI | (qd + off), DHI | (kd + off), kk != 0);
    }
    wgmma_commit();
  };
  auto issue_pv = [&](uint32_t vd, bool accumulate, int nk) {
#pragma unroll
    for (int kk = 0; kk < 8; kk++) {
      if (kk < nk)
        wgmma_m64n128_rs<1>(o, p[4 * kk], p[4 * kk + 1], p[4 * kk + 2], p[4 * kk + 3], DHI | (vd + kk * 128),
                            accumulate || (kk != 0));
    }
    wgmma_commit();
  };
  auto exp_lo = [&](float& a0, float& a1) {
#pragma unroll
    for (int j = 0; j < 8; j++) {
      e[4 * j] = ex2(s[4 * j]);
      e[4 * j + 1] = ex2(s[4 * j + 1]);
      e[4 * j + 2] = ex2(s[4 * j + 2]);
      e[4 * j + 3] = ex2(s[4 * j + 3]);
      a0 += e[4 * j];
      a0 += e[4 * j + 1];
      a1 += e[4 * j + 2];
      a1 += e[4 * j + 3];
      if (j == MIDJ) dep = (__float_as_uint(a0) | __float_as_uint(a1)) & rt_zero;
    }
  };
  auto pack_lo = [&]() {
#pragma unroll
    for (int j = 0; j < 16; j++) p[j] = pack_bf16(e[2 * j], e[2 * j + 1]);
  };
  auto finish_p = [&](float& a0, float& a1) {
    pack_lo();
#pragma unroll
    for (int j = 8; j < 16; j++) {
      const float e0 = ex2(s[4 * j]), e1 = ex2(s[4 * j + 1]), e2 = ex2(s[4 * j + 2]), e3 = ex2(s[4 * j + 3]);
      a0 += e0;
      a0 += e1;
      a1 += e2;
      a1 += e3;
      p[2 * j] = pack_bf16(e0, e1);
      p[2 * j + 1] = pack_bf16(e2, e3);
      if (j == 8 + MIDJ) dep = __float_as_uint(a0) & rt_zero;
    }
  };
  auto quad_sum = [&](float t) {
    t += __shfl_xor_sync(0xffffffffu, t, 1);
    return t + __shfl_xor_sync(0xffffffffu, t, 2);
  };
  auto write_o = [&](float i0, float i1) {
    st_wait(bar, wg, sn - 1);
    put_o(sbase, wg, warp, lane, o, i0, i1);
  };
  auto store_o = [&](uint32_t r, int kind, uint32_t lazy) {
    const uint32_t it = item_at(maps, kind == ST_BOX2Q ? 1 : head_of(maps, r));
    st_cmd(bar, wg, wtid, sn, kind, (INPLACE & 1) || kind != ST_BOX2Q ? &maps.o : &maps.c[0], sbase + A_O_OFF + wg * 16384, item_h(it) * 128,
            item_m(it) * 128 + hf * 64, CNT_CTX + (r >> 1), lazy);
    if (kind != ST_BOX2L) st_go(bar, wg, wtid, sn);
    sn++;
  };
  auto mask_half = [&](float* sh) {
    const int u = warp * 16 + (lane >> 2) - (lane & 3) * 2;
#pragma unroll
    for (int j = 0; j < 8; j++) {
      if (8 * j > u) sh[4 * j] = -INFINITY;
      if (8 * j + 1 > u) sh[4 * j + 1] = -INFINITY;
      if (8 * j - 8 > u) sh[4 * j + 2] = -INFINITY;
      if (8 * j - 7 > u) sh[4 * j + 3] = -INFINITY;
    }
  };
  ST(0)
  const uint32_t qa = sbase + A_Q_OFF + hf * 8192 + (warp * 16 + (lane & 15)) * 128;
  auto q_at = [&](int j) { return qa + (j >> 2) * 16384 + ((((j & 3) * 2 + (lane >> 4)) ^ (lane & 7)) << 4); };
  if (!after_qkv) {
    mbar_wait(q_full, 0);
    if (blockIdx.x >= 128) return sn;
#pragma unroll
    for (int j = 0; j < 8; j++)
      asm volatile("ldmatrix.sync.aligned.m8n8.x4.shared.b16 {%0, %1, %2, %3}, [%4];"
                   : "=r"(p[4 * j]), "=r"(p[4 * j + 1]), "=r"(p[4 * j + 2]), "=r"(p[4 * j + 3])
                   : "r"(q_at(j))
                   : "memory");
  }
  for (uint32_t i = 0; !(mbar_try(k_full, 0) & mbar_try(bar + B_GEMPTY + 8, 1)) && i < (1u << 22); i++) {}
  named_bar_sync(sched_own, 256);
  fence_regs_u(p);
  wgmma_fence();
#pragma unroll
  for (int kk = 0; kk < 8; kk++)
    wgmma_m64n128_rs<0>(s, p[4 * kk], p[4 * kk + 1], p[4 * kk + 2], p[4 * kk + 3],
                        DHI | (kd0 + (((kk >> 2) * 16384 + (kk & 3) * 32) >> 4)), kk != 0);
  wgmma_commit();
  named_bar_arrive(sched_other, 256);
#pragma unroll
  for (int j = 0; j < 8; j++) stmatrix_x4(q_at(j), p[4 * j], p[4 * j + 1], p[4 * j + 2], p[4 * j + 3]);
  fence_regs(rest);
#pragma unroll
  for (int i = 0; i < 64; i++) o[i] = rest[i] * __uint_as_float(0x3f800000u | rt_zero);
  fence_regs(o);
  fence_proxy_async();
  fence_regs(o);
  wgmma_wait<0>();
  fence_regs(s);
  mbar_arrive_if(k_empty, wtid == 32);
  uint32_t g = 0;
  uint32_t rnd = 0;
  int rem = item_m(item_of(maps, 0));
  uint32_t first = 1;
  uint32_t fl = 0;
#define redo (fl & 1)
#define shifted (fl & 2)
  float d0 = 0.f, d1 = 0.f;
  pi0 = pi1 = 1.f;
  ST(1)
  for (;;) {
    if (shifted) {
#pragma unroll
      for (int j = 0; j < 16; j++) {
        s[4 * j] -= d0;
        s[4 * j + 1] -= d0;
        s[4 * j + 2] -= d1;
        s[4 * j + 3] -= d1;
      }
    }
    if (rem == 0 && !redo) {
      mbar_arrive_if(q_empty + 8 * (rnd & 1), wtid == 96);
      rnd++;
      if (hf == 0) mask_half(s);
      else mask_half(s + 32);
    }
    for (;;) {
      const bool kill = rem == 0 && hf == 0;
      const uint32_t kd = kd0 + ((g + 1) & 1) * 2 * DST, vd = vd0 + (g & 1) * DST;
      float a0 = 0.f, a1 = 0.f;
      exp_lo(a0, a1);
      fence_regs(e);
      const uint32_t kb = k_full + 8 * ((g + 1) & 1);
      const uint32_t kpar = (((g + 1) >> 1) & 1) ^ (g == A_STEPS - 1 ? 1u : 0u);
      const uint32_t qb = q_full + 8 * (rnd & 1), qpar = ((rnd >> 1) & 1) | dep;
      if (!mbar_try(qb, qpar)) mbar_wait(qb, qpar | ((__float_as_uint(a0) | __float_as_uint(a1)) & rt_zero));
      wgmma_wait<0>();
      fence_regs(o);
      if (kill) {
        mbar_arrive_if(kb + (B_VEMPTY - B_KFULL), wtid == 64 && !redo && g > 0);
        fence_regs(e);
        pack_lo();
#pragma unroll
        for (int j = 16; j < 32; j++) asm volatile("" : "=r"(p[j]));
        goto check;
      }
#pragma unroll
      for (int i = 32; i < 64; i++) asm volatile("" : "+f"(s[i])::"memory");
      mbar_arrive_if(kb + (B_VEMPTY - B_KFULL), wtid == 64 && !redo && g > 0);
      finish_p(a0, a1);
      if (__any_sync(0xffffffffu, !(mbar_try(v_full + 8 * (g & 1), ((g >> 1) & 1) | dep) &
                                    mbar_try(kb, kpar | dep)) ||
                                      !(a0 + a1 < 1.0995116e12f) || !(fminf(a0, a1) > (first ? 9.094947e-13f : -1.f)))) {
      check:
        bool bad = !(a0 + a1 < 1.0995116e12f);
        if (first) bad |= !(fminf(quad_sum(a0), quad_sum(a1)) > 9.094947e-13f);
        if (!redo && __any_sync(0xffffffffu, bad)) {
          d0 = d1 = first ? -INFINITY : 0.f;
#pragma unroll
          for (int j = 0; j < 16; j++) {
            if (j < 8 || !kill) {
              d0 = fmaxf(d0, fmaxf(s[4 * j], s[4 * j + 1]));
              d1 = fmaxf(d1, fmaxf(s[4 * j + 2], s[4 * j + 3]));
            }
          }
#pragma unroll
          for (int x = 1; x <= 2; x++) {
            d0 = fmaxf(d0, __shfl_xor_sync(0xffffffffu, d0, x));
            d1 = fmaxf(d1, __shfl_xor_sync(0xffffffffu, d1, x));
          }
          b0 += d0;
          b1 += d1;
          if (!first) {
            const float al0 = ex2(-d0), al1 = ex2(-d1);
            l0 *= al0;
            l1 *= al1;
#pragma unroll
            for (int j = 0; j < 16; j++) {
              o[4 * j] *= al0;
              o[4 * j + 1] *= al0;
              o[4 * j + 2] *= al1;
              o[4 * j + 3] *= al1;
            }
          }
          fl = 3;
          break;
        }
        mbar_wait(v_full + 8 * (g & 1), (g >> 1) & 1);
        mbar_wait(kb, kpar);
      }
      named_bar_sync(sched_own, 256);
      if (g == A_STEPS - 1) {
        fence_regs(o);
        if (hf == 0) {
          wgmma_fence();
          issue_pv(vd, 1, 4);
        } else {
          wgmma_fence();
          issue_pv(vd, 1, 8);
        }
        named_bar_arrive(sched_other, 256);
        pi0 = rcp(quad_sum(l0 + a0));
        pi1 = rcp(quad_sum(l1 + a1));
        goto done;
      }
      wgmma_fence();
      issue_qk(qd0 + (rnd & 1) * 4 * DST, kd);
      if (first) write_o(pi0, pi1);
      fence_regs(o);
      if (kill) {
        wgmma_fence();
        issue_pv(vd, !first, 4);
      } else {
        wgmma_fence();
        issue_pv(vd, !first, 8);
      }
      named_bar_arrive(sched_other, 256);
      fl &= 2;
      l0 += a0;
      l1 += a1;
      if (rem == 0 || first) {
        if (first && (g > 0 || after_qkv)) store_o(g ? rnd - (rem == 0 ? 2 : 1) : 2, g ? ST_BOX2 : ST_BOX2Q, rem);
        first = rem == 0;
        if (first) {
          pi0 = rcp(quad_sum(l0));
          pi1 = rcp(quad_sum(l1));
          l0 = l1 = b0 = b1 = 0.f;
          fl = 0;
          rem = item_m(item_of(maps, rnd)) + 1;
        }
      }
      rem--;
      g++;
      wgmma_wait<1>();
      fence_regs(s);
      mbar_arrive_if(kb + (B_KEMPTY - B_KFULL), wtid == 32);
      ST(g + 1)
      if (rem == 0 || shifted) {
        d0 = b0;
        d1 = b1;
        break;
      }
    }
  }
done:
#undef redo
#undef shifted
  st_wait(bar, wg, sn - 1);
  store_o(3, ST_BOX2L, 4);
  ST(35)
  return sn;
}

constexpr int O_STAGES = 5;
constexpr int O_STAGE_BYTES = 32768;
constexpr int O_Y_OFF = 4 * 32768;
constexpr int O_X_OFF = 6 * 32768;
constexpr int O_G_OFF = 7 * 32768;
constexpr int O_NK = HDIM / 64;

__device__ __forceinline__ uint32_t out_stage(uint32_t st) { return ((0x32501u >> (4 * st)) & 7) * O_STAGE_BYTES; }

__device__ __forceinline__ void out_producer(const Maps& maps, uint32_t sbase, bool after_attn, bool dry) {
  const uint32_t bar = sbase + BAR_OFF;
  const uint32_t rank = blockIdx.x & 1;
  const int m_tile = maps.id[blockIdx.x][2] & 15, n_tile = maps.id[blockIdx.x][2] >> 4;
  uint32_t stage = 0, phase = 0, xi = 0;
#pragma unroll 1
  for (int ki = 0; ki < (dry ? 1 : O_NK); ki++) {
    const int kt = (ki & 14) * 4 + ((A_ORDER >> ((ki >> 4) * 4)) & 3) * 2 + (ki & 1);
    const uint32_t fb = bar + B_OFULL + 8 * stage, eb = bar + B_OEMPTY + 8 * stage;
    const uint32_t sa = sbase + out_stage(stage);
    if (ki < O_STAGES) {
      constexpr uint32_t LASTB = B_KEMPTY | ((B_QEMPTY + 8) << 8) | ((B_KEMPTY + 8) << 16) | (B_VEMPTY << 24);
      if (ki > 0 && after_attn) mbar_wait_sleep(bar + ((LASTB >> (8 * ki - 8)) & 255), ki == 2);
      mbar_arrive_cluster_if(eb, 0, !dry);
      mbar_arrive_cluster_if(eb, 1, !dry);
    }
    if (ki == 32) mbar_wait_sleep(bar + seen_bar(2), 0);
    if (!dry) {
      mbar_wait_sleep(eb, phase);
      mbar_expect_tx(fb, O_STAGE_BYTES);
      tma_load_2d_mc(sa + 16384 + rank * 8192, &maps.ob, fb, n_tile * 128 + rank * 64, kt * 64, (uint16_t)3);
      tma_load_2d(sa, &maps.oa, fb, kt * 64, m_tile * 128);
    }
    if (++stage == O_STAGES) { stage = 0; phase ^= 1; }
    if ((ki & XMASK) == XMASK && ki >= XFIRST && xi < 8) {
      if (after_attn && xi < 2) mbar_wait_sleep(bar + B_OFREE + 8 * xi, 0);
      tma_load_3d(sbase + O_X_OFF + (xi & 1) * 16384 + (xi >> 1) * 4096, &maps.xs, bar + B_OY, 0,
                  m_tile * 128 + (xi & 1) * 64 + (xi >> 1) * 16, n_tile * 2);
      xi++;
    }
  }
  if (!dry) mbar_wait_sleep(bar + B_OY2, 0);
}

__device__ __forceinline__ void out_side(const Maps& maps, uint32_t smem0) {
  PHASE_PROLOGUE
  const int m_tile = maps.id[blockIdx.x][2] & 15, n_tile = maps.id[blockIdx.x][2] >> 4;
  const float* gp = g_gate + m_tile * 128 + warp * 16 + (lane >> 2);
  const float gv[4] = {__ldcg(gp), __ldcg(gp + 8), __ldcg(gp + 64), __ldcg(gp + 72)};
  const bool w0 = __shfl_sync(0xffffffffu, warp, 0) == 0;
  bool have = false;
  auto late = [&](uint32_t spins) {
    have = cnt_wait(CNT_Y2 + 1, 128, spins) || !spins;
    TD(11)
    if (have) {
      mbar_expect_tx(bar + B_OY2, 4096);
      tma_load_3d(sbase + O_Y_OFF + 7 * 4096, &maps.y, bar + B_OY2, 0, n_tile * 128 + 112, m_tile * 2);
    }
  };
  if (w0) {
    if (elect_one()) {
      mbar_expect_tx(bar + B_OY, 65536 - 4096);
      TD(10)
      cnt_wait(CNT_Y2, DM - 128);
      TD(7)
#pragma unroll 1
      for (int i = 0; i < 7; i++) {
        tma_load_3d(sbase + O_Y_OFF + i * 4096, &maps.y, bar + B_OY, 0, n_tile * 128 + i * 16, m_tile * 2);
        __nanosleep(PACE);
      }
      late(1u << 18);
    }
  }
  mbar_wait_sleep(bar + B_OY, 0);
  if (wtid == 0) { TD(12) }
  const int mrow = (lane & 7) + ((lane >> 4) & 1) * 8;
  const int mchunk = warp * 2 + ((lane >> 3) & 1);
  const uint32_t xrow = sbase + O_X_OFF + warp * 4096 + (lane & 15) * 128;
  const uint32_t yrow = sbase + O_Y_OFF + mrow * 128 + ((mchunk ^ (lane & 7)) << 4);
  uint32_t y[7][4], x[7][4], om[4];
#pragma unroll
  for (int i = 0; i < 4; i++) om[i] = pack_bf16(1.0f - gv[i], 1.0f - gv[i]);
  sts128(sbase + O_G_OFF + wtid * 16, make_uint4(pack_bf16(gv[0], gv[0]), pack_bf16(gv[1], gv[1]), pack_bf16(gv[2], gv[2]),
                                                 pack_bf16(gv[3], gv[3])));
  auto xa = [&](int h, int i) { return xrow + h * 16384 + (i >> 2) * 2048 + ((((i & 3) * 2 + (lane >> 4)) ^ (lane & 7)) << 4); };
  auto load = [&](int r, int h, int i) {
    ldsm4t(y[r], yrow + h * 2048 + i * 4096);
    asm volatile("ldmatrix.sync.aligned.m8n8.x4.shared.b16 {%0, %1, %2, %3}, [%4];"
                 : "=r"(x[r][0]), "=r"(x[r][1]), "=r"(x[r][2]), "=r"(x[r][3])
                 : "r"(xa(h, i)));
  };
  auto store = [&](int r, int h, int i, uint32_t om0, uint32_t om1) {
    stmatrix_x4(xa(h, i), mul_bf2(om0, mul_bf2(x[r][0], y[r][0])), mul_bf2(om1, mul_bf2(x[r][1], y[r][1])),
                mul_bf2(om0, mul_bf2(x[r][2], y[r][2])), mul_bf2(om1, mul_bf2(x[r][3], y[r][3])));
  };
#pragma unroll 1
  for (int h = 0; h < 2; h++) {
#pragma unroll
    for (int i = 0; i < 7; i++) load(i, h, i);
#pragma unroll
    for (int i = 0; i < 7; i++) store(i, h, i, h ? om[2] : om[0], h ? om[3] : om[1]);
  }
  __syncwarp();
  mbar_arrive_if(bar + B_OE, lane == 0);
  if (w0 && !__any_sync(0xffffffffu, have)) {
    if (elect_one()) late(0);
  }
  mbar_wait_sleep(bar + B_OY2, 0);
  load(0, 0, 7);
  load(1, 1, 7);
  store(0, 0, 7, om[0], om[1]);
  store(1, 1, 7, om[2], om[3]);
  __syncwarp();
  mbar_arrive_if(bar + B_OY + 8, lane == 0);
  if (wtid == 0) { TD(13) }
}

__device__ __forceinline__ void out_gemm(const Maps& maps, const uint32_t sbase, uint32_t sn, bool post, float (&o)[64],
                                         float (&s)[64],                                          float i0, float i1) {
  PHASE_GIVEN
  auto acc = [&](int h) -> float (&)[64] { return h ? o : s; };
  constexpr uint64_t DHI = DESC_SW128 | ((uint64_t)(1024 >> 4) << 32);
  const uint32_t d0 = (uint32_t)make_desc(sbase, 0, 0, 0);
  auto mma0 = [&](int h) {
    wgmma_fence();
#pragma unroll
    for (int k = 0; k < 4; k++)
      wgmma_m64n128_ss_tb(acc(h), DHI | (d0 + 0x10800 + h * 512 + k * 2), DHI | (d0 + 0x2000c00 + k * 128), k != 0);
    wgmma_commit();
  };
  mbar_wait(bar + B_OFULL, 0);
  mma0(0);
  wgmma_wait<1>();
  fence_regs(o);
  if (post) {
    named_bar_arrive(3, 256);
    put_o(sbase, 0, warp, lane, o, i0, i1);
  }
  mma0(1);
  if (post) st_go(bar, 0, wtid, sn - 1);
  const int m_tile = maps.id[blockIdx.x][2] & 15, n_tile = maps.id[blockIdx.x][2] >> 4;
  uint32_t stage = 1, phase = 0, prev_stage = 0;
  GT(gti++)
  const uint32_t xrow = sbase + O_X_OFF + warp * 4096 + (lane & 15) * 128;
  auto addr = [&](int i) {
    return xrow + (i >> 3) * 16384 + ((i >> 2) & 1) * 2048 + ((((i & 3) * 2 + (lane >> 4)) ^ (lane & 7)) << 4);
  };
  uint32_t b[16][4];
#pragma unroll
  for (int i = 0; i < 64; i++) asm volatile("" : "=r"(b[i >> 2][i & 3]));
  auto ld_b = [&](int q0, int q1) {
#pragma unroll
    for (int i = 0; i < 16; i++)
      if ((i & 7) != 7)
        asm volatile(
            "{\n.reg .pred p;\nsetp.ge.s32 p, %5, %6;\nsetp.le.and.s32 p, %5, %7, p;\n"
            "@p ldmatrix.sync.aligned.m8n8.x4.shared.b16 {%0, %1, %2, %3}, [%4];\n}\n"
            : "+r"(b[i][0]), "+r"(b[i][1]), "+r"(b[i][2]), "+r"(b[i][3])
            : "r"(addr(i)), "r"(i / 4), "r"(q0), "r"(q1)
            : "memory");
  };
  int nq = 0;
#pragma unroll 1
  for (int kt = 1; kt < O_NK - 2; kt++) {
    uint32_t da = (uint32_t)make_desc(sbase + out_stage(stage), 16, 0, 0);
    uint32_t db = (uint32_t)make_desc(sbase + out_stage(stage) + 16384, 8192, 0, 0);
    asm volatile("" : "+r"(da), "+r"(db));
    mbar_wait(bar + B_OFULL + 8 * stage, phase);
    GT(gti++)
#pragma unroll
    for (int kk = 0; kk < 4; kk++) {
      wgmma_wait<2>();
      if (kk == 2)
        mbar_arrive_cluster_if(bar + B_OEMPTY + 8 * prev_stage, wtid >> 6, (wtid & 63) == 32 && kt - 1 + O_STAGES < O_NK);
      wgmma_fence();
      wgmma_m64n128_ss_tb(acc(0), DHI | (da + kk * 2), DHI | (db + kk * 128), 1);
      wgmma_m64n128_ss_tb(acc(1), DHI | (da + 512 + kk * 2), DHI | (db + kk * 128), 1);
      wgmma_commit();
      if (kk == 0 && kt >= 52) {
        uint32_t ok;
        asm volatile("{\n.reg .pred p;\nmbarrier.test_wait.parity.shared::cta.b64 p, [%1], 0;\nselp.u32 %0, 1, 0, p;\n}\n"
                     : "=r"(ok)
                     : "r"(bar + B_OE)
                     : "memory");
        if (__all_sync(0xffffffffu, ok)) {
          ld_b(nq, nq);
          nq++;
        }
      }
    }
    prev_stage = stage;
    if (++stage == O_STAGES) { stage = 0; phase ^= 1; }
  }
  if (tid == 0) { TD(14) }
  constexpr int S0 = (O_NK - 2) % O_STAGES, P0 = ((O_NK - 2) / O_STAGES) & 1;
  auto mma = [&](int h, int k0, int k1) {
    wgmma_fence();
#pragma unroll
    for (int k = k0; k < k1; k++) {
      const uint32_t d = d0 + (out_stage(S0 + (k >> 2)) >> 4);
      wgmma_m64n128_ss_tb(acc(h), DHI | (d + 0x10000 + h * 512 + (k & 3) * 2), DHI | (d + 0x2000400 + (k & 3) * 128), 1);
    }
    wgmma_commit();
  };
#pragma unroll
  for (int p = 0; p < 2; p++) {
    mbar_wait(bar + B_OFULL + 8 * (S0 + p), P0);
    mma(0, 4 * p, 4 * p + 4);
  }
  mma(1, 0, 8);
  if (nq < 4) {
    mbar_wait(bar + B_OE, 0);
    ld_b(nq, 3);
  }
  const uint4 g4 = lds128(sbase + O_G_OFF + wtid * 16);
  const uint32_t gg[4] = {g4.x, g4.y, g4.z, g4.w};
  const int w4 = __shfl_sync(0xffffffffu, warp, 0);
#pragma unroll
  for (int i = 0; i < 16; i++) {
    const int h = i >> 3;
    if (i == 0) wgmma_wait<1>();
    if (i == 8) wgmma_wait<0>();
    if ((i & 7) == 0) fence_regs(acc(h));
    if (i == 8) {   }
    if (i == 7) {
      mbar_wait(bar + B_OY + 8, 0);
#pragma unroll
      for (int j = 7; j < 16; j += 8)
        asm volatile("ldmatrix.sync.aligned.m8n8.x4.shared.b16 {%0, %1, %2, %3}, [%4];"
                     : "=r"(b[j][0]), "=r"(b[j][1]), "=r"(b[j][2]), "=r"(b[j][3])
                     : "r"(addr(j))
                     : "memory");
    }
    const float* a = acc(h) + 8 * (i & 7);
    stmatrix_x4(addr(i), fma_bf2(gg[2 * h], pack_bf16(a[0], a[1]), b[i][0]), fma_bf2(gg[2 * h + 1], pack_bf16(a[2], a[3]), b[i][1]),
                fma_bf2(gg[2 * h], pack_bf16(a[4], a[5]), b[i][2]), fma_bf2(gg[2 * h + 1], pack_bf16(a[6], a[7]), b[i][3]));
    if ((i & 7) == 7) {
      fence_proxy_async();
      __syncwarp();
      if (elect_one()) {
        tma_store_3d(&maps.oc, sbase + O_X_OFF + (h * 4 + w4) * 4096, 0, m_tile * 128 + h * 64 + w4 * 16, n_tile * 2);
        if (h == 1) {
          tma_store_commit();
        }
      }
    }
  }
  GT(gti++)
}

__device__ __noinline__ void leave_kernel(int mask) {
  if (!(mask & 4)) return;
  if (atomicAdd(g_cnt + CNT_DONE * 32, 1u) == 2 * gridDim.x - 1) {
    for (int i = 0; i < CNT_N; i++) g_cnt[i * 32] = 0;
#pragma unroll 4
    for (int i = 0; i < 128; i++) g_slot[i] = 0;
  }
}

__global__ void __launch_bounds__(384, 1)
    fused_kernel(int mask, const bf16* px, const bf16* pw, const __grid_constant__ Maps maps) {
  extern __shared__ __align__(1024) uint8_t smem_raw[];
  {
    const uint32_t t = threadIdx.x, l = t & 31, u = (blockIdx.x & 127) * 16 + (l >> 1);
    const uint32_t ow = (u >> 5) * HDIM + ((u >> 2) & 7) * 512 + 256 + (u & 3) * 64, ox = u * DM;
    const bf16* p = ((l & 1) ? pw : px) + ((l & 1) ? ow : ox);
    asm volatile("{\n.reg .pred p;\nsetp.ne.u32 p, %1, 0;\n@p prefetch.global.L2 [%0];\n}\n" ::"l"(p), "r"((uint32_t)(t < 32)));
  }
  {
    const uint32_t sbase = __shfl_sync(0xffffffffu, smem_u32(smem_raw), 0);
    const uint32_t bar = sbase + BAR_OFF;
    const int tid = threadIdx.x;
    const bool do_qkv = (mask & 1) && blockIdx.x < 128;
    TL(0, 0)
    if (__shfl_sync(0xffffffffu, tid >> 5, 0) == 1 && do_qkv) {
      if (elect_one()) {
        for (int i = 0; i < G_STAGES; i++) mbar_init(bar + B_GFULL + 8 * i, 1);
        fence_barrier_init();
        qkv_producer(maps, sbase, true);
      }
    }
    if (tid == 0) {
      for (int i = 0; i < G_STAGES; i++) {
        mbar_init(bar + B_GEMPTY + 8 * i, 2);
        mbar_init(bar + B_SFULL + 8 * i, 4);
        mbar_init(bar + B_SFREE + 8 * i, 1);
      }
      for (int i = 0; i < 2; i++) {
        mbar_init(bar + B_OFREE + 8 * i, 1);
        mbar_init(bar + B_QFULL + 8 * i, 1);
        mbar_init(bar + B_QEMPTY + 8 * i, 2);
        mbar_init(bar + B_KFULL + 8 * i, 1);
        mbar_init(bar + B_KEMPTY + 8 * i, 2);
        mbar_init(bar + B_VFULL + 8 * i, 1);
        mbar_init(bar + B_VEMPTY + 8 * i, 2);
      }
      for (int i = 0; i < O_STAGES; i++) {
        mbar_init(bar + B_OFULL + 8 * i, 1);
        mbar_init(bar + B_OEMPTY + 8 * i, 2);
      }
      mbar_init(bar + B_OY, 1);
      for (int i = 0; i < 3; i++) mbar_init(bar + seen_bar(i), 1);
      mbar_init(bar + B_OY2, 1);
      mbar_init(bar + B_DEAL, 1);
      mbar_init(bar + B_DEAL2, 1);
      mbar_init(bar + B_PAIR, 1);
      mbar_init(bar + B_OY + 8, 4);
      mbar_init(bar + B_OE, 4);
      mbar_init(bar + B_QDONE, 2);
      for (int i = 0; i < 8; i++) mbar_init(bar + B_CFULL + 8 * i, 1);
      for (int i = 0; i < CNT_N; i++) asm volatile("st.shared.u32 [%0], 0;" ::"r"(bar + B_PEND + 4 * i) : "memory");
      fence_barrier_init();
    }
    __syncthreads();
    asm volatile("barrier.cluster.arrive.relaxed.aligned;" ::: "memory");
  }
  uint32_t smem0 = smem_u32(smem_raw);
  PHASE_PROLOGUE
  const bool do_qkv = (mask & 1) && blockIdx.x < 128, do_out = (mask & 4) && blockIdx.x < 128;
  TL(0, 1)

  if (wg != 2) {
    reg_alloc<232>();
    asm volatile("barrier.cluster.wait.acquire.aligned;" ::: "memory");
    if (wg == 1) named_bar_arrive(4, 256);
    uint32_t sn = 0;
    float rest[64], o[64], s[64];
    uint32_t q[32];
    if (do_qkv) {
      sn = qkv_consumer(maps, sbase, wg, mask & 2, q, rest, rt_zero);
    } else {
      undef_regs(rest);
#pragma unroll
      for (int j = 0; j < 32; j++) asm volatile("" : "=r"(q[j]));
    }
    undef_regs(o);
    undef_regs(s);
    TL(0, 2) TL(1, 0) TL(1, 1)
    const bool direct = do_out && wg == 0;
    float i0 = 0.f, i1 = 0.f;
    if (mask & 2) sn = attn_consumer(maps, sbase, wg, rt_zero, sn, q, rest, do_qkv, o, s, i0, i1);
    TL(2, 0)
    bool side = false;
    if (!direct) {
      wgmma_wait<0>();
      fence_regs(o);
      if (mask & 2) {
        const bool fused = mask & 4, mainc = blockIdx.x < 128;
        if (mainc) {
          PHASE_GIVEN
          put_o(sbase, wg, warp, lane, o, i0, i1);
          st_go(bar, wg, wtid, sn - 1);
        }
        const uint32_t b2 = blockIdx.x * 2 + (threadIdx.x >> 7);
        const uint32_t first = __shfl_sync(0xffffffffu, !fused ? b2 : mainc ? conv_first(maps) : (b2 - 255) * 128 - C_SIDE, 0);
        conv_consumer(maps, smem_u32(smem_raw), first, !fused ? 264 : mainc ? 16 : 1,
                      !fused ? DM : mainc ? (first | 127) + 1 - C_SIDE : first + C_SIDE, fused && !mainc,
                      fused && mainc);
      }
      side = (mask & 4) && blockIdx.x < 128;
    } else {
      out_gemm(maps, sbase, sn, mask & 2, o, s, i0, i1);
    }
    TL(1, 2) TL(2, 1) TL(2, 2) TL(3, 0) TL(3, 1)
    if (side + rt_zero) out_side(maps, smem_u32(smem_raw));
    tma_store_wait_read<0>();
  } else {
    reg_dealloc<40>();
    asm volatile("barrier.cluster.wait.acquire.aligned;" ::: "memory");
    const int w = __shfl_sync(0xffffffffu, tid >> 5, 0) - 8;
    if (w < 2) {
      if (do_qkv) prep_agent(maps, sbase, w, lane);
      if (elect_one()) store_agent(bar, w, w && do_out ? conv_first(maps) + 48 : 0, blockIdx.x >= 128 || mask == 4 ? 0 : mask == 1 ? 24 : 99);
      TL2(3, 2)
    } else {
      if (elect_one()) {
        const bool dry = w == 2;
        if (do_qkv && !dry) qkv_producer(maps, sbase, false);
        if (mask & 2) attn_producer(maps, sbase, do_qkv, do_out, dry);
        if (do_out) out_producer(maps, sbase, mask & 2, dry);
        if (dry) { TD(5) }
      }
      __syncwarp();
      if (w == 2 && do_qkv) gate_rows(maps, bar, tid & 31);
      if (w == 2) publisher(bar, tid & 31, !(mask & 2) ? 2 : do_out ? 3 : 4, !do_out ? 3 : do_qkv ? 0 : 2, do_qkv ? 4 : 0);
      if ((tid & 31) == 0) leave_kernel(mask);
    }
  }
}

typedef CUresult (*PFN_tmapEncode)(CUtensorMap*, CUtensorMapDataType, cuuint32_t, void*, const cuuint64_t*,
                                   const cuuint64_t*, const cuuint32_t*, const cuuint32_t*, CUtensorMapInterleave,
                                   CUtensorMapSwizzle, CUtensorMapL2promotion, CUtensorMapFloatOOBfill);
static PFN_tmapEncode s_encode = nullptr;

static void make_map_2d(CUtensorMap* m, const void* ptr, int rows, int cols, int box_rows) {
  cuuint64_t dims[2] = {(cuuint64_t)cols, (cuuint64_t)rows};
  cuuint64_t strides[1] = {(cuuint64_t)cols * 2};
  cuuint32_t box[2] = {cols < 64 ? 32u : 64u, (cuuint32_t)box_rows};
  cuuint32_t es[2] = {1, 1};
  s_encode(m, CU_TENSOR_MAP_DATA_TYPE_BFLOAT16, 2, const_cast<void*>(ptr), dims, strides, box, es,
           CU_TENSOR_MAP_INTERLEAVE_NONE, cols < 64 ? CU_TENSOR_MAP_SWIZZLE_64B : CU_TENSOR_MAP_SWIZZLE_128B, CU_TENSOR_MAP_L2_PROMOTION_L2_256B,
           CU_TENSOR_MAP_FLOAT_OOB_FILL_NONE);
}
static void make_map_3d(CUtensorMap* m, const void* ptr, int rows, int cols, int box_rows, int box_chunks) {
  cuuint64_t dims[3] = {64, (cuuint64_t)rows, (cuuint64_t)(cols / 64)};
  cuuint64_t strides[2] = {(cuuint64_t)cols * 2, 128};
  cuuint32_t box[3] = {64, (cuuint32_t)box_rows, (cuuint32_t)box_chunks};
  cuuint32_t es[3] = {1, 1, 1};
  s_encode(m, CU_TENSOR_MAP_DATA_TYPE_BFLOAT16, 3, const_cast<void*>(ptr), dims, strides, box, es,
           CU_TENSOR_MAP_INTERLEAVE_NONE, CU_TENSOR_MAP_SWIZZLE_128B, CU_TENSOR_MAP_L2_PROMOTION_L2_256B,
           CU_TENSOR_MAP_FLOAT_OOB_FILL_NONE);
}

static cudaLaunchConfig_t fused_cfg(cudaLaunchAttribute* at) {
  cudaLaunchConfig_t cfg = {};
  cfg.gridDim = dim3(132);
  cfg.blockDim = dim3(384);
  cfg.dynamicSmemBytes = SMEM_BYTES;
  cfg.stream = cudaStreamPerThread;
  at[0].id = cudaLaunchAttributeClusterDimension;
  at[0].val.clusterDim.x = 2;
  at[0].val.clusterDim.y = 1;
  at[0].val.clusterDim.z = 1;
  cfg.attrs = at;
  cfg.numAttrs = 1;
  return cfg;
}

extern "C" void kernel_launch(void* const* d_in, const int* in_sizes, int n_in, void* d_out, int out_size) {
  const bf16* x = (const bf16*)d_in[0];
  const bf16* ckv = (const bf16*)d_in[1];
  const bf16* wq = (const bf16*)d_in[2];
  const bf16* wuk = (const bf16*)d_in[3];
  const bf16* wuv = (const bf16*)d_in[4];
  const bf16* wo = (const bf16*)d_in[5];
  const bf16* bk = (const bf16*)d_in[7];
  const bf16* bv = (const bf16*)d_in[8];
  const bf16* shift_k = (const bf16*)d_in[9];
  const bf16* ssm_k = (const bf16*)d_in[10];
  const bf16* ssm_D = (const bf16*)d_in[11];
  const bf16* gate_w = (const bf16*)d_in[12];
  bf16* out = (bf16*)d_out;

  static void *pq = nullptr, *pk = nullptr, *pv = nullptr, *pctx = nullptr, *pb = nullptr, *pu = nullptr;
  static int max_clusters = 0;
  if (!s_encode) {
    void* fn = nullptr;
    cudaDriverEntryPointQueryResult qres;
    cudaGetDriverEntryPoint("cuTensorMapEncodeTiled", &fn, cudaEnableDefault, &qres);
    s_encode = (PFN_tmapEncode)fn;
    cudaGetSymbolAddress(&pq, g_q);
    cudaGetSymbolAddress(&pk, g_k);
    cudaGetSymbolAddress(&pv, g_v);
    cudaGetSymbolAddress(&pctx, g_ctx);
    cudaGetSymbolAddress(&pb, g_y2T);
    cudaGetSymbolAddress(&pu, g_kvT);
    cudaFuncSetAttribute(fused_kernel, cudaFuncAttributeMaxDynamicSharedMemorySize, SMEM_BYTES);
    cudaLaunchAttribute at[1];
    cudaLaunchConfig_t cfg = fused_cfg(at);
    if (cudaOccupancyMaxActiveClusters(&max_clusters, fused_kernel, &cfg) != cudaSuccess) max_clusters = 0;
  }

  Maps all = {};
  make_map_2d(&all.a[0], x, S_LEN, DM, 128);
  make_map_2d(&all.a[1], ckv, S_LEN, DC, 128);
  make_map_3d(&all.b[0], wq, DM, HDIM, 64, 4);
  make_map_3d(&all.b[1], wuk, DC, HDIM, 64, 4);
  make_map_3d(&all.b[2], wuv, DC, HDIM, 64, 4);
  make_map_2d(&all.c[0], pq, S_LEN, HDIM, 64);
  make_map_2d(&all.c[1], pk, S_LEN, HDIM, 64);
  make_map_2d(&all.c[2], pv, S_LEN, HDIM, 64);
  make_map_3d(&all.q, pq, S_LEN, HDIM, 128, 2);
  make_map_3d(&all.k, pk, S_LEN, HDIM, 128, 2);
  make_map_3d(&all.v, pv, S_LEN, HDIM, 128, 2);
  make_map_2d(&all.o, pctx, S_LEN, HDIM, 64);
  all.ssm_k = ssm_k;
  all.ssm_D = ssm_D;
  make_map_2d(&all.oa, pctx, S_LEN, HDIM, 128);
  make_map_2d(&all.ob, wo, HDIM, DM, 64);
  make_map_3d(&all.oc, out, S_LEN, DM, 16, 2);
  make_map_3d(&all.y, pb, DM, S_LEN, 16, 2);
  make_map_3d(&all.xs, x, S_LEN, DM, 16, 2);
  make_map_2d(&all.cu, pu, DM * 64, 32, 64);
  make_map_2d(&all.ch, ssm_k, DM * 64, 32, 64);

  make_map_2d(&all.bk, bk, S_LEN, DM, 35);
  make_map_2d(&all.bv, bv, S_LEN, DM, 32);
  for (int b = 0; b < 128; b++) {
    const int c = b >> 1, r = b & 1;
    const int G = c < 4 ? 0 : c < 36 ? (c - 4) % 8 : 1 + (c - 36) % 7;
    const int i = c < 4 ? 4 + c : c < 36 ? (c - 4) / 8 : 4 + (c - 36) / 7;
    all.id[b][0] = r + 2 * (i & 1) + 4 * (G & 3) + 16 * (i >> 1) + 64 * (G >> 2);
    all.id[b][1] = r + 2 * i + 16 * G;
    all.id[b][2] = r + 2 * G + 16 * i;
    all.id[b][3] = r + 2 * i == 15 ? 0x78 : 0xd8;
  }
  all.shift_k = shift_k;
  all.x = x;
  all.gate_w = gate_w;
  cudaLaunchAttribute at[1];
  cudaLaunchConfig_t cfg = fused_cfg(at);
  if (max_clusters >= 66) {
    cudaLaunchKernelEx(&cfg, fused_kernel, 7, x, wq, all);
  } else {
    for (int m = 1; m <= 4; m <<= 1) cudaLaunchKernelEx(&cfg, fused_kernel, m, x, wq, all);
  }
}
```

```cpp
#include <cuda_runtime.h>
#include <cuda_bf16.h>
#include <cuda.h>
#include <stdint.h>

typedef __nv_bfloat16 bf16;
#define INPLACE 3

constexpr int S_LEN = 2048;
constexpr int DM = 1024;
constexpr int NH = 32;
constexpr int HD = 128;
constexpr int DC = 512;
constexpr int HDIM = NH * HD;

__device__ __align__(1024) bf16 g_q[S_LEN * HDIM];
__device__ __align__(1024) bf16 g_k[S_LEN * HDIM];
__device__ __align__(1024) bf16 g_v[S_LEN * HDIM];
#define g_ctx g_q
__device__ __align__(1024) bf16 g_kvT[DM * S_LEN];
#define g_y2T g_kvT
__device__ __align__(1024) float g_gate[S_LEN];
enum { CNT_KV = 0, CNT_PREP = CNT_KV + 2, CNT_CTX, CNT_Y2 = CNT_CTX + 2, CNT_PREP1 = CNT_Y2 + 2, CNT_DONE, CNT_RANK, CNT_N };
__device__ unsigned int g_cnt[CNT_N * 32];
__device__ unsigned long long g_slot[128];

#define TL(k, i)
#define TL2(k, i)
#define TD(i)
#define CT(i)
#define GT(i)
#define GA(i)
#define ST(i)

__device__ __forceinline__ uint32_t smem_u32(const void* p) { return (uint32_t)__cvta_generic_to_shared(p); }

__device__ __forceinline__ void mbar_init(uint32_t bar, uint32_t count) {
  asm volatile("mbarrier.init.shared::cta.b64 [%0], %1;" ::"r"(bar), "r"(count));
}
__device__ __forceinline__ void mbar_expect_tx(uint32_t bar, uint32_t bytes) {
  asm volatile("mbarrier.arrive.expect_tx.shared::cta.b64 _, [%0], %1;" ::"r"(bar), "r"(bytes) : "memory");
}
__device__ __forceinline__ void mbar_arrive(uint32_t bar) {
  asm volatile("mbarrier.arrive.shared::cta.b64 _, [%0];" ::"r"(bar) : "memory");
}
__device__ __forceinline__ void mbar_wait(uint32_t bar, uint32_t parity) {
  uint32_t done;
  uint32_t spins = 0;
  do {
    asm volatile(
        "{\n.reg .pred p;\n"
        "mbarrier.try_wait.parity.shared::cta.b64 p, [%1], %2;\n"
        "selp.u32 %0, 1, 0, p;\n}\n"
        : "=r"(done)
        : "r"(bar), "r"(parity)
        : "memory");
    if (++spins > (1u << 22)) break;
  } while (!done);
}
__device__ __forceinline__ bool mbar_try(uint32_t bar, uint32_t parity) {
  uint32_t done;
  asm volatile(
      "{\n.reg .pred p;\n"
      "mbarrier.try_wait.parity.shared::cta.b64 p, [%1], %2;\n"
      "selp.u32 %0, 1, 0, p;\n}\n"
      : "=r"(done)
      : "r"(bar), "r"(parity)
      : "memory");
  return done != 0;
}
__device__ __forceinline__ bool mbar_test(uint32_t bar, uint32_t parity) {
  uint32_t done;
  asm volatile(
      "{\n.reg .pred p;\n"
      "mbarrier.test_wait.parity.shared::cta.b64 p, [%1], %2;\n"
      "selp.u32 %0, 1, 0, p;\n}\n"
      : "=r"(done)
      : "r"(bar), "r"(parity)
      : "memory");
  return done != 0;
}
__device__ __forceinline__ bool elect_one() {
  uint32_t pred;
  asm volatile("{\n.reg .pred p;\nelect.sync _|p, 0xffffffff;\nselp.u32 %0, 1, 0, p;\n}\n" : "=r"(pred));
  return pred != 0;
}
__device__ __forceinline__ void mbar_arrive_if(uint32_t bar, bool pred) {
  asm volatile(
      "{\n.reg .pred p;\nsetp.ne.b32 p, %1, 0;\n"
      "@p mbarrier.arrive.shared::cta.b64 _, [%0];\n}\n" ::"r"(bar),
      "r"((uint32_t)pred)
      : "memory");
}
__device__ __forceinline__ void mbar_wait_sleep(uint32_t bar, uint32_t parity) {
  uint32_t done;
  uint32_t spins = 0;
  do {
    asm volatile(
        "{\n.reg .pred p;\n"
        "mbarrier.try_wait.parity.shared::cta.b64 p, [%1], %2, %3;\n"
        "selp.u32 %0, 1, 0, p;\n}\n"
        : "=r"(done)
        : "r"(bar), "r"(parity), "r"(20000u)
        : "memory");
    if (++spins > (1u << 16)) break;
  } while (!done);
}
__device__ __forceinline__ void fence_barrier_init() {
  asm volatile("fence.mbarrier_init.release.cluster;" ::: "memory");
}
__device__ __forceinline__ void fence_proxy_async() {
  asm volatile("fence.proxy.async.shared::cta;" ::: "memory");
}
__device__ __forceinline__ void named_bar_sync(int id, int nthreads) {
  asm volatile("bar.sync %0, %1;" ::"r"(id), "r"(nthreads) : "memory");
}
__device__ __forceinline__ void named_bar_arrive(int id, int nthreads) {
  asm volatile("bar.arrive %0, %1;" ::"r"(id), "r"(nthreads) : "memory");
}
__device__ __forceinline__ void tma_load_2d(uint32_t dst, const CUtensorMap* m, uint32_t bar, int c0, int c1) {
  asm volatile(
      "cp.async.bulk.tensor.2d.shared::cluster.global.mbarrier::complete_tx::bytes [%0], [%1, {%3, %4}], [%2];" ::"r"(dst),
      "l"(reinterpret_cast<uint64_t>(m)), "r"(bar), "r"(c0), "r"(c1)
      : "memory");
}
__device__ __forceinline__ void tma_load_3d(uint32_t dst, const CUtensorMap* m, uint32_t bar, int c0, int c1, int c2) {
  asm volatile(
      "cp.async.bulk.tensor.3d.shared::cluster.global.mbarrier::complete_tx::bytes [%0], [%1, {%3, %4, %5}], [%2];" ::"r"(dst),
      "l"(reinterpret_cast<uint64_t>(m)), "r"(bar), "r"(c0), "r"(c1), "r"(c2)
      : "memory");
}
__device__ __forceinline__ void tma_store_2d(const CUtensorMap* m, uint32_t src, int c0, int c1) {
  asm volatile("cp.async.bulk.tensor.2d.global.shared::cta.bulk_group [%0, {%2, %3}], [%1];" ::"l"(
                   reinterpret_cast<uint64_t>(m)),
               "r"(src), "r"(c0), "r"(c1)
               : "memory");
}
__device__ __forceinline__ void tma_load_2d_mc(uint32_t dst, const CUtensorMap* m, uint32_t bar, int c0, int c1,
                                               uint16_t mask) {
  asm volatile(
      "cp.async.bulk.tensor.2d.shared::cluster.global.mbarrier::complete_tx::bytes.multicast::cluster [%0], [%1, {%3, "
      "%4}], [%2], %5;" ::"r"(dst),
      "l"(reinterpret_cast<uint64_t>(m)), "r"(bar), "r"(c0), "r"(c1), "h"(mask)
      : "memory");
}
__device__ __forceinline__ void mbar_arrive_cluster_if(uint32_t bar, uint32_t cta, bool pred) {
  asm volatile(
      "{\n.reg .b32 ra;\n.reg .pred p;\nsetp.ne.b32 p, %2, 0;\n"
      "mapa.shared::cluster.u32 ra, %0, %1;\n"
      "@p mbarrier.arrive.shared::cluster.b64 _, [ra];\n}\n" ::"r"(bar),
      "r"(cta), "r"((uint32_t)pred)
      : "memory");
}
__device__ __forceinline__ uint64_t policy_evict_first() {
  uint64_t pol;
  asm volatile("createpolicy.fractional.L2::evict_first.b64 %0, 1.0;" : "=l"(pol));
  return pol;
}
__device__ __forceinline__ void tma_load_2d_hint(uint32_t dst, const CUtensorMap* m, uint32_t bar, int c0, int c1,
                                                 uint64_t pol) {
  asm volatile(
      "cp.async.bulk.tensor.2d.shared::cluster.global.mbarrier::complete_tx::bytes.L2::cache_hint [%0], [%1, {%3, %4}], "
      "[%2], %5;" ::"r"(dst),
      "l"(reinterpret_cast<uint64_t>(m)), "r"(bar), "r"(c0), "r"(c1), "l"(pol)
      : "memory");
}
__device__ __forceinline__ void tma_load_3d_hint(uint32_t dst, const CUtensorMap* m, uint32_t bar, int c0, int c1,
                                                 int c2, uint64_t pol) {
  asm volatile(
      "cp.async.bulk.tensor.3d.shared::cluster.global.mbarrier::complete_tx::bytes.L2::cache_hint [%0], [%1, {%3, %4, "
      "%5}], [%2], %6;" ::"r"(dst),
      "l"(reinterpret_cast<uint64_t>(m)), "r"(bar), "r"(c0), "r"(c1), "r"(c2), "l"(pol)
      : "memory");
}
__device__ __forceinline__ void cnt_signal_release(int which, uint32_t n) {
  asm volatile("red.release.gpu.global.add.u32 [%0], %1;" ::"l"(g_cnt + which * 32), "r"(n) : "memory");
}
__device__ __forceinline__ bool cnt_wait(int which, uint32_t target, uint32_t spins = 0) {
  uint32_t v;
  while (true) {
    asm volatile("ld.acquire.gpu.global.u32 %0, [%1];" : "=r"(v) : "l"(g_cnt + which * 32) : "memory");
    if (v >= target || ++spins > (1u << 18)) break;
    __nanosleep(64);
  }
  asm volatile("fence.proxy.async.global;" ::: "memory");
  return v >= target;
}
__device__ __forceinline__ void tma_store_3d(const CUtensorMap* m, uint32_t src, int c0, int c1, int c2) {
  asm volatile("cp.async.bulk.tensor.3d.global.shared::cta.bulk_group [%0, {%2, %3, %4}], [%1];" ::"l"(
                   reinterpret_cast<uint64_t>(m)),
               "r"(src), "r"(c0), "r"(c1), "r"(c2)
               : "memory");
}
__device__ __forceinline__ void tma_store_commit() { asm volatile("cp.async.bulk.commit_group;" ::: "memory"); }
template <int N>
__device__ __forceinline__ void tma_store_wait_read() {
  asm volatile("cp.async.bulk.wait_group.read %0;" ::"n"(N) : "memory");
}
template <int N>
__device__ __forceinline__ void tma_store_wait() {
  asm volatile("cp.async.bulk.wait_group %0;" ::"n"(N) : "memory");
}
__device__ __forceinline__ void wgmma_fence() { asm volatile("wgmma.fence.sync.aligned;" ::: "memory"); }
__device__ __forceinline__ void wgmma_commit() { asm volatile("wgmma.commit_group.sync.aligned;" ::: "memory"); }
template <int N>
__device__ __forceinline__ void wgmma_wait() {
  asm volatile("wgmma.wait_group.sync.aligned %0;" ::"n"(N) : "memory");
}
template <int R>
__device__ __forceinline__ void reg_alloc() { asm volatile("setmaxnreg.inc.sync.aligned.u32 %0;" ::"n"(R)); }
template <int R>
__device__ __forceinline__ void reg_dealloc() { asm volatile("setmaxnreg.dec.sync.aligned.u32 %0;" ::"n"(R)); }

__device__ __forceinline__ void stmatrix_x4(uint32_t addr, uint32_t r0, uint32_t r1, uint32_t r2, uint32_t r3) {
  asm volatile("stmatrix.sync.aligned.m8n8.x4.shared.b16 [%0], {%1, %2, %3, %4};" ::"r"(addr), "r"(r0), "r"(r1),
               "r"(r2), "r"(r3)
               : "memory");
}
__device__ __forceinline__ uint32_t pack_bf16(float lo, float hi) {
  uint32_t r;
  asm("cvt.rn.bf16x2.f32 %0, %1, %2;" : "=r"(r) : "f"(hi), "f"(lo));
  return r;
}
__device__ __forceinline__ float bf16_round(float x) { return __bfloat162float(__float2bfloat16_rn(x)); }
__device__ __forceinline__ float bf_lo(uint32_t v) { return __uint_as_float(v << 16); }
__device__ __forceinline__ float bf_hi(uint32_t v) { return __uint_as_float(v & 0xffff0000u); }
__device__ __forceinline__ uint4 lds128(uint32_t a) {
  uint4 v;
  asm volatile("ld.shared.v4.u32 {%0, %1, %2, %3}, [%4];" : "=r"(v.x), "=r"(v.y), "=r"(v.z), "=r"(v.w) : "r"(a));
  return v;
}
__device__ __forceinline__ void sts128(uint32_t a, uint4 v) {
  asm volatile("st.shared.v4.u32 [%0], {%1, %2, %3, %4};" ::"r"(a), "r"(v.x), "r"(v.y), "r"(v.z), "r"(v.w) : "memory");
}
__device__ __forceinline__ uint32_t mul_bf2(uint32_t a, uint32_t b) {
  uint32_t r;
  asm("mul.rn.bf16x2 %0, %1, %2;" : "=r"(r) : "r"(a), "r"(b));
  return r;
}
__device__ __forceinline__ float ex2(float x) {
  float y;
  asm("ex2.approx.ftz.f32 %0, %1;" : "=f"(y) : "f"(x));
  return y;
}
__device__ __forceinline__ float rcp(float x) {
  float y;
  asm("rcp.approx.ftz.f32 %0, %1;" : "=f"(y) : "f"(x));
  return y;
}
template <int N>
__device__ __forceinline__ void fence_regs(float (&r)[N]) {
#pragma unroll
  for (int i = 0; i < N; i++) asm volatile("" : "+f"(r[i])::"memory");
}

template <int N>
__device__ __forceinline__ void undef_regs(float (&r)[N]) {
#pragma unroll
  for (int i = 0; i < N; i++) asm volatile("" : "=f"(r[i]));
}
template <int N>
__device__ __forceinline__ void fence_regs_u(uint32_t (&r)[N]) {
#pragma unroll
  for (int i = 0; i < N; i++) asm volatile("" : "+r"(r[i])::"memory");
}

constexpr uint64_t DESC_SW128 = 1ull << 62;
__device__ __forceinline__ uint64_t make_desc(uint32_t addr, uint32_t lbo_bytes, uint32_t sbo_bytes, uint64_t swz) {
  return (uint64_t)((addr & 0x3FFFF) >> 4) | ((uint64_t)((lbo_bytes & 0x3FFFF) >> 4) << 16) |
         ((uint64_t)((sbo_bytes & 0x3FFFF) >> 4) << 32) | swz;
}

__device__ __forceinline__ uint64_t desc_add(uint64_t d, uint32_t off16) {
  return (d & 0xFFFFFFFF00000000ull) | (uint64_t)((uint32_t)d + off16);
}

__device__ __forceinline__ void wgmma_m64n256_ss_tb(float (&d)[128], uint64_t da, uint64_t db, int sd) {
  asm volatile(
    "{\n.reg .pred p;\nsetp.ne.b32 p, %130, 0;\n"
    "wgmma.mma_async.sync.aligned.m64n256k16.f32.bf16.bf16 "
    "{%0, %1, %2, %3, %4, %5, %6, %7, %8, %9, %10, %11, %12, %13, %14, %15, %16, %17, %18, %19, %20, %21, %22, %23, %24, %25, %26, %27, %28, %29, %30, %31, %32, %33, %34, %35, %36, %37, %38, %39, %40, %41, %42, %43, %44, %45, %46, %47, %48, %49, %50, %51, %52, %53, %54, %55, %56, %57, %58, %59, %60, %61, %62, %63, %64, %65, %66, %67, %68, %69, %70, %71, %72, %73, %74, %75, %76, %77, %78, %79, %80, %81, %82, %83, %84, %85, %86, %87, %88, %89, %90, %91, %92, %93, %94, %95, %96, %97, %98, %99, %100, %101, %102, %103, %104, %105, %106, %107, %108, %109, %110, %111, %112, %113, %114, %115, %116, %117, %118, %119, %120, %121, %122, %123, %124, %125, %126, %127}, %128, %129, p, 1, 1, 0, 1;\n}\n"
    : "+f"(d[0]), "+f"(d[1]), "+f"(d[2]), "+f"(d[3]), "+f"(d[4]), "+f"(d[5]), "+f"(d[6]), "+f"(d[7]), "+f"(d[8]), "+f"(d[9]), "+f"(d[10]), "+f"(d[11]), "+f"(d[12]), "+f"(d[13]), "+f"(d[14]), "+f"(d[15]), "+f"(d[16]), "+f"(d[17]), "+f"(d[18]), "+f"(d[19]), "+f"(d[20]), "+f"(d[21]), "+f"(d[22]), "+f"(d[23]), "+f"(d[24]), "+f"(d[25]), "+f"(d[26]), "+f"(d[27]), "+f"(d[28]), "+f"(d[29]), "+f"(d[30]), "+f"(d[31]), "+f"(d[32]), "+f"(d[33]), "+f"(d[34]), "+f"(d[35]), "+f"(d[36]), "+f"(d[37]), "+f"(d[38]), "+f"(d[39]), "+f"(d[40]), "+f"(d[41]), "+f"(d[42]), "+f"(d[43]), "+f"(d[44]), "+f"(d[45]), "+f"(d[46]), "+f"(d[47]), "+f"(d[48]), "+f"(d[49]), "+f"(d[50]), "+f"(d[51]), "+f"(d[52]), "+f"(d[53]), "+f"(d[54]), "+f"(d[55]), "+f"(d[56]), "+f"(d[57]), "+f"(d[58]), "+f"(d[59]), "+f"(d[60]), "+f"(d[61]), "+f"(d[62]), "+f"(d[63]), "+f"(d[64]), "+f"(d[65]), "+f"(d[66]), "+f"(d[67]), "+f"(d[68]), "+f"(d[69]), "+f"(d[70]), "+f"(d[71]), "+f"(d[72]), "+f"(d[73]), "+f"(d[74]), "+f"(d[75]), "+f"(d[76]), "+f"(d[77]), "+f"(d[78]), "+f"(d[79]), "+f"(d[80]), "+f"(d[81]), "+f"(d[82]), "+f"(d[83]), "+f"(d[84]), "+f"(d[85]), "+f"(d[86]), "+f"(d[87]), "+f"(d[88]), "+f"(d[89]), "+f"(d[90]), "+f"(d[91]), "+f"(d[92]), "+f"(d[93]), "+f"(d[94]), "+f"(d[95]), "+f"(d[96]), "+f"(d[97]), "+f"(d[98]), "+f"(d[99]), "+f"(d[100]), "+f"(d[101]), "+f"(d[102]), "+f"(d[103]), "+f"(d[104]), "+f"(d[105]), "+f"(d[106]), "+f"(d[107]), "+f"(d[108]), "+f"(d[109]), "+f"(d[110]), "+f"(d[111]), "+f"(d[112]), "+f"(d[113]), "+f"(d[114]), "+f"(d[115]), "+f"(d[116]), "+f"(d[117]), "+f"(d[118]), "+f"(d[119]), "+f"(d[120]), "+f"(d[121]), "+f"(d[122]), "+f"(d[123]), "+f"(d[124]), "+f"(d[125]), "+f"(d[126]), "+f"(d[127])
    : "l"(da), "l"(db), "r"(sd));
}

__device__ __forceinline__ void wgmma_m64n128_ss(float (&d)[64], uint64_t da, uint64_t db, int sd) {
  asm volatile(
    "{\n.reg .pred p;\nsetp.ne.b32 p, %66, 0;\n"
    "wgmma.mma_async.sync.aligned.m64n128k16.f32.bf16.bf16 "
    "{%0, %1, %2, %3, %4, %5, %6, %7, %8, %9, %10, %11, %12, %13, %14, %15, %16, %17, %18, %19, %20, %21, %22, %23, %24, %25, %26, %27, %28, %29, %30, %31, %32, %33, %34, %35, %36, %37, %38, %39, %40, %41, %42, %43, %44, %45, %46, %47, %48, %49, %50, %51, %52, %53, %54, %55, %56, %57, %58, %59, %60, %61, %62, %63}, %64, %65, p, 1, 1, 0, 0;\n}\n"
    : "+f"(d[0]), "+f"(d[1]), "+f"(d[2]), "+f"(d[3]), "+f"(d[4]), "+f"(d[5]), "+f"(d[6]), "+f"(d[7]), "+f"(d[8]), "+f"(d[9]), "+f"(d[10]), "+f"(d[11]), "+f"(d[12]), "+f"(d[13]), "+f"(d[14]), "+f"(d[15]), "+f"(d[16]), "+f"(d[17]), "+f"(d[18]), "+f"(d[19]), "+f"(d[20]), "+f"(d[21]), "+f"(d[22]), "+f"(d[23]), "+f"(d[24]), "+f"(d[25]), "+f"(d[26]), "+f"(d[27]), "+f"(d[28]), "+f"(d[29]), "+f"(d[30]), "+f"(d[31]), "+f"(d[32]), "+f"(d[33]), "+f"(d[34]), "+f"(d[35]), "+f"(d[36]), "+f"(d[37]), "+f"(d[38]), "+f"(d[39]), "+f"(d[40]), "+f"(d[41]), "+f"(d[42]), "+f"(d[43]), "+f"(d[44]), "+f"(d[45]), "+f"(d[46]), "+f"(d[47]), "+f"(d[48]), "+f"(d[49]), "+f"(d[50]), "+f"(d[51]), "+f"(d[52]), "+f"(d[53]), "+f"(d[54]), "+f"(d[55]), "+f"(d[56]), "+f"(d[57]), "+f"(d[58]), "+f"(d[59]), "+f"(d[60]), "+f"(d[61]), "+f"(d[62]), "+f"(d[63])
    : "l"(da), "l"(db), "r"(sd));
}

__device__ __forceinline__ void wgmma_m64n128_ss_tb(float (&d)[64], uint64_t da, uint64_t db, int sd) {
  asm volatile(
    "{\n.reg .pred p;\nsetp.ne.b32 p, %66, 0;\n"
    "wgmma.mma_async.sync.aligned.m64n128k16.f32.bf16.bf16 "
    "{%0, %1, %2, %3, %4, %5, %6, %7, %8, %9, %10, %11, %12, %13, %14, %15, %16, %17, %18, %19, %20, %21, %22, %23, %24, %25, %26, %27, %28, %29, %30, %31, %32, %33, %34, %35, %36, %37, %38, %39, %40, %41, %42, %43, %44, %45, %46, %47, %48, %49, %50, %51, %52, %53, %54, %55, %56, %57, %58, %59, %60, %61, %62, %63}, %64, %65, p, 1, 1, 0, 1;\n}\n"
    : "+f"(d[0]), "+f"(d[1]), "+f"(d[2]), "+f"(d[3]), "+f"(d[4]), "+f"(d[5]), "+f"(d[6]), "+f"(d[7]), "+f"(d[8]), "+f"(d[9]), "+f"(d[10]), "+f"(d[11]), "+f"(d[12]), "+f"(d[13]), "+f"(d[14]), "+f"(d[15]), "+f"(d[16]), "+f"(d[17]), "+f"(d[18]), "+f"(d[19]), "+f"(d[20]), "+f"(d[21]), "+f"(d[22]), "+f"(d[23]), "+f"(d[24]), "+f"(d[25]), "+f"(d[26]), "+f"(d[27]), "+f"(d[28]), "+f"(d[29]), "+f"(d[30]), "+f"(d[31]), "+f"(d[32]), "+f"(d[33]), "+f"(d[34]), "+f"(d[35]), "+f"(d[36]), "+f"(d[37]), "+f"(d[38]), "+f"(d[39]), "+f"(d[40]), "+f"(d[41]), "+f"(d[42]), "+f"(d[43]), "+f"(d[44]), "+f"(d[45]), "+f"(d[46]), "+f"(d[47]), "+f"(d[48]), "+f"(d[49]), "+f"(d[50]), "+f"(d[51]), "+f"(d[52]), "+f"(d[53]), "+f"(d[54]), "+f"(d[55]), "+f"(d[56]), "+f"(d[57]), "+f"(d[58]), "+f"(d[59]), "+f"(d[60]), "+f"(d[61]), "+f"(d[62]), "+f"(d[63])
    : "l"(da), "l"(db), "r"(sd));
}

template <int TB>
__device__ __forceinline__ void wgmma_m64n128_rs(float* d, uint32_t a0, uint32_t a1, uint32_t a2, uint32_t a3, uint64_t db, int sd) {
  asm volatile(
    "{\n.reg .pred p;\nsetp.ne.b32 p, %69, 0;\n"
    "wgmma.mma_async.sync.aligned.m64n128k16.f32.bf16.bf16 "
    "{%0, %1, %2, %3, %4, %5, %6, %7, %8, %9, %10, %11, %12, %13, %14, %15, %16, %17, %18, %19, %20, %21, %22, %23, %24, %25, %26, %27, %28, %29, %30, %31, %32, %33, %34, %35, %36, %37, %38, %39, %40, %41, %42, %43, %44, %45, %46, %47, %48, %49, %50, %51, %52, %53, %54, %55, %56, %57, %58, %59, %60, %61, %62, %63}, {%64, %65, %66, %67}, %68, p, 1, 1, %70;\n}\n"
    : "+f"(d[0]), "+f"(d[1]), "+f"(d[2]), "+f"(d[3]), "+f"(d[4]), "+f"(d[5]), "+f"(d[6]), "+f"(d[7]), "+f"(d[8]), "+f"(d[9]), "+f"(d[10]), "+f"(d[11]), "+f"(d[12]), "+f"(d[13]), "+f"(d[14]), "+f"(d[15]), "+f"(d[16]), "+f"(d[17]), "+f"(d[18]), "+f"(d[19]), "+f"(d[20]), "+f"(d[21]), "+f"(d[22]), "+f"(d[23]), "+f"(d[24]), "+f"(d[25]), "+f"(d[26]), "+f"(d[27]), "+f"(d[28]), "+f"(d[29]), "+f"(d[30]), "+f"(d[31]), "+f"(d[32]), "+f"(d[33]), "+f"(d[34]), "+f"(d[35]), "+f"(d[36]), "+f"(d[37]), "+f"(d[38]), "+f"(d[39]), "+f"(d[40]), "+f"(d[41]), "+f"(d[42]), "+f"(d[43]), "+f"(d[44]), "+f"(d[45]), "+f"(d[46]), "+f"(d[47]), "+f"(d[48]), "+f"(d[49]), "+f"(d[50]), "+f"(d[51]), "+f"(d[52]), "+f"(d[53]), "+f"(d[54]), "+f"(d[55]), "+f"(d[56]), "+f"(d[57]), "+f"(d[58]), "+f"(d[59]), "+f"(d[60]), "+f"(d[61]), "+f"(d[62]), "+f"(d[63])
    : "r"(a0), "r"(a1), "r"(a2), "r"(a3), "l"(db), "r"(sd), "n"(TB));
}

__device__ __forceinline__ void wgmma_m64n64_rs_tb(float (&d)[32], const uint32_t (&a)[4], uint64_t db, int sd) {
  asm volatile(
    "{\n.reg .pred p;\nsetp.ne.b32 p, %37, 0;\n"
    "wgmma.mma_async.sync.aligned.m64n64k16.f32.bf16.bf16 "
    "{%0, %1, %2, %3, %4, %5, %6, %7, %8, %9, %10, %11, %12, %13, %14, %15, %16, %17, %18, %19, %20, %21, %22, %23, %24, %25, %26, %27, %28, %29, %30, %31}, {%32, %33, %34, %35}, %36, p, 1, 1, 1;\n}\n"
    : "+f"(d[0]), "+f"(d[1]), "+f"(d[2]), "+f"(d[3]), "+f"(d[4]), "+f"(d[5]), "+f"(d[6]), "+f"(d[7]), "+f"(d[8]), "+f"(d[9]), "+f"(d[10]), "+f"(d[11]), "+f"(d[12]), "+f"(d[13]), "+f"(d[14]), "+f"(d[15]), "+f"(d[16]), "+f"(d[17]), "+f"(d[18]), "+f"(d[19]), "+f"(d[20]), "+f"(d[21]), "+f"(d[22]), "+f"(d[23]), "+f"(d[24]), "+f"(d[25]), "+f"(d[26]), "+f"(d[27]), "+f"(d[28]), "+f"(d[29]), "+f"(d[30]), "+f"(d[31])
    : "r"(a[0]), "r"(a[1]), "r"(a[2]), "r"(a[3]), "l"(db), "r"(sd));
}

__device__ __forceinline__ void wgmma_m64n32_rs_tb(float (&d)[16], const uint32_t (&a)[4], uint64_t db, int sd) {
  asm volatile(
    "{\n.reg .pred p;\nsetp.ne.b32 p, %21, 0;\n"
    "wgmma.mma_async.sync.aligned.m64n32k16.f32.bf16.bf16 "
    "{%0, %1, %2, %3, %4, %5, %6, %7, %8, %9, %10, %11, %12, %13, %14, %15}, {%16, %17, %18, %19}, %20, p, 1, 1, 1;\n}\n"
    : "+f"(d[0]), "+f"(d[1]), "+f"(d[2]), "+f"(d[3]), "+f"(d[4]), "+f"(d[5]), "+f"(d[6]), "+f"(d[7]), "+f"(d[8]), "+f"(d[9]), "+f"(d[10]), "+f"(d[11]), "+f"(d[12]), "+f"(d[13]), "+f"(d[14]), "+f"(d[15])
    : "r"(a[0]), "r"(a[1]), "r"(a[2]), "r"(a[3]), "l"(db), "r"(sd));
}

constexpr int G_STAGES = 4;
constexpr int G_A_BYTES = 128 * 64 * 2;
constexpr int G_B_BYTES = 256 * 64 * 2;
constexpr int G_STAGE_BYTES = G_A_BYTES + G_B_BYTES;
constexpr int G_STG_OFF = G_STAGES * G_STAGE_BYTES;
constexpr int BAR_OFF = G_STG_OFF + 32768 + 2048;
constexpr int SMEM_BYTES = BAR_OFF + 1024;
constexpr int B_GFULL = 0, B_GEMPTY = 32, B_SEEN = 64, B_PFULL = 224;
constexpr int B_KFULL = 80, B_KEMPTY = 96, B_VFULL = 112, B_VEMPTY = 128, B_QFULL = 144, B_QEMPTY = 160,
              B_QDONE = 184;
constexpr int B_CFULL = 192;
constexpr int B_OFREE = 256, B_OFULL = 272, B_OEMPTY = 320, B_OY = 368, B_OY2 = 384, B_OE = 768;
constexpr int B_DEAL = 312, B_DEAL2 = 360, B_LIST = 640, B_PAIR = 504;
constexpr int B_SFULL = 392, B_SFREE = 424, B_PEND = 456, B_SCMD = 512;

#define PHASE_PROLOGUE                                                                \
  uint32_t tid, rt_zero;                                                              \
  asm volatile("mov.u32 %0, %%tid.x;" : "=r"(tid));                                   \
  asm volatile("mov.u32 %0, %%nctaid.y;" : "=r"(rt_zero));                            \
  asm volatile("" : "+r"(smem0));                                                     \
  rt_zero = __shfl_sync(0xffffffffu, rt_zero >> 8, 0);   \
  const uint32_t sbase = __shfl_sync(0xffffffffu, smem0, 0);                          \
  const uint32_t bar = sbase + BAR_OFF;                                               \
  const int wg = __shfl_sync(0xffffffffu, tid >> 7, 0);                               \
  const int warp = (tid >> 5) & 3, lane = tid & 31, wtid = tid & 127;                 \
  (void)rt_zero; (void)bar; (void)warp; (void)lane; (void)wtid;

#define PHASE_GIVEN PHASE_GIVEN_(0)
#define PHASE_GIVEN_(z)                                                               \
  uint32_t tid;                                                                       \
  asm volatile("mov.u32 %0, %%tid.x;" : "=r"(tid));                                   \
  tid |= z;                               \
  const uint32_t bar = sbase + BAR_OFF;                                               \
  const int warp = (tid >> 5) & 3, lane = tid & 31, wtid = tid & 127;

enum { ST_BOX1, ST_BOX2, ST_BOX2Q, ST_BOX2L };
__device__ __forceinline__ void st_cmd(uint32_t bar, int wg, int wtid, uint32_t n, int kind, const void* dst,
                                       uint32_t src, int c0, int c1, int sig, uint32_t lazy = 0) {
  if (wtid == 0) {
    const uint32_t c = bar + B_SCMD + wg * 64 + (n & 1) * 32;
    const uint64_t d = reinterpret_cast<uint64_t>(dst);
    sts128(c, make_uint4(kind, src, c0, c1));
    sts128(c + 16, make_uint4((uint32_t)d, (uint32_t)(d >> 32), sig, lazy));
  }
}
__device__ __forceinline__ void st_go(uint32_t bar, int wg, int wtid, uint32_t n) {
  fence_proxy_async();
  __syncwarp();
  mbar_arrive_if(bar + B_SFULL + wg * 16 + (n & 1) * 8, (wtid & 31) == 0);
}
__device__ __forceinline__ void st_post(uint32_t bar, int wg, int wtid, uint32_t n, int kind, const void* dst,
                                        uint32_t src, int c0, int c1, int sig, uint32_t lazy = 0) {
  st_cmd(bar, wg, wtid, n, kind, dst, src, c0, c1, sig, lazy);
  st_go(bar, wg, wtid, n);
}
__device__ __forceinline__ void st_wait(uint32_t bar, int wg, uint32_t n) {
  const uint32_t b = bar + B_SFREE + wg * 16 + (n & 1) * 8;
  if (!mbar_try(b, ~(n >> 1) & 1)) mbar_wait(b, ~(n >> 1) & 1);
}
__device__ __forceinline__ void note(uint32_t bar, uint32_t cnt) {
  asm volatile("red.release.cta.shared.add.u32 [%0], 1;" ::"r"(bar + B_PEND + 4 * cnt) : "memory");
}
#define LAZY_NS 250
#define DEAL_NS 400
#define DEAL_NS2 1250
constexpr uint32_t C_NONE = 0x10000;
__device__ __forceinline__ void deal(uint32_t bar, uint32_t r, uint32_t t, uint32_t own) {
  uint64_t p;
  uint32_t spins = 0;
  while (true) {
    asm volatile("ld.relaxed.gpu.global.u64 %0, [%1];" : "=l"(p) : "l"(g_slot + 127 - r) : "memory");
    if (p || ++spins > (1u << 18)) break;
    __nanosleep(100);
  }
  const uint32_t pc = (uint32_t)p;
  int dt = (uint32_t)(p >> 32) - t;
  if (r >= 64) {
    sts128(bar + B_LIST, make_uint4(-dt > DEAL_NS2 ? C_NONE : own - 16, -dt > DEAL_NS ? C_NONE : own, C_NONE, C_NONE));
    mbar_arrive(bar + B_DEAL);
    dt = 0;
  }
  sts128(bar + B_LIST + 16, make_uint4(dt > DEAL_NS ? pc : C_NONE, dt > DEAL_NS2 ? pc - 16 : C_NONE, C_NONE, C_NONE));
  mbar_arrive(bar + B_DEAL2);
}
__device__ __forceinline__ void store_agent(uint32_t bar, int wg, uint32_t last_ch, uint32_t n_end) {
  mbar_arrive(bar + B_SFREE + wg * 16);
  mbar_arrive(bar + B_SFREE + wg * 16 + 8);
  bool more = true;
  for (uint32_t n = 0; n < n_end && more; n++) {
    mbar_wait_sleep(bar + B_SFULL + wg * 16 + (n & 1) * 8, (n >> 1) & 1);
    const uint4 c = lds128(bar + B_SCMD + wg * 64 + (n & 1) * 32);
    const uint4 d = lds128(bar + B_SCMD + wg * 64 + (n & 1) * 32 + 16);
    uint32_t t;
    asm volatile("mov.u32 %0, %%globaltimer_lo;" : "=r"(t));
    uint32_t r = 0, tp = t;
    if (c.x == ST_BOX2L && last_ch) {
      mbar_expect_tx(bar + B_PAIR, 4);
      asm volatile(
          "{\n.reg .b32 ra;\nmapa.shared::cluster.u32 ra, %0, %1;\n"
          "st.async.weak.shared::cluster.mbarrier::complete_tx::bytes.u32 [ra + 224], %2, [ra];\n}\n" ::"r"(bar + B_PAIR),
          "r"(~blockIdx.x & 1), "r"(t)
          : "memory");
      mbar_wait_sleep(bar + B_PAIR, 0);
      r = atomicAdd(g_cnt + CNT_RANK * 32, 1u) & 127;
      asm volatile("ld.shared.u32 %0, [%1];" : "=r"(tp) : "r"(bar + B_PAIR + 224) : "memory");
      if ((int)(tp - t) < 0) tp = t;
      asm volatile("st.relaxed.gpu.global.u64 [%0], %1;" ::"l"(g_slot + r), "l"(((uint64_t)tp << 32) | last_ch) : "memory");
      if (r < 64) {
        sts128(bar + B_LIST, make_uint4(last_ch - 16, last_ch, C_NONE, C_NONE));
        mbar_arrive(bar + B_DEAL);
      } else {
        deal(bar, r, tp, last_ch);
      }
    }
    for (uint32_t t1 = t; d.w && t1 - t < (2 * d.w + wg) * LAZY_NS;) {
      __nanosleep(200);
      asm volatile("mov.u32 %0, %%globaltimer_lo;" : "=r"(t1));
    }
    const CUtensorMap* dst = reinterpret_cast<const CUtensorMap*>((uint64_t)d.x | ((uint64_t)d.y << 32));
    tma_store_2d(dst, c.y, c.z, c.w);
    if (c.x >= ST_BOX2) tma_store_2d(dst, c.y + 8192, c.z + 64, c.w);
    tma_store_commit();
    tma_store_wait_read<0>();
    mbar_arrive(bar + B_SFREE + wg * 16 + (n & 1) * 8);
    if (c.x == ST_BOX2L) mbar_arrive(bar + B_OFREE + 8 * wg);
    if ((int)d.z >= 0) {
      tma_store_wait<0>();
      if (d.z == 0) { TD(6) }
      asm volatile("fence.proxy.async.global;" ::: "memory");
      if (c.x == ST_BOX2Q) mbar_arrive(bar + B_QDONE);
      else note(bar, d.z);
      if (c.x == ST_BOX2L) {
        note(bar, CNT_DONE);
        more = false;
        if (last_ch && r < 64) deal(bar, r, tp, last_ch);
      }
    }
  }
  if (more) note(bar, CNT_DONE);
}

struct Maps {
  const bf16 *shift_k, *x, *gate_w, *ssm_k, *ssm_D;
  uint8_t id[128][4];
  CUtensorMap a[2];
  CUtensorMap b[3];
  CUtensorMap c[3];
  CUtensorMap bk, bv;
  CUtensorMap q, k, v, o;
  CUtensorMap oa, ob, oc;
  CUtensorMap y, xs;
  CUtensorMap cu, ch;
};

constexpr int P_SLOT = 67 * 128, P_V = 35 * 128;
__device__ __forceinline__ void ldsm4t(uint32_t (&r)[4], uint32_t a) {
  asm volatile("ldmatrix.sync.aligned.m8n8.x4.trans.shared.b16 {%0, %1, %2, %3}, [%4];"
               : "=r"(r[0]), "=r"(r[1]), "=r"(r[2]), "=r"(r[3])
               : "r"(a));
}
__device__ __forceinline__ uint32_t fma_bf2(uint32_t a, uint32_t b, uint32_t c) {
  uint32_t r;
  asm("fma.rn.bf16x2 %0, %1, %2, %3;" : "=r"(r) : "r"(a), "r"(b), "r"(c));
  return r;
}
__device__ __forceinline__ void prep_agent(const Maps& maps, uint32_t sbase, int w, int lane) {
  const uint32_t bar = sbase + BAR_OFF, pb = bar + B_PFULL + w * 16;
  const int d0 = (blockIdx.x >> 4) * 128, t0 = (blockIdx.x & 15) * 128 + w * 64;
  mbar_wait_sleep(bar + B_GFULL + 8 * (G_STAGES - 1), 0);
#pragma unroll 1
  for (int i = -1; i < 4; i++) {
    GA(82 + 2 * i)
    const int dc = d0 + (~i & 2) * 32;
    const uint2 ta = __ldg(reinterpret_cast<const uint2*>(maps.shift_k) + dc + lane);
    const uint2 tb = __ldg(reinterpret_cast<const uint2*>(maps.shift_k) + dc + lane + 32);
    if (i >= 0) mbar_wait_sleep(pb + (i & 1) * 8, i >> 1);
    GA(83 + 2 * i)
    const uint32_t so = sbase + G_STG_OFF + (w * 2 + (i & 1)) * P_SLOT;
    if (i < 3 && elect_one()) {
      const uint32_t b = pb + (~i & 1) * 8, dst = so + (i & 1 ? -P_SLOT : P_SLOT);
      mbar_expect_tx(b, P_SLOT);
      const int dn = d0 + (i < 1 ? 64 : 0), tn = t0 + 32 * (~i & 1);
      const uint64_t pol = policy_evict_first();
      tma_load_2d_hint(dst, &maps.bk, b, dn, tn - 3, pol);
      tma_load_2d_hint(dst + P_V, &maps.bv, b, dn, tn, pol);
    }
    if (i < 0) continue;
    uint32_t ak[4];
#pragma unroll
    for (int r = 0; r < 4; r++) {
      const uint32_t a = so / 128 + r + 4 * (lane & 6) + (((lane >> 2) ^ lane) & 6) + (lane & 1);
      ak[r] = a * 128 + (a & 7) * 16;
    }
    bf16* dst = g_kvT + (size_t)(dc + (lane >> 2)) * S_LEN + t0 + ((lane & 3) + 4 * (i & 1)) * 8;
#pragma unroll 1
    for (int cg = 0; cg < 128; cg += 16) {
      uint32_t k[4][4], v[4];
      const uint32_t t01 = __shfl_sync(0xffffffffu, cg < 64 ? ta.x : tb.x, cg / 2 + (lane >> 2));
      const uint32_t t23 = __shfl_sync(0xffffffffu, cg < 64 ? ta.y : tb.y, cg / 2 + (lane >> 2));
#pragma unroll
      for (int r = 0; r < 4; r++) ldsm4t(k[r], ak[r] ^ cg);
      ldsm4t(v, (ak[3] ^ cg) + 4096);
      const uint32_t w0 = __byte_perm(t01, 0, 0x1010), w1 = __byte_perm(t01, 0, 0x3232);
      const uint32_t w2 = __byte_perm(t23, 0, 0x1010), w3 = __byte_perm(t23, 0, 0x3232);
#pragma unroll
      for (int j = 0; j < 4; j++)
        v[j] = mul_bf2(fma_bf2(k[3][j], w0, fma_bf2(k[2][j], w1, fma_bf2(k[1][j], w2, mul_bf2(k[0][j], w3)))), v[j]);
      const bool s1 = lane & 1, s2 = lane & 2;
      const uint32_t a0 = s1 ? v[1] : v[0], a1 = s1 ? v[0] : v[1], a2 = s1 ? v[3] : v[2], a3 = s1 ? v[2] : v[3];
      *reinterpret_cast<uint4*>(dst) = make_uint4(s2 ? a2 : a0, s2 ? a3 : a1, s2 ? a0 : a2, s2 ? a1 : a3);
      dst += 8 * S_LEN;
    }
    fence_proxy_async();
    __syncwarp();
    if (lane == 0 && (i & 1)) note(bar, i == 1 ? CNT_PREP1 : CNT_PREP);
  }
  GA(90)
  __syncwarp();
  GA(91)
}

__device__ __forceinline__ void qkv_tile(const Maps& maps, int it, int& which, int& m_tile, int& n_tile) {
  const bool q = it == 0 || it >= 5;
  const int b = maps.id[blockIdx.x][it >= 5];
  which = q ? 0 : 2 - (it & 1);
  m_tile = b & 15;
  n_tile = (b >> 4) * 2 + ((0x19 >> it) & 1);
}

constexpr int G_NTILES = 6;
__device__ __forceinline__ uint32_t qkv_flip(int it) { return ((0x0b >> it) & 1) * 3; }
__device__ __forceinline__ void qkv_producer(const Maps& maps, uint32_t sbase, bool first) {
  const uint32_t bar = sbase + BAR_OFF;
  uint32_t stage = 0, phase = 0;
#pragma unroll 1
  for (int it = 0; it < (first ? 1 : G_NTILES); it++) {
    int which, m_tile, n_tile;
    qkv_tile(maps, it, which, m_tile, n_tile);
    const CUtensorMap* ma = &maps.a[which == 0 ? 0 : 1];
    const CUtensorMap* mb = &maps.b[which];
    const int nk = first ? G_STAGES : which == 0 ? 16 : 8;
#pragma unroll 1
    for (int kt = (it == 0 && !first) ? G_STAGES : 0; kt < nk; kt++) {
      if (!first) mbar_wait_sleep(bar + B_GEMPTY + 8 * stage, phase);
      const uint32_t fb = bar + B_GFULL + 8 * stage;
      const uint32_t sa = sbase + stage * G_STAGE_BYTES;
      const int k0 = (kt ^ ((0x14 >> it) & 1) * 7) * 64;
      const bool keep = ((0x1c >> it) & 1) && kt < G_STAGES;
      mbar_expect_tx(fb, keep ? G_B_BYTES : G_STAGE_BYTES);
      if (!keep) tma_load_2d(sbase + (stage ^ qkv_flip(it)) * G_STAGE_BYTES, ma, fb, k0, m_tile * 128);
      tma_load_3d(sa + G_A_BYTES, mb, fb, 0, k0, n_tile * 4);
      if (++stage == G_STAGES) { stage = 0; phase ^= 1; }
      {
        const int b = maps.id[blockIdx.x][1];
        if (it == 2 && kt == (b & 7)) {
          for (int i = 0; i < 2; i++)
            asm volatile("cp.async.bulk.prefetch.tensor.2d.L2.global.tile [%0, {%1, %2}];" ::"l"(&maps.a[0]),
                         "r"((b >> 4) * 128 + i * 64), "r"((b & 15) * 128)
                         : "memory");
          asm volatile("cp.async.bulk.prefetch.tensor.3d.L2.global.tile [%0, {%1, %2, %3}];" ::"l"(&maps.b[1 + ((b >> 3) & 1)]),
                       "r"(0), "r"((b & 7) * 64), "r"((b >> 4) * 8 + 4)
                       : "memory");
        }
        if (it == 3 && kt == (b & 7))
          asm volatile("cp.async.bulk.prefetch.tensor.3d.L2.global.tile [%0, {%1, %2, %3}];" ::"l"(&maps.b[0]), "r"(0),
                       "r"((b & 15) * 64), "r"((b >> 4) * 8)
                       : "memory");
      }
    }
  }
}

__device__ __forceinline__ void gate_rows(const Maps& maps, uint32_t bar, int lane) {
  if (lane == 0) {
    uint32_t v = 0, w;
#pragma unroll 1
    for (uint32_t spins = 0; v < 2 && spins < (1u << 20); spins++, v += w) {
      asm volatile("atom.acquire.cta.shared.exch.b32 %0, [%1], 0;" : "=r"(w) : "r"(bar + B_PEND + 4 * CNT_PREP1) : "memory");
      if (!w) __nanosleep(100);
    }
    cnt_signal_release(CNT_PREP1, v);
  }
  __syncwarp();
  const uint4 *x = reinterpret_cast<const uint4*>(maps.x), *wp = reinterpret_cast<const uint4*>(maps.gate_w);
  float mine = 0.f;
#pragma unroll 1
  for (int r = 0; r < 16; r++) {
    float sum = 0.f;
#pragma unroll
    for (int i = 0; i < 4; i++) {
      const uint4 xv = __ldcg(x + (blockIdx.x * 16 + r) * (DM / 8) + i * 32 + lane), wv = __ldg(wp + i * 32 + lane);
      const uint32_t p0 = mul_bf2(xv.x, wv.x), p1 = mul_bf2(xv.y, wv.y), p2 = mul_bf2(xv.z, wv.z), p3 = mul_bf2(xv.w, wv.w);
      sum += ((bf_lo(p0) + bf_hi(p0)) + (bf_lo(p1) + bf_hi(p1))) + ((bf_lo(p2) + bf_hi(p2)) + (bf_lo(p3) + bf_hi(p3)));
    }
#pragma unroll
    for (int off = 16; off; off >>= 1) sum += __shfl_xor_sync(0xffffffffu, sum, off);
    if (lane == r) mine = sum;
  }
  if (lane < 16) g_gate[blockIdx.x * 16 + lane] = bf16_round(rcp(1.0f + __expf(-bf16_round(mine))));
  __syncwarp();
  if (lane == 0) note(bar, CNT_PREP);
  __syncwarp();
}

__device__ __forceinline__ uint32_t seen_bar(uint32_t item) { return B_SEEN + ((0x700800u >> (8 * item)) & 255); }
__device__ __noinline__ void publisher(uint32_t bar, int lane, uint32_t nsrc, uint32_t item, uint32_t mine) {
  uint32_t done = 0, tot = 0;
#pragma unroll 1
  for (uint32_t spins = 0; (done < nsrc || item < 3) && spins < (1u << 20); spins++) {
    const uint32_t cnt = item ? CNT_CTX - 1 + item : CNT_KV + 1;
    if (item < 3 && __shfl_sync(0xffffffffu, tot, cnt) >= mine >> !item) {
      uint32_t v;
      asm volatile("ld.acquire.gpu.global.u32 %0, [%1];" : "=r"(v) : "l"(g_cnt + (lane ? cnt : CNT_PREP) * 32) : "memory");
      if (__all_sync(0xffffffffu, v >= (lane ? 512 >> !item : 384))) {
        asm volatile("fence.proxy.async.global;" ::: "memory");
        mbar_arrive_if(bar + seen_bar(item), lane == 0);
        item++;
      }
    }
    uint32_t v = 0;
    if (lane < CNT_N)
      asm volatile("atom.acquire.cta.shared.exch.b32 %0, [%1], 0;" : "=r"(v) : "r"(bar + B_PEND + 4 * lane) : "memory");
    done += __shfl_sync(0xffffffffu, v, CNT_DONE);
    if (lane == CNT_DONE) v = 0;
    if (done == nsrc && lane < CNT_DONE) {
      uint32_t w;
      asm volatile("atom.acquire.cta.shared.exch.b32 %0, [%1], 0;" : "=r"(w) : "r"(bar + B_PEND + 4 * lane) : "memory");
      v += w;
    }
    if (v && lane == 0) { TD(0) }
    if (v) cnt_signal_release(lane, v);
    tot += v;
    if (v && lane == 0) { TD(1) }
    if (!__any_sync(0xffffffffu, v != 0)) __nanosleep(item == 1 ? 1000 : 200);
  }
  __threadfence();
  __syncwarp();
}

constexpr float K_SCALE = 0.08838834764831845f * 1.4426950408889634f;
__device__ __forceinline__ uint32_t qkv_consumer(const Maps& maps, const uint32_t sbase, const int wg, bool fused,
                                                 uint32_t (&q)[32], float (&rest)[64], uint32_t rt_zero) {
  PHASE_GIVEN_(rt_zero)
  constexpr int NTILES = G_NTILES;
  float acc[128];
  const uint32_t stg = sbase + G_STG_OFF + wg * 18432;
  const int st_row = warp * 16 + (lane & 7) + ((lane >> 3) & 1) * 8;
  const int st_cb = lane >> 4;
  uint32_t pend[64];
  const CUtensorMap* pend_map = nullptr;
  int pend_c0 = 0, pend_c1 = 0;
  uint32_t sn = 0;
  uint32_t st_a[4];
#pragma unroll
  for (int jp = 0; jp < 4; jp++) {
    st_a[jp] = stg + st_row * 128 + (((jp * 2 + st_cb) ^ (st_row & 7)) << 4);
    asm volatile("" : "+r"(st_a[jp]));
  }
  auto put_box = [&](uint32_t off, const uint32_t* v) {
#pragma unroll
    for (int jp = 0; jp < 4; jp++) stmatrix_x4(st_a[jp] + off, v[jp * 4], v[jp * 4 + 1], v[jp * 4 + 2], v[jp * 4 + 3]);
  };
  GT(gti++)
  const int hf = wg ^ 1;
  const uint64_t da0 = make_desc(sbase + hf * 8192, 16, 1024, DESC_SW128);
  const uint64_t db0 = make_desc(sbase + G_A_BYTES, 8192, 1024, DESC_SW128);
  uint32_t g = 0, oa = 3 * (G_STAGE_BYTES / 16), ob = 0;
  bool go = false;
  mbar_wait(bar + B_GFULL, 0);
  uint32_t gend = 16, when = 0;
#pragma unroll 1
  for (int it = 0;; it++) {
    bool more = false;
#pragma unroll 1
    do {
      GT(gti++)
      wgmma_fence();
#pragma unroll
      for (int kk = 0; kk < 4; kk++)
        wgmma_m64n256_ss_tb(acc, desc_add(da0, oa + kk * 2), desc_add(db0, ob + kk * 128), kk || more);
      wgmma_commit();
      if (go) st_go(bar, wg, wtid, sn - 1);
      g++;
      if (g + wg * 64 == 63) named_bar_arrive(6, 256);
      const uint32_t full = (bar + B_GFULL) + 8 * (g & 3);
      const bool here = mbar_test(full, (g >> 2) & 1) || g >= 64;
      oa = ((g & 3) ^ ((0x17 >> (g >> 3)) & 1) * 3) * (G_STAGE_BYTES / 16);
      ob = (g & 3) * (G_STAGE_BYTES / 16);
      go = when & 1;
      when >>= 1;
      if (go) {
        const int c = sn & 3;
        st_wait(bar, wg, sn - 2);
        st_cmd(bar, wg, wtid, sn, ST_BOX1, pend_map, stg + (c & 1) * 8192, pend_c0 + c * 64, pend_c1,
               (c == 3 && it > 1) ? CNT_KV + (it > 4) : -1);
        switch (c) {
          case 0: put_box(0, pend); break;
          case 1: put_box(8192, pend + 16); break;
          case 2: put_box(0, pend + 32); break;
          default: put_box(8192, pend + 48); break;
        }
        sn++;
      }
      if (it < NTILES) {
        wgmma_wait<1>();
        mbar_arrive_if((bar + B_GEMPTY) + 8 * ((g + 2) & 3), wtid == 32 && more);
        if (wg && g == 62) named_bar_sync(6, 256);
        if (!here) mbar_wait(full, (g >> 2) & 1);
      }
      more = true;
    } while (g != gend);
    wgmma_wait<0>();
    fence_regs(acc);
    GT(gti++)
    mbar_arrive_if((bar + B_GEMPTY) + 8 * 3, wtid == 32);
    int which, m_tile, n_tile;
    qkv_tile(maps, it, which, m_tile, n_tile);
    if (it == NTILES - fused) break;
    if (which == 1) {
#pragma unroll
      for (int j = 0; j < 128; j++) acc[j] *= K_SCALE;
    }
#pragma unroll
    for (int j = 0; j < 64; j++) pend[j] = pack_bf16(acc[2 * j], acc[2 * j + 1]);
    pend_map = &maps.c[which];
    pend_c0 = n_tile * 256;
    pend_c1 = m_tile * 128 + hf * 64;
    gend += it == 4 ? 16 : 8;
    when = (it == 4 ? 0x922 : 0x55) << wg;
  }
  if (go) st_go(bar, wg, wtid, sn - 1);
#pragma unroll
  for (int j = 0; j < 32; j++) q[j] = pack_bf16(acc[2 * j], acc[2 * j + 1]);
#pragma unroll
  for (int j = 0; j < 64; j++) rest[j] = acc[64 + j];
  GT(gti++)
  return sn;
}

constexpr int A_TILE = 128 * 128 * 2;
constexpr int A_K_OFF = 0, A_Q_OFF = A_TILE, A_V_OFF = 3 * A_TILE;
constexpr int A_O_OFF = 6 * A_TILE;
constexpr int A_ITEMS = NH * (S_LEN / 128);

constexpr uint32_t A_ORDER = 0x3120, A_STEPS = 34;
__device__ __forceinline__ int item_m(uint32_t it) { return it & 15; }
__device__ __forceinline__ int item_h(uint32_t it) { return it >> 4; }

constexpr int C_V = 16384, C_MAT = 24576;
constexpr float C_ALPHA = 0.07874506561842957f;
__device__ __forceinline__ void sincos_turn(int p, float inv, float& c, float& s) {
  const float a = (float)p * (inv * 6.283185307179586f);
  asm("cos.approx.ftz.f32 %0, %1;" : "=f"(c) : "f"(a));
  asm("sin.approx.ftz.f32 %0, %1;" : "=f"(s) : "f"(a));
}

__device__ __forceinline__ uint32_t head_of(const Maps& maps, uint32_t r) { return (maps.id[blockIdx.x & 127][3] >> (2 * r)) & 3; }
__device__ __forceinline__ uint32_t item_at(const Maps& maps, uint32_t h) {
  const uint32_t b = maps.id[blockIdx.x & 127][1];
  return (b >> 4) * 64 + h * 16 + ((b ^ ((h >> 1) * 15)) & 15);
}
__device__ __forceinline__ uint32_t item_of(const Maps& maps, uint32_t r) { return item_at(maps, head_of(maps, r)); }

#define PACE 250
#define LCHK 1
#define XMASK 3
#define XFIRST 12
#define C_SIDE 64
__device__ __forceinline__ uint32_t conv_first(const Maps& maps) {
  const uint32_t b = maps.id[blockIdx.x & 127][1];
  return (b >> 4) * 128 + ((b + 15) & 15);
}

__device__ __forceinline__ void conv_consumer(const Maps& maps, uint32_t smem0, uint32_t first, uint32_t step,
                                              uint32_t end, bool pp, bool dealt) {
  PHASE_PROLOGUE
  const uint32_t in_full = bar + B_CFULL + wg * 16;
  const uint32_t ca = sbase + (wg ? A_V_OFF + A_TILE : A_Q_OFF);
  const int w = __shfl_sync(0xffffffffu, warp, 0), g = lane >> 2, c = lane & 3;
  auto fetch = [&](uint32_t ch, uint32_t n) {
    if (w == 2 && ch < C_NONE) {
      if (elect_one()) {
        const uint32_t b = in_full + (n & 1) * 8, d = ca + (n & 1) * 8192;
        const uint64_t pol = policy_evict_first();
        mbar_expect_tx(b, 8192);
        tma_load_2d_hint(d, &maps.cu, b, 0, ch * 64, pol);
        tma_load_2d_hint(d + 4096, &maps.ch, b, 0, ch * 64, pol);
      }
    }
  };
  if (wtid == 96 && wg) { TD(15) }
  uint32_t f1[8][4];
  float tt[16], ts[16];
  uint32_t cc[4], ss[4];
#pragma unroll
  for (int i = 0; i < 16; i++) {
    const int k = 2 * (16 * w + g + 8 * (i & 1)) + 1, n = 2 * (8 * (i >> 1) + 2 * c) + 1;
    float c0, s0, c1, s1;
    sincos_turn(((k * n) << 23) >> 23, 1.f / 512, c0, s0);
    sincos_turn(((k * n + 2 * k) << 23) >> 23, 1.f / 512, c1, s1);
    f1[i >> 2][i & 3] = pack_bf16(c0 * C_ALPHA, c1 * C_ALPHA);
    f1[4 + (i >> 2)][i & 3] = pack_bf16(s0 * -C_ALPHA, s1 * -C_ALPHA);
  }
#pragma unroll
  for (int i = 0; i < 16; i++) {
    const int k = 2 * (16 * w + g + 8 * ((i >> 1) & 1)) + 1, n = 16 - (8 * (i >> 2) + 2 * c + (i & 1));
    float cs;
    sincos_turn(k * n, 1.f / 8192, cs, ts[i]);
    tt[i] = ts[i] * rcp(1.f + cs);
  }
#pragma unroll
  for (int j = 0; j < 4; j++) {
    const int k = 8 * w + g, n = 8 * c + 2 * j;
    float c0, s0, c1, s1;
    sincos_turn((int8_t)(k * n * 8), 1.f / 256, c0, s0);
    sincos_turn((int8_t)((k * n + k) * 8), 1.f / 256, c1, s1);
    cc[j] = pack_bf16(c0, c1);
    ss[j] = pack_bf16(s0, s1);
  }
  named_bar_sync(3, 256);
  fetch(first, 0);
  fetch(first + step, 1);
  const uint32_t va = ca + g * 64 + ((c ^ (g >> 1)) << 4);
  {
    const uint32_t a = va + C_MAT + w * 512, m = 0x80008000u;
    sts128(a, make_uint4(cc[0], cc[1], cc[2], cc[3]));
    sts128(a + 2048, make_uint4(ss[0], ss[1], ss[2], ss[3]));
    sts128(a + 4096, make_uint4(ss[0] ^ m, ss[1] ^ m, ss[2] ^ m, ss[3] ^ m));
    sts128(a + 6144, make_uint4(cc[0], cc[1], cc[2], cc[3]));
  }
  fence_proxy_async();
  named_bar_sync(1 + wg, 128);
  constexpr uint64_t DHI = (2ull << 62) | ((uint64_t)(512 >> 4) << 32);
  const uint32_t d0 = (uint32_t)make_desc(ca, 4096, 0, 0);
  float a5[16];
  uint4* const yb = reinterpret_cast<uint4*>(g_y2T) + (16 * w + g) * 4 + c;
  auto issue5 = [&]() {
#pragma unroll
    for (int ks = 0; ks < 8; ks++) wgmma_m64n32_rs_tb(a5, f1[ks], DHI | (d0 + (C_V >> 4) + ks * 64), ks != 0);
    wgmma_commit();
  };
  auto finish = [&](uint32_t ch, bool on) {
    fence_regs(a5);
    uint4* y = yb + (size_t)ch * 256;
    if (on) {
      y[0] = make_uint4(pack_bf16(a5[0], a5[1]), pack_bf16(a5[4], a5[5]), pack_bf16(a5[8], a5[9]), pack_bf16(a5[12], a5[13]));
      y[32] = make_uint4(pack_bf16(a5[2], a5[3]), pack_bf16(a5[6], a5[7]), pack_bf16(a5[10], a5[11]), pack_bf16(a5[14], a5[15]));
    }
  };
  auto dft32 = [&](float (&d)[32], const float* re, const float* im) {
    uint32_t a[4][4];
#pragma unroll
    for (int i = 0; i < 8; i++) {
      a[i >> 2][i & 3] = pack_bf16(re[2 * i], re[2 * i + 1]);
      a[2 + (i >> 2)][i & 3] = pack_bf16(im[2 * i], im[2 * i + 1]);
    }
    wgmma_fence();
#pragma unroll
    for (int ks = 0; ks < 4; ks++) wgmma_m64n64_rs_tb(d, a[ks], DHI | (d0 + (C_MAT >> 4) + ks * 64), ks != 0);
    wgmma_commit();
  };
  auto rot = [&](float* x, float* y) {
#pragma unroll
    for (int i = 0; i < 16; i++) {
      x[i] = fmaf(-tt[i], y[i], x[i]);
      y[i] = fmaf(ts[i], x[i], y[i]);
      x[i] = fmaf(-tt[i], y[i], x[i]);
    }
  };
  auto load_d = [&](uint32_t ch) {
    return __ldg(reinterpret_cast<const unsigned short*>(maps.ssm_D) + ((ch & (DM - 1)) | (lane & rt_zero)));
  };
  uint32_t dn = load_d(first);
  uint32_t n = 0, prev = 0, ch = first, next = first + step;
#pragma unroll 1
  for (; ch < C_NONE; n++) {
    CT(0)
    float a1[2][32], a2[2][32], a4[32];
    const float dsk = c ? 0.f : __uint_as_float(dn << 16) * C_ALPHA;
    dn = load_d(next);
    uint32_t next2 = next + step < end ? next + step : C_NONE;
    mbar_wait(in_full + (n & 1) * 8, (n >> 1) & 1);
    if (pp) named_bar_sync(4 + wg, 256);
    CT(1)
    wgmma_fence();
#pragma unroll
    for (int ks = 0; ks < 8; ks++)
      wgmma_m64n64_rs_tb(a1[ks >> 2], f1[ks], DHI | (d0 + (n & 1) * 512 + (ks & 3) * 64), (ks & 3) != 0);
    wgmma_commit();
    issue5();
    wgmma_wait<1>();
    fence_regs(a1[0]);
    fence_regs(a1[1]);
    CT(2)
    rot(a1[0], a1[1]);
    dft32(a2[0], a1[0], a1[1]);
    rot(a1[0] + 16, a1[1] + 16);
    a1[0][16] += dsk;
    a1[0][18] += dsk;
    dft32(a2[1], a1[0] + 16, a1[1] + 16);
    CT(3)
    wgmma_wait<2>();
    finish(prev, n > 0);
    wgmma_wait<0>();
    fence_regs(a2[0]);
    fence_regs(a2[1]);
    CT(4)
    if (pp) named_bar_arrive(5 - wg, 256);
    float re[16], im[16];
#pragma unroll
    for (int i = 0; i < 16; i++) {
      re[i] = a2[0][i] * a2[1][i] - a2[0][16 + i] * a2[1][16 + i];
      im[i] = a2[0][i] * a2[1][16 + i] + a2[0][16 + i] * a2[1][i];
    }
    dft32(a4, im, re);
    if (dealt) {
      mbar_wait(bar + (n < 2 ? B_DEAL : B_DEAL2), 0);
      asm volatile("ld.shared.u32 %0, [%1];" : "=r"(next2) : "r"(bar + B_LIST + 4 * n + (n < 2 ? 0 : 8)));
    }
    wgmma_wait<0>();
    fence_regs(a4);
    CT(5)
    rot(a4, a4 + 16);
#pragma unroll
    for (int i = 0; i < 4; i++) {
      const float* x = a4 + 16 - 16 * (i >> 1) + 2 * (i & 1);
      sts128(va + C_V + w * 1024 + (i >> 1) * 4096 + (i & 1) * 512,
             make_uint4(pack_bf16(x[0], x[1]), pack_bf16(x[4], x[5]), pack_bf16(x[8], x[9]), pack_bf16(x[12], x[13])));
    }
    CT(6)
    fence_proxy_async();
    named_bar_sync(1 + wg, 128);
    fetch(next2, n);
    if (wtid == 96 && n > 0) note(bar, CNT_Y2 + ((0x8c >> ((prev >> 4) & 7)) & 1));
    prev = ch;
    ch = next;
    next = next2;
    CT(7)
  }
  wgmma_fence();
  issue5();
  wgmma_wait<0>();
  finish(prev, (dn | ~rt_zero) != 0);
  named_bar_sync(1 + wg, 128);
  if (wtid == 96 && wg) { TD(8) }
  if (wtid == 96) cnt_signal_release(CNT_Y2 + ((0x8c >> ((prev >> 4) & 7)) & 1), 1);
  if (wtid == 64) note(bar, CNT_DONE);
  if (wtid == 96 && wg) { TD(9) }
}

__device__ __forceinline__ void attn_producer(const Maps& maps, uint32_t sbase, bool after_qkv, bool to_out,
                                              bool dry) {
  const uint32_t bar = sbase + BAR_OFF;
  const uint32_t q_full = bar + B_QFULL, q_empty = bar + B_QEMPTY;
  const uint32_t k_full = bar + B_KFULL, k_empty = bar + B_KEMPTY, v_full = bar + B_VFULL, v_empty = bar + B_VEMPTY;
  int ndrained = after_qkv ? 0 : G_STAGES;
  auto wait = [&](uint32_t b, uint32_t par) {
    if (!dry) mbar_wait_sleep(b, par);
  };
  auto drained = [&](int upto) {
#pragma unroll 1
    for (; ndrained <= upto; ndrained++) wait(bar + B_GEMPTY + 8 * ndrained, 1);
  };
  uint32_t st = 0, ph = 1, vs = 0, vp = 1;
  int pend_j = -1, pend_h = 0;
  int round = -1, m = -1, h = 0;
  bool last = false;
#pragma unroll 1
  for (;; round++) {
    uint32_t nitem = 0;
    const int tpost = m >= 3 ? m - 1 : m;
#pragma unroll 1
    for (int t = m < 0 ? -1 : 0; t <= m; t++) {
      const int j = (t < m && (h & 2)) ? m - 1 - t : t;
      if (t >= 0) {
        drained(st);
        wait(k_empty + 8 * st, ph);
        if (!dry) {
          mbar_expect_tx(k_full + 8 * st, A_TILE);
          tma_load_3d(sbase + A_K_OFF + st * 2 * A_TILE, &maps.k, k_full + 8 * st, 0, j * 128, h * 2);
        }
        if (++st == 2) { st = 0; ph ^= 1; }
      }
      if (pend_j >= 0) {
        drained(2 + vs);
        if ((pend_h & 2) && after_qkv) wait(bar + seen_bar(0), 0);
        wait(v_empty + 8 * vs, vp);
        if (!dry) {
          mbar_expect_tx(v_full + 8 * vs, A_TILE);
          tma_load_3d(sbase + A_V_OFF + vs * A_TILE, &maps.v, v_full + 8 * vs, 0, pend_j * 128, pend_h * 2);
        }
        if (++vs == 2) { vs = 0; vp ^= 1; }
      }
      pend_j = j;
      pend_h = h;
      if (t == tpost && !last) {
        nitem = dry ? 1 : item_of(maps, round + 1);
        if (round == (dry ? 0 : 3) || blockIdx.x >= 128) {
          nitem = A_ITEMS;
          if (!to_out) cnt_wait(CNT_PREP1, dry ? 0 : 256);
          if (to_out) {
            wait(bar + seen_bar(1), 0);
            asm volatile("cp.async.bulk.prefetch.L2.global [%0], 4096;" ::"l"(maps.ssm_k + (size_t)conv_first(maps) * S_LEN));
            if (!dry)
              asm volatile("cp.async.bulk.prefetch.L2.global [%0], 4096;" ::"l"(g_kvT + (size_t)conv_first(maps) * S_LEN));
          }
        }
        const uint32_t qs = (round + 1) & 1;
        wait(q_empty + 8 * qs, (((round + 1) >> 1) & 1) ^ 1);
        if (round == 1 && after_qkv) wait(bar + B_QDONE, 0);
        if (round < 0 && after_qkv) {
          if (!dry) { TD(2) }
          cnt_wait(CNT_KV, dry ? 0 : 768);
          if (!dry) { TD(3) }
        }
        if (nitem >= A_ITEMS || (round < 0 && after_qkv && !dry)) {
          if (!dry) mbar_arrive(q_full + 8 * qs);
        } else {
          drained(1 + 2 * qs);
          if (!dry) {
            mbar_expect_tx(q_full + 8 * qs, A_TILE);
            tma_load_3d_hint(sbase + A_Q_OFF + qs * 4 * A_TILE, &maps.q, q_full + 8 * qs, 0, item_m(nitem) * 128,
                             item_h(nitem) * 2, policy_evict_first());
          }
        }
      }
    }
    if (last) break;
    last = nitem >= A_ITEMS;
    m = last ? -1 : item_m(nitem);
    h = item_h(nitem);
  }
}

__device__ __forceinline__ void put_o(uint32_t sbase, int wg, int warp, int lane, const float (&o)[64], float i0, float i1) {
  const int st_row = warp * 16 + (lane & 7) + ((lane >> 3) & 1) * 8;
  const uint32_t so = sbase + A_O_OFF + wg * 16384 + st_row * 128;
#pragma unroll
  for (int j = 0; j < 16; j += 2)
    stmatrix_x4(so + (j >> 3) * 8192 + ((((j & 7) + (lane >> 4)) ^ (lane & 7)) << 4),
                pack_bf16(o[4 * j] * i0, o[4 * j + 1] * i0), pack_bf16(o[4 * j + 2] * i1, o[4 * j + 3] * i1),
                pack_bf16(o[4 * j + 4] * i0, o[4 * j + 5] * i0), pack_bf16(o[4 * j + 6] * i1, o[4 * j + 7] * i1));
}
__device__ __forceinline__ uint32_t attn_consumer(const Maps& maps, const uint32_t sbase, const int wg,
                                                  const uint32_t rt_zero, uint32_t sn, uint32_t (&p)[32], float (&rest)[64],
                                                  bool after_qkv, float (&o)[64], float (&s)[64], float& pi0, float& pi1) {
  PHASE_GIVEN
  const uint32_t q_full = bar + B_QFULL, q_empty = bar + B_QEMPTY;
  const uint32_t k_full = bar + B_KFULL, k_empty = bar + B_KEMPTY, v_full = bar + B_VFULL;
  float e[32];
  uint32_t dep = 0;
  constexpr int MIDJ = 5;
  float l0 = 0.f, l1 = 0.f, b0 = 0.f, b1 = 0.f;
  const int sched_own = 4 + wg, sched_other = 5 - wg;

  const int hf = wg ^ 1;
  const uint32_t qd0 = (uint32_t)make_desc(sbase + A_Q_OFF + hf * 8192, 16, 0, 0);
  const uint32_t kd0 = (uint32_t)make_desc(sbase + A_K_OFF, 16, 0, 0);
  const uint32_t vd0 = (uint32_t)make_desc(sbase + A_V_OFF, 16384, 0, 0);
  constexpr uint64_t DHI = DESC_SW128 | ((uint64_t)(1024 >> 4) << 32);
  constexpr uint32_t DST = A_TILE >> 4;
  auto issue_qk = [&](uint32_t qd, uint32_t kd) {
#pragma unroll
    for (int kk = 0; kk < 8; kk++) {
      const uint32_t off = ((kk >> 2) * 16384 + (kk & 3) * 32) >> 4;
      wgmma_m64n128_ss(s, DHI | (qd + off), DHI | (kd + off), kk != 0);
    }
    wgmma_commit();
  };
  auto issue_pv = [&](uint32_t vd, bool accumulate, int nk) {
#pragma unroll
    for (int kk = 0; kk < 8; kk++) {
      if (kk < nk)
        wgmma_m64n128_rs<1>(o, p[4 * kk], p[4 * kk + 1], p[4 * kk + 2], p[4 * kk + 3], DHI | (vd + kk * 128),
                            accumulate || (kk != 0));
    }
    wgmma_commit();
  };
  auto exp_lo = [&](float& a0, float& a1) {
#pragma unroll
    for (int j = 0; j < 8; j++) {
      e[4 * j] = ex2(s[4 * j]);
      e[4 * j + 1] = ex2(s[4 * j + 1]);
      e[4 * j + 2] = ex2(s[4 * j + 2]);
      e[4 * j + 3] = ex2(s[4 * j + 3]);
      a0 += e[4 * j];
      a0 += e[4 * j + 1];
      a1 += e[4 * j + 2];
      a1 += e[4 * j + 3];
      if (j == MIDJ) dep = (__float_as_uint(a0) | __float_as_uint(a1)) & rt_zero;
    }
  };
  auto pack_lo = [&]() {
#pragma unroll
    for (int j = 0; j < 16; j++) p[j] = pack_bf16(e[2 * j], e[2 * j + 1]);
  };
  auto finish_p = [&](float& a0, float& a1) {
    pack_lo();
#pragma unroll
    for (int j = 8; j < 16; j++) {
      const float e0 = ex2(s[4 * j]), e1 = ex2(s[4 * j + 1]), e2 = ex2(s[4 * j + 2]), e3 = ex2(s[4 * j + 3]);
      a0 += e0;
      a0 += e1;
      a1 += e2;
      a1 += e3;
      p[2 * j] = pack_bf16(e0, e1);
      p[2 * j + 1] = pack_bf16(e2, e3);
      if (j == 8 + MIDJ) dep = __float_as_uint(a0) & rt_zero;
    }
  };
  auto quad_sum = [&](float t) {
    t += __shfl_xor_sync(0xffffffffu, t, 1);
    return t + __shfl_xor_sync(0xffffffffu, t, 2);
  };
  auto write_o = [&](float i0, float i1) {
    st_wait(bar, wg, sn - 1);
    put_o(sbase, wg, warp, lane, o, i0, i1);
  };
  auto store_o = [&](uint32_t r, int kind, uint32_t lazy) {
    const uint32_t it = item_at(maps, kind == ST_BOX2Q ? 1 : head_of(maps, r));
    st_cmd(bar, wg, wtid, sn, kind, (INPLACE & 1) || kind != ST_BOX2Q ? &maps.o : &maps.c[0], sbase + A_O_OFF + wg * 16384, item_h(it) * 128,
            item_m(it) * 128 + hf * 64, CNT_CTX + (r >> 1), lazy);
    if (kind != ST_BOX2L) st_go(bar, wg, wtid, sn);
    sn++;
  };
  auto mask_half = [&](float* sh) {
    const int u = warp * 16 + (lane >> 2) - (lane & 3) * 2;
#pragma unroll
    for (int j = 0; j < 8; j++) {
      if (8 * j > u) sh[4 * j] = -INFINITY;
      if (8 * j + 1 > u) sh[4 * j + 1] = -INFINITY;
      if (8 * j - 8 > u) sh[4 * j + 2] = -INFINITY;
      if (8 * j - 7 > u) sh[4 * j + 3] = -INFINITY;
    }
  };
  ST(0)
  const uint32_t qa = sbase + A_Q_OFF + hf * 8192 + (warp * 16 + (lane & 15)) * 128;
  auto q_at = [&](int j) { return qa + (j >> 2) * 16384 + ((((j & 3) * 2 + (lane >> 4)) ^ (lane & 7)) << 4); };
  if (!after_qkv) {
    mbar_wait(q_full, 0);
    if (blockIdx.x >= 128) return sn;
#pragma unroll
    for (int j = 0; j < 8; j++)
      asm volatile("ldmatrix.sync.aligned.m8n8.x4.shared.b16 {%0, %1, %2, %3}, [%4];"
                   : "=r"(p[4 * j]), "=r"(p[4 * j + 1]), "=r"(p[4 * j + 2]), "=r"(p[4 * j + 3])
                   : "r"(q_at(j))
                   : "memory");
  }
  for (uint32_t i = 0; !(mbar_try(k_full, 0) & mbar_try(bar + B_GEMPTY + 8, 1)) && i < (1u << 22); i++) {}
  named_bar_sync(sched_own, 256);
  fence_regs_u(p);
  wgmma_fence();
#pragma unroll
  for (int kk = 0; kk < 8; kk++)
    wgmma_m64n128_rs<0>(s, p[4 * kk], p[4 * kk + 1], p[4 * kk + 2], p[4 * kk + 3],
                        DHI | (kd0 + (((kk >> 2) * 16384 + (kk & 3) * 32) >> 4)), kk != 0);
  wgmma_commit();
  named_bar_arrive(sched_other, 256);
#pragma unroll
  for (int j = 0; j < 8; j++) stmatrix_x4(q_at(j), p[4 * j], p[4 * j + 1], p[4 * j + 2], p[4 * j + 3]);
  fence_regs(rest);
#pragma unroll
  for (int i = 0; i < 64; i++) o[i] = rest[i] * __uint_as_float(0x3f800000u | rt_zero);
  fence_regs(o);
  fence_proxy_async();
  fence_regs(o);
  wgmma_wait<0>();
  fence_regs(s);
  mbar_arrive_if(k_empty, wtid == 32);
  uint32_t g = 0;
  uint32_t rnd = 0;
  int rem = item_m(item_of(maps, 0));
  uint32_t first = 1;
  uint32_t fl = 0;
#define redo (fl & 1)
#define shifted (fl & 2)
  float d0 = 0.f, d1 = 0.f;
  pi0 = pi1 = 1.f;
  ST(1)
  for (;;) {
    if (shifted) {
#pragma unroll
      for (int j = 0; j < 16; j++) {
        s[4 * j] -= d0;
        s[4 * j + 1] -= d0;
        s[4 * j + 2] -= d1;
        s[4 * j + 3] -= d1;
      }
    }
    if (rem == 0 && !redo) {
      mbar_arrive_if(q_empty + 8 * (rnd & 1), wtid == 96);
      rnd++;
      if (hf == 0) mask_half(s);
      else mask_half(s + 32);
    }
    for (;;) {
      const bool kill = rem == 0 && hf == 0;
      const uint32_t kd = kd0 + ((g + 1) & 1) * 2 * DST, vd = vd0 + (g & 1) * DST;
      float a0 = 0.f, a1 = 0.f;
      exp_lo(a0, a1);
      fence_regs(e);
      const uint32_t kb = k_full + 8 * ((g + 1) & 1);
      const uint32_t kpar = (((g + 1) >> 1) & 1) ^ (g == A_STEPS - 1 ? 1u : 0u);
      const uint32_t qb = q_full + 8 * (rnd & 1), qpar = ((rnd >> 1) & 1) | dep;
      if (!mbar_try(qb, qpar)) mbar_wait(qb, qpar | ((__float_as_uint(a0) | __float_as_uint(a1)) & rt_zero));
      wgmma_wait<0>();
      fence_regs(o);
      if (kill) {
        mbar_arrive_if(kb + (B_VEMPTY - B_KFULL), wtid == 64 && !redo && g > 0);
        fence_regs(e);
        pack_lo();
#pragma unroll
        for (int j = 16; j < 32; j++) asm volatile("" : "=r"(p[j]));
        goto check;
      }
#pragma unroll
      for (int i = 32; i < 64; i++) asm volatile("" : "+f"(s[i])::"memory");
      mbar_arrive_if(kb + (B_VEMPTY - B_KFULL), wtid == 64 && !redo && g > 0);
      finish_p(a0, a1);
      if (__any_sync(0xffffffffu, !(mbar_try(v_full + 8 * (g & 1), ((g >> 1) & 1) | dep) &
                                    mbar_try(kb, kpar | dep)) ||
                                      !(a0 + a1 < 1.0995116e12f) || !(fminf(a0, a1) > (first ? 9.094947e-13f : -1.f)))) {
      check:
        bool bad = !(a0 + a1 < 1.0995116e12f);
        if (first) bad |= !(fminf(quad_sum(a0), quad_sum(a1)) > 9.094947e-13f);
        if (!redo && __any_sync(0xffffffffu, bad)) {
          d0 = d1 = first ? -INFINITY : 0.f;
#pragma unroll
          for (int j = 0; j < 16; j++) {
            if (j < 8 || !kill) {
              d0 = fmaxf(d0, fmaxf(s[4 * j], s[4 * j + 1]));
              d1 = fmaxf(d1, fmaxf(s[4 * j + 2], s[4 * j + 3]));
            }
          }
#pragma unroll
          for (int x = 1; x <= 2; x++) {
            d0 = fmaxf(d0, __shfl_xor_sync(0xffffffffu, d0, x));
            d1 = fmaxf(d1, __shfl_xor_sync(0xffffffffu, d1, x));
          }
          b0 += d0;
          b1 += d1;
          if (!first) {
            const float al0 = ex2(-d0), al1 = ex2(-d1);
            l0 *= al0;
            l1 *= al1;
#pragma unroll
            for (int j = 0; j < 16; j++) {
              o[4 * j] *= al0;
              o[4 * j + 1] *= al0;
              o[4 * j + 2] *= al1;
              o[4 * j + 3] *= al1;
            }
          }
          fl = 3;
          break;
        }
        mbar_wait(v_full + 8 * (g & 1), (g >> 1) & 1);
        mbar_wait(kb, kpar);
      }
      named_bar_sync(sched_own, 256);
      if (g == A_STEPS - 1) {
        fence_regs(o);
        if (hf == 0) {
          wgmma_fence();
          issue_pv(vd, 1, 4);
        } else {
          wgmma_fence();
          issue_pv(vd, 1, 8);
        }
        named_bar_arrive(sched_other, 256);
        pi0 = rcp(quad_sum(l0 + a0));
        pi1 = rcp(quad_sum(l1 + a1));
        goto done;
      }
      wgmma_fence();
      issue_qk(qd0 + (rnd & 1) * 4 * DST, kd);
      if (first) write_o(pi0, pi1);
      fence_regs(o);
      if (kill) {
        wgmma_fence();
        issue_pv(vd, !first, 4);
      } else {
        wgmma_fence();
        issue_pv(vd, !first, 8);
      }
      named_bar_arrive(sched_other, 256);
      fl &= 2;
      l0 += a0;
      l1 += a1;
      if (rem == 0 || first) {
        if (first && (g > 0 || after_qkv)) store_o(g ? rnd - (rem == 0 ? 2 : 1) : 2, g ? ST_BOX2 : ST_BOX2Q, rem);
        first = rem == 0;
        if (first) {
          pi0 = rcp(quad_sum(l0));
          pi1 = rcp(quad_sum(l1));
          l0 = l1 = b0 = b1 = 0.f;
          fl = 0;
          rem = item_m(item_of(maps, rnd)) + 1;
        }
      }
      rem--;
      g++;
      wgmma_wait<1>();
      fence_regs(s);
      mbar_arrive_if(kb + (B_KEMPTY - B_KFULL), wtid == 32);
      ST(g + 1)
      if (rem == 0 || shifted) {
        d0 = b0;
        d1 = b1;
        break;
      }
    }
  }
done:
#undef redo
#undef shifted
  st_wait(bar, wg, sn - 1);
  store_o(3, ST_BOX2L, 4);
  ST(35)
  return sn;
}

constexpr int O_STAGES = 5;
constexpr int O_STAGE_BYTES = 32768;
constexpr int O_Y_OFF = 4 * 32768;
constexpr int O_X_OFF = 6 * 32768;
constexpr int O_G_OFF = 7 * 32768;
constexpr int O_NK = HDIM / 64;

__device__ __forceinline__ uint32_t out_stage(uint32_t st) { return ((0x32501u >> (4 * st)) & 7) * O_STAGE_BYTES; }

__device__ __forceinline__ void out_producer(const Maps& maps, uint32_t sbase, bool after_attn, bool dry) {
  const uint32_t bar = sbase + BAR_OFF;
  const uint32_t rank = blockIdx.x & 1;
  const int m_tile = maps.id[blockIdx.x][2] & 15, n_tile = maps.id[blockIdx.x][2] >> 4;
  uint32_t stage = 0, phase = 0, xi = 0;
#pragma unroll 1
  for (int ki = 0; ki < (dry ? 1 : O_NK); ki++) {
    const int kt = (ki & 14) * 4 + ((A_ORDER >> ((ki >> 4) * 4)) & 3) * 2 + (ki & 1);
    const uint32_t fb = bar + B_OFULL + 8 * stage, eb = bar + B_OEMPTY + 8 * stage;
    const uint32_t sa = sbase + out_stage(stage);
    if (ki < O_STAGES) {
      constexpr uint32_t LASTB = B_KEMPTY | ((B_QEMPTY + 8) << 8) | ((B_KEMPTY + 8) << 16) | (B_VEMPTY << 24);
      if (ki > 0 && after_attn) mbar_wait_sleep(bar + ((LASTB >> (8 * ki - 8)) & 255), ki == 2);
      mbar_arrive_cluster_if(eb, 0, !dry);
      mbar_arrive_cluster_if(eb, 1, !dry);
    }
    if (ki == 32) mbar_wait_sleep(bar + seen_bar(2), 0);
    if (!dry) {
      mbar_wait_sleep(eb, phase);
      mbar_expect_tx(fb, O_STAGE_BYTES);
      tma_load_2d_mc(sa + 16384 + rank * 8192, &maps.ob, fb, n_tile * 128 + rank * 64, kt * 64, (uint16_t)3);
      tma_load_2d(sa, &maps.oa, fb, kt * 64, m_tile * 128);
    }
    if (++stage == O_STAGES) { stage = 0; phase ^= 1; }
    if ((ki & XMASK) == XMASK && ki >= XFIRST && xi < 8) {
      if (after_attn && xi < 2) mbar_wait_sleep(bar + B_OFREE + 8 * xi, 0);
      tma_load_3d(sbase + O_X_OFF + (xi & 1) * 16384 + (xi >> 1) * 4096, &maps.xs, bar + B_OY, 0,
                  m_tile * 128 + (xi & 1) * 64 + (xi >> 1) * 16, n_tile * 2);
      xi++;
    }
  }
  if (!dry) mbar_wait_sleep(bar + B_OY2, 0);
}

__device__ __forceinline__ void out_side(const Maps& maps, uint32_t smem0) {
  PHASE_PROLOGUE
  const int m_tile = maps.id[blockIdx.x][2] & 15, n_tile = maps.id[blockIdx.x][2] >> 4;
  const float* gp = g_gate + m_tile * 128 + warp * 16 + (lane >> 2);
  const float gv[4] = {__ldcg(gp), __ldcg(gp + 8), __ldcg(gp + 64), __ldcg(gp + 72)};
  const bool w0 = __shfl_sync(0xffffffffu, warp, 0) == 0;
  bool have = false;
  auto late = [&](uint32_t spins) {
    have = cnt_wait(CNT_Y2 + 1, 384, spins) || !spins;
    TD(11)
    if (have) {
      mbar_expect_tx(bar + B_OY2, 3 * 4096);
#pragma unroll 1
      for (uint32_t i = 0x732; i; i >>= 4)
        tma_load_3d(sbase + O_Y_OFF + (i & 7) * 4096, &maps.y, bar + B_OY2, 0, n_tile * 128 + (i & 7) * 16, m_tile * 2);
    }
  };
  if (w0) {
    if (elect_one()) {
      mbar_expect_tx(bar + B_OY, 65536 - 3 * 4096);
      TD(10)
      cnt_wait(CNT_Y2, DM - 384);
      TD(7)
#pragma unroll 1
      for (uint32_t i = 0x65410; i; i >>= 4) {
        tma_load_3d(sbase + O_Y_OFF + (i & 7) * 4096, &maps.y, bar + B_OY, 0, n_tile * 128 + (i & 7) * 16, m_tile * 2);
        __nanosleep(PACE);
      }
      late(1u << 18);
    }
  }
  mbar_wait_sleep(bar + B_OY, 0);
  if (wtid == 0) { TD(12) }
  const int mrow = (lane & 7) + ((lane >> 4) & 1) * 8;
  const int mchunk = warp * 2 + ((lane >> 3) & 1);
  const uint32_t xrow = sbase + O_X_OFF + warp * 4096 + (lane & 15) * 128;
  const uint32_t yrow = sbase + O_Y_OFF + mrow * 128 + ((mchunk ^ (lane & 7)) << 4);
  uint32_t y[6][4], x[6][4], om[4];
#pragma unroll
  for (int i = 0; i < 4; i++) om[i] = pack_bf16(1.0f - gv[i], 1.0f - gv[i]);
  sts128(sbase + O_G_OFF + wtid * 16, make_uint4(pack_bf16(gv[0], gv[0]), pack_bf16(gv[1], gv[1]), pack_bf16(gv[2], gv[2]),
                                                 pack_bf16(gv[3], gv[3])));
  auto xa = [&](int h, int i) { return xrow + h * 16384 + (i >> 2) * 2048 + ((((i & 3) * 2 + (lane >> 4)) ^ (lane & 7)) << 4); };
  auto load = [&](int r, int h, int i) {
    ldsm4t(y[r], yrow + h * 2048 + i * 4096);
    asm volatile("ldmatrix.sync.aligned.m8n8.x4.shared.b16 {%0, %1, %2, %3}, [%4];"
                 : "=r"(x[r][0]), "=r"(x[r][1]), "=r"(x[r][2]), "=r"(x[r][3])
                 : "r"(xa(h, i)));
  };
  auto store = [&](int r, int h, int i, uint32_t om0, uint32_t om1) {
    stmatrix_x4(xa(h, i), mul_bf2(om0, mul_bf2(x[r][0], y[r][0])), mul_bf2(om1, mul_bf2(x[r][1], y[r][1])),
                mul_bf2(om0, mul_bf2(x[r][2], y[r][2])), mul_bf2(om1, mul_bf2(x[r][3], y[r][3])));
  };
#pragma unroll 1
  for (int h = 0; h < 2; h++) {
#pragma unroll
    for (int i = 0; i < 5; i++) load(i, h, i + (i & 6 ? 2 : 0));
#pragma unroll
    for (int i = 0; i < 5; i++) store(i, h, i + (i & 6 ? 2 : 0), h ? om[2] : om[0], h ? om[3] : om[1]);
  }
  if (w0 && !__any_sync(0xffffffffu, have)) {
    if (elect_one()) late(0);
  }
  mbar_wait_sleep(bar + B_OY2, 0);
#pragma unroll
  for (int i = 0; i < 6; i++) load(i, i & 1, (0x732 >> (i / 2 * 4)) & 7);
#pragma unroll
  for (int i = 0; i < 6; i++) store(i, i & 1, (0x732 >> (i / 2 * 4)) & 7, om[(i & 1) * 2], om[(i & 1) * 2 + 1]);
  __syncwarp();
  mbar_arrive_if(bar + B_OE, lane == 0);
  if (wtid == 0) { TD(13) }
}

__device__ __forceinline__ void out_gemm(const Maps& maps, const uint32_t sbase, uint32_t sn, bool post, float (&o)[64],
                                         float (&s)[64],                                          float i0, float i1) {
  PHASE_GIVEN
  auto acc = [&](int h) -> float (&)[64] { return h ? o : s; };
  constexpr uint64_t DHI = DESC_SW128 | ((uint64_t)(1024 >> 4) << 32);
  const uint32_t d0 = (uint32_t)make_desc(sbase, 0, 0, 0);
  auto mma0 = [&](int h) {
    wgmma_fence();
#pragma unroll
    for (int k = 0; k < 4; k++)
      wgmma_m64n128_ss_tb(acc(h), DHI | (d0 + 0x10800 + h * 512 + k * 2), DHI | (d0 + 0x2000c00 + k * 128), k != 0);
    wgmma_commit();
  };
  mbar_wait(bar + B_OFULL, 0);
  mma0(0);
  wgmma_wait<1>();
  fence_regs(o);
  if (post) {
    named_bar_arrive(3, 256);
    put_o(sbase, 0, warp, lane, o, i0, i1);
  }
  mma0(1);
  if (post) st_go(bar, 0, wtid, sn - 1);
  const int m_tile = maps.id[blockIdx.x][2] & 15, n_tile = maps.id[blockIdx.x][2] >> 4;
  uint32_t stage = 1, phase = 0, prev_stage = 0;
  GT(gti++)
  const uint32_t xrow = sbase + O_X_OFF + warp * 4096 + (lane & 15) * 128;
  auto addr = [&](int i) {
    return xrow + (i >> 3) * 16384 + ((i >> 2) & 1) * 2048 + ((((i & 3) * 2 + (lane >> 4)) ^ (lane & 7)) << 4);
  };
  uint32_t b[16][4];
#pragma unroll
  for (int i = 0; i < 64; i++) asm volatile("" : "=r"(b[i >> 2][i & 3]));
  auto ld_b = [&](int q0, int q1) {
#pragma unroll
    for (int i = 0; i < 16; i++)
        asm volatile(
            "{\n.reg .pred p;\nsetp.ge.s32 p, %5, %6;\nsetp.le.and.s32 p, %5, %7, p;\n"
            "@p ldmatrix.sync.aligned.m8n8.x4.shared.b16 {%0, %1, %2, %3}, [%4];\n}\n"
            : "+r"(b[i][0]), "+r"(b[i][1]), "+r"(b[i][2]), "+r"(b[i][3])
            : "r"(addr(i)), "r"(i / 4), "r"(q0), "r"(q1)
            : "memory");
  };
  int nq = 0;
#pragma unroll 1
  for (int kt = 1; kt < O_NK - 2; kt++) {
    uint32_t da = (uint32_t)make_desc(sbase + out_stage(stage), 16, 0, 0);
    uint32_t db = (uint32_t)make_desc(sbase + out_stage(stage) + 16384, 8192, 0, 0);
    asm volatile("" : "+r"(da), "+r"(db));
    mbar_wait(bar + B_OFULL + 8 * stage, phase);
    GT(gti++)
#pragma unroll
    for (int kk = 0; kk < 4; kk++) {
      wgmma_wait<2>();
      if (kk == 2)
        mbar_arrive_cluster_if(bar + B_OEMPTY + 8 * prev_stage, wtid >> 6, (wtid & 63) == 32 && kt - 1 + O_STAGES < O_NK);
      wgmma_fence();
      wgmma_m64n128_ss_tb(acc(0), DHI | (da + kk * 2), DHI | (db + kk * 128), 1);
      wgmma_m64n128_ss_tb(acc(1), DHI | (da + 512 + kk * 2), DHI | (db + kk * 128), 1);
      wgmma_commit();
      if (kk == 0 && kt >= 52) {
        uint32_t ok;
        asm volatile("{\n.reg .pred p;\nmbarrier.test_wait.parity.shared::cta.b64 p, [%1], 0;\nselp.u32 %0, 1, 0, p;\n}\n"
                     : "=r"(ok)
                     : "r"(bar + B_OE)
                     : "memory");
        if (__all_sync(0xffffffffu, ok)) {
          ld_b(nq, nq);
          nq++;
        }
      }
    }
    prev_stage = stage;
    if (++stage == O_STAGES) { stage = 0; phase ^= 1; }
  }
  if (tid == 0) { TD(14) }
  constexpr int S0 = (O_NK - 2) % O_STAGES, P0 = ((O_NK - 2) / O_STAGES) & 1;
  auto mma = [&](int h, int k0, int k1) {
    wgmma_fence();
#pragma unroll
    for (int k = k0; k < k1; k++) {
      const uint32_t d = d0 + (out_stage(S0 + (k >> 2)) >> 4);
      wgmma_m64n128_ss_tb(acc(h), DHI | (d + 0x10000 + h * 512 + (k & 3) * 2), DHI | (d + 0x2000400 + (k & 3) * 128), 1);
    }
    wgmma_commit();
  };
#pragma unroll
  for (int p = 0; p < 2; p++) {
    mbar_wait(bar + B_OFULL + 8 * (S0 + p), P0);
    mma(0, 4 * p, 4 * p + 4);
  }
  mma(1, 0, 8);
  if (nq < 4) {
    mbar_wait(bar + B_OE, 0);
    ld_b(nq, 3);
  }
  const uint4 g4 = lds128(sbase + O_G_OFF + wtid * 16);
  const uint32_t gg[4] = {g4.x, g4.y, g4.z, g4.w};
  const int w4 = __shfl_sync(0xffffffffu, warp, 0);
#pragma unroll
  for (int i = 0; i < 16; i++) {
    const int h = i >> 3;
    if (i == 0) wgmma_wait<1>();
    if (i == 8) wgmma_wait<0>();
    if ((i & 7) == 0) fence_regs(acc(h));
    if (i == 8) {   }
    const float* a = acc(h) + 8 * (i & 7);
    stmatrix_x4(addr(i), fma_bf2(gg[2 * h], pack_bf16(a[0], a[1]), b[i][0]), fma_bf2(gg[2 * h + 1], pack_bf16(a[2], a[3]), b[i][1]),
                fma_bf2(gg[2 * h], pack_bf16(a[4], a[5]), b[i][2]), fma_bf2(gg[2 * h + 1], pack_bf16(a[6], a[7]), b[i][3]));
    if ((i & 7) == 7) {
      fence_proxy_async();
      __syncwarp();
      if (elect_one()) {
        tma_store_3d(&maps.oc, sbase + O_X_OFF + (h * 4 + w4) * 4096, 0, m_tile * 128 + h * 64 + w4 * 16, n_tile * 2);
        if (h == 1) {
          tma_store_commit();
        }
      }
    }
  }
  GT(gti++)
}

__device__ __noinline__ void leave_kernel(int mask) {
  if (!(mask & 4)) return;
  if (atomicAdd(g_cnt + CNT_DONE * 32, 1u) == 2 * gridDim.x - 1) {
    for (int i = 0; i < CNT_N; i++) g_cnt[i * 32] = 0;
#pragma unroll 4
    for (int i = 0; i < 128; i++) g_slot[i] = 0;
  }
}

__global__ void __launch_bounds__(384, 1)
    fused_kernel(int mask, const bf16* px, const bf16* pw, const __grid_constant__ Maps maps) {
  extern __shared__ __align__(1024) uint8_t smem_raw[];
  {
    const uint32_t t = threadIdx.x, l = t & 31, u = (blockIdx.x & 127) * 16 + (l >> 1);
    const uint32_t ow = (u >> 5) * HDIM + ((u >> 2) & 7) * 512 + 256 + (u & 3) * 64, ox = u * DM;
    const bf16* p = ((l & 1) ? pw : px) + ((l & 1) ? ow : ox);
    asm volatile("{\n.reg .pred p;\nsetp.ne.u32 p, %1, 0;\n@p prefetch.global.L2 [%0];\n}\n" ::"l"(p), "r"((uint32_t)(t < 32)));
  }
  {
    const uint32_t sbase = __shfl_sync(0xffffffffu, smem_u32(smem_raw), 0);
    const uint32_t bar = sbase + BAR_OFF;
    const int tid = threadIdx.x;
    const bool do_qkv = (mask & 1) && blockIdx.x < 128;
    TL(0, 0)
    if (__shfl_sync(0xffffffffu, tid >> 5, 0) == 1 && do_qkv) {
      if (elect_one()) {
        for (int i = 0; i < G_STAGES; i++) mbar_init(bar + B_GFULL + 8 * i, 1);
        fence_barrier_init();
        qkv_producer(maps, sbase, true);
      }
    }
    if (tid == 0) {
      for (int i = 0; i < G_STAGES; i++) {
        mbar_init(bar + B_GEMPTY + 8 * i, 2);
        mbar_init(bar + B_SFULL + 8 * i, 4);
        mbar_init(bar + B_SFREE + 8 * i, 1);
      }
      for (int i = 0; i < 2; i++) {
        mbar_init(bar + B_OFREE + 8 * i, 1);
        mbar_init(bar + B_QFULL + 8 * i, 1);
        mbar_init(bar + B_QEMPTY + 8 * i, 2);
        mbar_init(bar + B_KFULL + 8 * i, 1);
        mbar_init(bar + B_KEMPTY + 8 * i, 2);
        mbar_init(bar + B_VFULL + 8 * i, 1);
        mbar_init(bar + B_VEMPTY + 8 * i, 2);
      }
      for (int i = 0; i < O_STAGES; i++) {
        mbar_init(bar + B_OFULL + 8 * i, 1);
        mbar_init(bar + B_OEMPTY + 8 * i, 2);
      }
      mbar_init(bar + B_OY, 1);
      for (int i = 0; i < 3; i++) mbar_init(bar + seen_bar(i), 1);
      mbar_init(bar + B_OY2, 1);
      mbar_init(bar + B_DEAL, 1);
      mbar_init(bar + B_DEAL2, 1);
      mbar_init(bar + B_PAIR, 1);
      mbar_init(bar + B_OE, 4);
      mbar_init(bar + B_QDONE, 2);
      for (int i = 0; i < 8; i++) mbar_init(bar + B_CFULL + 8 * i, 1);
      for (int i = 0; i < CNT_N; i++) asm volatile("st.shared.u32 [%0], 0;" ::"r"(bar + B_PEND + 4 * i) : "memory");
      fence_barrier_init();
    }
    __syncthreads();
    asm volatile("barrier.cluster.arrive.relaxed.aligned;" ::: "memory");
  }
  uint32_t smem0 = smem_u32(smem_raw);
  PHASE_PROLOGUE
  const bool do_qkv = (mask & 1) && blockIdx.x < 128, do_out = (mask & 4) && blockIdx.x < 128;
  TL(0, 1)

  if (wg != 2) {
    reg_alloc<232>();
    asm volatile("barrier.cluster.wait.acquire.aligned;" ::: "memory");
    if (wg == 1) named_bar_arrive(4, 256);
    uint32_t sn = 0;
    float rest[64], o[64], s[64];
    uint32_t q[32];
    if (do_qkv) {
      sn = qkv_consumer(maps, sbase, wg, mask & 2, q, rest, rt_zero);
    } else {
      undef_regs(rest);
#pragma unroll
      for (int j = 0; j < 32; j++) asm volatile("" : "=r"(q[j]));
    }
    undef_regs(o);
    undef_regs(s);
    TL(0, 2) TL(1, 0) TL(1, 1)
    const bool direct = do_out && wg == 0;
    float i0 = 0.f, i1 = 0.f;
    if (mask & 2) sn = attn_consumer(maps, sbase, wg, rt_zero, sn, q, rest, do_qkv, o, s, i0, i1);
    TL(2, 0)
    bool side = false;
    if (!direct) {
      wgmma_wait<0>();
      fence_regs(o);
      if (mask & 2) {
        const bool fused = mask & 4, mainc = blockIdx.x < 128;
        if (mainc) {
          PHASE_GIVEN
          put_o(sbase, wg, warp, lane, o, i0, i1);
          st_go(bar, wg, wtid, sn - 1);
        }
        const uint32_t b2 = blockIdx.x * 2 + (threadIdx.x >> 7);
        const uint32_t first = __shfl_sync(0xffffffffu, !fused ? b2 : mainc ? conv_first(maps) : (b2 - 255) * 128 - C_SIDE, 0);
        conv_consumer(maps, smem_u32(smem_raw), first, !fused ? 264 : mainc ? 16 : 1,
                      !fused ? DM : mainc ? (first | 127) + 1 - C_SIDE : first + C_SIDE, fused && !mainc,
                      fused && mainc);
      }
      side = (mask & 4) && blockIdx.x < 128;
    } else {
      out_gemm(maps, sbase, sn, mask & 2, o, s, i0, i1);
    }
    TL(1, 2) TL(2, 1) TL(2, 2) TL(3, 0) TL(3, 1)
    if (side + rt_zero) out_side(maps, smem_u32(smem_raw));
    tma_store_wait_read<0>();
  } else {
    reg_dealloc<40>();
    asm volatile("barrier.cluster.wait.acquire.aligned;" ::: "memory");
    const int w = __shfl_sync(0xffffffffu, tid >> 5, 0) - 8;
    if (w < 2) {
      if (do_qkv) prep_agent(maps, sbase, w, lane);
      if (elect_one()) store_agent(bar, w, w && do_out ? conv_first(maps) + 48 : 0, blockIdx.x >= 128 || mask == 4 ? 0 : mask == 1 ? 24 : 99);
      TL2(3, 2)
    } else {
      if (elect_one()) {
        const bool dry = w == 2;
        if (do_qkv && !dry) qkv_producer(maps, sbase, false);
        if (mask & 2) attn_producer(maps, sbase, do_qkv, do_out, dry);
        if (do_out) out_producer(maps, sbase, mask & 2, dry);
        if (dry) { TD(5) }
      }
      __syncwarp();
      if (w == 2 && do_qkv) gate_rows(maps, bar, tid & 31);
      if (w == 2) publisher(bar, tid & 31, !(mask & 2) ? 2 : do_out ? 3 : 4, !do_out ? 3 : do_qkv ? 0 : 2, do_qkv ? 4 : 0);
      if ((tid & 31) == 0) leave_kernel(mask);
    }
  }
}

typedef CUresult (*PFN_tmapEncode)(CUtensorMap*, CUtensorMapDataType, cuuint32_t, void*, const cuuint64_t*,
                                   const cuuint64_t*, const cuuint32_t*, const cuuint32_t*, CUtensorMapInterleave,
                                   CUtensorMapSwizzle, CUtensorMapL2promotion, CUtensorMapFloatOOBfill);
static PFN_tmapEncode s_encode = nullptr;

static void make_map_2d(CUtensorMap* m, const void* ptr, int rows, int cols, int box_rows) {
  cuuint64_t dims[2] = {(cuuint64_t)cols, (cuuint64_t)rows};
  cuuint64_t strides[1] = {(cuuint64_t)cols * 2};
  cuuint32_t box[2] = {cols < 64 ? 32u : 64u, (cuuint32_t)box_rows};
  cuuint32_t es[2] = {1, 1};
  s_encode(m, CU_TENSOR_MAP_DATA_TYPE_BFLOAT16, 2, const_cast<void*>(ptr), dims, strides, box, es,
           CU_TENSOR_MAP_INTERLEAVE_NONE, cols < 64 ? CU_TENSOR_MAP_SWIZZLE_64B : CU_TENSOR_MAP_SWIZZLE_128B, CU_TENSOR_MAP_L2_PROMOTION_L2_256B,
           CU_TENSOR_MAP_FLOAT_OOB_FILL_NONE);
}
static void make_map_3d(CUtensorMap* m, const void* ptr, int rows, int cols, int box_rows, int box_chunks) {
  cuuint64_t dims[3] = {64, (cuuint64_t)rows, (cuuint64_t)(cols / 64)};
  cuuint64_t strides[2] = {(cuuint64_t)cols * 2, 128};
  cuuint32_t box[3] = {64, (cuuint32_t)box_rows, (cuuint32_t)box_chunks};
  cuuint32_t es[3] = {1, 1, 1};
  s_encode(m, CU_TENSOR_MAP_DATA_TYPE_BFLOAT16, 3, const_cast<void*>(ptr), dims, strides, box, es,
           CU_TENSOR_MAP_INTERLEAVE_NONE, CU_TENSOR_MAP_SWIZZLE_128B, CU_TENSOR_MAP_L2_PROMOTION_L2_256B,
           CU_TENSOR_MAP_FLOAT_OOB_FILL_NONE);
}

static cudaLaunchConfig_t fused_cfg(cudaLaunchAttribute* at) {
  cudaLaunchConfig_t cfg = {};
  cfg.gridDim = dim3(132);
  cfg.blockDim = dim3(384);
  cfg.dynamicSmemBytes = SMEM_BYTES;
  cfg.stream = cudaStreamPerThread;
  at[0].id = cudaLaunchAttributeClusterDimension;
  at[0].val.clusterDim.x = 2;
  at[0].val.clusterDim.y = 1;
  at[0].val.clusterDim.z = 1;
  cfg.attrs = at;
  cfg.numAttrs = 1;
  return cfg;
}

extern "C" void kernel_launch(void* const* d_in, const int* in_sizes, int n_in, void* d_out, int out_size) {
  const bf16* x = (const bf16*)d_in[0];
  const bf16* ckv = (const bf16*)d_in[1];
  const bf16* wq = (const bf16*)d_in[2];
  const bf16* wuk = (const bf16*)d_in[3];
  const bf16* wuv = (const bf16*)d_in[4];
  const bf16* wo = (const bf16*)d_in[5];
  const bf16* bk = (const bf16*)d_in[7];
  const bf16* bv = (const bf16*)d_in[8];
  const bf16* shift_k = (const bf16*)d_in[9];
  const bf16* ssm_k = (const bf16*)d_in[10];
  const bf16* ssm_D = (const bf16*)d_in[11];
  const bf16* gate_w = (const bf16*)d_in[12];
  bf16* out = (bf16*)d_out;

  static void *pq = nullptr, *pk = nullptr, *pv = nullptr, *pctx = nullptr, *pb = nullptr, *pu = nullptr;
  static int max_clusters = 0;
  if (!s_encode) {
    void* fn = nullptr;
    cudaDriverEntryPointQueryResult qres;
    cudaGetDriverEntryPoint("cuTensorMapEncodeTiled", &fn, cudaEnableDefault, &qres);
    s_encode = (PFN_tmapEncode)fn;
    cudaGetSymbolAddress(&pq, g_q);
    cudaGetSymbolAddress(&pk, g_k);
    cudaGetSymbolAddress(&pv, g_v);
    cudaGetSymbolAddress(&pctx, g_ctx);
    cudaGetSymbolAddress(&pb, g_y2T);
    cudaGetSymbolAddress(&pu, g_kvT);
    cudaFuncSetAttribute(fused_kernel, cudaFuncAttributeMaxDynamicSharedMemorySize, SMEM_BYTES);
    cudaLaunchAttribute at[1];
    cudaLaunchConfig_t cfg = fused_cfg(at);
    if (cudaOccupancyMaxActiveClusters(&max_clusters, fused_kernel, &cfg) != cudaSuccess) max_clusters = 0;
  }

  Maps all = {};
  make_map_2d(&all.a[0], x, S_LEN, DM, 128);
  make_map_2d(&all.a[1], ckv, S_LEN, DC, 128);
  make_map_3d(&all.b[0], wq, DM, HDIM, 64, 4);
  make_map_3d(&all.b[1], wuk, DC, HDIM, 64, 4);
  make_map_3d(&all.b[2], wuv, DC, HDIM, 64, 4);
  make_map_2d(&all.c[0], pq, S_LEN, HDIM, 64);
  make_map_2d(&all.c[1], pk, S_LEN, HDIM, 64);
  make_map_2d(&all.c[2], pv, S_LEN, HDIM, 64);
  make_map_3d(&all.q, pq, S_LEN, HDIM, 128, 2);
  make_map_3d(&all.k, pk, S_LEN, HDIM, 128, 2);
  make_map_3d(&all.v, pv, S_LEN, HDIM, 128, 2);
  make_map_2d(&all.o, pctx, S_LEN, HDIM, 64);
  all.ssm_k = ssm_k;
  all.ssm_D = ssm_D;
  make_map_2d(&all.oa, pctx, S_LEN, HDIM, 128);
  make_map_2d(&all.ob, wo, HDIM, DM, 64);
  make_map_3d(&all.oc, out, S_LEN, DM, 16, 2);
  make_map_3d(&all.y, pb, DM, S_LEN, 16, 2);
  make_map_3d(&all.xs, x, S_LEN, DM, 16, 2);
  make_map_2d(&all.cu, pu, DM * 64, 32, 64);
  make_map_2d(&all.ch, ssm_k, DM * 64, 32, 64);

  make_map_2d(&all.bk, bk, S_LEN, DM, 35);
  make_map_2d(&all.bv, bv, S_LEN, DM, 32);
  for (int b = 0; b < 128; b++) {
    const int c = b >> 1, r = b & 1;
    const int G = c < 4 ? 0 : c < 36 ? (c - 4) % 8 : 1 + (c - 36) % 7;
    const int i = c < 4 ? 4 + c : c < 36 ? (c - 4) / 8 : 4 + (c - 36) / 7;
    all.id[b][0] = r + 2 * (i & 1) + 4 * (G & 3) + 16 * (i >> 1) + 64 * (G >> 2);
    all.id[b][1] = r + 2 * i + 16 * G;
    all.id[b][2] = r + 2 * G + 16 * i;
    all.id[b][3] = r + 2 * i == 15 ? 0x78 : 0xd8;
  }
  all.shift_k = shift_k;
  all.x = x;
  all.gate_w = gate_w;
  cudaLaunchAttribute at[1];
  cudaLaunchConfig_t cfg = fused_cfg(at);
  if (max_clusters >= 66) {
    cudaLaunchKernelEx(&cfg, fused_kernel, 7, x, wq, all);
  } else {
    for (int m = 1; m <= 4; m <<= 1) cudaLaunchKernelEx(&cfg, fused_kernel, m, x, wq, all);
  }
}
```
